```python
import torch

def _softmax(x, axis=-1):
    return torch.softmax(x, dim=axis)
def _gelu(x):
    return torch.nn.functional.gelu(x, approximate="tanh")
def _silu(x):
    return torch.nn.functional.silu(x)
def _sigmoid(x):
    return torch.sigmoid(x)
def _layernorm(x, axis=-1, eps=1e-5):
    m = x.mean(dim=axis, keepdim=True)
    v = x.var(dim=axis, keepdim=True, unbiased=False)
    return (x - m) / torch.sqrt(v + eps)
def _scatter_add(tgt, idx, src, axis=0):
    return tgt.clone().index_add_(axis, idx, src)
def _segment_sum(src, seg, n):
    out = torch.zeros((n,) + src.shape[1:], dtype=src.dtype)
    return out.index_add_(0, seg, src)
def _pad(x, pw):
    flat = tuple(v for pair in reversed(pw) for v in pair)
    return torch.nn.functional.pad(x, flat)

kernel_name = 'interleave_layers__spectral_gfnet__ssm_conv_s5__prompt'

def setup_inputs():

    _w = (lambda a: (lambda t: t.to(torch.bfloat16) if t.is_floating_point() else t)(torch.as_tensor(a)))
    def _A_setup():
        B, S, D = 1, 2048, 512
        Df = D // 2 + 1
        return {
            "x": _w((lambda *s: torch.randn(*s, dtype=torch.bfloat16) * 0.05)(B, S, D)),
            "w_r": _w((lambda *s: torch.randn(*s, dtype=torch.bfloat16) * 1.6)(S, Df) * 0.02),
            "w_i": _w((lambda *s: torch.randn(*s, dtype=torch.bfloat16) * 1.6)(S, Df) * 0.02),
        }
    _A_in = _A_setup()

    def _B_setup():
        B, S, D = 1, 2048, 512
        P = D
        Lambda_re = -0.5 * (lambda _x: torch.exp(torch.as_tensor(_x)))((lambda *s: torch.randn(*s, dtype=torch.bfloat16) * 0.2)(P))
        Lambda_im = (lambda *s: torch.randn(*s, dtype=torch.bfloat16) * 0.4)(P) * 1.0
        B_re = (lambda *s: torch.randn(*s, dtype=torch.bfloat16) * 0.2)(P, D) * (D ** -0.5)
        B_im = (lambda *s: torch.randn(*s, dtype=torch.bfloat16) * 0.2)(P, D) * (D ** -0.5)
        C_re = (lambda *s: torch.randn(*s, dtype=torch.bfloat16) * 0.2)(D, P) * (P ** -0.5)
        C_im = (lambda *s: torch.randn(*s, dtype=torch.bfloat16) * 0.2)(D, P) * (P ** -0.5)
        log_dt = (lambda *s: torch.randn(*s, dtype=torch.bfloat16) * 0.2)(P) * 0.3 - 2.0
        Dskip = (lambda *s: torch.randn(*s, dtype=torch.bfloat16) * 0.05)(D)
        return {
            "x": _w((lambda *s: torch.randn(*s, dtype=torch.bfloat16) * 0.05)(B, S, D)),
            "Lambda_re": _w(Lambda_re),
            "Lambda_im": _w(Lambda_im),
            "B_re": _w(B_re),
            "B_im": _w(B_im),
            "C_re": _w(C_re),
            "C_im": _w(C_im),
            "log_dt": _w(log_dt),
            "Dskip": _w(Dskip),
        }
    _B_in = _B_setup()

    return {
        "A_x": _A_in["x"],
        "A_w_r": _A_in["w_r"],
        "A_w_i": _A_in["w_i"],
        "B_x": _B_in["x"],
        "B_Lambda_re": _B_in["Lambda_re"],
        "B_Lambda_im": _B_in["Lambda_im"],
        "B_B_re": _B_in["B_re"],
        "B_B_im": _B_in["B_im"],
        "B_C_re": _B_in["C_re"],
        "B_C_im": _B_in["C_im"],
        "B_log_dt": _B_in["log_dt"],
        "B_Dskip": _B_in["Dskip"],
    }

def reference(A_x, A_w_r, A_w_i, B_x, B_Lambda_re, B_Lambda_im, B_B_re, B_B_im, B_C_re, B_C_im, B_log_dt, B_Dskip):
    def _A_ref(x, w_r, w_i):
        B, S, D = x.shape
        X = (lambda x, axes=(-2,-1): torch.fft.rfft2(x.float(), dim=axes))(x, axes=(-2, -1))
        W = w_r + 1j * w_i
        X = X * W
        y = (lambda x, s, axes=(-2,-1): torch.fft.irfft2(x, s=s, dim=axes).to(torch.bfloat16))(X, (S, D), axes=(-2, -1))
        return y

    def _B_ref(x, Lambda_re, Lambda_im, B_re, B_im, C_re, C_im, log_dt, Dskip):
        Bsz, L, H = x.shape
        Lam = Lambda_re + 1j * Lambda_im
        Bmat = B_re + 1j * B_im
        Cmat = C_re + 1j * C_im
        dt = torch.exp(log_dt)
        Lam_bar = torch.exp(dt * Lam)
        B_bar = ((Lam_bar - 1.0) / Lam)[:, None] * Bmat
        Bu = torch.einsum("bld,pd->blp", x + 0j, B_bar)
        h = torch.zeros_like(Bu[:, 0, :])
        hs = []
        for t in range(L):
            h = Lam_bar[None, :] * h + Bu[:, t, :]
            hs.append(h)
        hseq = torch.stack(hs, 1)
        y = 2.0 * torch.einsum("blp,dp->bld", hseq, Cmat).real + x * Dskip[None, None, :]
        return y

    x = A_x
    x = x + _A_ref(_layernorm(x, axis=-1), A_w_r, A_w_i)
    x = x + _B_ref(_layernorm(x, axis=-1), B_Lambda_re, B_Lambda_im, B_B_re, B_B_im, B_C_re, B_C_im, B_log_dt, B_Dskip)
    x = x + _A_ref(_layernorm(x, axis=-1), A_w_r, A_w_i)
    x = x + _B_ref(_layernorm(x, axis=-1), B_Lambda_re, B_Lambda_im, B_B_re, B_B_im, B_C_re, B_C_im, B_log_dt, B_Dskip)
    return x
```

```cpp
#include <cuda_runtime.h>
#include <cuda_bf16.h>
#include <cuda.h>
#include <stdint.h>

namespace {

constexpr int NCTA = 128;
constexpr int NTHREADS = 416;
constexpr int SM_A = 0;
constexpr int SM_X = 131072;
constexpr int SM_H = 196608;
constexpr int SM_M = 229376;
constexpr int SM_TOTAL = 232448;
constexpr int SM_BAR = SM_M;
constexpr int SM_RSTD = SM_M + 384;
constexpr int SM_MEAN = SM_M + 896;
constexpr int SM_TAB = SM_M + 1408;
constexpr int B_FULL0 = 0;
constexpr int B_EMPTY0 = 8;
constexpr int B_FULLC = 12;
constexpr int B_AFULL = 13;
constexpr int B_AEMPTY = 21;
constexpr int B_XFULL = 29;
constexpr int B_XEMPTY = 33;
constexpr int B_AFREE = 37;
constexpr int NBARS = 38;

__device__ __align__(1024) uint8_t g_XA[16 * 8 * 16384];
__device__ __align__(1024) uint8_t g_XB[16 * 8 * 16384];
__device__ __align__(1024) uint8_t g_A1[8 * 8 * 16384];
__device__ __align__(1024) uint8_t g_A2[8 * 8 * 16384];
__device__ __align__(1024) uint8_t g_E[2 * 8 * 8 * 8192];
__device__ __align__(16) float g_rstd0[2048];
__device__ __align__(16) float g_part1[128 * 2048];
__device__ __align__(16) float g_part2[8 * 2048];
__device__ __align__(16) float g_Dh[512];
__device__ __align__(16) uint4 g_Wfrag[128 * 4 * 256];
__device__ __align__(16) float4 g_Ebuf[2 * 16 * 512];
__device__ __align__(16) uint4 g_P[16 * 8 * 8 * 1024];
__device__ unsigned g_bar[8];
__device__ unsigned g_pcnt[2 * 128];
__device__ unsigned g_err;

constexpr unsigned SPIN_LIMIT = 1u << 22;

__device__ __forceinline__ uint32_t s2u(const void* p) { return (uint32_t)__cvta_generic_to_shared(p); }
__device__ __forceinline__ void mbar_init(uint32_t a, uint32_t c) {
    asm volatile("mbarrier.init.shared::cta.b64 [%0], %1;" ::"r"(a), "r"(c) : "memory");
}
__device__ __forceinline__ void mbar_expect(uint32_t a, uint32_t bytes) {
    asm volatile("mbarrier.arrive.expect_tx.shared::cta.b64 _, [%0], %1;" ::"r"(a), "r"(bytes) : "memory");
}
__device__ __forceinline__ void mbar_arrive(uint32_t a, uint32_t cnt) {
    asm volatile("mbarrier.arrive.shared::cta.b64 _, [%0], %1;" ::"r"(a), "r"(cnt) : "memory");
}
__device__ __forceinline__ bool mbar_try(uint32_t a, uint32_t parity) {
    uint32_t ok;
    asm volatile("{\n.reg .pred p;\nmbarrier.try_wait.parity.shared::cta.b64 p, [%1], %2;\nselp.u32 %0, 1, 0, p;\n}"
                 : "=r"(ok) : "r"(a), "r"(parity) : "memory");
    return ok != 0;
}
__device__ __forceinline__ void mbar_wait(uint32_t a, uint32_t parity) {
    unsigned n = 0;
    while (!mbar_try(a, parity)) {
        if (++n > SPIN_LIMIT) { g_err = 1; break; }
    }
}
__device__ __forceinline__ void bulk_g2s(uint32_t dst, const void* src, uint32_t bytes, uint32_t bar) {
    asm volatile("cp.async.bulk.shared::cluster.global.mbarrier::complete_tx::bytes [%0], [%1], %2, [%3];" ::"r"(dst),
                 "l"(src), "r"(bytes), "r"(bar) : "memory");
}
__device__ __forceinline__ void tma_2d(uint32_t dst, const CUtensorMap* m, int c0, int c1, uint32_t bar) {
    asm volatile("cp.async.bulk.tensor.2d.shared::cluster.global.mbarrier::complete_tx::bytes [%0], [%1, {%3,%4}], [%2];" ::"r"(dst),
                 "l"(m), "r"(bar), "r"(c0), "r"(c1) : "memory");
}
__device__ __forceinline__ void tma_5d(uint32_t dst, const CUtensorMap* m, int c0, int c1, int c2, int c3, int c4, uint32_t bar) {
    asm volatile("cp.async.bulk.tensor.5d.shared::cluster.global.mbarrier::complete_tx::bytes [%0], [%1, {%3,%4,%5,%6,%7}], [%2];" ::"r"(dst),
                 "l"(m), "r"(bar), "r"(c0), "r"(c1), "r"(c2), "r"(c3), "r"(c4) : "memory");
}
__device__ __forceinline__ void fence_async() { asm volatile("fence.proxy.async;" ::: "memory"); }
__device__ __forceinline__ void fence_async_smem() { asm volatile("fence.proxy.async.shared::cta;" ::: "memory"); }
__device__ __forceinline__ void wg_fence() { asm volatile("wgmma.fence.sync.aligned;" ::: "memory"); }
__device__ __forceinline__ void wg_commit() { asm volatile("wgmma.commit_group.sync.aligned;" ::: "memory"); }
template <int N> __device__ __forceinline__ void wg_wait() { asm volatile("wgmma.wait_group.sync.aligned %0;" ::"n"(N) : "memory"); }
__device__ __forceinline__ void bar_sync(int id, int n) { asm volatile("bar.sync %0, %1;" ::"r"(id), "r"(n) : "memory"); }
__device__ __forceinline__ void bar_arrive(int id, int n) { asm volatile("bar.arrive %0, %1;" ::"r"(id), "r"(n) : "memory"); }
__device__ __forceinline__ unsigned ld_acquire(const unsigned* p) {
    unsigned v;
    asm volatile("ld.acquire.gpu.global.u32 %0, [%1];" : "=r"(v) : "l"(p) : "memory");
    return v;
}
__device__ __forceinline__ void red_release(unsigned* p, unsigned v) {
    asm volatile("red.release.gpu.global.add.u32 [%0], %1;" ::"l"(p), "r"(v) : "memory");
}
__device__ __forceinline__ void wait_count(const unsigned* p, unsigned target) {
    unsigned n = 0;
    while ((int)(ld_acquire(p) - target) < 0) {
        if (++n > SPIN_LIMIT) { g_err = 2; break; }
    }
}
__device__ __forceinline__ float4 ld_relaxed_f4(const float4* p) {
    float4 v;
    asm volatile("ld.relaxed.gpu.global.v4.f32 {%0,%1,%2,%3}, [%4];" : "=f"(v.x), "=f"(v.y), "=f"(v.z), "=f"(v.w) : "l"(p) : "memory");
    return v;
}
__device__ __forceinline__ void st_relaxed_f4(float4* p, float4 v) {
    asm volatile("st.relaxed.gpu.global.v4.f32 [%0], {%1,%2,%3,%4};" ::"l"(p), "f"(v.x), "f"(v.y), "f"(v.z), "f"(v.w) : "memory");
}
__device__ __forceinline__ uint32_t pack_bf16(float lo, float hi) {
    uint32_t r;
    asm("cvt.rn.bf16x2.f32 %0, %1, %2;" : "=r"(r) : "f"(hi), "f"(lo));
    return r;
}
__device__ __forceinline__ float bf_lo(uint32_t v) { return __uint_as_float(v << 16); }
__device__ __forceinline__ float bf_hi(uint32_t v) { return __uint_as_float(v & 0xffff0000u); }
__device__ __forceinline__ void sts32(uint32_t a, uint32_t v) { asm volatile("st.shared.u32 [%0], %1;" ::"r"(a), "r"(v) : "memory"); }
__device__ __forceinline__ void sts128(uint32_t a, uint4 v) {
    asm volatile("st.shared.v4.u32 [%0], {%1,%2,%3,%4};" ::"r"(a), "r"(v.x), "r"(v.y), "r"(v.z), "r"(v.w) : "memory");
}

__device__ __forceinline__ uint64_t desc_k(uint32_t addr) {
    return (uint64_t)((addr & 0x3FFFF) >> 4) | (1ull << 16) | (64ull << 32) | (1ull << 62);
}
__device__ __forceinline__ uint64_t desc_mn(uint32_t addr, uint32_t lbo) {
    return (uint64_t)((addr & 0x3FFFF) >> 4) | ((uint64_t)(lbo >> 4) << 16) | (64ull << 32) | (1ull << 62);
}

#define ACC8(d, o) "+f"(d[o + 0]), "+f"(d[o + 1]), "+f"(d[o + 2]), "+f"(d[o + 3]), "+f"(d[o + 4]), "+f"(d[o + 5]), "+f"(d[o + 6]), "+f"(d[o + 7])
template <int TB>
__device__ __forceinline__ void wgmma_n128(float (&d)[64], uint64_t da, uint64_t db, int sd) {
    asm volatile(
        "{\n.reg .pred p;\nsetp.ne.b32 p, %66, 0;\n"
        "wgmma.mma_async.sync.aligned.m64n128k16.f32.bf16.bf16 "
        "{%0,%1,%2,%3,%4,%5,%6,%7,%8,%9,%10,%11,%12,%13,%14,%15,%16,%17,%18,%19,%20,%21,%22,%23,%24,%25,%26,%27,%28,%29,%30,%31,"
        "%32,%33,%34,%35,%36,%37,%38,%39,%40,%41,%42,%43,%44,%45,%46,%47,%48,%49,%50,%51,%52,%53,%54,%55,%56,%57,%58,%59,%60,%61,%62,%63},"
        " %64, %65, p, 1, 1, 0, %67;\n}"
        : ACC8(d, 0), ACC8(d, 8), ACC8(d, 16), ACC8(d, 24), ACC8(d, 32), ACC8(d, 40), ACC8(d, 48), ACC8(d, 56)
        : "l"(da), "l"(db), "r"(sd), "n"(TB));
}
template <int TB>
__device__ __forceinline__ void wgmma_n64(float (&d)[32], uint64_t da, uint64_t db, int sd) {
    asm volatile(
        "{\n.reg .pred p;\nsetp.ne.b32 p, %34, 0;\n"
        "wgmma.mma_async.sync.aligned.m64n64k16.f32.bf16.bf16 "
        "{%0,%1,%2,%3,%4,%5,%6,%7,%8,%9,%10,%11,%12,%13,%14,%15,%16,%17,%18,%19,%20,%21,%22,%23,%24,%25,%26,%27,%28,%29,%30,%31},"
        " %32, %33, p, 1, 1, 0, %35;\n}"
        : ACC8(d, 0), ACC8(d, 8), ACC8(d, 16), ACC8(d, 24)
        : "l"(da), "l"(db), "r"(sd), "n"(TB));
}
__device__ __forceinline__ void wgmma_n64_rs(float (&d)[32], uint32_t a0, uint32_t a1, uint32_t a2, uint32_t a3, uint64_t db, int sd) {
    asm volatile(
        "{\n.reg .pred p;\nsetp.ne.b32 p, %37, 0;\n"
        "wgmma.mma_async.sync.aligned.m64n64k16.f32.bf16.bf16 "
        "{%0,%1,%2,%3,%4,%5,%6,%7,%8,%9,%10,%11,%12,%13,%14,%15,%16,%17,%18,%19,%20,%21,%22,%23,%24,%25,%26,%27,%28,%29,%30,%31},"
        " {%32,%33,%34,%35}, %36, p, 1, 1, 1;\n}"
        : ACC8(d, 0), ACC8(d, 8), ACC8(d, 16), ACC8(d, 24)
        : "r"(a0), "r"(a1), "r"(a2), "r"(a3), "l"(db), "r"(sd));
}

struct Params {
    const __nv_bfloat16* x0;
    const __nv_bfloat16* w_r;
    const __nv_bfloat16* w_i;
    const __nv_bfloat16* lam_re;
    const __nv_bfloat16* lam_im;
    const __nv_bfloat16* log_dt;
    const __nv_bfloat16* dskip;
    float* out;
    int stop;
};

__device__ __forceinline__ float ldbf(const __nv_bfloat16* p) { return __bfloat162float(*p); }

__device__ __forceinline__ void dft_fp(int j, int& f, int& ph) {
    int cs = j >> 1;
    if (j == 1) { f = 256; ph = 0; }
    else { f = cs; ph = (j & 1) ? 128 : 0; }
}

__device__ __forceinline__ void gen_col_consts(uint8_t* sm, int tid, int nthr) {
    const unsigned short* tab = (const unsigned short*)(sm + SM_TAB);
    uint32_t sb = s2u(sm);
    for (int ch = tid; ch < 2048; ch += nthr) {
        int c8 = ch & 7, m = (ch >> 3) & 63, pi = (ch >> 9) & 1, wg = ch >> 10;
        int k1 = 32 * wg + 8 * (m >> 4) + (m & 7), po = (m >> 3) & 1;
        int ph = (po == pi) ? 0 : (po == 0 ? 384 : 128);
        uint32_t v[4];
#pragma unroll
        for (int e = 0; e < 4; e++) {
            int n1 = c8 * 8 + 2 * e;
            uint32_t lo = tab[(8 * k1 * n1 + ph) & 511], hi = tab[(8 * k1 * (n1 + 1) + ph) & 511];
            v[e] = lo | (hi << 16);
        }
        sts128(sb + SM_X + wg * 16384 + pi * 8192 + m * 128 + ((c8 ^ (m & 7)) << 4), make_uint4(v[0], v[1], v[2], v[3]));
    }
    for (int ch = tid; ch < 512; ch += nthr) {
        int c8 = ch & 7, kk = ch >> 3;
        int n2 = kk & 31, pi = kk >> 5, po = c8 >> 2;
        int ph = (po == pi) ? 0 : (po == 0 ? 384 : 128);
        uint32_t v[4];
#pragma unroll
        for (int e = 0; e < 4; e++) {
            int k2 = (c8 & 3) * 8 + 2 * e;
            uint32_t lo = tab[(16 * n2 * k2 + ph) & 511], hi = tab[(16 * n2 * (k2 + 1) + ph) & 511];
            v[e] = lo | (hi << 16);
        }
        sts128(sb + SM_X + 32768 + kk * 128 + ((c8 ^ (kk & 7)) << 4), make_uint4(v[0], v[1], v[2], v[3]));
    }
}

__device__ __forceinline__ void col_phase(uint8_t* sm, int b, int tid, uint8_t* ximg, int layer, const uint32_t (&wf)[16]) {
    const uint32_t sb = s2u(sm);
    const int wg = tid >> 7, w = (tid >> 5) & 3, lane = tid & 31, g = lane >> 2, q = lane & 3;
    const int n1 = 32 * wg + 8 * w + g;
    const int c = n1 >> 2;
    uint32_t xr[4][4];
    const int kbase = 4 * (b & 15);
    uint8_t* xb = ximg + (size_t)(c * 8 + (b >> 4)) * 16384;
#pragma unroll
    for (int jj = 0; jj < 4; jj++) {
        int k = kbase + jj;
#pragma unroll
        for (int i = 0; i < 4; i++) {
            int off = (i >> 1) * 8192 + k * 128 + (((4 * (i & 1) + q) ^ (k & 7)) << 4) + (g & 3) * 4;
            xr[jj][i] = __ldcg((const uint32_t*)(xb + off));
        }
    }
    float rs[8];
#pragma unroll
    for (int i = 0; i < 4; i++) {
        int pos = 128 * c + 32 * i + 8 * q + 2 * (g & 3);
        if (layer == 0) {
            float2 v = __ldcg((const float2*)(g_rstd0 + pos));
            rs[2 * i] = v.x; rs[2 * i + 1] = v.y;
        } else {
            float sx = 0.f, sy = 0.f;
#pragma unroll
            for (int r = 0; r < 8; r++) {
                float2 v = __ldcg((const float2*)(g_part2 + r * 2048 + pos));
                sx += v.x; sy += v.y;
            }
            rs[2 * i] = rsqrtf(sx * (1.f / 512.f) + 1e-5f);
            rs[2 * i + 1] = rsqrtf(sy * (1.f / 512.f) + 1e-5f);
        }
    }
    float twr[8], twi[8];
#pragma unroll
    for (int i = 0; i < 4; i++) {
#pragma unroll
        for (int e = 0; e < 2; e++) {
            int n2 = 8 * i + 2 * q + e;
            float s, co;
            sincospif((float)(n1 * n2) * (1.f / 1024.f), &s, &co);
            twr[2 * i + e] = co; twi[2 * i + e] = -s;
        }
    }
    const uint32_t st0 = sb + SM_H, st1 = sb + SM_H + 16384;
#pragma unroll
    for (int col = 0; col < 2; col++) {
#pragma unroll
        for (int part = 0; part < 2; part++) {
#pragma unroll
            for (int i = 0; i < 4; i++) {
                uint32_t v = xr[2 * col + part][i];
                if (b == 0 && col == 0) v = (part == 0) ? xr[1][i] : 0u;
                uint32_t o = pack_bf16(bf_lo(v) * rs[2 * i], bf_hi(v) * rs[2 * i + 1]);
                sts32(st0 + (64 * part + n1) * 128 + (((4 * col + i) ^ g) << 4) + 4 * q, o);
            }
        }
    }
    fence_async_smem();
    bar_sync(1, 256);
    float acc[32];
    wg_fence();
#pragma unroll
    for (int ks = 0; ks < 8; ks++)
        wgmma_n64<1>(acc, desc_k(sb + SM_X + wg * 16384 + (ks >> 2) * 8192 + (ks & 3) * 32), desc_mn(st0 + ks * 2048, 8192), ks != 0);
    wg_commit();
    wg_wait<0>();
    uint32_t are[2][4], aim[2][4];
#pragma unroll
    for (int col = 0; col < 2; col++) {
#pragma unroll
        for (int i = 0; i < 4; i++) {
            int o = 4 * (4 * col + i);
            float r0 = acc[o] * twr[2 * i] - acc[o + 2] * twi[2 * i], i0 = acc[o] * twi[2 * i] + acc[o + 2] * twr[2 * i];
            float r1 = acc[o + 1] * twr[2 * i + 1] - acc[o + 3] * twi[2 * i + 1], i1 = acc[o + 1] * twi[2 * i + 1] + acc[o + 3] * twr[2 * i + 1];
            are[col][i] = pack_bf16(r0, r1);
            aim[col][i] = pack_bf16(i0, i1);
        }
    }
    const uint32_t s2b = sb + SM_X + 32768;
    wg_fence();
#pragma unroll
    for (int ks = 0; ks < 2; ks++)
        wgmma_n64_rs(acc, are[0][2 * ks], are[1][2 * ks], are[0][2 * ks + 1], are[1][2 * ks + 1], desc_mn(s2b + ks * 2048, 8192), ks != 0);
#pragma unroll
    for (int ks = 0; ks < 2; ks++)
        wgmma_n64_rs(acc, aim[0][2 * ks], aim[1][2 * ks], aim[0][2 * ks + 1], aim[1][2 * ks + 1], desc_mn(s2b + 4096 + ks * 2048, 8192), 1);
    wg_commit();
    wg_wait<0>();
#pragma unroll
    for (int col = 0; col < 2; col++) {
#pragma unroll
        for (int i = 0; i < 4; i++) {
            float gr[2], gi[2];
#pragma unroll
            for (int e = 0; e < 2; e++) {
                uint32_t wv = wf[col * 8 + 2 * i + e];
                float wr = bf_lo(wv), wi = bf_hi(wv);
                float zr = acc[4 * i + 2 * col + e], zi = acc[16 + 4 * i + 2 * col + e];
                gr[e] = zr * wr - zi * wi;
                gi[e] = -(zr * wi + zi * wr);
            }
            are[col][i] = pack_bf16(gr[0], gr[1]);
            aim[col][i] = pack_bf16(gi[0], gi[1]);
        }
    }
    wg_fence();
#pragma unroll
    for (int ks = 0; ks < 2; ks++)
        wgmma_n64_rs(acc, are[0][2 * ks], are[1][2 * ks], are[0][2 * ks + 1], are[1][2 * ks + 1], desc_mn(s2b + ks * 2048, 8192), ks != 0);
#pragma unroll
    for (int ks = 0; ks < 2; ks++)
        wgmma_n64_rs(acc, aim[0][2 * ks], aim[1][2 * ks], aim[0][2 * ks + 1], aim[1][2 * ks + 1], desc_mn(s2b + 4096 + ks * 2048, 8192), 1);
    wg_commit();
    wg_wait<0>();
#pragma unroll
    for (int col = 0; col < 2; col++) {
#pragma unroll
        for (int i = 0; i < 4; i++) {
            float r[2], im[2];
#pragma unroll
            for (int e = 0; e < 2; e++) {
                float zr = acc[4 * i + 2 * col + e], zi = acc[16 + 4 * i + 2 * col + e];
                r[e] = zr * twr[2 * i + e] - zi * twi[2 * i + e];
                im[e] = zr * twi[2 * i + e] + zi * twr[2 * i + e];
            }
            sts32(st1 + n1 * 128 + (((4 * col + i) ^ g) << 4) + 4 * q, pack_bf16(r[0], r[1]));
            sts32(st1 + (64 + n1) * 128 + (((4 * col + i) ^ g) << 4) + 4 * q, pack_bf16(im[0], im[1]));
        }
    }
    fence_async_smem();
    bar_sync(1, 256);
    wg_fence();
#pragma unroll
    for (int ks = 0; ks < 8; ks++)
        wgmma_n64<1>(acc, desc_k(sb + SM_X + wg * 16384 + (ks >> 2) * 8192 + (ks & 3) * 32), desc_mn(st1 + ks * 2048, 8192), ks != 0);
    wg_commit();
    wg_wait<0>();
    const float sc = 1.f / 2048.f;
#pragma unroll
    for (int i = 0; i < 4; i++) {
        float ss0 = 0.f, ss1 = 0.f;
#pragma unroll
        for (int col = 0; col < 2; col++) {
            int o = 4 * (4 * col + i);
            float yr0 = acc[o] * sc, yr1 = acc[o + 1] * sc, yi0 = -acc[o + 2] * sc, yi1 = -acc[o + 3] * sc;
            uint32_t vr = xr[2 * col][i], vi = xr[2 * col + 1][i];
            uint32_t nr, ni;
            if (b == 0 && col == 0) {
                nr = vr;
                ni = pack_bf16(bf_lo(vi) + yr0, bf_hi(vi) + yr1);
                ss0 += 0.5f * bf_lo(ni) * bf_lo(ni);
                ss1 += 0.5f * bf_hi(ni) * bf_hi(ni);
            } else {
                nr = pack_bf16(bf_lo(vr) + yr0, bf_hi(vr) + yr1);
                ni = pack_bf16(bf_lo(vi) + yi0, bf_hi(vi) + yi1);
                ss0 += bf_lo(nr) * bf_lo(nr) + bf_lo(ni) * bf_lo(ni);
                ss1 += bf_hi(nr) * bf_hi(nr) + bf_hi(ni) * bf_hi(ni);
            }
            int k = kbase + 2 * col;
            *(uint32_t*)(xb + (i >> 1) * 8192 + k * 128 + (((4 * (i & 1) + q) ^ (k & 7)) << 4) + (g & 3) * 4) = nr;
            k++;
            *(uint32_t*)(xb + (i >> 1) * 8192 + k * 128 + (((4 * (i & 1) + q) ^ (k & 7)) << 4) + (g & 3) * 4) = ni;
        }
        int pos = 128 * c + 32 * i + 8 * q + 2 * (g & 3);
        *(float2*)(g_part1 + b * 2048 + pos) = make_float2(ss0 * (2.f / 512.f), ss1 * (2.f / 512.f));
    }
}

__device__ __forceinline__ void cexp_scaled(float ar, float ai, float n, float& r, float& i) {
    float m = expf(ar * n), s, c;
    sincosf(ai * n, &s, &c);
    r = m * c; i = m * s;
}

__global__ void __launch_bounds__(NTHREADS, 1)
fused_kernel(const __grid_constant__ CUtensorMap tm_x, const __grid_constant__ CUtensorMap tm_bre,
             const __grid_constant__ CUtensorMap tm_bim, const __grid_constant__ CUtensorMap tm_cre,
             const __grid_constant__ CUtensorMap tm_cim, const Params p) {
    extern __shared__ __align__(1024) uint8_t sm[];
    const uint32_t sb = s2u(sm);
    const int tid = threadIdx.x, b = blockIdx.x;
    const int c = b >> 3, r = b & 7;
    const int wg = tid >> 7, w = (tid >> 5) & 3, lane = tid & 31, g = lane >> 2, q = lane & 3;
    auto BAR = [&](int i) { return sb + SM_BAR + 8 * i; };

    if (tid == 0) {
        for (int i = 0; i < 8; i++) mbar_init(BAR(B_FULL0 + i), 1);
        for (int i = 0; i < 4; i++) mbar_init(BAR(B_EMPTY0 + i), 12);
        mbar_init(BAR(B_FULLC), 1);
        mbar_init(BAR(B_AFREE), 4);
        for (int i = 0; i < 8; i++) { mbar_init(BAR(B_AFULL + i), 1); mbar_init(BAR(B_AEMPTY + i), 8); }
        for (int i = 0; i < 4; i++) { mbar_init(BAR(B_XFULL + i), 1); mbar_init(BAR(B_XEMPTY + i), 8); }
        asm volatile("fence.mbarrier_init.release.cluster;" ::: "memory");
    }
    for (int i = tid; i < 256; i += NTHREADS) {
        float v = cospif((float)i * (1.f / 256.f));
        if (i == 128) v = 0.f;
        __nv_bfloat16 h = __float2bfloat16(v);
        ((__nv_bfloat16*)(sm + SM_TAB))[i] = h;
        ((__nv_bfloat16*)(sm + SM_TAB))[i + 256] = __hneg(h);
    }
    unsigned tgt[4];
#pragma unroll
    for (int i = 0; i < 4; i++) tgt[i] = ((ld_acquire(&g_bar[i]) >> 7) + 1u) << 7;
    const unsigned ptgt0 = ld_acquire(&g_pcnt[b]) + 7u, ptgt1 = ld_acquire(&g_pcnt[128 + b]) + 7u;
    const unsigned tag = tgt[0] >> 7;
    __syncthreads();

    if (wg == 3) {
        if (lane == 0) {
            for (int kb = 0; kb < 8; kb++) {
                int s = kb < 6 ? kb : kb - 4;
                uint32_t dst = s < 2 ? sb + SM_A + 65536 + s * 24576 : sb + SM_X + (s - 2) * 24576;
                if (kb >= 6) mbar_wait(BAR(B_EMPTY0 + s), 0);
                uint32_t fb = BAR(B_FULL0 + kb);
                mbar_expect(fb, 24576);
                tma_5d(dst, &tm_x, kb * 64, 0, 0, 0, c, fb);
                tma_2d(dst + 16384, &tm_bre, kb * 64, 32 * c, fb);
                tma_2d(dst + 20480, &tm_bim, kb * 64, 32 * c, fb);
                if (kb == 5) {
                    mbar_wait(BAR(B_EMPTY0 + 0), 0);
                    mbar_wait(BAR(B_EMPTY0 + 1), 0);
                    mbar_expect(BAR(B_FULLC), 65536);
                    for (int k2 = 0; k2 < 8; k2++)
                        tma_2d(sb + SM_A + 65536 + k2 * 8192, (c & 1) ? &tm_cim : &tm_cre, 64 * (c >> 1), k2 * 64, BAR(B_FULLC));
                }
            }
            if (p.stop <= 1) mbar_wait(BAR(B_FULLC), 0);
            if (p.stop > 1) {
                for (int layer = 0; layer < 2; layer++) {
                    if (layer == 1 && p.stop <= 3) break;
                    if (layer == 0) {
                        mbar_wait(BAR(B_AFREE), 0);
                        wait_count(&g_bar[0], tgt[0]);
                        fence_async();
                    }
                    for (int s = 0; s < 8; s++) {
                        int nf = (s < 4 ? 3 : 2) * layer;
                        if (nf > 0) mbar_wait(BAR(B_AEMPTY + s), (nf - 1) & 1);
                        mbar_expect(BAR(B_AFULL + s), 16384);
                        bulk_g2s(sb + SM_A + s * 16384, g_A1 + (size_t)(r * 8 + s) * 16384, 16384, BAR(B_AFULL + s));
                    }
                    if (p.stop <= 2 + 2 * layer) {
                        for (int s = 0; s < 8; s++) mbar_wait(BAR(B_AFULL + s), ((s < 4 ? 3 : 2) * layer) & 1);
                        break;
                    }
                    wait_count(&g_bar[1 + 2 * layer], tgt[1 + 2 * layer]);
                    fence_async();
                    const uint8_t* xsrc = (layer == 0 ? g_XA : g_XB) + (size_t)c * 8 * 16384;
                    auto load_x = [&](int i) {
                        int st = i & 3, f = layer * 4 + (i >> 2);
                        if (f > 0) mbar_wait(BAR(B_XEMPTY + st), (f - 1) & 1);
                        mbar_expect(BAR(B_XFULL + st), 16384);
                        bulk_g2s(sb + SM_X + st * 16384, xsrc + (size_t)(i & 7) * 16384, 16384, BAR(B_XFULL + st));
                    };
                    auto load_c = [&](int s, int nf, int ord) {
                        int tile = (r + 1 + ord) & 7;
                        mbar_wait(BAR(B_AEMPTY + s), (nf - 1) & 1);
                        mbar_expect(BAR(B_AFULL + s), 16384);
                        if (layer == 0) {
                            bulk_g2s(sb + SM_A + s * 16384, g_A2 + (size_t)(r * 8 + tile) * 16384, 16384, BAR(B_AFULL + s));
                        } else {
                            tma_2d(sb + SM_A + s * 16384, &tm_cre, 64 * r, 64 * tile, BAR(B_AFULL + s));
                            tma_2d(sb + SM_A + s * 16384 + 8192, &tm_cim, 64 * r, 64 * tile, BAR(B_AFULL + s));
                        }
                    };
                    for (int i = 0; i < 4; i++) load_x(i);
                    for (int i = 4; i < 8; i++) {
                        load_x(i);
                        int s = i - 4, nf = 3 * layer + 1;
                        mbar_wait(BAR(B_AEMPTY + s), (nf - 1) & 1);
                        mbar_expect(BAR(B_AFULL + s), 16384);
                        bulk_g2s(sb + SM_A + s * 16384, g_E + (size_t)((layer * 8 + r) * 8 + 2 * s) * 8192, 16384, BAR(B_AFULL + s));
                    }
                    for (int i = 8; i < 12; i++) {
                        load_x(i);
                        load_c(i - 4, 2 * layer + 1, i - 8);
                    }
                    for (int i = 12; i < 16; i++) load_x(i);
                    for (int s = 0; s < 4; s++) load_c(s, 3 * layer + 2, 4 + s);
                }
            }
        }
        return;
    }

    uint32_t wf[16];
    if (wg < 2) {
        const int k1 = 32 * wg + 8 * w + g;
#pragma unroll
        for (int col = 0; col < 2; col++) {
            int slot = 2 * b + col;
            int wc = slot == 0 ? 256 : slot;
#pragma unroll
            for (int i = 0; i < 4; i++) {
#pragma unroll
                for (int e = 0; e < 2; e++) {
                    int k = k1 + 64 * (8 * i + 2 * q + e);
                    uint32_t a = __ldg((const unsigned short*)p.w_r + k * 257 + wc);
                    uint32_t bb = __ldg((const unsigned short*)p.w_i + k * 257 + wc);
                    wf[col * 8 + 2 * i + e] = a | (bb << 16);
                }
            }
        }
    }
    {
        const unsigned short* tab = (const unsigned short*)(sm + SM_TAB);
        for (int ch = tid; ch < 4096; ch += 384) {
            int c8 = ch & 7, m = (ch >> 3) & 63, kb = ch >> 9;
            int f, ph;
            dft_fp(64 * r + m, f, ph);
            int d0 = kb * 64 + c8 * 8;
            uint32_t v[4];
#pragma unroll
            for (int e = 0; e < 4; e++) {
                uint32_t lo = tab[((d0 + 2 * e) * f + ph) & 511], hi = tab[((d0 + 2 * e + 1) * f + ph) & 511];
                v[e] = lo | (hi << 16);
            }
            sts128(sb + SM_A + kb * 8192 + m * 128 + ((c8 ^ (m & 7)) << 4), make_uint4(v[0], v[1], v[2], v[3]));
        }
    }
    if (wg == 2) {
#pragma unroll
        for (int rr = 0; rr < 4; rr++) {
            int t = 16 * r + 4 * w + rr;
            const uint4* src = (const uint4*)(p.x0 + (size_t)(128 * c + t) * 512);
            uint4 a = __ldg(src + lane), bq = __ldg(src + 32 + lane);
            float v[16];
            uint32_t u[8] = {a.x, a.y, a.z, a.w, bq.x, bq.y, bq.z, bq.w};
            float s = 0.f;
#pragma unroll
            for (int i = 0; i < 8; i++) { v[2 * i] = bf_lo(u[i]); v[2 * i + 1] = bf_hi(u[i]); s += v[2 * i] + v[2 * i + 1]; }
#pragma unroll
            for (int o = 16; o; o >>= 1) s += __shfl_xor_sync(~0u, s, o);
            float m = s * (1.f / 512.f), ss = 0.f;
#pragma unroll
            for (int i = 0; i < 16; i++) { float d = v[i] - m; ss += d * d; }
#pragma unroll
            for (int o = 16; o; o >>= 1) ss += __shfl_xor_sync(~0u, ss, o);
            if (lane == 0) {
                int pos = 8 * ((t >> 1) & 15) + 2 * (t >> 5) + (t & 1);
                g_rstd0[128 * c + pos] = rsqrtf(ss * (1.f / 512.f) + 1e-5f);
            }
        }
        {
            int j = 64 * r + 4 * c + w, f, ph;
            dft_fp(j, f, ph);
            float s = 0.f;
#pragma unroll 4
            for (int i = 0; i < 16; i++) {
                int d = lane + 32 * i;
                s += ldbf(p.dskip + d) * cospif((float)((d * f + ph) & 511) * (1.f / 256.f));
            }
#pragma unroll
            for (int o = 16; o; o >>= 1) s += __shfl_xor_sync(~0u, s, o);
            if (lane == 0) g_Dh[j] = s;
        }
    }
    fence_async_smem();
    bar_sync(2, 384);
    {
        float acc[32];
        for (int kb = 0; kb < 8; kb++) {
            int s = kb < 6 ? kb : kb - 4;
            uint32_t src = (s < 2 ? sb + SM_A + 65536 + s * 24576 : sb + SM_X + (s - 2) * 24576) + wg * 8192;
            mbar_wait(BAR(B_FULL0 + kb), 0);
            wg_fence();
#pragma unroll
            for (int ks = 0; ks < 4; ks++)
                wgmma_n64<0>(acc, desc_k(sb + SM_A + kb * 8192 + ks * 32), desc_k(src + ks * 32), (kb | ks) != 0);
            wg_commit();
            if (kb > 0 && kb <= 4) {
                wg_wait<1>();
                if (lane == 0) mbar_arrive(BAR(B_EMPTY0 + kb - 1), 1);
            }
        }
        wg_wait<0>();
        if (wg < 2) {
            uint8_t* dst = g_XA + (size_t)(c * 8 + r) * 16384 + wg * 8192;
#pragma unroll
            for (int i = 0; i < 8; i++) {
                int k = 16 * w + g;
                *(uint32_t*)(dst + k * 128 + ((i ^ g) << 4) + 4 * q) = pack_bf16(acc[4 * i], acc[4 * i + 1]);
                *(uint32_t*)(dst + (k + 8) * 128 + ((i ^ g) << 4) + 4 * q) = pack_bf16(acc[4 * i + 2], acc[4 * i + 3]);
            }
            uint4* wd = g_Wfrag + (size_t)b * 1024 + tid;
#pragma unroll
            for (int i = 0; i < 4; i++) wd[i * 256] = make_uint4(wf[4 * i], wf[4 * i + 1], wf[4 * i + 2], wf[4 * i + 3]);
        } else {
            uint8_t* dst = g_A1 + (size_t)((c >> 1) * 8 + r) * 16384 + (c & 1) * 8192;
#pragma unroll
            for (int i = 0; i < 4; i++) {
#pragma unroll
                for (int e = 0; e < 2; e++) {
                    int ps = 32 * c + 8 * i + 2 * q + e;
                    float lr = ldbf(p.lam_re + ps), li = ldbf(p.lam_im + ps);
                    float dt = __bfloat162float(__float2bfloat16(expf(ldbf(p.log_dt + ps))));
                    float er, ei;
                    cexp_scaled(lr * dt, li * dt, 1.f, er, ei);
                    er -= 1.f;
                    float inv = 1.f / (lr * lr + li * li);
                    float cr = (er * lr + ei * li) * inv, ci = (ei * lr - er * li) * inv;
#pragma unroll
                    for (int h = 0; h < 2; h++) {
                        int k = 16 * w + g + 8 * h, j = 64 * r + k;
                        float wj = j == 0 ? 0.f : (j == 1 ? 1.f / 512.f : 2.f / 512.f);
                        float pr = acc[4 * i + 2 * h + e] * wj, pi = acc[16 + 4 * i + 2 * h + e] * wj;
                        int row = 16 * i + 2 * q + e;
                        *(__nv_bfloat16*)(dst + row * 128 + (((k >> 3) ^ (row & 7)) << 4) + (k & 7) * 2) = __float2bfloat16(cr * pr - ci * pi);
                        row += 8;
                        *(__nv_bfloat16*)(dst + row * 128 + (((k >> 3) ^ (row & 7)) << 4) + (k & 7) * 2) = __float2bfloat16(cr * pi + ci * pr);
                    }
                }
            }
        }
        fence_async();
        bar_sync(2, 384);
        if (tid == 0) red_release(&g_bar[0], 1);
    }
    if (p.stop <= 1) return;

    if (wg == 2) {
        float acc[32];
        mbar_wait(BAR(B_FULLC), 0);
        wg_fence();
#pragma unroll 1
        for (int kb = 0; kb < 8; kb++) {
#pragma unroll
            for (int ks = 0; ks < 4; ks++)
                wgmma_n64<1>(acc, desc_k(sb + SM_A + kb * 8192 + ks * 32), desc_mn(sb + SM_A + 65536 + kb * 8192 + ks * 2048, 8192), (kb | ks) != 0);
        }
        wg_commit();
        wg_wait<0>();
        fence_async_smem();
        if (lane == 0) mbar_arrive(BAR(B_AFREE), 1);
        uint8_t* dst = g_A2 + (size_t)((c >> 1) * 8 + r) * 16384 + (c & 1) * 8192;
#pragma unroll
        for (int i = 0; i < 8; i++) {
            int m = 16 * w + g;
            *(uint32_t*)(dst + m * 128 + ((i ^ g) << 4) + 4 * q) = pack_bf16(acc[4 * i], acc[4 * i + 1]);
            *(uint32_t*)(dst + (m + 8) * 128 + ((i ^ g) << 4) + 4 * q) = pack_bf16(acc[4 * i + 2], acc[4 * i + 3]);
        }
        if (tid == 256) wait_count(&g_bar[0], tgt[0]);
        bar_sync(3, 128);
        {
            int t2 = tid - 256;
            int m = 4 * c + (t2 >> 5);
            int jp = 64 * r + m;
            int fp, php;
            dft_fp(jp, fp, php);
#pragma unroll 1
            for (int it = 0; it < 2; it++) {
                int ch = (t2 & 31) + 32 * it;
                uint32_t v0[4], v1[4];
#pragma unroll
                for (int e = 0; e < 4; e++) {
                    float a0[2], a1[2];
#pragma unroll
                    for (int h = 0; h < 2; h++) {
                        int j = ch * 8 + 2 * e + h, f, ph;
                        dft_fp(j, f, ph);
                        float wj = j == 0 ? 0.f : (j == 1 ? 1.f / 512.f : 2.f / 512.f);
                        float gsum = 0.f;
#pragma unroll
                        for (int sgn = 0; sgn < 2; sgn++) {
                            int mm = sgn ? f - fp : f + fp, pp = sgn ? ph - php : ph + php;
                            mm &= 511; pp &= 511;
                            if (mm > 256) { mm = 512 - mm; pp = (512 - pp) & 511; }
                            float cc = mm == 256 ? __ldcg(g_Dh + 1) : __ldcg(g_Dh + 2 * mm);
                            float sn = (mm == 0 || mm == 256) ? 0.f : __ldcg(g_Dh + 2 * mm + 1);
                            gsum += pp == 0 ? cc : (pp == 128 ? sn : (pp == 256 ? -cc : -sn));
                        }
                        a0[h] = 0.5f * wj * gsum;
                        a1[h] = wj * cospif((float)((jp * f + ph) & 511) * (1.f / 256.f));
                    }
                    v0[e] = pack_bf16(a0[0], a0[1]);
                    v1[e] = pack_bf16(a1[0], a1[1]);
                }
                size_t off = (size_t)(r * 8 + (ch >> 3)) * 8192 + m * 128 + (((ch & 7) ^ (m & 7)) << 4);
                *(uint4*)(g_E + off) = make_uint4(v0[0], v0[1], v0[2], v0[3]);
                *(uint4*)(g_E + 8 * 8 * 8192 + off) = make_uint4(v1[0], v1[1], v1[2], v1[3]);
            }
        }
    } else {
        gen_col_consts(sm, tid, 256);
        if (tid == 0) wait_count(&g_bar[0], tgt[0]);
        bar_sync(1, 256);
        col_phase(sm, b, tid, g_XA, 0, wf);
    }

    float lr1 = 0.f, li1 = 0.f, lr32 = 0.f, li32 = 0.f, lr128 = 0.f, li128 = 0.f;
    if (wg < 2) {
        int ps = 64 * r + 32 * wg + 8 * w + g;
        float lr = ldbf(p.lam_re + ps), li = ldbf(p.lam_im + ps);
        float dt = __bfloat162float(__float2bfloat16(expf(ldbf(p.log_dt + ps))));
        cexp_scaled(lr * dt, li * dt, 1.f, lr1, li1);
        cexp_scaled(lr * dt, li * dt, 32.f, lr32, li32);
        cexp_scaled(lr * dt, li * dt, 128.f, lr128, li128);
    }

#pragma unroll 1
    for (int layer = 0; layer < 2; layer++) {
        fence_async();
        bar_sync(2, 384);
        if (tid == 0) red_release(&g_bar[1 + 2 * layer], 1);
        if (p.stop <= 2 + 2 * layer) return;

        float acc[64];
        float* s_rstd = (float*)(sm + SM_RSTD);
        float* s_mean = (float*)(sm + SM_MEAN);
        const uint8_t* ximg = layer == 0 ? g_XA : g_XB;
        if (wg < 2) {
            for (int kb = 0; kb < 8; kb++) {
                int nfa = (kb < 4 ? 3 : 2) * layer;
                mbar_wait(BAR(B_AFULL + kb), nfa & 1);
                mbar_wait(BAR(B_XFULL + (kb & 3)), (layer * 4 + (kb >> 2)) & 1);
                wg_fence();
#pragma unroll
                for (int ks = 0; ks < 4; ks++)
                    wgmma_n128<1>(acc, desc_k(sb + SM_A + kb * 16384 + wg * 8192 + ks * 32),
                                  desc_mn(sb + SM_X + (kb & 3) * 16384 + ks * 2048, 8192), (kb | ks) != 0);
                wg_commit();
                if (kb > 0) {
                    wg_wait<1>();
                    if (lane == 0) { mbar_arrive(BAR(B_AEMPTY + kb - 1), 1); mbar_arrive(BAR(B_XEMPTY + ((kb - 1) & 3)), 1); }
                }
            }
            wg_wait<0>();
            if (lane == 0) { mbar_arrive(BAR(B_AEMPTY + 7), 1); mbar_arrive(BAR(B_XEMPTY + 3), 1); }
            bar_sync(4, 384);
            float er = 0.f, ei = 0.f;
#pragma unroll
            for (int i = 0; i < 16; i++) {
                float2 rs = *(const float2*)(s_rstd + 8 * i + 2 * q);
                acc[4 * i] *= rs.x; acc[4 * i + 1] *= rs.y; acc[4 * i + 2] *= rs.x; acc[4 * i + 3] *= rs.y;
                float nr = lr1 * er - li1 * ei + acc[4 * i], ni = lr1 * ei + li1 * er + acc[4 * i + 2];
                er = lr1 * nr - li1 * ni + acc[4 * i + 1];
                ei = lr1 * ni + li1 * nr + acc[4 * i + 3];
            }
            float cr = 0.f, ci = 0.f, tr = 0.f, ti = 0.f;
#pragma unroll
            for (int qq = 0; qq < 4; qq++) {
                float xr_ = __shfl_sync(~0u, er, (lane & ~3) | qq), xi_ = __shfl_sync(~0u, ei, (lane & ~3) | qq);
                if (qq == q) { cr = tr; ci = ti; }
                float nr = lr32 * tr - li32 * ti + xr_, ni = lr32 * ti + li32 * tr + xi_;
                tr = nr; ti = ni;
            }
            const int ps = 64 * r + 32 * wg + 8 * w + g;
            float4* eb = g_Ebuf + (size_t)layer * 16 * 512;
            if (q == 0 && c < 15) st_relaxed_f4(eb + c * 512 + ps, make_float4(tr, ti, __uint_as_float(tag), 0.f));
            float pr[4], pi[4];
#pragma unroll
            for (int k = 0; k < 4; k++) {
                int cc = 4 * k + q;
                pr[k] = 0.f; pi[k] = 0.f;
                if (cc < c) {
                    unsigned n = 0;
                    float4 v = ld_relaxed_f4(eb + cc * 512 + ps);
                    while (__float_as_uint(v.z) != tag) {
                        if (++n > SPIN_LIMIT) { g_err = 3; break; }
                        v = ld_relaxed_f4(eb + cc * 512 + ps);
                    }
                    pr[k] = v.x; pi[k] = v.y;
                }
            }
            __syncwarp();
            float hr = 0.f, hi = 0.f;
#pragma unroll
            for (int cc = 0; cc < 15; cc++) {
                float xr_ = __shfl_sync(~0u, pr[cc >> 2], (lane & ~3) | (cc & 3)), xi_ = __shfl_sync(~0u, pi[cc >> 2], (lane & ~3) | (cc & 3));
                if (cc < c) {
                    float nr = lr128 * hr - li128 * hi + xr_, ni = lr128 * hi + li128 * hr + xi_;
                    hr = nr; hi = ni;
                }
            }
#pragma unroll
            for (int qq = 0; qq < 3; qq++) {
                if (qq < q) { float nr = lr32 * hr - li32 * hi, ni = lr32 * hi + li32 * hr; hr = nr; hi = ni; }
            }
            er = cr + hr; ei = ci + hi;
            const int prow = 32 * wg + 8 * w + g;
#pragma unroll
            for (int i = 0; i < 16; i++) {
                float nr = lr1 * er - li1 * ei + acc[4 * i], ni = lr1 * ei + li1 * er + acc[4 * i + 2];
                er = lr1 * nr - li1 * ni + acc[4 * i + 1];
                ei = lr1 * ni + li1 * nr + acc[4 * i + 3];
                uint32_t a = sb + SM_H + (i >> 3) * 16384 + (((i & 7) ^ g) << 4) + 4 * q;
                sts32(a + prow * 128, pack_bf16(2.f * nr, 2.f * er));
                sts32(a + (64 + prow) * 128, pack_bf16(-2.f * ni, -2.f * ei));
            }
            fence_async_smem();
            bar_sync(6, 384);
#pragma unroll 1
            for (int ord = wg; ord < 7; ord += 2) {
                int s = ord < 4 ? 4 + ord : ord - 4;
                int nf = ord < 4 ? 2 * layer + 1 : 3 * layer + 2;
                mbar_wait(BAR(B_AFULL + s), nf & 1);
                wg_fence();
#pragma unroll
                for (int ks = 0; ks < 8; ks++)
                    wgmma_n128<1>(acc, desc_k(sb + SM_A + s * 16384 + (ks >> 2) * 8192 + (ks & 3) * 32),
                                  desc_mn(sb + SM_H + ks * 2048, 16384), ks != 0);
                wg_commit();
                wg_wait<0>();
                if (lane == 0) mbar_arrive(BAR(B_AEMPTY + s), 2);
                int owner = (r + 1 + ord) & 7;
                uint4* dst = g_P + (size_t)((c * 8 + owner) * 8 + r) * 1024 + (tid & 127);
#pragma unroll
                for (int i = 0; i < 8; i++)
                    dst[i * 128] = make_uint4(pack_bf16(acc[8 * i], acc[8 * i + 1]), pack_bf16(acc[8 * i + 2], acc[8 * i + 3]),
                                              pack_bf16(acc[8 * i + 4], acc[8 * i + 5]), pack_bf16(acc[8 * i + 6], acc[8 * i + 7]));
                bar_sync(7 + wg, 128);
                if ((tid & 127) == 0) { __threadfence(); red_release(&g_pcnt[layer * 128 + c * 8 + owner], 1); }
            }
            if (layer == 0) {
                bar_sync(9, 384);
                gen_col_consts(sm, tid, 256);
                const uint4* ws = g_Wfrag + (size_t)b * 1024 + tid;
#pragma unroll
                for (int i = 0; i < 4; i++) {
                    uint4 v = __ldcg(ws + i * 256);
                    wf[4 * i] = v.x; wf[4 * i + 1] = v.y; wf[4 * i + 2] = v.z; wf[4 * i + 3] = v.w;
                }
            }
        } else {
            const int t2 = tid - 256;
            if (t2 == 0) wait_count(&g_bar[1 + 2 * layer], tgt[1 + 2 * layer]);
            bar_sync(3, 128);
            {
                float4 s4 = make_float4(0.f, 0.f, 0.f, 0.f);
                const float4* src = (const float4*)(g_part1 + (size_t)(32 * w) * 2048 + 128 * c) + lane;
#pragma unroll 1
                for (int h = 0; h < 2; h++) {
                    float4 v[16];
#pragma unroll
                    for (int i = 0; i < 16; i++) v[i] = __ldcg(src + (size_t)(16 * h + i) * 512);
#pragma unroll
                    for (int i = 0; i < 16; i++) { s4.x += v[i].x; s4.y += v[i].y; s4.z += v[i].z; s4.w += v[i].w; }
                }
                float4* red = (float4*)(sm + SM_H);
                red[w * 32 + lane] = s4;
                bar_sync(3, 128);
                const float* rf = (const float*)(sm + SM_H);
                float tot = rf[t2] + rf[128 + t2] + rf[256 + t2] + rf[384 + t2];
                s_rstd[t2] = rsqrtf(tot * (1.f / 512.f) + 1e-5f);
                if (layer == 1) {
                    unsigned short u = __ldcg((const unsigned short*)(ximg + (size_t)(c * 8) * 16384 + (t2 >> 6) * 8192 + (t2 & 63) * 2));
                    s_mean[t2] = __uint_as_float((uint32_t)u << 16) * (1.f / 512.f);
                }
            }
            bar_sync(4, 384);
            for (int kb = 0; kb < 8; kb++) {
                if ((kb & 1) == 0) mbar_wait(BAR(B_AFULL + (kb >> 1)), (3 * layer + 1) & 1);
                mbar_wait(BAR(B_XFULL + (kb & 3)), (layer * 4 + 2 + (kb >> 2)) & 1);
                wg_fence();
#pragma unroll
                for (int ks = 0; ks < 4; ks++)
                    wgmma_n128<1>(acc, desc_k(sb + SM_A + kb * 8192 + ks * 32), desc_mn(sb + SM_X + (kb & 3) * 16384 + ks * 2048, 8192), (kb | ks) != 0);
                wg_commit();
                if (kb > 0) {
                    wg_wait<1>();
                    if (lane == 0) {
                        mbar_arrive(BAR(B_XEMPTY + ((kb - 1) & 3)), 2);
                        if ((kb & 1) == 0) mbar_arrive(BAR(B_AEMPTY + ((kb - 1) >> 1)), 2);
                    }
                }
            }
            wg_wait<0>();
            if (lane == 0) { mbar_arrive(BAR(B_XEMPTY + 3), 2); mbar_arrive(BAR(B_AEMPTY + 3), 2); }
            const int m0 = 16 * w + g;
            if (layer == 0) {
                const uint8_t* xs = ximg + (size_t)(c * 8 + r) * 16384;
#pragma unroll
                for (int i = 0; i < 16; i++) {
                    float2 rs = *(const float2*)(s_rstd + 8 * i + 2 * q);
                    int off = (i >> 3) * 8192 + (((i & 7) ^ g) << 4) + 4 * q;
                    uint32_t x0v = __ldcg((const uint32_t*)(xs + off + m0 * 128)), x1v = __ldcg((const uint32_t*)(xs + off + (m0 + 8) * 128));
                    acc[4 * i] = acc[4 * i] * rs.x + bf_lo(x0v);
                    acc[4 * i + 1] = acc[4 * i + 1] * rs.y + bf_hi(x0v);
                    acc[4 * i + 2] = acc[4 * i + 2] * rs.x + bf_lo(x1v);
                    acc[4 * i + 3] = acc[4 * i + 3] * rs.y + bf_hi(x1v);
                }
            } else {
                float d0 = ldbf(p.dskip + 64 * r + m0), d1 = ldbf(p.dskip + 64 * r + m0 + 8);
#pragma unroll
                for (int i = 0; i < 16; i++) {
                    float2 rs = *(const float2*)(s_rstd + 8 * i + 2 * q);
                    float2 mn = *(const float2*)(s_mean + 8 * i + 2 * q);
                    acc[4 * i] = acc[4 * i] * (1.f + rs.x * d0) + mn.x;
                    acc[4 * i + 1] = acc[4 * i + 1] * (1.f + rs.y * d0) + mn.y;
                    acc[4 * i + 2] = acc[4 * i + 2] * (1.f + rs.x * d1) + mn.x;
                    acc[4 * i + 3] = acc[4 * i + 3] * (1.f + rs.y * d1) + mn.y;
                }
            }
            bar_sync(6, 384);
            mbar_wait(BAR(B_AFULL + 3), (3 * layer + 2) & 1);
            wg_fence();
#pragma unroll
            for (int ks = 0; ks < 8; ks++)
                wgmma_n128<1>(acc, desc_k(sb + SM_A + 3 * 16384 + (ks >> 2) * 8192 + (ks & 3) * 32), desc_mn(sb + SM_H + ks * 2048, 16384), 1);
            wg_commit();
            wg_wait<0>();
            if (lane == 0) mbar_arrive(BAR(B_AEMPTY + 3), 2);
            if (layer == 0) bar_arrive(9, 384);
            if (t2 == 0) wait_count(&g_pcnt[layer * 128 + b], layer == 0 ? ptgt0 : ptgt1);
            bar_sync(3, 128);
#pragma unroll 1
            for (int sidx = 1; sidx < 8; sidx++) {
                int src = (r + sidx) & 7;
                const uint4* ps_ = g_P + (size_t)((c * 8 + r) * 8 + src) * 1024 + t2;
                uint4 v[8];
#pragma unroll
                for (int i = 0; i < 8; i++) v[i] = __ldcg(ps_ + i * 128);
#pragma unroll
                for (int i = 0; i < 8; i++) {
                    acc[8 * i] += bf_lo(v[i].x); acc[8 * i + 1] += bf_hi(v[i].x);
                    acc[8 * i + 2] += bf_lo(v[i].y); acc[8 * i + 3] += bf_hi(v[i].y);
                    acc[8 * i + 4] += bf_lo(v[i].z); acc[8 * i + 5] += bf_hi(v[i].z);
                    acc[8 * i + 6] += bf_lo(v[i].w); acc[8 * i + 7] += bf_hi(v[i].w);
                }
            }
            if (layer == 0) {
                uint8_t* xd = g_XB + (size_t)(c * 8 + r) * 16384;
                float w0 = (r == 0 && m0 == 0) ? 0.f : ((r == 0 && m0 == 1) ? 1.f / 512.f : 2.f / 512.f);
                float* red = (float*)(sm + SM_M + 2432);
                (void)red;
#pragma unroll
                for (int i = 0; i < 16; i++) {
                    uint32_t v0 = pack_bf16(acc[4 * i], acc[4 * i + 1]), v1 = pack_bf16(acc[4 * i + 2], acc[4 * i + 3]);
                    int off = (i >> 3) * 8192 + (((i & 7) ^ g) << 4) + 4 * q;
                    *(uint32_t*)(xd + off + m0 * 128) = v0;
                    *(uint32_t*)(xd + off + (m0 + 8) * 128) = v1;
                    float s0 = w0 * bf_lo(v0) * bf_lo(v0) + (2.f / 512.f) * bf_lo(v1) * bf_lo(v1);
                    float s1 = w0 * bf_hi(v0) * bf_hi(v0) + (2.f / 512.f) * bf_hi(v1) * bf_hi(v1);
#pragma unroll
                    for (int o = 4; o < 32; o <<= 1) { s0 += __shfl_xor_sync(~0u, s0, o); s1 += __shfl_xor_sync(~0u, s1, o); }
                    acc[4 * i] = s0; acc[4 * i + 1] = s1;
                }
                float* rbuf = (float*)(sm + SM_RSTD);
                bar_sync(3, 128);
                if (w >= 2 && g == 0) {
#pragma unroll
                    for (int i = 0; i < 16; i++) *(float2*)(rbuf + (w - 2) * 128 + 8 * i + 2 * q) = make_float2(acc[4 * i], acc[4 * i + 1]);
                }
                bar_sync(3, 128);
                if (w < 2 && g == 0) {
#pragma unroll
                    for (int i = 0; i < 16; i++) {
                        float2 v = *(float2*)(rbuf + w * 128 + 8 * i + 2 * q);
                        acc[4 * i] += v.x; acc[4 * i + 1] += v.y;
                    }
                }
                bar_sync(3, 128);
                if (w == 1 && g == 0) {
#pragma unroll
                    for (int i = 0; i < 16; i++) *(float2*)(rbuf + 8 * i + 2 * q) = make_float2(acc[4 * i], acc[4 * i + 1]);
                }
                bar_sync(3, 128);
                if (w == 0 && g == 0) {
#pragma unroll
                    for (int i = 0; i < 16; i++) {
                        float2 v = *(float2*)(rbuf + 8 * i + 2 * q);
                        *(float2*)(g_part2 + r * 2048 + 128 * c + 8 * i + 2 * q) = make_float2(acc[4 * i] + v.x, acc[4 * i + 1] + v.y);
                    }
                }
            } else {
                float* o = p.out + (size_t)(128 * c + 32 * q) * 512 + 64 * r + m0;
#pragma unroll
                for (int i = 0; i < 16; i++) {
                    o[(2 * i) * 512] = acc[4 * i];
                    o[(2 * i + 1) * 512] = acc[4 * i + 1];
                    o[(2 * i) * 512 + 8] = acc[4 * i + 2];
                    o[(2 * i + 1) * 512 + 8] = acc[4 * i + 3];
                }
            }
        }
        if (layer == 1) break;
        fence_async();
        bar_sync(2, 384);
        if (tid == 0) red_release(&g_bar[2], 1);
        if (p.stop <= 3) return;
        if (wg < 2) {
            if (tid == 0) wait_count(&g_bar[2], tgt[2]);
            bar_sync(1, 256);
            col_phase(sm, b, tid, g_XB, 1, wf);
        }
    }
}

typedef CUresult (*EncFn)(CUtensorMap*, CUtensorMapDataType, cuuint32_t, void*, const cuuint64_t*, const cuuint64_t*,
                          const cuuint32_t*, const cuuint32_t*, CUtensorMapInterleave, CUtensorMapSwizzle,
                          CUtensorMapL2promotion, CUtensorMapFloatOOBfill);

void launch_impl(void* const* d_in, void* d_out, int stop) {
    static EncFn enc = nullptr;
    if (!enc) {
        void* fn = nullptr;
        cudaDriverEntryPointQueryResult qr;
        cudaGetDriverEntryPoint("cuTensorMapEncodeTiled", &fn, cudaEnableDefault, &qr);
        enc = (EncFn)fn;
        cudaFuncSetAttribute(fused_kernel, cudaFuncAttributeMaxDynamicSharedMemorySize, SM_TOTAL);
    }
    CUtensorMap tx, tbr, tbi, tcr, tci;
    {
        cuuint64_t gd[5] = {512, 2, 4, 16, 16};
        cuuint64_t gs[4] = {1024, 32 * 1024, 2 * 1024, 128 * 1024};
        cuuint32_t bx[5] = {64, 2, 4, 16, 1};
        cuuint32_t es[5] = {1, 1, 1, 1, 1};
        enc(&tx, CU_TENSOR_MAP_DATA_TYPE_BFLOAT16, 5, d_in[0], gd, gs, bx, es, CU_TENSOR_MAP_INTERLEAVE_NONE,
            CU_TENSOR_MAP_SWIZZLE_128B, CU_TENSOR_MAP_L2_PROMOTION_L2_128B, CU_TENSOR_MAP_FLOAT_OOB_FILL_NONE);
    }
    auto mk2 = [&](CUtensorMap* m, void* ptr, cuuint32_t rows) {
        cuuint64_t gd[2] = {512, 512};
        cuuint64_t gs[1] = {1024};
        cuuint32_t bx[2] = {64, rows};
        cuuint32_t es[2] = {1, 1};
        enc(m, CU_TENSOR_MAP_DATA_TYPE_BFLOAT16, 2, ptr, gd, gs, bx, es, CU_TENSOR_MAP_INTERLEAVE_NONE,
            CU_TENSOR_MAP_SWIZZLE_128B, CU_TENSOR_MAP_L2_PROMOTION_L2_128B, CU_TENSOR_MAP_FLOAT_OOB_FILL_NONE);
    };
    mk2(&tbr, d_in[6], 32);
    mk2(&tbi, d_in[7], 32);
    mk2(&tcr, d_in[8], 64);
    mk2(&tci, d_in[9], 64);
    Params p;
    p.x0 = (const __nv_bfloat16*)d_in[0];
    p.w_r = (const __nv_bfloat16*)d_in[1];
    p.w_i = (const __nv_bfloat16*)d_in[2];
    p.lam_re = (const __nv_bfloat16*)d_in[4];
    p.lam_im = (const __nv_bfloat16*)d_in[5];
    p.log_dt = (const __nv_bfloat16*)d_in[10];
    p.dskip = (const __nv_bfloat16*)d_in[11];
    p.out = (float*)d_out;
    p.stop = stop;
    fused_kernel<<<NCTA, NTHREADS, SM_TOTAL>>>(tx, tbr, tbi, tcr, tci, p);
}

}

extern "C" void kernel_launch(void* const* d_in, const int* in_sizes, int n_in, void* d_out, int out_size) {
    (void)in_sizes; (void)n_in; (void)out_size;
    launch_impl(d_in, d_out, 100);
}
```

```cpp
#include <cuda_runtime.h>
#include <cuda_bf16.h>
#include <cuda.h>
#include <stdint.h>

namespace {

constexpr int NCTA = 128;
constexpr int NTHREADS = 512;
constexpr int SM_A = 0;
constexpr int SM_X = 131072;
constexpr int SM_H = 196608;
constexpr int SM_M = 229376;
constexpr int SM_TOTAL = 232448;
constexpr int SM_BAR = SM_M;
constexpr int SM_TGT = SM_M + 384;
constexpr int SM_LAM = SM_M + 416;
constexpr int SM_TAB = SM_M + 928;
constexpr int SM_RSTD = SM_M + 1952;
constexpr int SM_MEAN = SM_TAB;
constexpr int B_FULL0 = 0;
constexpr int B_EMPTY0 = 8;
constexpr int B_FULLC = 12;
constexpr int B_AFULL = 13;
constexpr int B_AEMPTY = 21;
constexpr int B_XFULL = 29;
constexpr int B_XEMPTY = 33;
constexpr int B_AFREE = 37;
constexpr int B_PDONE = 38;
constexpr int NBARS = 45;

__device__ __align__(1024) uint8_t g_XA[16 * 8 * 16384];
__device__ __align__(1024) uint8_t g_XB[16 * 8 * 16384];
__device__ __align__(1024) uint8_t g_A1[8 * 8 * 16384];
__device__ __align__(1024) uint8_t g_A2[8 * 8 * 16384];
__device__ __align__(1024) uint8_t g_E[2 * 8 * 8 * 8192];
__device__ __align__(16) float g_rstd0[2048];
__device__ __align__(16) float g_part1[128 * 2048];
__device__ __align__(16) float g_part2[8 * 2048];
__device__ __align__(16) float g_Dh[512];
__device__ __align__(16) uint4 g_Wfrag[128 * 4 * 256];
__device__ __align__(16) float4 g_Ebuf[2 * 16 * 512];
__device__ __align__(16) uint4 g_P[16 * 8 * 8 * 1024];
__device__ unsigned g_bar[8];
__device__ unsigned g_pcnt[2 * 128];
__device__ unsigned g_err;
#define TS(i)
#define TC(i)

constexpr unsigned SPIN_LIMIT = 1u << 22;

__device__ __forceinline__ uint32_t s2u(const void* p) { return (uint32_t)__cvta_generic_to_shared(p); }
__device__ __forceinline__ void mbar_init(uint32_t a, uint32_t c) {
    asm volatile("mbarrier.init.shared::cta.b64 [%0], %1;" ::"r"(a), "r"(c) : "memory");
}
__device__ __forceinline__ void mbar_expect(uint32_t a, uint32_t bytes) {
    asm volatile("mbarrier.arrive.expect_tx.shared::cta.b64 _, [%0], %1;" ::"r"(a), "r"(bytes) : "memory");
}
__device__ __forceinline__ void mbar_arrive(uint32_t a, uint32_t cnt) {
    asm volatile("mbarrier.arrive.shared::cta.b64 _, [%0], %1;" ::"r"(a), "r"(cnt) : "memory");
}
__device__ __forceinline__ bool mbar_try(uint32_t a, uint32_t parity) {
    uint32_t ok;
    asm volatile("{\n.reg .pred p;\nmbarrier.try_wait.parity.shared::cta.b64 p, [%1], %2;\nselp.u32 %0, 1, 0, p;\n}"
                 : "=r"(ok) : "r"(a), "r"(parity) : "memory");
    return ok != 0;
}
__device__ __forceinline__ void mbar_wait(uint32_t a, uint32_t parity) {
    asm volatile("{\n.reg .pred p, q;\n.reg .u32 n;\nmov.u32 n, 0;\n"
                 "W_%=:\nmbarrier.try_wait.parity.shared::cta.b64 p, [%0], %1;\n@p bra D_%=;\n"
                 "add.u32 n, n, 1;\nsetp.lt.u32 q, n, 4194304;\n@q bra W_%=;\nD_%=:\n}" ::"r"(a), "r"(parity) : "memory");
}
__device__ __forceinline__ void bulk_g2s(uint32_t dst, const void* src, uint32_t bytes, uint32_t bar) {
    asm volatile("cp.async.bulk.shared::cluster.global.mbarrier::complete_tx::bytes [%0], [%1], %2, [%3];" ::"r"(dst),
                 "l"(src), "r"(bytes), "r"(bar) : "memory");
}
__device__ __forceinline__ void tma_2d(uint32_t dst, const CUtensorMap* m, int c0, int c1, uint32_t bar) {
    asm volatile("cp.async.bulk.tensor.2d.shared::cluster.global.mbarrier::complete_tx::bytes [%0], [%1, {%3,%4}], [%2];" ::"r"(dst),
                 "l"(m), "r"(bar), "r"(c0), "r"(c1) : "memory");
}
__device__ __forceinline__ void tma_5d(uint32_t dst, const CUtensorMap* m, int c0, int c1, int c2, int c3, int c4, uint32_t bar) {
    asm volatile("cp.async.bulk.tensor.5d.shared::cluster.global.mbarrier::complete_tx::bytes [%0], [%1, {%3,%4,%5,%6,%7}], [%2];" ::"r"(dst),
                 "l"(m), "r"(bar), "r"(c0), "r"(c1), "r"(c2), "r"(c3), "r"(c4) : "memory");
}
__device__ __forceinline__ void fence_async() { asm volatile("fence.proxy.async;" ::: "memory"); }
__device__ __forceinline__ void fence_async_smem() { asm volatile("fence.proxy.async.shared::cta;" ::: "memory"); }
__device__ __forceinline__ void wg_fence() { asm volatile("wgmma.fence.sync.aligned;" ::: "memory"); }
__device__ __forceinline__ void wg_commit() { asm volatile("wgmma.commit_group.sync.aligned;" ::: "memory"); }
template <int N> __device__ __forceinline__ void wg_wait() { asm volatile("wgmma.wait_group.sync.aligned %0;" ::"n"(N) : "memory"); }
__device__ __forceinline__ void bar_sync(int id, int n) { asm volatile("bar.sync %0, %1;" ::"r"(id), "r"(n) : "memory"); }
__device__ __forceinline__ void bar_arrive(int id, int n) { asm volatile("bar.arrive %0, %1;" ::"r"(id), "r"(n) : "memory"); }
__device__ __forceinline__ unsigned ld_acquire(const unsigned* p) {
    unsigned v;
    asm volatile("ld.acquire.gpu.global.u32 %0, [%1];" : "=r"(v) : "l"(p) : "memory");
    return v;
}
__device__ __forceinline__ void red_release(unsigned* p, unsigned v) {
    asm volatile("red.release.gpu.global.add.u32 [%0], %1;" ::"l"(p), "r"(v) : "memory");
}
__device__ __forceinline__ void wait_count(const unsigned* p, unsigned target) {
    unsigned n = 0;
#pragma unroll 1
    while ((int)(ld_acquire(p) - target) < 0 && ++n < SPIN_LIMIT) {}
}
__device__ __forceinline__ float4 ld_relaxed_f4(const float4* p) {
    float4 v;
    asm volatile("ld.relaxed.gpu.global.v4.f32 {%0,%1,%2,%3}, [%4];" : "=f"(v.x), "=f"(v.y), "=f"(v.z), "=f"(v.w) : "l"(p) : "memory");
    return v;
}
__device__ __forceinline__ void st_relaxed_f4(float4* p, float4 v) {
    asm volatile("st.relaxed.gpu.global.v4.f32 [%0], {%1,%2,%3,%4};" ::"l"(p), "f"(v.x), "f"(v.y), "f"(v.z), "f"(v.w) : "memory");
}
__device__ __forceinline__ uint32_t pack_bf16(float lo, float hi) {
    uint32_t r;
    asm("cvt.rn.bf16x2.f32 %0, %1, %2;" : "=r"(r) : "f"(hi), "f"(lo));
    return r;
}
__device__ __forceinline__ float bf_lo(uint32_t v) { return __uint_as_float(v << 16); }
__device__ __forceinline__ float bf_hi(uint32_t v) { return __uint_as_float(v & 0xffff0000u); }
__device__ __forceinline__ void sts32(uint32_t a, uint32_t v) { asm volatile("st.shared.u32 [%0], %1;" ::"r"(a), "r"(v) : "memory"); }
__device__ __forceinline__ void sts128(uint32_t a, uint4 v) {
    asm volatile("st.shared.v4.u32 [%0], {%1,%2,%3,%4};" ::"r"(a), "r"(v.x), "r"(v.y), "r"(v.z), "r"(v.w) : "memory");
}

__device__ __forceinline__ uint64_t desc_ni(uint32_t addr, uint32_t lbo, uint32_t sbo) {
    return (uint64_t)((addr & 0x3FFFF) >> 4) | ((uint64_t)(lbo >> 4) << 16) | ((uint64_t)(sbo >> 4) << 32);
}
__device__ __forceinline__ uint64_t desc_a(uint32_t addr) { return desc_ni(addr, 128, 1024); }
template <int N> __device__ __forceinline__ uint64_t desc_b(uint32_t addr) { return desc_ni(addr, 16 * N, 128); }
__device__ __forceinline__ uint64_t desc_k(uint32_t addr) {
    return (uint64_t)((addr & 0x3FFFF) >> 4) | (1ull << 16) | (64ull << 32) | (1ull << 62);
}
__device__ __forceinline__ uint64_t desc_mn(uint32_t addr, uint32_t lbo) {
    return (uint64_t)((addr & 0x3FFFF) >> 4) | ((uint64_t)(lbo >> 4) << 16) | (64ull << 32) | (1ull << 62);
}

#define ACC8(d, o) "+f"(d[o + 0]), "+f"(d[o + 1]), "+f"(d[o + 2]), "+f"(d[o + 3]), "+f"(d[o + 4]), "+f"(d[o + 5]), "+f"(d[o + 6]), "+f"(d[o + 7])
template <int TB, int SA = 1>
__device__ __forceinline__ void wgmma_n128(float (&d)[64], uint64_t da, uint64_t db, int sd) {
    asm volatile(
        "{\n.reg .pred p;\nsetp.ne.b32 p, %66, 0;\n"
        "wgmma.mma_async.sync.aligned.m64n128k16.f32.bf16.bf16 "
        "{%0,%1,%2,%3,%4,%5,%6,%7,%8,%9,%10,%11,%12,%13,%14,%15,%16,%17,%18,%19,%20,%21,%22,%23,%24,%25,%26,%27,%28,%29,%30,%31,"
        "%32,%33,%34,%35,%36,%37,%38,%39,%40,%41,%42,%43,%44,%45,%46,%47,%48,%49,%50,%51,%52,%53,%54,%55,%56,%57,%58,%59,%60,%61,%62,%63},"
        " %64, %65, p, %68, 1, 0, %67;\n}"
        : ACC8(d, 0), ACC8(d, 8), ACC8(d, 16), ACC8(d, 24), ACC8(d, 32), ACC8(d, 40), ACC8(d, 48), ACC8(d, 56)
        : "l"(da), "l"(db), "r"(sd), "n"(TB), "n"(SA));
}
template <int N> __device__ __forceinline__ void acc_def(float (&d)[N]) {
#pragma unroll
    for (int i = 0; i < N; i++) d[i] = 0.f;
}
template <int TB>
__device__ __forceinline__ void wgmma_n64(float (&d)[32], uint64_t da, uint64_t db, int sd) {
    asm volatile(
        "{\n.reg .pred p;\nsetp.ne.b32 p, %34, 0;\n"
        "wgmma.mma_async.sync.aligned.m64n64k16.f32.bf16.bf16 "
        "{%0,%1,%2,%3,%4,%5,%6,%7,%8,%9,%10,%11,%12,%13,%14,%15,%16,%17,%18,%19,%20,%21,%22,%23,%24,%25,%26,%27,%28,%29,%30,%31},"
        " %32, %33, p, 1, 1, 0, %35;\n}"
        : ACC8(d, 0), ACC8(d, 8), ACC8(d, 16), ACC8(d, 24)
        : "l"(da), "l"(db), "r"(sd), "n"(TB));
}
__device__ __forceinline__ void wgmma_n64_rs(float (&d)[32], uint32_t a0, uint32_t a1, uint32_t a2, uint32_t a3, uint64_t db, int sd) {
    asm volatile(
        "{\n.reg .pred p;\nsetp.ne.b32 p, %37, 0;\n"
        "wgmma.mma_async.sync.aligned.m64n64k16.f32.bf16.bf16 "
        "{%0,%1,%2,%3,%4,%5,%6,%7,%8,%9,%10,%11,%12,%13,%14,%15,%16,%17,%18,%19,%20,%21,%22,%23,%24,%25,%26,%27,%28,%29,%30,%31},"
        " {%32,%33,%34,%35}, %36, p, 1, 1, 1;\n}"
        : ACC8(d, 0), ACC8(d, 8), ACC8(d, 16), ACC8(d, 24)
        : "r"(a0), "r"(a1), "r"(a2), "r"(a3), "l"(db), "r"(sd));
}

struct Params {
    const __nv_bfloat16* x0;
    const __nv_bfloat16* w_r;
    const __nv_bfloat16* w_i;
    const __nv_bfloat16* lam_re;
    const __nv_bfloat16* lam_im;
    const __nv_bfloat16* log_dt;
    const __nv_bfloat16* dskip;
    float* out;
    int stop;
};

__device__ __forceinline__ float ldbf(const __nv_bfloat16* p) { return __bfloat162float(*p); }

__device__ __forceinline__ void dft_fp(int j, int& f, int& ph) {
    int cs = j >> 1;
    if (j == 1) { f = 256; ph = 0; }
    else { f = cs; ph = (j & 1) ? 128 : 0; }
}

__device__ __forceinline__ void gen_col_consts(uint8_t* sm, int tid) {
    const unsigned short* tab = (const unsigned short*)(sm + SM_TAB);
    const uint32_t sb = s2u(sm);
#pragma unroll 1
    for (int ch = tid; ch < 2560; ch += 256) {
        int c8 = (ch >> 3) & 7, m = (ch & 7) | ((ch >> 3) & 56), po, pi, step, base;
        if (ch < 2048) {
            pi = (ch >> 9) & 1; po = (m >> 3) & 1;
            step = 8 * (32 * (ch >> 10) + 8 * (m >> 4) + (m & 7));
            base = c8 * 8;
        } else {
            pi = m >> 5; po = c8 >> 2;
            step = 16 * (m & 31);
            base = (c8 & 3) * 8;
        }
        int idx = base * step + ((po == pi) ? 0 : (po == 0 ? 384 : 128));
        uint32_t v[4];
#pragma unroll
        for (int e = 0; e < 4; e++) {
            uint32_t lo = tab[idx & 511], hi = tab[(idx + step) & 511];
            idx += 2 * step;
            v[e] = lo | (hi << 16);
        }
        sts128(sb + SM_X + (ch >> 9) * 8192 + (m >> 3) * 1024 + c8 * 128 + (m & 7) * 16, make_uint4(v[0], v[1], v[2], v[3]));
    }
}

__device__ __forceinline__ void col_phase(uint8_t* sm, int b, int wg, int w, int g, int q, uint8_t* ximg, int layer) {
    const uint32_t sb = s2u(sm);
    const int n1 = 32 * wg + 8 * w + g;
    const int c = n1 >> 2;
    if (wg == 0) TC(0 + 10 * layer);
    uint32_t xr[4][4];
    const int kbase = 4 * (b & 15);
    uint8_t* xb = ximg + (uint32_t)((c * 8 + (b >> 4)) * 16384 + (kbase >> 3) * 2048 + (kbase & 7) * 16 + q * 128 + (g & 3) * 4);
#pragma unroll
    for (int jj = 0; jj < 4; jj++)
#pragma unroll
        for (int i = 0; i < 4; i++)
            xr[jj][i] = __ldcg((const uint32_t*)(xb + i * 512 + jj * 16));
    uint32_t wf[16];
    {
        const uint4* ws = g_Wfrag + (uint32_t)(b * 1024 + (n1 * 4 + q) * 4);
#pragma unroll
        for (int i = 0; i < 4; i++) {
            uint4 v = __ldcg(ws + i);
            wf[4 * i] = v.x; wf[4 * i + 1] = v.y; wf[4 * i + 2] = v.z; wf[4 * i + 3] = v.w;
        }
    }
    float rs[8];
    const int pos0 = 128 * c + 8 * q + 2 * (g & 3);
    if (layer == 0) {
#pragma unroll
        for (int i = 0; i < 4; i++) {
            float2 v = __ldcg((const float2*)(g_rstd0 + pos0 + 32 * i));
            rs[2 * i] = v.x; rs[2 * i + 1] = v.y;
        }
    } else {
#pragma unroll
        for (int i = 0; i < 8; i++) rs[i] = 0.f;
#pragma unroll 4
        for (int r = 0; r < 8; r++) {
#pragma unroll
            for (int i = 0; i < 4; i++) {
                float2 v = __ldcg((const float2*)(g_part2 + r * 2048 + pos0 + 32 * i));
                rs[2 * i] += v.x; rs[2 * i + 1] += v.y;
            }
        }
#pragma unroll
        for (int i = 0; i < 8; i++) rs[i] = rsqrtf(rs[i] * (1.f / 512.f) + 1e-5f);
    }
    float twr[8], twi[8];
#pragma unroll
    for (int i = 0; i < 8; i++) {
        int n2 = 8 * (i >> 1) + 2 * q + (i & 1);
        int a = (n1 * n2) & 2047;
        a = a >= 1024 ? a - 2048 : a;
        float ang = (float)a * (-6.283185307179586f / 2048.f);
        twr[i] = __cosf(ang); twi[i] = __sinf(ang);
    }
    const uint32_t st0 = sb + SM_H + (n1 >> 3) * 1024 + g * 16 + 4 * q;
    if (b == 0) {
#pragma unroll
        for (int i = 0; i < 4; i++) { uint32_t t = xr[0][i]; xr[0][i] = xr[1][i]; xr[1][i] = t; }
    }
#pragma unroll
    for (int jj = 0; jj < 4; jj++) {
#pragma unroll
        for (int i = 0; i < 4; i++) {
            uint32_t v = xr[jj][i];
            uint32_t o = pack_bf16(bf_lo(v) * rs[2 * i], bf_hi(v) * rs[2 * i + 1]);
            if (jj == 1 && b == 0) o = 0u;
            sts32(st0 + (jj & 1) * 8192 + (4 * (jj >> 1) + i) * 128, o);
        }
    }
    if (wg == 0) TC(1 + 10 * layer);
    fence_async_smem();
    bar_sync(1, 256);
    float acc[32];
    const uint32_t s1a = sb + SM_X + wg * 16384, s2b = sb + SM_X + 32768;
    wg_fence();
#pragma unroll
    for (int ks = 0; ks < 8; ks++)
        wgmma_n64<1>(acc, desc_a(s1a + (ks >> 2) * 8192 + (ks & 3) * 256), desc_b<64>(sb + SM_H + ks * 2048), ks != 0);
    wg_commit();
    wg_wait<0>();
    if (wg == 0) TC(2 + 10 * layer);
    uint32_t are[2][4], aim[2][4];
#pragma unroll
    for (int col = 0; col < 2; col++) {
#pragma unroll
        for (int i = 0; i < 4; i++) {
            int o = 4 * (4 * col + i);
            float r0 = acc[o] * twr[2 * i] - acc[o + 2] * twi[2 * i], i0 = acc[o] * twi[2 * i] + acc[o + 2] * twr[2 * i];
            float r1 = acc[o + 1] * twr[2 * i + 1] - acc[o + 3] * twi[2 * i + 1], i1 = acc[o + 1] * twi[2 * i + 1] + acc[o + 3] * twr[2 * i + 1];
            are[col][i] = pack_bf16(r0, r1);
            aim[col][i] = pack_bf16(i0, i1);
        }
    }
    wg_fence();
#pragma unroll
    for (int ks = 0; ks < 2; ks++)
        wgmma_n64_rs(acc, are[0][2 * ks], are[1][2 * ks], are[0][2 * ks + 1], are[1][2 * ks + 1], desc_b<64>(s2b + ks * 2048), ks != 0);
#pragma unroll
    for (int ks = 0; ks < 2; ks++)
        wgmma_n64_rs(acc, aim[0][2 * ks], aim[1][2 * ks], aim[0][2 * ks + 1], aim[1][2 * ks + 1], desc_b<64>(s2b + 4096 + ks * 2048), 1);
    wg_commit();
    wg_wait<0>();
    if (wg == 0) TC(3 + 10 * layer);
#pragma unroll
    for (int col = 0; col < 2; col++) {
#pragma unroll
        for (int i = 0; i < 4; i++) {
            float gr[2], gi[2];
#pragma unroll
            for (int e = 0; e < 2; e++) {
                uint32_t wv = wf[col * 8 + 2 * i + e];
                float wr = bf_lo(wv), wi = bf_hi(wv);
                float zr = acc[4 * i + 2 * col + e], zi = acc[16 + 4 * i + 2 * col + e];
                gr[e] = zr * wr - zi * wi;
                gi[e] = -(zr * wi + zi * wr);
            }
            are[col][i] = pack_bf16(gr[0], gr[1]);
            aim[col][i] = pack_bf16(gi[0], gi[1]);
        }
    }
    wg_fence();
#pragma unroll
    for (int ks = 0; ks < 2; ks++)
        wgmma_n64_rs(acc, are[0][2 * ks], are[1][2 * ks], are[0][2 * ks + 1], are[1][2 * ks + 1], desc_b<64>(s2b + ks * 2048), ks != 0);
#pragma unroll
    for (int ks = 0; ks < 2; ks++)
        wgmma_n64_rs(acc, aim[0][2 * ks], aim[1][2 * ks], aim[0][2 * ks + 1], aim[1][2 * ks + 1], desc_b<64>(s2b + 4096 + ks * 2048), 1);
    wg_commit();
    wg_wait<0>();
    if (wg == 0) TC(4 + 10 * layer);
#pragma unroll
    for (int col = 0; col < 2; col++) {
#pragma unroll
        for (int i = 0; i < 4; i++) {
            float r[2], im[2];
#pragma unroll
            for (int e = 0; e < 2; e++) {
                float zr = acc[4 * i + 2 * col + e], zi = acc[16 + 4 * i + 2 * col + e];
                r[e] = zr * twr[2 * i + e] - zi * twi[2 * i + e];
                im[e] = zr * twi[2 * i + e] + zi * twr[2 * i + e];
            }
            sts32(st0 + 16384 + (4 * col + i) * 128, pack_bf16(r[0], r[1]));
            sts32(st0 + 16384 + 8192 + (4 * col + i) * 128, pack_bf16(im[0], im[1]));
        }
    }
    if (wg == 0) TC(5 + 10 * layer);
    fence_async_smem();
    bar_sync(1, 256);
    wg_fence();
#pragma unroll
    for (int ks = 0; ks < 8; ks++)
        wgmma_n64<1>(acc, desc_a(s1a + (ks >> 2) * 8192 + (ks & 3) * 256), desc_b<64>(sb + SM_H + 16384 + ks * 2048), ks != 0);
    wg_commit();
    wg_wait<0>();
    if (wg == 0) TC(6 + 10 * layer);
    const float sc = 1.f / 2048.f;
    const float sci0 = b == 0 ? 0.f : -sc;
    const float wr0 = b == 0 ? 0.5f : 1.f, wi0 = b == 0 ? 0.f : 1.f;
    const int sw = b == 0 ? 1 : 0;
#pragma unroll
    for (int i = 0; i < 4; i++) {
        float ss0 = 0.f, ss1 = 0.f;
#pragma unroll
        for (int col = 0; col < 2; col++) {
            int o = 4 * (4 * col + i);
            uint32_t vr = xr[2 * col][i], vi = xr[2 * col + 1][i];
            float si = col == 0 ? sci0 : -sc;
            uint32_t nr = pack_bf16(fmaf(acc[o], sc, bf_lo(vr)), fmaf(acc[o + 1], sc, bf_hi(vr)));
            uint32_t ni = pack_bf16(fmaf(acc[o + 2], si, bf_lo(vi)), fmaf(acc[o + 3], si, bf_hi(vi)));
            float a0 = bf_lo(nr), a1 = bf_hi(nr), b0 = bf_lo(ni), b1 = bf_hi(ni);
            if (col == 0) {
                ss0 = wr0 * a0 * a0 + wi0 * b0 * b0;
                ss1 = wr0 * a1 * a1 + wi0 * b1 * b1;
            } else {
                ss0 += a0 * a0 + b0 * b0;
                ss1 += a1 * a1 + b1 * b1;
            }
            if (col == 0) {
                *(uint32_t*)(xb + i * 512) = sw ? ni : nr;
                *(uint32_t*)(xb + i * 512 + 16) = sw ? nr : ni;
            } else {
                *(uint32_t*)(xb + i * 512 + 32) = nr;
                *(uint32_t*)(xb + i * 512 + 48) = ni;
            }
        }
        *(float2*)(g_part1 + b * 2048 + pos0 + 32 * i) = make_float2(ss0 * (2.f / 512.f), ss1 * (2.f / 512.f));
    }
}

__global__ void __launch_bounds__(NTHREADS, 1)
fused_kernel(const __grid_constant__ CUtensorMap tm_x, const __grid_constant__ CUtensorMap tm_bre,
             const __grid_constant__ CUtensorMap tm_bim, const __grid_constant__ CUtensorMap tm_cre,
             const __grid_constant__ CUtensorMap tm_cim, const Params p) {
    extern __shared__ __align__(1024) uint8_t sm[];
    const uint32_t sb = s2u(sm);
    const int tid = threadIdx.x, b = blockIdx.x;
    const int c = b >> 3, r = b & 7;
    const int wg = __shfl_sync(~0u, tid >> 7, 0), w = __shfl_sync(~0u, (tid >> 5) & 3, 0), lane = tid & 31, g = lane >> 2, q = lane & 3;
    auto BAR = [&](int i) { return sb + SM_BAR + 8 * i; };
    unsigned* s_tgt = (unsigned*)(sm + SM_TGT);

    if (tid < NBARS) {
        int cnt = 1;
        if (tid >= B_EMPTY0 && tid < B_EMPTY0 + 4) cnt = 12;
        if ((tid >= B_AEMPTY && tid < B_AEMPTY + 8) || (tid >= B_XEMPTY && tid < B_XEMPTY + 4)) cnt = 8;
        if (tid >= B_AFREE) cnt = 4;
        mbar_init(BAR(tid), cnt);
        asm volatile("fence.mbarrier_init.release.cluster;" ::: "memory");
    } else if (tid >= 64 && tid < 70) {
        int i = tid - 64;
        unsigned v = ld_acquire(i < 4 ? &g_bar[i] : &g_pcnt[(i - 4) * 128 + b]);
        s_tgt[i] = i < 4 ? ((v >> 7) + 1u) << 7 : v + 7u;
    } else if (tid >= 128 && tid < 384) {
        int i = tid - 128;
        float v = cospif((float)i * (1.f / 256.f));
        __nv_bfloat16 h = __float2bfloat16(v);
        ((__nv_bfloat16*)(sm + SM_TAB))[i] = h;
        ((__nv_bfloat16*)(sm + SM_TAB))[i + 256] = __hneg(h);
    } else if (tid >= 384 && tid < 480) {
        int i = tid - 384;
        int ps = i < 64 ? 64 * r + i : 32 * c + i - 64;
        float lr = ldbf(p.lam_re + ps), li = ldbf(p.lam_im + ps);
        float dt = __bfloat162float(__float2bfloat16(expf(ldbf(p.log_dt + ps))));
        float mag = expf(lr * dt), t = li * dt * 0.15915494309189535f, sn, cs;
        t -= rintf(t);
        sincospif(2.f * t, &sn, &cs);
        float er = mag * cs, ei = mag * sn;
        if (i < 64) {
            *(float2*)(sm + SM_LAM + i * 8) = make_float2(er, ei);
        } else {
            er -= 1.f;
            float inv = 1.f / (lr * lr + li * li);
            *(float2*)(sm + SM_RSTD + (i - 64) * 8) = make_float2((er * lr + ei * li) * inv, (ei * lr - er * li) * inv);
        }
    }
    __syncthreads();

    if (wg == 3) {
        asm volatile("setmaxnreg.dec.sync.aligned.u32 56;");
        if (w > 0) {
#pragma unroll 1
            for (int task = tid - 416; task < 256; task += 96) {
                const int cb = task & 127, kq = 2 * b + (task >> 7), k1 = kq >> 2, qq = kq & 3;
                const unsigned short* wr_ = (const unsigned short*)p.w_r + (k1 + 128 * qq) * 257;
                const unsigned short* wi_ = (const unsigned short*)p.w_i + (k1 + 128 * qq) * 257;
                const int c0 = cb == 0 ? 256 : 2 * cb, c1 = 2 * cb + 1;
                uint32_t wf[16];
#pragma unroll
                for (int i = 0; i < 8; i++) {
                    int o = (512 * (i >> 1) + 64 * (i & 1)) * 257;
                    wf[i] = (uint32_t)__ldg(wr_ + o + c0) | ((uint32_t)__ldg(wi_ + o + c0) << 16);
                    wf[8 + i] = (uint32_t)__ldg(wr_ + o + c1) | ((uint32_t)__ldg(wi_ + o + c1) << 16);
                }
                uint4* wd = g_Wfrag + (uint32_t)(cb * 1024 + kq * 4);
#pragma unroll
                for (int i = 0; i < 4; i++) wd[i] = make_uint4(wf[4 * i], wf[4 * i + 1], wf[4 * i + 2], wf[4 * i + 3]);
            }
            __syncwarp();
            bar_sync(2, 480);
            if (tid == 416) { fence_async(); red_release(&g_bar[0], 1); }
            if (w == 3) return;
#pragma unroll 1
            for (int layer = 0; layer < 2; layer++) {
                __syncwarp();
                if (w == 1) {
                    bar_sync(5, 416);
                    if (lane == 0) { fence_async(); red_release(&g_bar[1 + 2 * layer], 1); }
                }
#pragma unroll 1
                for (int ord = w - 1; ord < 7; ord += 2) {
                    if (lane == 0) mbar_wait(BAR(B_PDONE + ord), layer);
                    if (lane == 0) red_release(&g_pcnt[layer * 128 + c * 8 + ((r + 1 + ord) & 7)], 1);
                }
            }
        } else if (tid == 384) {
#pragma unroll 1
            for (int kb = 0; kb < 8; kb++) {
                int s = kb < 6 ? kb : kb - 4;
                uint32_t dst = s < 2 ? sb + SM_A + 65536 + s * 24576 : sb + SM_X + (s - 2) * 24576;
                if (kb >= 6) mbar_wait(BAR(B_EMPTY0 + s), 0);
                uint32_t fb = BAR(B_FULL0 + kb);
                mbar_expect(fb, 24576);
                tma_5d(dst, &tm_x, kb * 64, 0, 0, 0, c, fb);
                tma_2d(dst + 16384, &tm_bre, kb * 64, 32 * c, fb);
                tma_2d(dst + 20480, &tm_bim, kb * 64, 32 * c, fb);
                if (kb == 5) {
                    mbar_wait(BAR(B_EMPTY0 + 0), 0);
                    mbar_wait(BAR(B_EMPTY0 + 1), 0);
                    mbar_expect(BAR(B_FULLC), 65536);
#pragma unroll 1
                    for (int k2 = 0; k2 < 8; k2++)
                        tma_2d(sb + SM_A + 65536 + k2 * 8192, (c & 1) ? &tm_cim : &tm_cre, 64 * (c >> 1), k2 * 64, BAR(B_FULLC));
                }
            }
            mbar_wait(BAR(B_AFREE), 0);
            wait_count(&g_bar[0], s_tgt[0]);
            fence_async();
#pragma unroll 1
            for (int layer = 0; layer < 2; layer++) {
                const uint8_t* xsrc = (layer == 0 ? g_XA : g_XB) + (uint32_t)c * 8 * 16384;
#pragma unroll 1
                for (int it = 0; it < 36; it++) {
                    int isx, idx;
                    if (it < 8) { isx = 0; idx = it; }
                    else if (it < 12) { isx = 1; idx = it - 8; }
                    else if (it < 28) { isx = !(it & 1); idx = isx ? 4 + ((it - 12) >> 1) : 8 + ((it - 12) >> 1); }
                    else if (it < 32) { isx = 1; idx = it - 16; }
                    else { isx = 0; idx = it - 16; }
                    if (it == 8) {
                        wait_count(&g_bar[1 + 2 * layer], s_tgt[1 + 2 * layer]);
                        fence_async();
                    }
                    if (isx) {
                        int st = idx & 3, f = layer * 4 + (idx >> 2);
                        if (f > 0) mbar_wait(BAR(B_XEMPTY + st), (f - 1) & 1);
                        mbar_expect(BAR(B_XFULL + st), 16384);
                        bulk_g2s(sb + SM_X + st * 16384, xsrc + (uint32_t)(idx & 7) * 16384, 16384, BAR(B_XFULL + st));
                    } else {
                        int s = idx & 7, nf = (s < 4 ? 3 : 2) * layer + (idx >> 3);
                        if (nf > 0) mbar_wait(BAR(B_AEMPTY + s), (nf - 1) & 1);
                        uint32_t fb = BAR(B_AFULL + s), dst = sb + SM_A + s * 16384;
                        mbar_expect(fb, 16384);
                        int tile = (r + 1 + idx - 12) & 7;
                        if (idx >= 12 && layer == 1) {
                            tma_2d(dst, &tm_cre, 64 * r, 64 * tile, fb);
                            tma_2d(dst + 8192, &tm_cim, 64 * r, 64 * tile, fb);
                        } else {
                            const uint8_t* src = idx < 8 ? g_A1 + (uint32_t)(r * 8 + s) * 16384
                                               : (idx < 12 ? g_E + (uint32_t)((layer * 8 + r) * 4 + s) * 16384 : g_A2 + (uint32_t)(r * 8 + tile) * 16384);
                            bulk_g2s(dst, src, 16384, fb);
                        }
                    }
                }
            }
        }
        return;
    }

    asm volatile("setmaxnreg.inc.sync.aligned.u32 152;");
    TS(0);
    if (wg == 0) TC(30);
    uint4 pre[4];
    if (wg < 2) {
        const uint4* src = (const uint4*)(p.x0 + (uint32_t)(128 * c + 16 * r + 8 * wg + 2 * w) * 512) + lane;
#pragma unroll
        for (int i = 0; i < 4; i++) pre[i] = __ldg(src + 32 * i);
    } else {
        pre[0] = __ldg((const uint4*)p.dskip + 2 * lane);
        pre[1] = __ldg((const uint4*)p.dskip + 2 * lane + 1);
    }
    {
        const unsigned short* tab = (const unsigned short*)(sm + SM_TAB);
#pragma unroll 1
        for (int ch = tid; ch < 4096; ch += 384) {
            int c8 = (ch >> 3) & 7, m = (ch & 7) | ((ch >> 3) & 56), kb = ch >> 9;
            int f, ph;
            dft_fp(64 * r + m, f, ph);
            int idx = (kb * 64 + c8 * 8) * f + ph;
            uint32_t v[4];
#pragma unroll
            for (int e = 0; e < 4; e++) {
                uint32_t lo = tab[idx & 511], hi = tab[(idx + f) & 511];
                idx += 2 * f;
                v[e] = lo | (hi << 16);
            }
            sts128(sb + SM_A + ch * 16, make_uint4(v[0], v[1], v[2], v[3]));
        }
    }
    fence_async_smem();
    if (wg < 2) {
#pragma unroll
        for (int rr = 0; rr < 2; rr++) {
            int t = 16 * r + 8 * wg + 2 * w + rr;
            uint32_t u[8] = {pre[2 * rr].x, pre[2 * rr].y, pre[2 * rr].z, pre[2 * rr].w, pre[2 * rr + 1].x, pre[2 * rr + 1].y, pre[2 * rr + 1].z, pre[2 * rr + 1].w};
            float s = 0.f;
#pragma unroll
            for (int i = 0; i < 8; i++) s += bf_lo(u[i]) + bf_hi(u[i]);
#pragma unroll
            for (int o = 16; o; o >>= 1) s += __shfl_xor_sync(~0u, s, o);
            float m = s * (1.f / 512.f), ss = 0.f;
#pragma unroll
            for (int i = 0; i < 8; i++) { float d0 = bf_lo(u[i]) - m, d1 = bf_hi(u[i]) - m; ss += d0 * d0 + d1 * d1; }
#pragma unroll
            for (int o = 16; o; o >>= 1) ss += __shfl_xor_sync(~0u, ss, o);
            if (lane == 0) g_rstd0[128 * c + 8 * ((t >> 1) & 15) + 2 * (t >> 5) + (t & 1)] = rsqrtf(ss * (1.f / 512.f) + 1e-5f);
        }
    } else {
        int j = 64 * r + 4 * c + w, f, ph;
        dft_fp(j, f, ph);
        uint32_t u[8] = {pre[0].x, pre[0].y, pre[0].z, pre[0].w, pre[1].x, pre[1].y, pre[1].z, pre[1].w};
        float s = 0.f;
        int idx = 16 * lane * f + ph;
#pragma unroll
        for (int i = 0; i < 16; i++) {
            int a = idx & 511;
            idx += f;
            a = a >= 256 ? a - 512 : a;
            s += ((i & 1) ? bf_hi(u[i >> 1]) : bf_lo(u[i >> 1])) * __cosf((float)a * (6.283185307179586f / 512.f));
        }
#pragma unroll
        for (int o = 16; o; o >>= 1) s += __shfl_xor_sync(~0u, s, o);
        if (lane == 0) g_Dh[j] = s;
    }
    bar_sync(10, 384);
    TS(1);
    {
        float acc[32];
        acc_def(acc);
#pragma unroll 1
        for (int kb = 0; kb < 8; kb++) {
            int s = kb < 6 ? kb : kb - 4;
            uint32_t src = (s < 2 ? sb + SM_A + 65536 + s * 24576 : sb + SM_X + (s - 2) * 24576) + wg * 8192;
            mbar_wait(BAR(B_FULL0 + kb), 0);
            wg_fence();
#pragma unroll
            for (int ks = 0; ks < 4; ks++)
                wgmma_n64<0>(acc, desc_a(sb + SM_A + kb * 8192 + ks * 256), desc_k(src + ks * 32), 1);
            wg_commit();
            wg_wait<1>();
            if (kb > 0 && kb <= 4 && lane == 0) mbar_arrive(BAR(B_EMPTY0 + kb - 1), 1);
        }
        wg_wait<0>();
        TS(2);
        if (wg < 2) {
            uint8_t* dst = g_XA + (uint32_t)((c * 8 + r) * 16384 + w * 4096 + wg * 1024 + g * 16 + 4 * q);
#pragma unroll
            for (int i = 0; i < 8; i++) {
                *(uint32_t*)(dst + i * 128) = pack_bf16(acc[4 * i], acc[4 * i + 1]);
                *(uint32_t*)(dst + 2048 + i * 128) = pack_bf16(acc[4 * i + 2], acc[4 * i + 3]);
            }
        } else {
            uint8_t* dst = g_A1 + (uint32_t)(((c >> 1) * 8 + r) * 16384 + (c & 1) * 8192 + w * 256 + q * 32 + g * 2);
            const float wj0 = (r == 0 && w == 0 && g < 2) ? (g == 0 ? 0.f : 1.f / 512.f) : 2.f / 512.f;
#pragma unroll
            for (int i = 0; i < 4; i++) {
#pragma unroll
                for (int e = 0; e < 2; e++) {
                    float2 cf = *(const float2*)(sm + SM_RSTD + (8 * i + 2 * q + e) * 8);
#pragma unroll
                    for (int h = 0; h < 2; h++) {
                        float wj = h == 0 ? wj0 : 2.f / 512.f;
                        float pr = acc[4 * i + 2 * h + e] * wj, pi = acc[16 + 4 * i + 2 * h + e] * wj;
                        uint8_t* d2 = dst + i * 2048 + h * 128 + e * 16;
                        *(__nv_bfloat16*)(d2) = __float2bfloat16(cf.x * pr - cf.y * pi);
                        *(__nv_bfloat16*)(d2 + 1024) = __float2bfloat16(cf.x * pi + cf.y * pr);
                    }
                }
            }
        }
        bar_sync(2, 480);
        TS(3);
    }

    if (wg == 2) {
        float acc[32];
        acc_def(acc);
        mbar_wait(BAR(B_FULLC), 0);
        wg_fence();
#pragma unroll 1
        for (int kb = 0; kb < 8; kb++) {
#pragma unroll
            for (int ks = 0; ks < 4; ks++)
                wgmma_n64<1>(acc, desc_a(sb + SM_A + kb * 8192 + ks * 256), desc_mn(sb + SM_A + 65536 + kb * 8192 + ks * 2048, 8192), 1);
            wg_commit();
        }
        wg_wait<0>();
        fence_async_smem();
        if (lane == 0) mbar_arrive(BAR(B_AFREE), 1);
        uint8_t* dst = g_A2 + (uint32_t)(((c >> 1) * 8 + r) * 16384 + (c & 1) * 8192 + w * 2048 + g * 16 + 4 * q);
#pragma unroll
        for (int i = 0; i < 8; i++) {
            *(uint32_t*)(dst + i * 128) = pack_bf16(acc[4 * i], acc[4 * i + 1]);
            *(uint32_t*)(dst + 1024 + i * 128) = pack_bf16(acc[4 * i + 2], acc[4 * i + 3]);
        }
        if (tid == 256) wait_count(&g_bar[0], s_tgt[0]);
        bar_sync(3, 128);
        float* s_dh = (float*)(sm + SM_X + 49152);
        ((float4*)s_dh)[tid - 256] = __ldcg((const float4*)g_Dh + (tid - 256));
        bar_sync(3, 128);
        const int m = 4 * c + w, jp = 64 * r + m;
        int fp, php;
        dft_fp(jp, fp, php);
#pragma unroll 1
        for (int it = 0; it < 16; it++) {
            int j = lane + 32 * it, f, ph;
            dft_fp(j, f, ph);
            float wj = j == 0 ? 0.f : (j == 1 ? 1.f / 512.f : 2.f / 512.f);
            float gsum = 0.f;
#pragma unroll
            for (int sgn = 0; sgn < 2; sgn++) {
                int mm = (sgn ? f - fp : f + fp) & 511, pp = (sgn ? ph - php : ph + php) & 511;
                if (mm > 256) { mm = 512 - mm; pp = (512 - pp) & 511; }
                int odd = (pp >> 7) & 1;
                float v = s_dh[mm == 256 ? 1 : 2 * mm + odd];
                if (odd && (mm & 255) == 0) v = 0.f;
                gsum += (pp & 256) ? -v : v;
            }
            uint32_t off = (uint32_t)(r * 8 + (j >> 6)) * 8192 + (m >> 3) * 1024 + ((j >> 3) & 7) * 128 + (m & 7) * 16 + (j & 7) * 2;
            *(__nv_bfloat16*)(g_E + off) = __float2bfloat16(0.5f * wj * gsum);
            *(__nv_bfloat16*)(g_E + 8 * 8 * 8192 + off) = __float2bfloat16(wj * __bfloat162float(((const __nv_bfloat16*)(sm + SM_TAB))[(jp * f + ph) & 511]));
        }
    }

#pragma unroll 1
    for (int layer = 0; layer < 2; layer++) {
        uint8_t* ximg = layer == 0 ? g_XA : g_XB;
        if (wg < 2) {
            gen_col_consts(sm, tid);
            if (tid == 0) wait_count(&g_bar[2 * layer], s_tgt[2 * layer]);
            bar_sync(1, 256);
            TS(4 + 12 * layer);
            col_phase(sm, b, wg, w, g, q, ximg, layer);
        }
        TS(5 + 12 * layer);
        if (wg == 0) TC(7 + 10 * layer);
        bar_arrive(5, 416);

        float acc[64];
        float* s_rstd = (float*)(sm + SM_RSTD);
        float* s_mean = (float*)(sm + SM_MEAN);
        if (wg < 2) {
            const int prow = 32 * wg + 8 * w + g;
            const float2 l1 = *(const float2*)(sm + SM_LAM + prow * 8);
            float lr32 = l1.x, li32 = l1.y;
#pragma unroll
            for (int i = 0; i < 5; i++) { float t = lr32 * lr32 - li32 * li32; li32 = 2.f * lr32 * li32; lr32 = t; }
            float lr128 = lr32, li128 = li32;
#pragma unroll
            for (int i = 0; i < 2; i++) { float t = lr128 * lr128 - li128 * li128; li128 = 2.f * lr128 * li128; lr128 = t; }
            const float lr1 = l1.x, li1 = l1.y;
            acc_def(acc);
#pragma unroll 1
            for (int kb = 0; kb < 8; kb++) {
                mbar_wait(BAR(B_AFULL + kb), ((kb < 4 ? 3 : 2) * layer) & 1);
                mbar_wait(BAR(B_XFULL + (kb & 3)), (kb >> 2) & 1);
                wg_fence();
#pragma unroll
                for (int ks = 0; ks < 4; ks++)
                    wgmma_n128<1>(acc, desc_a(sb + SM_A + kb * 16384 + wg * 8192 + ks * 256),
                                  desc_b<128>(sb + SM_X + (kb & 3) * 16384 + ks * 4096), 1);
                wg_commit();
                wg_wait<1>();
                if (kb > 0 && lane == 0) { mbar_arrive(BAR(B_AEMPTY + kb - 1), 1); mbar_arrive(BAR(B_XEMPTY + ((kb - 1) & 3)), 1); }
            }
            wg_wait<0>();
            if (lane == 0) { mbar_arrive(BAR(B_AEMPTY + 7), 1); mbar_arrive(BAR(B_XEMPTY + 3), 1); }
            TS(6 + 12 * layer);
            bar_sync(4, 384);
            float er = 0.f, ei = 0.f;
#pragma unroll
            for (int i = 0; i < 16; i++) {
                float2 rs = *(const float2*)(s_rstd + 128 + 8 * i + 2 * q);
                acc[4 * i] *= rs.x; acc[4 * i + 1] *= rs.y; acc[4 * i + 2] *= rs.x; acc[4 * i + 3] *= rs.y;
                float nr = lr1 * er - li1 * ei + acc[4 * i], ni = lr1 * ei + li1 * er + acc[4 * i + 2];
                er = lr1 * nr - li1 * ni + acc[4 * i + 1];
                ei = lr1 * ni + li1 * nr + acc[4 * i + 3];
            }
            float cr = 0.f, ci = 0.f, tr = 0.f, ti = 0.f;
#pragma unroll
            for (int qq = 0; qq < 4; qq++) {
                float xr_ = __shfl_sync(~0u, er, (lane & ~3) | qq), xi_ = __shfl_sync(~0u, ei, (lane & ~3) | qq);
                if (qq == q) { cr = tr; ci = ti; }
                float nr = lr32 * tr - li32 * ti + xr_, ni = lr32 * ti + li32 * tr + xi_;
                tr = nr; ti = ni;
            }
            const unsigned tag = s_tgt[0] >> 7;
            float4* eb = g_Ebuf + (uint32_t)(layer * 16 * 512 + 64 * r + prow);
            if (q == 0 && c < 15) st_relaxed_f4(eb + c * 512, make_float4(tr, ti, __uint_as_float(tag), 0.f));
            TS(8 + 12 * layer);
            float hr = 0.f, hi = 0.f;
#pragma unroll 1
            for (int k = 0; 4 * k < c; k++) {
                int cc = 4 * k + q;
                float4 v = make_float4(0.f, 0.f, 0.f, 0.f);
                if (cc < c) {
                    unsigned n = 0;
                    do { v = ld_relaxed_f4(eb + cc * 512); } while (__float_as_uint(v.z) != tag && ++n < SPIN_LIMIT);
                }
                __syncwarp();
#pragma unroll
                for (int qq = 0; qq < 4; qq++) {
                    float xr_ = __shfl_sync(~0u, v.x, (lane & ~3) | qq), xi_ = __shfl_sync(~0u, v.y, (lane & ~3) | qq);
                    if (4 * k + qq < c) {
                        float nr = lr128 * hr - li128 * hi + xr_, ni = lr128 * hi + li128 * hr + xi_;
                        hr = nr; hi = ni;
                    }
                }
            }
            TS(9 + 12 * layer);
#pragma unroll
            for (int qq = 0; qq < 3; qq++) {
                if (qq < q) { float nr = lr32 * hr - li32 * hi, ni = lr32 * hi + li32 * hr; hr = nr; hi = ni; }
            }
            er = cr + hr; ei = ci + hi;
            const uint32_t ha = sb + SM_H + (prow >> 3) * 2048 + g * 16 + 4 * q;
#pragma unroll
            for (int i = 0; i < 16; i++) {
                float nr = lr1 * er - li1 * ei + acc[4 * i], ni = lr1 * ei + li1 * er + acc[4 * i + 2];
                er = lr1 * nr - li1 * ni + acc[4 * i + 1];
                ei = lr1 * ni + li1 * nr + acc[4 * i + 3];
                sts32(ha + i * 128, pack_bf16(nr, er));
                sts32(ha + 16384 + i * 128, pack_bf16(ni, ei));
            }
            fence_async_smem();
            TS(10 + 12 * layer);
            bar_sync(6, 384);
#pragma unroll 1
            for (int ord = wg; ord < 7; ord += 2) {
                int s = (ord + 4) & 7;
                int nf = ord < 4 ? 2 * layer + 1 : 3 * layer + 2;
                mbar_wait(BAR(B_AFULL + s), nf & 1);
                wg_fence();
                {
                    const uint64_t da = layer == 0 ? desc_a(sb + SM_A + s * 16384) : desc_k(sb + SM_A + s * 16384);
                    const uint32_t kst = layer == 0 ? 16 : 2;
#pragma unroll
                    for (int ks = 0; ks < 4; ks++) wgmma_n128<1, 1>(acc, da + ks * kst, desc_b<128>(sb + SM_H + ks * 4096), ks != 0);
#pragma unroll
                    for (int ks = 0; ks < 4; ks++) wgmma_n128<1, -1>(acc, da + 512 + ks * kst, desc_b<128>(sb + SM_H + 16384 + ks * 4096), 1);
                }
                wg_commit();
                wg_wait<0>();
                if (lane == 0) mbar_arrive(BAR(B_AEMPTY + s), 2);
                int owner = (r + 1 + ord) & 7;
                uint4* dst = g_P + (uint32_t)(((c * 8 + owner) * 8 + r) * 1024 + (tid & 127));
#pragma unroll
                for (int i = 0; i < 8; i++)
                    dst[i * 128] = make_uint4(pack_bf16(acc[8 * i], acc[8 * i + 1]), pack_bf16(acc[8 * i + 2], acc[8 * i + 3]),
                                              pack_bf16(acc[8 * i + 4], acc[8 * i + 5]), pack_bf16(acc[8 * i + 6], acc[8 * i + 7]));
                __syncwarp();
                if (lane == 0) mbar_arrive(BAR(B_PDONE + ord), 1);
            }
            TS(12 + 12 * layer);
            if (layer == 0) {
                bar_sync(9, 384);
            }
        } else {
            const int t2 = tid - 256;
            if (t2 == 0) wait_count(&g_bar[1 + 2 * layer], s_tgt[1 + 2 * layer]);
            bar_sync(3, 128);
            TS(6 + 12 * layer);
            {
                float4 s4 = make_float4(0.f, 0.f, 0.f, 0.f);
                const float4* src = (const float4*)(g_part1 + (uint32_t)(32 * w * 2048 + 128 * c)) + lane;
#pragma unroll 1
                for (int h = 0; h < 2; h++) {
                    float4 v[16];
#pragma unroll
                    for (int i = 0; i < 16; i++) v[i] = __ldcg(src + (uint32_t)(16 * h + i) * 512);
#pragma unroll
                    for (int i = 0; i < 16; i++) { s4.x += v[i].x; s4.y += v[i].y; s4.z += v[i].z; s4.w += v[i].w; }
                }
                float4* red = (float4*)(sm + SM_H);
                red[w * 32 + lane] = s4;
                unsigned short u = __ldcg((const unsigned short*)(ximg + (uint32_t)(c * 8 * 16384 + (t2 >> 3) * 128 + (t2 & 7) * 2)));
                if (layer == 1) s_mean[t2] = __uint_as_float((uint32_t)u << 16) * (1.f / 512.f);
                bar_sync(3, 128);
                const float* rf = (const float*)(sm + SM_H);
                float tot = rf[t2] + rf[128 + t2] + rf[256 + t2] + rf[384 + t2];
                tot = rsqrtf(tot * (1.f / 512.f) + 1e-5f);
                s_rstd[t2] = tot;
                s_rstd[128 + t2] = 2.f * tot;
            }
            TS(7 + 12 * layer);
            bar_sync(4, 384);
            acc_def(acc);
#pragma unroll 1
            for (int kb = 0; kb < 8; kb++) {
                mbar_wait(BAR(B_AFULL + (kb >> 1)), (3 * layer + 1) & 1);
                mbar_wait(BAR(B_XFULL + (kb & 3)), (kb >> 2) & 1);
                wg_fence();
#pragma unroll
                for (int ks = 0; ks < 4; ks++)
                    wgmma_n128<1>(acc, desc_a(sb + SM_A + kb * 8192 + ks * 256), desc_b<128>(sb + SM_X + (kb & 3) * 16384 + ks * 4096), 1);
                wg_commit();
                wg_wait<1>();
                if (kb > 0 && lane == 0) {
                    mbar_arrive(BAR(B_XEMPTY + ((kb - 1) & 3)), 2);
                    if ((kb & 1) == 0) mbar_arrive(BAR(B_AEMPTY + ((kb - 1) >> 1)), 2);
                }
            }
            wg_wait<0>();
            if (lane == 0) { mbar_arrive(BAR(B_XEMPTY + 3), 2); mbar_arrive(BAR(B_AEMPTY + 3), 2); }
            TS(9 + 12 * layer);
            const int m0 = 16 * w + g;
            const uint32_t xoff = (uint32_t)((c * 8 + r) * 16384 + w * 4096 + g * 16 + 4 * q);
            if (layer == 0) {
                const uint8_t* xs = g_XA + xoff;
#pragma unroll
                for (int i = 0; i < 16; i++) {
                    float2 rs = *(const float2*)(s_rstd + 8 * i + 2 * q);
                    uint32_t x0v = __ldcg((const uint32_t*)(xs + i * 128)), x1v = __ldcg((const uint32_t*)(xs + 2048 + i * 128));
                    acc[4 * i] = acc[4 * i] * rs.x + bf_lo(x0v);
                    acc[4 * i + 1] = acc[4 * i + 1] * rs.y + bf_hi(x0v);
                    acc[4 * i + 2] = acc[4 * i + 2] * rs.x + bf_lo(x1v);
                    acc[4 * i + 3] = acc[4 * i + 3] * rs.y + bf_hi(x1v);
                }
            } else {
                float d0 = ldbf(p.dskip + 64 * r + m0), d1 = ldbf(p.dskip + 64 * r + m0 + 8);
#pragma unroll
                for (int i = 0; i < 16; i++) {
                    float2 rs = *(const float2*)(s_rstd + 8 * i + 2 * q);
                    float2 mn = *(const float2*)(s_mean + 8 * i + 2 * q);
                    acc[4 * i] = acc[4 * i] * (1.f + rs.x * d0) + mn.x;
                    acc[4 * i + 1] = acc[4 * i + 1] * (1.f + rs.y * d0) + mn.y;
                    acc[4 * i + 2] = acc[4 * i + 2] * (1.f + rs.x * d1) + mn.x;
                    acc[4 * i + 3] = acc[4 * i + 3] * (1.f + rs.y * d1) + mn.y;
                }
            }
            TS(10 + 12 * layer);
            bar_sync(6, 384);
            mbar_wait(BAR(B_AFULL + 3), (3 * layer + 2) & 1);
            wg_fence();
            {
                const uint64_t da = layer == 0 ? desc_a(sb + SM_A + 3 * 16384) : desc_k(sb + SM_A + 3 * 16384);
                const uint32_t kst = layer == 0 ? 16 : 2;
#pragma unroll
                for (int ks = 0; ks < 4; ks++) wgmma_n128<1, 1>(acc, da + ks * kst, desc_b<128>(sb + SM_H + ks * 4096), 1);
#pragma unroll
                for (int ks = 0; ks < 4; ks++) wgmma_n128<1, -1>(acc, da + 512 + ks * kst, desc_b<128>(sb + SM_H + 16384 + ks * 4096), 1);
            }
            wg_commit();
            wg_wait<0>();
            if (lane == 0) mbar_arrive(BAR(B_AEMPTY + 3), 2);
            if (layer == 0) bar_arrive(9, 384);
            TS(12 + 12 * layer);
            if (t2 == 0) wait_count(&g_pcnt[layer * 128 + b], s_tgt[4 + layer]);
            bar_sync(3, 128);
            TS(13 + 12 * layer);
            {
                const uint4* pb = g_P + (uint32_t)((c * 8 + r) * 8 * 1024 + t2);
                uint4 v[8], nx[8];
#pragma unroll
                for (int i = 0; i < 8; i++) v[i] = __ldcg(pb + ((r + 1) & 7) * 1024 + i * 128);
#pragma unroll 1
                for (int sidx = 2; sidx < 9; sidx++) {
                    if (sidx < 8) {
#pragma unroll
                        for (int i = 0; i < 8; i++) nx[i] = __ldcg(pb + ((r + sidx) & 7) * 1024 + i * 128);
                    }
#pragma unroll
                    for (int i = 0; i < 8; i++) {
                        acc[8 * i] += bf_lo(v[i].x); acc[8 * i + 1] += bf_hi(v[i].x);
                        acc[8 * i + 2] += bf_lo(v[i].y); acc[8 * i + 3] += bf_hi(v[i].y);
                        acc[8 * i + 4] += bf_lo(v[i].z); acc[8 * i + 5] += bf_hi(v[i].z);
                        acc[8 * i + 6] += bf_lo(v[i].w); acc[8 * i + 7] += bf_hi(v[i].w);
                        v[i] = nx[i];
                    }
                }
            }
            TS(14 + 12 * layer);
            if (layer == 0) {
                uint8_t* xd = g_XB + xoff;
                const float w0 = (r == 0 && m0 < 2) ? (m0 == 0 ? 0.f : 0.5f) : 1.f;
                float* sq = (float*)(sm + SM_X + 49152);
#pragma unroll
                for (int i = 0; i < 16; i++) {
                    uint32_t v0 = pack_bf16(acc[4 * i], acc[4 * i + 1]), v1 = pack_bf16(acc[4 * i + 2], acc[4 * i + 3]);
                    *(uint32_t*)(xd + i * 128) = v0;
                    *(uint32_t*)(xd + 2048 + i * 128) = v1;
                    float s0 = w0 * bf_lo(v0) * bf_lo(v0) + bf_lo(v1) * bf_lo(v1);
                    float s1 = w0 * bf_hi(v0) * bf_hi(v0) + bf_hi(v1) * bf_hi(v1);
                    *(float2*)(sq + (8 * w + g) * 128 + ((8 * i + 2 * q + 8 * g) & 127)) = make_float2(s0, s1);
                }
                bar_sync(3, 128);
                float tot = 0.f;
#pragma unroll 8
                for (int k = 0; k < 32; k++) tot += sq[k * 128 + ((t2 + 8 * (k & 7)) & 127)];
                g_part2[r * 2048 + 128 * c + t2] = tot * (2.f / 512.f);
            } else {
                float* o = p.out + (uint32_t)((128 * c + 32 * q) * 512 + 64 * r + m0);
#pragma unroll
                for (int i = 0; i < 16; i++) {
                    o[(2 * i) * 512] = acc[4 * i];
                    o[(2 * i + 1) * 512] = acc[4 * i + 1];
                    o[(2 * i) * 512 + 8] = acc[4 * i + 2];
                    o[(2 * i + 1) * 512 + 8] = acc[4 * i + 3];
                }
            }
            if (layer == 0) {
                bar_sync(3, 128);
                if (t2 == 0) { fence_async(); red_release(&g_bar[2], 1); }
            }
        }
        TS(15 + 12 * layer);
        if (wg == 0) TC(31);
    }
}

typedef CUresult (*EncFn)(CUtensorMap*, CUtensorMapDataType, cuuint32_t, void*, const cuuint64_t*, const cuuint64_t*,
                          const cuuint32_t*, const cuuint32_t*, CUtensorMapInterleave, CUtensorMapSwizzle,
                          CUtensorMapL2promotion, CUtensorMapFloatOOBfill);

void launch_impl(void* const* d_in, void* d_out, int stop) {
    static EncFn enc = nullptr;
    if (!enc) {
        void* fn = nullptr;
        cudaDriverEntryPointQueryResult qr;
        cudaGetDriverEntryPoint("cuTensorMapEncodeTiled", &fn, cudaEnableDefault, &qr);
        enc = (EncFn)fn;
        cudaFuncSetAttribute(fused_kernel, cudaFuncAttributeMaxDynamicSharedMemorySize, SM_TOTAL);
    }
    CUtensorMap tx, tbr, tbi, tcr, tci;
    {
        cuuint64_t gd[5] = {512, 2, 4, 16, 16};
        cuuint64_t gs[4] = {1024, 32 * 1024, 2 * 1024, 128 * 1024};
        cuuint32_t bx[5] = {64, 2, 4, 16, 1};
        cuuint32_t es[5] = {1, 1, 1, 1, 1};
        enc(&tx, CU_TENSOR_MAP_DATA_TYPE_BFLOAT16, 5, d_in[0], gd, gs, bx, es, CU_TENSOR_MAP_INTERLEAVE_NONE,
            CU_TENSOR_MAP_SWIZZLE_128B, CU_TENSOR_MAP_L2_PROMOTION_L2_128B, CU_TENSOR_MAP_FLOAT_OOB_FILL_NONE);
    }
    auto mk2 = [&](CUtensorMap* m, void* ptr, cuuint32_t rows) {
        cuuint64_t gd[2] = {512, 512};
        cuuint64_t gs[1] = {1024};
        cuuint32_t bx[2] = {64, rows};
        cuuint32_t es[2] = {1, 1};
        enc(m, CU_TENSOR_MAP_DATA_TYPE_BFLOAT16, 2, ptr, gd, gs, bx, es, CU_TENSOR_MAP_INTERLEAVE_NONE,
            CU_TENSOR_MAP_SWIZZLE_128B, CU_TENSOR_MAP_L2_PROMOTION_L2_128B, CU_TENSOR_MAP_FLOAT_OOB_FILL_NONE);
    };
    mk2(&tbr, d_in[6], 32);
    mk2(&tbi, d_in[7], 32);
    mk2(&tcr, d_in[8], 64);
    mk2(&tci, d_in[9], 64);
    Params p;
    p.x0 = (const __nv_bfloat16*)d_in[0];
    p.w_r = (const __nv_bfloat16*)d_in[1];
    p.w_i = (const __nv_bfloat16*)d_in[2];
    p.lam_re = (const __nv_bfloat16*)d_in[4];
    p.lam_im = (const __nv_bfloat16*)d_in[5];
    p.log_dt = (const __nv_bfloat16*)d_in[10];
    p.dskip = (const __nv_bfloat16*)d_in[11];
    p.out = (float*)d_out;
    p.stop = stop;
    fused_kernel<<<NCTA, NTHREADS, SM_TOTAL>>>(tx, tbr, tbi, tcr, tci, p);
}

}

extern "C" void kernel_launch(void* const* d_in, const int* in_sizes, int n_in, void* d_out, int out_size) {
    (void)in_sizes; (void)n_in; (void)out_size;
    launch_impl(d_in, d_out, 100);
}
```

```cpp
#include <cuda_runtime.h>
#include <cuda_bf16.h>
#include <cuda.h>
#include <stdint.h>

namespace {

constexpr int NCTA = 128;
constexpr int NTHREADS = 512;
constexpr int SM_A = 0;
constexpr int SM_X = 131072;
constexpr int SM_H = 196608;
constexpr int SM_HH = SM_X + 32768;
constexpr int SM_M = 229376;
constexpr int SM_TOTAL = 232448;
constexpr int SM_BAR = SM_M;
constexpr int SM_TGT = SM_M + 352;
constexpr int SM_LAM = SM_M + 368;
constexpr int SM_TAB = SM_M + 880;
constexpr int SM_RSTD = SM_M + 1904;
constexpr int SM_MEAN = SM_TAB;
constexpr int SM_T64 = SM_M + 2928;
constexpr int SM_RAW = SM_X + 40960;
constexpr int SM_SSQ = SM_X + 57344;
constexpr int B_FULL0 = 0;
constexpr int B_EMPTY0 = 8;
constexpr int B_FULLC = 12;
constexpr int B_AFULL = 13;
constexpr int B_AEMPTY = 21;
constexpr int B_XFULL = 29;
constexpr int B_XEMPTY = 33;
constexpr int B_AFREE = 37;
constexpr int B_COL = 38;
constexpr int B_SSQ = 39;
constexpr int B_HPEER = 40;
constexpr int B_RFREE = 41;
constexpr int B_HDONE = 42;
constexpr int NBARS = 43;

__device__ __align__(1024) uint8_t g_X[2 * 16 * 8 * 16384];
__device__ __align__(1024) uint8_t g_A1[8 * 8 * 16384];
__device__ __align__(1024) uint8_t g_A2[8 * 8 * 16384];
__device__ __align__(1024) uint8_t g_E[2 * 8 * 8 * 8192];
__device__ __align__(16) float g_ssq[4 * 2048];
__device__ __align__(16) float g_Dh[512];
__device__ __align__(16) uint4 g_Wfrag[128 * 4 * 256];
__device__ __align__(16) float4 g_Ebuf[2 * 16 * 512];
__device__ __align__(16) uint4 g_P[16 * 8 * 4 * 1024];
__device__ unsigned g_bar[8];
__device__ unsigned g_err;
#define TS(i)
#define TC(i)

constexpr unsigned SPIN_LIMIT = 1u << 22;

__device__ __forceinline__ uint32_t s2u(const void* p) { return (uint32_t)__cvta_generic_to_shared(p); }
__device__ __forceinline__ void mbar_init(uint32_t a, uint32_t c) {
    asm volatile("mbarrier.init.shared::cta.b64 [%0], %1;" ::"r"(a), "r"(c) : "memory");
}
__device__ __forceinline__ void mbar_expect(uint32_t a, uint32_t bytes) {
    asm volatile("mbarrier.arrive.expect_tx.shared::cta.b64 _, [%0], %1;" ::"r"(a), "r"(bytes) : "memory");
}
__device__ __forceinline__ void mbar_arrive(uint32_t a, uint32_t cnt) {
    asm volatile("mbarrier.arrive.shared::cta.b64 _, [%0], %1;" ::"r"(a), "r"(cnt) : "memory");
}
__device__ __forceinline__ bool mbar_try(uint32_t a, uint32_t parity) {
    uint32_t ok;
    asm volatile("{\n.reg .pred p;\nmbarrier.try_wait.parity.shared::cta.b64 p, [%1], %2;\nselp.u32 %0, 1, 0, p;\n}"
                 : "=r"(ok) : "r"(a), "r"(parity) : "memory");
    return ok != 0;
}
__device__ __forceinline__ void mbar_wait(uint32_t a, uint32_t parity) {
    asm volatile("{\n.reg .pred p, q;\n.reg .u32 n;\nmov.u32 n, 0;\n"
                 "W_%=:\nmbarrier.try_wait.parity.shared::cta.b64 p, [%0], %1;\n@p bra D_%=;\n"
                 "add.u32 n, n, 1;\nsetp.lt.u32 q, n, 4194304;\n@q bra W_%=;\nD_%=:\n}" ::"r"(a), "r"(parity) : "memory");
}
__device__ __forceinline__ void bulk_g2s(uint32_t dst, const void* src, uint32_t bytes, uint32_t bar) {
    asm volatile("cp.async.bulk.shared::cluster.global.mbarrier::complete_tx::bytes [%0], [%1], %2, [%3];" ::"r"(dst),
                 "l"(src), "r"(bytes), "r"(bar) : "memory");
}
__device__ __forceinline__ void tma_2d(uint32_t dst, const CUtensorMap* m, int c0, int c1, uint32_t bar) {
    asm volatile("cp.async.bulk.tensor.2d.shared::cluster.global.mbarrier::complete_tx::bytes [%0], [%1, {%3,%4}], [%2];" ::"r"(dst),
                 "l"(m), "r"(bar), "r"(c0), "r"(c1) : "memory");
}
__device__ __forceinline__ void tma_5d(uint32_t dst, const CUtensorMap* m, int c0, int c1, int c2, int c3, int c4, uint32_t bar) {
    asm volatile("cp.async.bulk.tensor.5d.shared::cluster.global.mbarrier::complete_tx::bytes [%0], [%1, {%3,%4,%5,%6,%7}], [%2];" ::"r"(dst),
                 "l"(m), "r"(bar), "r"(c0), "r"(c1), "r"(c2), "r"(c3), "r"(c4) : "memory");
}
__device__ __forceinline__ void tma_store_5d(const CUtensorMap* m, int c0, int c1, int c2, int c3, int c4, uint32_t src) {
    asm volatile("cp.async.bulk.tensor.5d.global.shared::cta.bulk_group [%0, {%2,%3,%4,%5,%6}], [%1];" ::"l"(m), "r"(src),
                 "r"(c0), "r"(c1), "r"(c2), "r"(c3), "r"(c4) : "memory");
}
__device__ __forceinline__ uint32_t lds32(uint32_t a) { uint32_t v; asm volatile("ld.shared.u32 %0, [%1];" : "=r"(v) : "r"(a) : "memory"); return v; }
__device__ __forceinline__ uint4 ld_relaxed_u4(const uint4* p) {
    uint4 v;
    asm volatile("ld.relaxed.gpu.global.v4.u32 {%0,%1,%2,%3}, [%4];" : "=r"(v.x), "=r"(v.y), "=r"(v.z), "=r"(v.w) : "l"(p) : "memory");
    return v;
}
__device__ __forceinline__ void fence_async() { asm volatile("fence.proxy.async.global;" ::: "memory"); }
__device__ __forceinline__ void red_relaxed(unsigned* p, unsigned v) {
    asm volatile("red.relaxed.gpu.global.add.u32 [%0], %1;" ::"l"(p), "r"(v) : "memory");
}
__device__ __forceinline__ uint32_t mapa(uint32_t a, uint32_t rank) {
    uint32_t d;
    asm("mapa.shared::cluster.u32 %0, %1, %2;" : "=r"(d) : "r"(a), "r"(rank));
    return d;
}
__device__ __forceinline__ void mbar_arrive_remote(uint32_t ra) {
    asm volatile("mbarrier.arrive.release.cluster.shared::cluster.b64 _, [%0];" ::"r"(ra) : "memory");
}
__device__ __forceinline__ void mbar_wait_cluster(uint32_t a, uint32_t parity) {
    asm volatile("{\n.reg .pred p, q;\n.reg .u32 n;\nmov.u32 n, 0;\n"
                 "W_%=:\nmbarrier.try_wait.parity.acquire.cluster.shared::cta.b64 p, [%0], %1;\n@p bra D_%=;\n"
                 "add.u32 n, n, 1;\nsetp.lt.u32 q, n, 4194304;\n@q bra W_%=;\nD_%=:\n}" ::"r"(a), "r"(parity) : "memory");
}
__device__ __forceinline__ void bulk_s2peer(uint32_t rdst, uint32_t src, uint32_t bytes, uint32_t rbar) {
    asm volatile("cp.async.bulk.shared::cluster.shared::cta.mbarrier::complete_tx::bytes [%0], [%1], %2, [%3];" ::"r"(rdst),
                 "r"(src), "r"(bytes), "r"(rbar) : "memory");
}
__device__ __forceinline__ void fence_async_smem() { asm volatile("fence.proxy.async.shared::cta;" ::: "memory"); }
__device__ __forceinline__ void wg_fence() { asm volatile("wgmma.fence.sync.aligned;" ::: "memory"); }
__device__ __forceinline__ void wg_commit() { asm volatile("wgmma.commit_group.sync.aligned;" ::: "memory"); }
template <int N> __device__ __forceinline__ void wg_wait() { asm volatile("wgmma.wait_group.sync.aligned %0;" ::"n"(N) : "memory"); }
__device__ __forceinline__ void bar_sync(int id, int n) { asm volatile("bar.sync %0, %1;" ::"r"(id), "r"(n) : "memory"); }
__device__ __forceinline__ void bar_arrive(int id, int n) { asm volatile("bar.arrive %0, %1;" ::"r"(id), "r"(n) : "memory"); }
__device__ __forceinline__ unsigned ld_acquire(const unsigned* p) {
    unsigned v;
    asm volatile("ld.acquire.gpu.global.u32 %0, [%1];" : "=r"(v) : "l"(p) : "memory");
    return v;
}
__device__ __forceinline__ void red_release(unsigned* p, unsigned v) {
    asm volatile("red.release.gpu.global.add.u32 [%0], %1;" ::"l"(p), "r"(v) : "memory");
}
__device__ __forceinline__ void wait_count(const unsigned* p, unsigned target) {
    unsigned n = 0;
#pragma unroll 1
    while ((int)(ld_acquire(p) - target) < 0 && ++n < SPIN_LIMIT) {}
}
__device__ __forceinline__ float4 ld_relaxed_f4(const float4* p) {
    float4 v;
    asm volatile("ld.relaxed.gpu.global.v4.f32 {%0,%1,%2,%3}, [%4];" : "=f"(v.x), "=f"(v.y), "=f"(v.z), "=f"(v.w) : "l"(p) : "memory");
    return v;
}
__device__ __forceinline__ void st_relaxed_f4(float4* p, float4 v) {
    asm volatile("st.relaxed.gpu.global.v4.f32 [%0], {%1,%2,%3,%4};" ::"l"(p), "f"(v.x), "f"(v.y), "f"(v.z), "f"(v.w) : "memory");
}
__device__ __forceinline__ uint32_t pack_bf16(float lo, float hi) {
    uint32_t r;
    asm("cvt.rn.bf16x2.f32 %0, %1, %2;" : "=r"(r) : "f"(hi), "f"(lo));
    return r;
}
__device__ __forceinline__ float bf_lo(uint32_t v) { return __uint_as_float(v << 16); }
__device__ __forceinline__ float bf_hi(uint32_t v) { return __uint_as_float(v & 0xffff0000u); }
__device__ __forceinline__ void sts32(uint32_t a, uint32_t v) { asm volatile("st.shared.u32 [%0], %1;" ::"r"(a), "r"(v) : "memory"); }
__device__ __forceinline__ void sts128(uint32_t a, uint4 v) {
    asm volatile("st.shared.v4.u32 [%0], {%1,%2,%3,%4};" ::"r"(a), "r"(v.x), "r"(v.y), "r"(v.z), "r"(v.w) : "memory");
}

__device__ __forceinline__ uint64_t desc_ni(uint32_t addr, uint32_t lbo, uint32_t sbo) {
    return (uint64_t)((addr & 0x3FFFF) >> 4) | ((uint64_t)(lbo >> 4) << 16) | ((uint64_t)(sbo >> 4) << 32);
}
__device__ __forceinline__ uint64_t desc_a(uint32_t addr) { return desc_ni(addr, 128, 1024); }
template <int N> __device__ __forceinline__ uint64_t desc_b(uint32_t addr) { return desc_ni(addr, 16 * N, 128); }
__device__ __forceinline__ uint64_t desc_k(uint32_t addr) {
    return (uint64_t)((addr & 0x3FFFF) >> 4) | (1ull << 16) | (64ull << 32) | (1ull << 62);
}
__device__ __forceinline__ uint64_t desc_mn(uint32_t addr, uint32_t lbo) {
    return (uint64_t)((addr & 0x3FFFF) >> 4) | ((uint64_t)(lbo >> 4) << 16) | (64ull << 32) | (1ull << 62);
}

#define ACC8(d, o) "+f"(d[o + 0]), "+f"(d[o + 1]), "+f"(d[o + 2]), "+f"(d[o + 3]), "+f"(d[o + 4]), "+f"(d[o + 5]), "+f"(d[o + 6]), "+f"(d[o + 7])
template <int TB, int SA = 1>
__device__ __forceinline__ void wgmma_n128(float (&d)[64], uint64_t da, uint64_t db, int sd) {
    asm volatile(
        "{\n.reg .pred p;\nsetp.ne.b32 p, %66, 0;\n"
        "wgmma.mma_async.sync.aligned.m64n128k16.f32.bf16.bf16 "
        "{%0,%1,%2,%3,%4,%5,%6,%7,%8,%9,%10,%11,%12,%13,%14,%15,%16,%17,%18,%19,%20,%21,%22,%23,%24,%25,%26,%27,%28,%29,%30,%31,"
        "%32,%33,%34,%35,%36,%37,%38,%39,%40,%41,%42,%43,%44,%45,%46,%47,%48,%49,%50,%51,%52,%53,%54,%55,%56,%57,%58,%59,%60,%61,%62,%63},"
        " %64, %65, p, %68, 1, 0, %67;\n}"
        : ACC8(d, 0), ACC8(d, 8), ACC8(d, 16), ACC8(d, 24), ACC8(d, 32), ACC8(d, 40), ACC8(d, 48), ACC8(d, 56)
        : "l"(da), "l"(db), "r"(sd), "n"(TB), "n"(SA));
}
template <int N> __device__ __forceinline__ void acc_def(float (&d)[N]) {
#pragma unroll
    for (int i = 0; i < N; i++) d[i] = 0.f;
}
template <int TB>
__device__ __forceinline__ void wgmma_n64(float (&d)[32], uint64_t da, uint64_t db, int sd) {
    asm volatile(
        "{\n.reg .pred p;\nsetp.ne.b32 p, %34, 0;\n"
        "wgmma.mma_async.sync.aligned.m64n64k16.f32.bf16.bf16 "
        "{%0,%1,%2,%3,%4,%5,%6,%7,%8,%9,%10,%11,%12,%13,%14,%15,%16,%17,%18,%19,%20,%21,%22,%23,%24,%25,%26,%27,%28,%29,%30,%31},"
        " %32, %33, p, 1, 1, 0, %35;\n}"
        : ACC8(d, 0), ACC8(d, 8), ACC8(d, 16), ACC8(d, 24)
        : "l"(da), "l"(db), "r"(sd), "n"(TB));
}
template <int SA>
__device__ __forceinline__ void wgmma_n64s(float (&d)[32], uint64_t da, uint64_t db, int sd) {
    asm volatile(
        "{\n.reg .pred p;\nsetp.ne.b32 p, %34, 0;\n"
        "wgmma.mma_async.sync.aligned.m64n64k16.f32.bf16.bf16 "
        "{%0,%1,%2,%3,%4,%5,%6,%7,%8,%9,%10,%11,%12,%13,%14,%15,%16,%17,%18,%19,%20,%21,%22,%23,%24,%25,%26,%27,%28,%29,%30,%31},"
        " %32, %33, p, %35, 1, 0, 1;\n}"
        : ACC8(d, 0), ACC8(d, 8), ACC8(d, 16), ACC8(d, 24)
        : "l"(da), "l"(db), "r"(sd), "n"(SA));
}
__device__ __forceinline__ void wgmma_n64_rs(float (&d)[32], uint32_t a0, uint32_t a1, uint32_t a2, uint32_t a3, uint64_t db, int sd) {
    asm volatile(
        "{\n.reg .pred p;\nsetp.ne.b32 p, %37, 0;\n"
        "wgmma.mma_async.sync.aligned.m64n64k16.f32.bf16.bf16 "
        "{%0,%1,%2,%3,%4,%5,%6,%7,%8,%9,%10,%11,%12,%13,%14,%15,%16,%17,%18,%19,%20,%21,%22,%23,%24,%25,%26,%27,%28,%29,%30,%31},"
        " {%32,%33,%34,%35}, %36, p, 1, 1, 1;\n}"
        : ACC8(d, 0), ACC8(d, 8), ACC8(d, 16), ACC8(d, 24)
        : "r"(a0), "r"(a1), "r"(a2), "r"(a3), "l"(db), "r"(sd));
}

struct Params {
    const __nv_bfloat16* x0;
    const __nv_bfloat16* w_r;
    const __nv_bfloat16* w_i;
    const __nv_bfloat16* lam_re;
    const __nv_bfloat16* lam_im;
    const __nv_bfloat16* log_dt;
    const __nv_bfloat16* dskip;
    float* out;
    int stop;
};

__device__ __forceinline__ float ldbf(const __nv_bfloat16* p) { return __bfloat162float(*p); }

__device__ __forceinline__ void dft_fp(int j, int& f, int& ph) {
    int cs = j >> 1;
    if (j == 1) { f = 256; ph = 0; }
    else { f = cs; ph = (j & 1) ? 128 : 0; }
}

__device__ __forceinline__ void gen_col_consts(uint8_t* sm, int tid) {
    const unsigned short* t64 = (const unsigned short*)(sm + SM_T64);
    const uint32_t sb = s2u(sm);
#pragma unroll 1
    for (int ch = tid; ch < 2560; ch += 256) {
        int c8 = (ch >> 3) & 7, m = (ch & 7) | ((ch >> 3) & 56), po, pi, step, base;
        if (ch < 2048) {
            pi = (ch >> 9) & 1; po = (m >> 3) & 1;
            step = 32 * (ch >> 10) + 8 * (m >> 4) + (m & 7);
            base = c8 * 8;
        } else {
            pi = m >> 5; po = c8 >> 2;
            step = 2 * (m & 31);
            base = (c8 & 3) * 8;
        }
        int idx = base * step + ((po == pi) ? 0 : (po == 0 ? 48 : 16));
        uint32_t v[4];
#pragma unroll
        for (int e = 0; e < 4; e++) {
            uint32_t lo = t64[idx & 63], hi = t64[(idx + step) & 63];
            idx += 2 * step;
            v[e] = lo | (hi << 16);
        }
        sts128(sb + SM_X + ch * 16, make_uint4(v[0], v[1], v[2], v[3]));
    }
}

__device__ __forceinline__ void fetch_partial(const uint4* ps_, uint32_t ptag, uint4 (&v)[8]) {
    unsigned n = 0;
#pragma unroll 1
    while (true) {
        if ((threadIdx.x & 31) == 31) {
#pragma unroll 1
            while (true) {
                uint32_t t0, t1;
                asm volatile("ld.relaxed.gpu.global.u32 %0, [%1];" : "=r"(t0) : "l"(ps_ + 3 * 128) : "memory");
                asm volatile("ld.relaxed.gpu.global.u32 %0, [%1];" : "=r"(t1) : "l"(ps_ + 7 * 128) : "memory");
                if (!(((t0 ^ ptag) | (t1 ^ ptag)) & 0x00010001u) || ++n >= SPIN_LIMIT) break;
            }
        }
        __syncwarp();
        uint32_t bad = 0;
#pragma unroll
        for (int i = 0; i < 8; i++) { v[i] = ld_relaxed_u4(ps_ + i * 128); bad |= (v[i].x ^ ptag) & 0x00010001u; }
        if (!__any_sync(~0u, bad) || ++n >= SPIN_LIMIT) break;
    }
}

__global__ void __launch_bounds__(NTHREADS, 1)
fused_kernel(const __grid_constant__ CUtensorMap tm_x, const __grid_constant__ CUtensorMap tm_bre,
             const __grid_constant__ CUtensorMap tm_bim, const __grid_constant__ CUtensorMap tm_cre,
             const __grid_constant__ CUtensorMap tm_cim, const __grid_constant__ CUtensorMap tm_col, const Params p) {
    extern __shared__ __align__(1024) uint8_t sm[];
    const uint32_t sb = s2u(sm);
    const int tid = threadIdx.x, b = blockIdx.x;
    const int c = b >> 3, r = b & 7;
    const int par = r & 1, pi_ = r >> 1, own = 4 * par + pi_;
    const int wg = __shfl_sync(~0u, tid >> 7, 0), w = __shfl_sync(~0u, (tid >> 5) & 3, 0), lane = tid & 31, g = lane >> 2, q = lane & 3;
    auto BAR = [&](int i) { return sb + SM_BAR + 8 * i; };
    unsigned* s_tgt = (unsigned*)(sm + SM_TGT);

    if (tid < NBARS) {
        int cnt = 1;
        if ((tid >= B_EMPTY0 && tid < B_EMPTY0 + 4) || (tid >= B_XEMPTY && tid < B_XEMPTY + 4) || tid == B_RFREE) cnt = 12;
        if (tid >= B_AEMPTY && tid < B_AEMPTY + 8) cnt = 8;
        if (tid == B_AFREE) cnt = 4;
        mbar_init(BAR(tid), cnt);
        asm volatile("fence.mbarrier_init.release.cluster;" ::: "memory");
    } else if (tid >= 64 && tid < 68) {
        s_tgt[tid - 64] = ((ld_acquire(&g_bar[tid - 64]) >> 7) + 1u) << 7;
    } else if (tid >= 72 && tid < 120) {
        g_ssq[2048 + 48 * b + tid - 72] = 0.f;
    } else if (tid >= 128 && tid < 384) {
        int i = tid - 128;
        __nv_bfloat16 h = __float2bfloat16(cospif((float)i * (1.f / 256.f)));
        ((__nv_bfloat16*)(sm + SM_TAB))[i] = h;
        ((__nv_bfloat16*)(sm + SM_TAB))[i + 256] = __hneg(h);
        if ((i & 7) == 0) {
            ((__nv_bfloat16*)(sm + SM_T64))[i >> 3] = h;
            ((__nv_bfloat16*)(sm + SM_T64))[(i >> 3) + 32] = __hneg(h);
        }
    } else if (tid >= 384 && tid < 480) {
        int i = tid - 384;
        int ps = i < 64 ? 64 * r + i : 32 * c + i - 64;
        float lr = ldbf(p.lam_re + ps), li = ldbf(p.lam_im + ps);
        float dt = __bfloat162float(__float2bfloat16(expf(ldbf(p.log_dt + ps))));
        float mag = expf(lr * dt), t = li * dt * 0.15915494309189535f, sn, cs;
        t -= rintf(t);
        sincospif(2.f * t, &sn, &cs);
        float er = mag * cs, ei = mag * sn;
        if (i < 64) {
            *(float2*)(sm + SM_LAM + i * 8) = make_float2(er, ei);
        } else {
            er -= 1.f;
            float inv = 1.f / (lr * lr + li * li);
            *(float2*)(sm + SM_RSTD + (i - 64) * 8) = make_float2((er * lr + ei * li) * inv, (ei * lr - er * li) * inv);
        }
    }
    __syncthreads();
    asm volatile("barrier.cluster.arrive.release.aligned;\nbarrier.cluster.wait.acquire.aligned;" ::: "memory");

    if (wg == 3) {
        asm volatile("setmaxnreg.dec.sync.aligned.u32 56;");
        if (w > 0) {
#pragma unroll 1
            for (int i = tid - 416; i < 1024 + 128; i += 96) {
                if (i < 1024) g_P[(uint32_t)(b * 4 + (i >> 8)) * 1024 + (3 + 4 * ((i >> 7) & 1)) * 128 + (i & 127)] = make_uint4(0, 0, 0, 0);
                else g_Ebuf[b * 128 + i - 1024] = make_float4(0.f, 0.f, 0.f, 0.f);
            }
#pragma unroll 1
            for (int task = tid - 416; task < 256; task += 96) {
                const int cb = task & 127, kq = 2 * b + (task >> 7), k1 = kq >> 2, qq = kq & 3;
                const unsigned short* wr_ = (const unsigned short*)p.w_r + (k1 + 128 * qq) * 257;
                const unsigned short* wi_ = (const unsigned short*)p.w_i + (k1 + 128 * qq) * 257;
                const int c0 = cb == 0 ? 256 : 2 * cb, c1 = 2 * cb + 1;
                uint32_t wf[16];
#pragma unroll
                for (int i = 0; i < 8; i++) {
                    int o = (512 * (i >> 1) + 64 * (i & 1)) * 257;
                    wf[i] = (uint32_t)__ldg(wr_ + o + c0) | ((uint32_t)__ldg(wi_ + o + c0) << 16);
                    wf[8 + i] = (uint32_t)__ldg(wr_ + o + c1) | ((uint32_t)__ldg(wi_ + o + c1) << 16);
                }
                uint4* wd = g_Wfrag + (uint32_t)(cb * 1024 + kq);
#pragma unroll
                for (int i = 0; i < 4; i++) wd[i * 256] = make_uint4(wf[4 * i], wf[4 * i + 1], wf[4 * i + 2], wf[4 * i + 3]);
            }
            __syncwarp();
            bar_sync(2, 480);
            if (w != 1) return;
            if (lane == 0) { fence_async(); red_release(&g_bar[0], 1); }
#pragma unroll 1
            for (int layer = 0; layer < 2; layer++) {
                __syncwarp();
                bar_sync(5, 416);
                if (lane == 0) {
                    tma_store_5d(&tm_col, 32 * (b & 1), 0, b >> 1, 0, layer, sb + SM_RAW);
                    asm volatile("cp.reduce.async.bulk.global.shared::cta.bulk_group.add.f32 [%0], [%1], 8192;" ::"l"(g_ssq + (1 + 2 * layer) * 2048),
                                 "r"(sb + SM_SSQ) : "memory");
                    asm volatile("cp.async.bulk.commit_group;" ::: "memory");
                    asm volatile("cp.async.bulk.wait_group 0;" ::: "memory");
                    fence_async();
                    red_release(&g_bar[1 + 2 * layer], 1);
                }
            }
        } else if (tid == 384) {
#pragma unroll 1
            for (int kb = 0; kb < 8; kb++) {
                int s = kb < 6 ? kb : kb - 4;
                uint32_t dst = s < 2 ? sb + SM_A + 65536 + s * 24576 : sb + SM_X + (s - 2) * 24576;
                if (kb >= 6) mbar_wait(BAR(B_EMPTY0 + s), 0);
                uint32_t fb = BAR(B_FULL0 + kb);
                mbar_expect(fb, 24576);
                tma_5d(dst, &tm_x, kb * 64, 0, 0, 0, c, fb);
                tma_2d(dst + 16384, &tm_bre, kb * 64, 32 * c, fb);
                tma_2d(dst + 20480, &tm_bim, kb * 64, 32 * c, fb);
                if (kb == 5) {
#pragma unroll 1
                    for (int k2 = 0; k2 < 8; k2++) {
                        asm volatile("cp.async.bulk.prefetch.tensor.2d.L2.global [%0, {%1,%2}];" ::"l"((c & 1) ? &tm_cim : &tm_cre), "r"(64 * (c >> 1)), "r"(k2 * 64) : "memory");
                        if (k2 >= 6) {
                            asm volatile("cp.async.bulk.prefetch.tensor.5d.L2.global [%0, {%1,%2,%3,%4,%5}];" ::"l"(&tm_x), "r"(k2 * 64), "r"(0), "r"(0), "r"(0), "r"(c) : "memory");
                            asm volatile("cp.async.bulk.prefetch.tensor.2d.L2.global [%0, {%1,%2}];" ::"l"(&tm_bre), "r"(k2 * 64), "r"(32 * c) : "memory");
                            asm volatile("cp.async.bulk.prefetch.tensor.2d.L2.global [%0, {%1,%2}];" ::"l"(&tm_bim), "r"(k2 * 64), "r"(32 * c) : "memory");
                        }
                    }
                }
                if (kb == 7) {
                    mbar_wait(BAR(B_EMPTY0 + 0), 0);
                    mbar_wait(BAR(B_EMPTY0 + 1), 0);
                    mbar_expect(BAR(B_FULLC), 65536);
#pragma unroll 1
                    for (int k2 = 0; k2 < 8; k2++)
                        tma_2d(sb + SM_A + 65536 + k2 * 8192, (c & 1) ? &tm_cim : &tm_cre, 64 * (c >> 1), k2 * 64, BAR(B_FULLC));
                }
            }
#pragma unroll 1
            for (int layer = 0; layer < 2; layer++) {
                if (layer == 1) {
                    mbar_wait(BAR(B_AEMPTY + 6), 1);
#pragma unroll 1
                    for (int s = 0; s < 8; s++) {
                        mbar_wait(BAR(B_AEMPTY + s), 1);
                        mbar_expect(BAR(B_AFULL + s), 16384);
                        bulk_g2s(sb + SM_A + s * 16384, g_A1 + (uint32_t)(r * 8 + s) * 16384, 16384, BAR(B_AFULL + s));
                    }
                }
                wait_count(&g_bar[2 * layer], s_tgt[2 * layer]);
                fence_async();
                mbar_expect(BAR(B_COL), 16384 + 8192);
                tma_5d(sb + SM_RAW, &tm_col, 32 * (b & 1), 0, b >> 1, 0, layer, BAR(B_COL));
                bulk_g2s(sb + SM_SSQ, g_ssq + 2 * layer * 2048, 8192, BAR(B_COL));
                if (layer == 0) {
                    mbar_wait(BAR(B_AFREE), 0);
                    mbar_wait(BAR(B_COL), 0);
#pragma unroll 1
                    for (int s = 0; s < 8; s++) {
                        mbar_expect(BAR(B_AFULL + s), 16384);
                        bulk_g2s(sb + SM_A + s * 16384, g_A1 + (uint32_t)(r * 8 + s) * 16384, 16384, BAR(B_AFULL + s));
                    }
                }
                wait_count(&g_bar[1 + 2 * layer], s_tgt[1 + 2 * layer]);
                fence_async();
                const uint8_t* xsrc = g_X + (uint32_t)(layer * 16 + c) * 8 * 16384;
                const uint8_t* esrc = g_E + (uint32_t)(layer * 8 + own) * 8 * 8192;
                mbar_expect(BAR(B_SSQ), 512);
                bulk_g2s(sb + SM_RSTD, g_ssq + (1 + 2 * layer) * 2048 + 128 * c, 512, BAR(B_SSQ));
                mbar_expect(BAR(B_HPEER), 32768);
#pragma unroll 1
                for (int it = 0; it < 12; it++) {
                    if (it < 8) {
                        int st = it & 3, f = layer * 2 + (it >> 2);
                        if (f > 0) mbar_wait(BAR(B_XEMPTY + st), (f - 1) & 1);
                        mbar_expect(BAR(B_XFULL + st), 24576);
                        bulk_g2s(sb + SM_X + st * 24576, xsrc + (uint32_t)it * 16384, 16384, BAR(B_XFULL + st));
                        bulk_g2s(sb + SM_X + st * 24576 + 16384, esrc + (uint32_t)it * 8192, 8192, BAR(B_XFULL + st));
                    }
                    if (it >= 4) {
                        int s = it - 4, tile = 4 * par + ((pi_ + 1 + (s >> 1)) & 3), sl = r ^ (s & 1);
                        mbar_wait(BAR(B_AEMPTY + s), 0);
                        uint32_t fb = BAR(B_AFULL + s), dst = sb + SM_A + s * 16384;
                        mbar_expect(fb, 16384);
                        if (layer == 1) {
                            tma_2d(dst, &tm_cre, 64 * sl, 64 * tile, fb);
                            tma_2d(dst + 8192, &tm_cim, 64 * sl, 64 * tile, fb);
                        } else {
                            bulk_g2s(dst, g_A2 + (uint32_t)(sl * 8 + tile) * 16384, 16384, fb);
                        }
                    }
                }
            }
        }
        return;
    }

    asm volatile("setmaxnreg.inc.sync.aligned.u32 152;");
    TS(0);
    if (wg == 0) TC(30);
    {
        const int f = 32 * r + lane;
        float cd, sd;
        __sincosf((float)f * (6.283185307179586f / 512.f), &sd, &cd);
        const uint32_t dst = sb + SM_A + (lane >> 2) * 1024 + (lane & 3) * 32;
#pragma unroll 1
        for (int ch = tid >> 5; ch < 64; ch += 12) {
            int a = (8 * ch * f) & 511;
            a = a >= 256 ? a - 512 : a;
            float cs, sn;
            __sincosf((float)a * (6.283185307179586f / 512.f), &sn, &cs);
            float cv[8], sv[8];
#pragma unroll
            for (int e = 0; e < 8; e++) {
                cv[e] = cs; sv[e] = -sn;
                float t = cs * cd - sn * sd;
                sn = sn * cd + cs * sd;
                cs = t;
            }
            uint4 o1 = make_uint4(pack_bf16(sv[0], sv[1]), pack_bf16(sv[2], sv[3]), pack_bf16(sv[4], sv[5]), pack_bf16(sv[6], sv[7]));
            if (f == 0) o1 = make_uint4(0xbf803f80u, 0xbf803f80u, 0xbf803f80u, 0xbf803f80u);
            uint32_t a0 = dst + (ch >> 3) * 8192 + (ch & 7) * 128;
            sts128(a0, make_uint4(pack_bf16(cv[0], cv[1]), pack_bf16(cv[2], cv[3]), pack_bf16(cv[4], cv[5]), pack_bf16(cv[6], cv[7])));
            sts128(a0 + 16, o1);
        }
    }
    fence_async_smem();
    bar_sync(10, 384);
    TS(1);
    uint4 pre[4];
    if (wg < 2) {
        const uint4* src = (const uint4*)(p.x0 + (uint32_t)(128 * c + 16 * r + 8 * wg + 2 * w) * 512) + lane;
#pragma unroll
        for (int i = 0; i < 4; i++) pre[i] = __ldg(src + 32 * i);
    } else {
        pre[0] = __ldg((const uint4*)p.dskip + 2 * lane);
        pre[1] = __ldg((const uint4*)p.dskip + 2 * lane + 1);
        pre[2] = pre[0]; pre[3] = pre[0];
    }

    {
        float acc[32];
        acc_def(acc);
#pragma unroll 1
        for (int kb = 0; kb < 8; kb++) {
            int s = kb < 6 ? kb : kb - 4;
            uint32_t src = (s < 2 ? sb + SM_A + 65536 + s * 24576 : sb + SM_X + (s - 2) * 24576) + wg * 8192;
            mbar_wait(BAR(B_FULL0 + kb), 0);
            wg_fence();
#pragma unroll
            for (int ks = 0; ks < 4; ks++)
                wgmma_n64<0>(acc, desc_a(sb + SM_A + kb * 8192 + ks * 256), desc_k(src + ks * 32), 1);
            wg_commit();
            wg_wait<1>();
            if (kb > 0 && kb <= 4 && lane == 0) mbar_arrive(BAR(B_EMPTY0 + kb - 1), 1);
        }
        wg_wait<0>();
        TS(2);
        if (wg < 2) {
            uint8_t* dst = g_X + (uint32_t)((c * 8 + r) * 16384 + w * 4096 + wg * 1024 + g * 16 + 4 * q);
#pragma unroll
            for (int i = 0; i < 8; i++) {
                *(uint32_t*)(dst + i * 128) = pack_bf16(acc[4 * i], acc[4 * i + 1]);
                *(uint32_t*)(dst + 2048 + i * 128) = pack_bf16(acc[4 * i + 2], acc[4 * i + 3]);
            }
#pragma unroll
            for (int rr = 0; rr < 2; rr++) {
                int t = 16 * r + 8 * wg + 2 * w + rr;
                uint32_t u[8] = {pre[2 * rr].x, pre[2 * rr].y, pre[2 * rr].z, pre[2 * rr].w, pre[2 * rr + 1].x, pre[2 * rr + 1].y, pre[2 * rr + 1].z, pre[2 * rr + 1].w};
                float s = 0.f;
#pragma unroll
                for (int i = 0; i < 8; i++) s += bf_lo(u[i]) + bf_hi(u[i]);
#pragma unroll
                for (int o = 16; o; o >>= 1) s += __shfl_xor_sync(~0u, s, o);
                float m = s * (1.f / 512.f), ss = 0.f;
#pragma unroll
                for (int i = 0; i < 8; i++) { float d0 = bf_lo(u[i]) - m, d1 = bf_hi(u[i]) - m; ss += d0 * d0 + d1 * d1; }
#pragma unroll
                for (int o = 16; o; o >>= 1) ss += __shfl_xor_sync(~0u, ss, o);
                if (lane == 0) g_ssq[128 * c + 8 * ((t >> 1) & 15) + 2 * (t >> 5) + (t & 1)] = ss;
            }
        } else {
            uint8_t* dst = g_A1 + (uint32_t)(((c >> 1) * 8 + r) * 16384 + (c & 1) * 8192 + w * 256 + q * 32 + g * 2);
            const float wj0 = (r == 0 && w == 0 && g < 2) ? (g == 0 ? 0.f : 1.f / 512.f) : 2.f / 512.f;
#pragma unroll
            for (int i = 0; i < 4; i++) {
#pragma unroll
                for (int e = 0; e < 2; e++) {
                    float2 cf = *(const float2*)(sm + SM_RSTD + (8 * i + 2 * q + e) * 8);
#pragma unroll
                    for (int h = 0; h < 2; h++) {
                        float wj = h == 0 ? wj0 : 2.f / 512.f;
                        float pr = acc[4 * i + 2 * h + e] * wj, pi = acc[16 + 4 * i + 2 * h + e] * wj;
                        uint8_t* d2 = dst + i * 2048 + h * 128 + e * 16;
                        *(__nv_bfloat16*)(d2) = __float2bfloat16(cf.x * pr - cf.y * pi);
                        *(__nv_bfloat16*)(d2 + 1024) = __float2bfloat16(cf.x * pi + cf.y * pr);
                    }
                }
            }
            int j = 64 * r + 4 * c + w, f, ph;
            dft_fp(j, f, ph);
            uint32_t u[8] = {pre[0].x, pre[0].y, pre[0].z, pre[0].w, pre[1].x, pre[1].y, pre[1].z, pre[1].w};
            float s = 0.f;
            int idx = 16 * lane * f + ph;
#pragma unroll
            for (int i = 0; i < 16; i++) {
                int a = idx & 511;
                idx += f;
                a = a >= 256 ? a - 512 : a;
                s += ((i & 1) ? bf_hi(u[i >> 1]) : bf_lo(u[i >> 1])) * __cosf((float)a * (6.283185307179586f / 512.f));
            }
#pragma unroll
            for (int o = 16; o; o >>= 1) s += __shfl_xor_sync(~0u, s, o);
            if (lane == 0) g_Dh[j] = s;
        }
        bar_sync(2, 480);
        TS(3);
    }

    if (wg == 2) {
        float acc[32];
        acc_def(acc);
        mbar_wait(BAR(B_FULLC), 0);
        wg_fence();
#pragma unroll 1
        for (int kb = 0; kb < 8; kb++) {
#pragma unroll
            for (int ks = 0; ks < 4; ks++)
                wgmma_n64<1>(acc, desc_a(sb + SM_A + kb * 8192 + ks * 256), desc_mn(sb + SM_A + 65536 + kb * 8192 + ks * 2048, 8192), 1);
            wg_commit();
        }
        wg_wait<0>();
        fence_async_smem();
        if (lane == 0) mbar_arrive(BAR(B_AFREE), 1);
        uint8_t* dst = g_A2 + (uint32_t)(((c >> 1) * 8 + r) * 16384 + (c & 1) * 8192 + w * 2048 + g * 16 + 4 * q);
#pragma unroll
        for (int i = 0; i < 8; i++) {
            *(uint32_t*)(dst + i * 128) = pack_bf16(acc[4 * i], acc[4 * i + 1]);
            *(uint32_t*)(dst + 1024 + i * 128) = pack_bf16(acc[4 * i + 2], acc[4 * i + 3]);
        }
        const int m = 4 * c + w, jp = 64 * r + m;
        int fp, php;
        dft_fp(jp, fp, php);
        const __nv_bfloat16* tab = (const __nv_bfloat16*)(sm + SM_TAB);
        const __nv_bfloat16* dh = (const __nv_bfloat16*)(sm + SM_RSTD);
#pragma unroll 1
        for (int it = 0; it < 4; it++) {
            if (it == 2) {
                if (tid == 256) wait_count(&g_bar[0], s_tgt[0]);
                bar_sync(3, 128);
                float4 d4 = __ldcg((const float4*)g_Dh + (tid - 256));
                *(uint2*)(sm + SM_RSTD + (tid - 256) * 8) = make_uint2(pack_bf16(d4.x, d4.y), pack_bf16(d4.z, d4.w));
                bar_sync(3, 128);
            }
            const int ch = lane + 32 * (it & 1);
            float v[8];
#pragma unroll
            for (int e = 0; e < 8; e++) {
                int j = 8 * ch + e, f, ph;
                dft_fp(j, f, ph);
                float wj = j == 0 ? 0.f : (j == 1 ? 1.f / 512.f : 2.f / 512.f);
                if (it < 2) {
                    v[e] = wj * __bfloat162float(tab[(jp * f + ph) & 511]);
                } else {
                    float gsum = 0.f;
#pragma unroll
                    for (int sgn = 0; sgn < 2; sgn++) {
                        int mm = (sgn ? f - fp : f + fp) & 511, pp = (sgn ? ph - php : ph + php) & 511;
                        if (mm > 256) { mm = 512 - mm; pp = (512 - pp) & 511; }
                        int odd = (pp >> 7) & 1;
                        float t = __bfloat162float(dh[mm == 256 ? 1 : 2 * mm + odd]);
                        if (odd && (mm & 255) == 0) t = 0.f;
                        gsum += (pp & 256) ? -t : t;
                    }
                    v[e] = 0.5f * wj * gsum;
                }
            }
            uint32_t off = (uint32_t)((it < 2 ? 64 : 0) + r * 8 + (ch >> 3)) * 8192 + (m >> 3) * 1024 + (ch & 7) * 128 + (m & 7) * 16;
            *(uint4*)(g_E + off) = make_uint4(pack_bf16(v[0], v[1]), pack_bf16(v[2], v[3]), pack_bf16(v[4], v[5]), pack_bf16(v[6], v[7]));
        }
        fence_async_smem();
    }

#pragma unroll 1
    for (int layer = 0; layer < 2; layer++) {
        if (wg < 2) {
            const int n1 = 32 * wg + 8 * w + g;
            const int ct = n1 >> 2;
            gen_col_consts(sm, tid);
            float twr[8], twi[8];
#pragma unroll
            for (int i = 0; i < 8; i++) {
                int n2 = 8 * (i >> 1) + 2 * q + (i & 1);
                int a = (n1 * n2) & 2047;
                a = a >= 1024 ? a - 2048 : a;
                float ang = (float)a * (-6.283185307179586f / 2048.f);
                twr[i] = __cosf(ang); twi[i] = __sinf(ang);
            }
            mbar_wait(BAR(B_COL), layer);
            TS(4 + 12 * layer);
            if (wg == 0) TC(0 + 10 * layer);
            uint32_t wf[16];
            {
                const uint4* ws = g_Wfrag + (uint32_t)(b * 1024 + n1 * 4 + q);
#pragma unroll
                for (int i = 0; i < 4; i++) {
                    uint4 v = __ldcg(ws + i * 256);
                    wf[4 * i] = v.x; wf[4 * i + 1] = v.y; wf[4 * i + 2] = v.z; wf[4 * i + 3] = v.w;
                }
            }
            const uint32_t rw0 = sb + SM_RAW + ct * 1024 + q * 64 + ((q >> 1) << 4) + (g & 3) * 4, rw1 = rw0 ^ 16;
            const int pos0 = 128 * ct + 8 * q + 2 * (g & 3);
            const int sw = b == 0 ? 1 : 0;
            uint32_t xr[4][4];
            const uint32_t st0 = sb + SM_H + (n1 >> 3) * 1024 + g * 16 + 4 * q;
#pragma unroll
            for (int i = 0; i < 4; i++) {
                float2 sq = *(const float2*)(sm + SM_SSQ + (pos0 + 32 * i) * 4);
                float r0 = rsqrtf(sq.x * (1.f / 512.f) + 1e-5f), r1 = rsqrtf(sq.y * (1.f / 512.f) + 1e-5f);
#pragma unroll
                for (int jj = 0; jj < 4; jj++) {
                    const int K = jj ^ (2 * (i & 1));
                    uint32_t a = ((K & 1) ? rw1 : rw0) + i * 256 + (K & 2) * 16;
                    if (jj < 2) a ^= sw << 4;
                    uint32_t v = lds32(a);
                    xr[jj][i] = v;
                    uint32_t o = pack_bf16(bf_lo(v) * r0, bf_hi(v) * r1);
                    if (jj == 1 && sw) o = 0u;
                    sts32(st0 + (jj & 1) * 8192 + (4 * (jj >> 1) + i) * 128, o);
                }
            }
            if (wg == 0) TC(1 + 10 * layer);
            fence_async_smem();
            bar_sync(1, 256);
            float acc[32];
            const uint32_t s1a = sb + SM_X + wg * 16384, s2b = sb + SM_X + 32768;
            wg_fence();
#pragma unroll
            for (int ks = 0; ks < 8; ks++)
                wgmma_n64<1>(acc, desc_a(s1a + (ks >> 2) * 8192 + (ks & 3) * 256), desc_b<64>(sb + SM_H + ks * 2048), ks != 0);
            wg_commit();
            wg_wait<0>();
            if (wg == 0) TC(2 + 10 * layer);
            uint32_t are[2][4], aim[2][4];
#pragma unroll
            for (int col = 0; col < 2; col++) {
#pragma unroll
                for (int i = 0; i < 4; i++) {
                    int o = 4 * (4 * col + i);
                    float r0 = acc[o] * twr[2 * i] - acc[o + 2] * twi[2 * i], i0 = acc[o] * twi[2 * i] + acc[o + 2] * twr[2 * i];
                    float r1 = acc[o + 1] * twr[2 * i + 1] - acc[o + 3] * twi[2 * i + 1], i1 = acc[o + 1] * twi[2 * i + 1] + acc[o + 3] * twr[2 * i + 1];
                    are[col][i] = pack_bf16(r0, r1);
                    aim[col][i] = pack_bf16(i0, i1);
                }
            }
            wg_fence();
#pragma unroll
            for (int ks = 0; ks < 2; ks++)
                wgmma_n64_rs(acc, are[0][2 * ks], are[1][2 * ks], are[0][2 * ks + 1], are[1][2 * ks + 1], desc_b<64>(s2b + ks * 2048), ks != 0);
#pragma unroll
            for (int ks = 0; ks < 2; ks++)
                wgmma_n64_rs(acc, aim[0][2 * ks], aim[1][2 * ks], aim[0][2 * ks + 1], aim[1][2 * ks + 1], desc_b<64>(s2b + 4096 + ks * 2048), 1);
            wg_commit();
            wg_wait<0>();
            if (wg == 0) TC(3 + 10 * layer);
#pragma unroll
            for (int col = 0; col < 2; col++) {
#pragma unroll
                for (int i = 0; i < 4; i++) {
                    float gr[2], gi[2];
#pragma unroll
                    for (int e = 0; e < 2; e++) {
                        uint32_t wv = wf[col * 8 + 2 * i + e];
                        float wr = bf_lo(wv), wi = bf_hi(wv);
                        float zr = acc[4 * i + 2 * col + e], zi = acc[16 + 4 * i + 2 * col + e];
                        gr[e] = zr * wr - zi * wi;
                        gi[e] = -(zr * wi + zi * wr);
                    }
                    are[col][i] = pack_bf16(gr[0], gr[1]);
                    aim[col][i] = pack_bf16(gi[0], gi[1]);
                }
            }
            wg_fence();
#pragma unroll
            for (int ks = 0; ks < 2; ks++)
                wgmma_n64_rs(acc, are[0][2 * ks], are[1][2 * ks], are[0][2 * ks + 1], are[1][2 * ks + 1], desc_b<64>(s2b + ks * 2048), ks != 0);
#pragma unroll
            for (int ks = 0; ks < 2; ks++)
                wgmma_n64_rs(acc, aim[0][2 * ks], aim[1][2 * ks], aim[0][2 * ks + 1], aim[1][2 * ks + 1], desc_b<64>(s2b + 4096 + ks * 2048), 1);
            wg_commit();
            wg_wait<0>();
            if (wg == 0) TC(4 + 10 * layer);
#pragma unroll
            for (int col = 0; col < 2; col++) {
#pragma unroll
                for (int i = 0; i < 4; i++) {
                    float rr[2], im[2];
#pragma unroll
                    for (int e = 0; e < 2; e++) {
                        float zr = acc[4 * i + 2 * col + e], zi = acc[16 + 4 * i + 2 * col + e];
                        rr[e] = zr * twr[2 * i + e] - zi * twi[2 * i + e];
                        im[e] = zr * twi[2 * i + e] + zi * twr[2 * i + e];
                    }
                    sts32(st0 + 16384 + (4 * col + i) * 128, pack_bf16(rr[0], rr[1]));
                    sts32(st0 + 16384 + 8192 + (4 * col + i) * 128, pack_bf16(im[0], im[1]));
                }
            }
            if (wg == 0) TC(5 + 10 * layer);
            fence_async_smem();
            bar_sync(1, 256);
            wg_fence();
#pragma unroll
            for (int ks = 0; ks < 8; ks++)
                wgmma_n64<1>(acc, desc_a(s1a + (ks >> 2) * 8192 + (ks & 3) * 256), desc_b<64>(sb + SM_H + 16384 + ks * 2048), ks != 0);
            wg_commit();
            wg_wait<0>();
            if (wg == 0) TC(6 + 10 * layer);
            const float sc = 1.f / 2048.f;
            const float sci0 = sw ? 0.f : -sc;
            const float wr0 = sw ? 0.5f : 1.f, wi0 = sw ? 0.f : 1.f;
#pragma unroll
            for (int i = 0; i < 4; i++) {
                float ss0, ss1;
#pragma unroll
                for (int col = 0; col < 2; col++) {
                    int o = 4 * (4 * col + i);
                    uint32_t vr = xr[2 * col][i], vi = xr[2 * col + 1][i];
                    float si = col == 0 ? sci0 : -sc;
                    uint32_t nr = pack_bf16(fmaf(acc[o], sc, bf_lo(vr)), fmaf(acc[o + 1], sc, bf_hi(vr)));
                    uint32_t ni = pack_bf16(fmaf(acc[o + 2], si, bf_lo(vi)), fmaf(acc[o + 3], si, bf_hi(vi)));
                    float a0 = bf_lo(nr), a1 = bf_hi(nr), b0 = bf_lo(ni), b1 = bf_hi(ni);
                    if (col == 0) {
                        ss0 = wr0 * a0 * a0 + wi0 * b0 * b0;
                        ss1 = wr0 * a1 * a1 + wi0 * b1 * b1;
                    } else {
                        ss0 += a0 * a0 + b0 * b0;
                        ss1 += a1 * a1 + b1 * b1;
                    }
                    const int K = (2 * col) ^ (2 * (i & 1));
                    uint32_t a = rw0 + i * 256 + K * 16;
                    if (col == 0) a ^= sw << 4;
                    sts32(a, nr);
                    sts32(a ^ 16, ni);
                }
                *(float2*)(sm + SM_SSQ + (pos0 + 32 * i) * 4) = make_float2(ss0 * (2.f / 512.f), ss1 * (2.f / 512.f));
            }
            fence_async_smem();
        }
        TS(5 + 12 * layer);
        if (wg == 0) TC(7 + 10 * layer);
        bar_arrive(5, 416);

        float acc[64];
        float* s_rstd = (float*)(sm + SM_RSTD);
        float* s_mean = (float*)(sm + SM_MEAN);
        const unsigned epoch = s_tgt[0] >> 7;
        const uint32_t pt3 = 1u + (2u * epoch + layer) % 3u;
        const uint32_t ptag = (pt3 & 1u) | ((pt3 & 2u) << 15);
        const uint64_t dstep = layer == 0 ? 16 : 2;
        auto c_desc = [&](int s) { return layer == 0 ? desc_a(sb + SM_A + s * 16384) : desc_k(sb + SM_A + s * 16384); };
        if (wg < 2) {
            const int prow = 32 * wg + 8 * w + g;
            const float2 l1 = *(const float2*)(sm + SM_LAM + prow * 8);
            float lr32 = l1.x, li32 = l1.y;
#pragma unroll
            for (int i = 0; i < 5; i++) { float t = lr32 * lr32 - li32 * li32; li32 = 2.f * lr32 * li32; lr32 = t; }
            float lr128 = lr32, li128 = li32;
#pragma unroll
            for (int i = 0; i < 2; i++) { float t = lr128 * lr128 - li128 * li128; li128 = 2.f * lr128 * li128; lr128 = t; }
            const float lr1 = l1.x, li1 = l1.y;
            acc_def(acc);
#pragma unroll 1
            for (int kb = 0; kb < 8; kb++) {
                mbar_wait(BAR(B_AFULL + kb), 0);
                mbar_wait(BAR(B_XFULL + (kb & 3)), (kb >> 2) & 1);
                wg_fence();
#pragma unroll
                for (int ks = 0; ks < 4; ks++)
                    wgmma_n128<1>(acc, desc_a(sb + SM_A + kb * 16384 + wg * 8192 + ks * 256),
                                  desc_b<128>(sb + SM_X + (kb & 3) * 24576 + ks * 4096), 1);
                wg_commit();
                wg_wait<1>();
                if (kb > 0 && lane == 0) { mbar_arrive(BAR(B_AEMPTY + kb - 1), 1); mbar_arrive(BAR(B_XEMPTY + ((kb - 1) & 3)), 1); }
            }
            wg_wait<0>();
            if (lane == 0) { mbar_arrive(BAR(B_AEMPTY + 7), 1); mbar_arrive(BAR(B_XEMPTY + 3), 1); mbar_arrive_remote(mapa(BAR(B_RFREE), par ^ 1)); }
            TS(6 + 12 * layer);
            bar_sync(4, 384);
            TS(7 + 12 * layer);
            float er = 0.f, ei = 0.f;
#pragma unroll
            for (int i = 0; i < 16; i++) {
                float2 rs = *(const float2*)(s_rstd + 128 + 8 * i + 2 * q);
                acc[4 * i] *= rs.x; acc[4 * i + 1] *= rs.y; acc[4 * i + 2] *= rs.x; acc[4 * i + 3] *= rs.y;
                float nr = lr1 * er - li1 * ei + acc[4 * i], ni = lr1 * ei + li1 * er + acc[4 * i + 2];
                er = lr1 * nr - li1 * ni + acc[4 * i + 1];
                ei = lr1 * ni + li1 * nr + acc[4 * i + 3];
            }
            float cr = 0.f, ci = 0.f, tr = 0.f, ti = 0.f;
#pragma unroll
            for (int qq = 0; qq < 4; qq++) {
                float xr_ = __shfl_sync(~0u, er, (lane & ~3) | qq), xi_ = __shfl_sync(~0u, ei, (lane & ~3) | qq);
                if (qq == q) { cr = tr; ci = ti; }
                float nr = lr32 * tr - li32 * ti + xr_, ni = lr32 * ti + li32 * tr + xi_;
                tr = nr; ti = ni;
            }
            float4* eb = g_Ebuf + (uint32_t)(layer * 16 * 512 + 64 * r + prow);
            if (q == 0 && c < 15) st_relaxed_f4(eb + c * 512, make_float4(tr, ti, __uint_as_float(epoch), 0.f));
            TS(8 + 12 * layer);
            float pr[4], pi[4];
            {
                unsigned n = 0;
                bool ok;
#pragma unroll 1
                do {
                    ok = true;
#pragma unroll
                    for (int k = 0; k < 4; k++) {
                        float4 v = make_float4(0.f, 0.f, __uint_as_float(epoch), 0.f);
                        if (4 * k + q < c) v = ld_relaxed_f4(eb + (4 * k + q) * 512);
                        pr[k] = v.x; pi[k] = v.y;
                        ok = ok && __float_as_uint(v.z) == epoch;
                    }
                } while (!ok && ++n < SPIN_LIMIT);
            }
            __syncwarp();
            TS(9 + 12 * layer);
            float hr = 0.f, hi = 0.f;
#pragma unroll
            for (int cc = 0; cc < 15; cc++) {
                float xr_ = __shfl_sync(~0u, pr[cc >> 2], (lane & ~3) | (cc & 3)), xi_ = __shfl_sync(~0u, pi[cc >> 2], (lane & ~3) | (cc & 3));
                if (cc < c) {
                    float nr = lr128 * hr - li128 * hi + xr_, ni = lr128 * hi + li128 * hr + xi_;
                    hr = nr; hi = ni;
                }
            }
#pragma unroll
            for (int qq = 0; qq < 3; qq++) {
                if (qq < q) { float nr = lr32 * hr - li32 * hi, ni = lr32 * hi + li32 * hr; hr = nr; hi = ni; }
            }
            er = cr + hr; ei = ci + hi;
            bar_sync(7, 384);
            const uint32_t ha = sb + SM_HH + par * 32768 + (prow >> 3) * 2048 + g * 16 + 4 * q;
#pragma unroll
            for (int i = 0; i < 16; i++) {
                float nr = lr1 * er - li1 * ei + acc[4 * i], ni = lr1 * ei + li1 * er + acc[4 * i + 2];
                er = lr1 * nr - li1 * ni + acc[4 * i + 1];
                ei = lr1 * ni + li1 * nr + acc[4 * i + 3];
                sts32(ha + i * 128, pack_bf16(nr, er));
                sts32(ha + 16384 + i * 128, pack_bf16(ni, ei));
            }
            fence_async_smem();
            TS(10 + 12 * layer);
            bar_sync(6, 384);
            TS(11 + 12 * layer);
            if (tid == 0) {
                mbar_wait_cluster(BAR(B_RFREE), layer);
                bulk_s2peer(mapa(sb + SM_HH + par * 32768, par ^ 1), sb + SM_HH + par * 32768, 32768, mapa(BAR(B_HPEER), par ^ 1));
            }
            __syncwarp();
            float acc2[32];
            acc_def(acc2);
#pragma unroll 1
            for (int k = 0; k < 2; k++) {
                const uint32_t hb = sb + SM_HH + (par ^ k) * 32768;
                if (k == 1) mbar_wait(BAR(B_HPEER), layer);
                mbar_wait(BAR(B_AFULL + 2 * wg + k), 1);
                mbar_wait(BAR(B_AFULL + 4 + k), 1);
                if (layer == 0) TS(28 + k);
                const uint64_t da = c_desc(2 * wg + k), da2 = c_desc(4 + k);
                wg_fence();
#pragma unroll
                for (int ks = 0; ks < 4; ks++) wgmma_n128<1, 1>(acc, da + ks * dstep, desc_b<128>(hb + ks * 4096), (ks | k) != 0);
#pragma unroll
                for (int ks = 0; ks < 4; ks++) wgmma_n128<1, -1>(acc, da + 512 + ks * dstep, desc_b<128>(hb + 16384 + ks * 4096), 1);
                wg_commit();
#pragma unroll
                for (int ks = 0; ks < 4; ks++) wgmma_n64s<1>(acc2, da2 + ks * dstep, desc_b<128>(hb + wg * 1024 + ks * 4096), 1);
#pragma unroll
                for (int ks = 0; ks < 4; ks++) wgmma_n64s<-1>(acc2, da2 + 512 + ks * dstep, desc_b<128>(hb + 16384 + wg * 1024 + ks * 4096), 1);
                wg_commit();
            }
            wg_wait<1>();
            TS(13 + 12 * layer);
            {
                uint4* dst = g_P + (uint32_t)(((c * 8 + 2 * ((pi_ + 1 + wg) & 3) + par) * 4 + pi_) * 1024 + (tid & 127));
#pragma unroll
                for (int i = 0; i < 8; i++)
                    dst[i * 128] = make_uint4((pack_bf16(acc[8 * i], acc[8 * i + 1]) & 0xfffefffeu) | ptag, pack_bf16(acc[8 * i + 2], acc[8 * i + 3]),
                                              pack_bf16(acc[8 * i + 4], acc[8 * i + 5]), pack_bf16(acc[8 * i + 6], acc[8 * i + 7]));
            }
            wg_wait<0>();
            TS(14 + 12 * layer);
            {
                uint4* dst = g_P + (uint32_t)(((c * 8 + 2 * ((pi_ + 3) & 3) + par) * 4 + pi_) * 1024 + wg * 512 + (tid & 127));
#pragma unroll
                for (int i = 0; i < 4; i++)
                    dst[i * 128] = make_uint4((pack_bf16(acc2[8 * i], acc2[8 * i + 1]) & 0xfffefffeu) | ptag, pack_bf16(acc2[8 * i + 2], acc2[8 * i + 3]),
                                              pack_bf16(acc2[8 * i + 4], acc2[8 * i + 5]), pack_bf16(acc2[8 * i + 6], acc2[8 * i + 7]));
            }
            if (layer == 0) TS(30);
            {
                uint4 v[8];
                fetch_partial(g_P + (uint32_t)(((c * 8 + r) * 4 + ((pi_ - 1 - wg) & 3)) * 1024 + (tid & 127)), ptag, v);
#pragma unroll
                for (int i = 0; i < 8; i++) *(uint4*)(sm + SM_A + wg * 32768 + i * 2048 + (tid & 127) * 16) = v[i];
                fence_async_smem();
                bar_arrive(8, 384);
            }
            if (lane == 0) {
                mbar_arrive(BAR(B_AEMPTY + 2 * wg), 2); mbar_arrive(BAR(B_AEMPTY + 2 * wg + 1), 2);
                mbar_arrive(BAR(B_AEMPTY + 4), 1); mbar_arrive(BAR(B_AEMPTY + 5), 1);
            }
            TS(12 + 12 * layer);
            mbar_wait_cluster(BAR(B_HDONE), layer);
            if (layer == 0) bar_sync(9, 384);
        } else {
            const int t2 = tid - 256;
            const uint8_t* ximg = g_X + (uint32_t)layer * 16 * 8 * 16384;
            mbar_wait(BAR(B_SSQ), layer);
            TS(6 + 12 * layer);
            {
                float rs = rsqrtf(s_rstd[t2] * (1.f / 512.f) + 1e-5f);
                s_rstd[t2] = rs;
                s_rstd[128 + t2] = 2.f * rs;
                if (layer == 1) {
                    unsigned short u = __ldcg((const unsigned short*)(ximg + (uint32_t)(c * 8 * 16384 + (t2 >> 3) * 128 + (t2 & 7) * 2)));
                    s_mean[t2] = __uint_as_float((uint32_t)u << 16) * (1.f / 512.f);
                }
            }
            TS(7 + 12 * layer);
            bar_arrive(4, 384);
            acc_def(acc);
#pragma unroll 1
            for (int kb = 0; kb < 8; kb++) {
                mbar_wait(BAR(B_XFULL + (kb & 3)), (kb >> 2) & 1);
                wg_fence();
#pragma unroll
                for (int ks = 0; ks < 4; ks++)
                    wgmma_n128<1>(acc, desc_a(sb + SM_X + (kb & 3) * 24576 + 16384 + ks * 256), desc_b<128>(sb + SM_X + (kb & 3) * 24576 + ks * 4096), 1);
                wg_commit();
                wg_wait<1>();
                if (kb > 0 && lane == 0) mbar_arrive(BAR(B_XEMPTY + ((kb - 1) & 3)), 1);
            }
            wg_wait<0>();
            if (lane == 0) { mbar_arrive(BAR(B_XEMPTY + 3), 1); mbar_arrive_remote(mapa(BAR(B_RFREE), par ^ 1)); }
            bar_arrive(7, 384);
            bar_sync(3, 128);
            TS(9 + 12 * layer);
            const int m0 = 16 * w + g;
            const uint32_t xoff = (uint32_t)((c * 8 + own) * 16384 + w * 4096 + g * 16 + 4 * q);
            if (layer == 0) {
                const uint8_t* xs = g_X + xoff;
#pragma unroll
                for (int i = 0; i < 16; i++) {
                    float2 rs = *(const float2*)(s_rstd + 8 * i + 2 * q);
                    uint32_t x0v = __ldcg((const uint32_t*)(xs + i * 128)), x1v = __ldcg((const uint32_t*)(xs + 2048 + i * 128));
                    acc[4 * i] = acc[4 * i] * rs.x + bf_lo(x0v);
                    acc[4 * i + 1] = acc[4 * i + 1] * rs.y + bf_hi(x0v);
                    acc[4 * i + 2] = acc[4 * i + 2] * rs.x + bf_lo(x1v);
                    acc[4 * i + 3] = acc[4 * i + 3] * rs.y + bf_hi(x1v);
                }
            } else {
                float d0 = ldbf(p.dskip + 64 * own + m0), d1 = ldbf(p.dskip + 64 * own + m0 + 8);
#pragma unroll
                for (int i = 0; i < 16; i++) {
                    float2 rs = *(const float2*)(s_rstd + 8 * i + 2 * q);
                    float2 mn = *(const float2*)(s_mean + 8 * i + 2 * q);
                    acc[4 * i] = acc[4 * i] * (1.f + rs.x * d0) + mn.x;
                    acc[4 * i + 1] = acc[4 * i + 1] * (1.f + rs.y * d0) + mn.y;
                    acc[4 * i + 2] = acc[4 * i + 2] * (1.f + rs.x * d1) + mn.x;
                    acc[4 * i + 3] = acc[4 * i + 3] * (1.f + rs.y * d1) + mn.y;
                }
            }
            TS(10 + 12 * layer);
            bar_sync(6, 384);
            TS(11 + 12 * layer);
#pragma unroll 1
            for (int k = 0; k < 2; k++) {
                const uint32_t hb = sb + SM_HH + (par ^ k) * 32768;
                if (k == 1) {
                    mbar_wait(BAR(B_HPEER), layer);
                    if (t2 == 0) mbar_arrive_remote(mapa(BAR(B_HDONE), par ^ 1));
                    __syncwarp();
                }
                mbar_wait(BAR(B_AFULL + 6 + k), 1);
                const uint64_t da = c_desc(6 + k);
                wg_fence();
#pragma unroll
                for (int ks = 0; ks < 4; ks++) wgmma_n128<1, 1>(acc, da + ks * dstep, desc_b<128>(hb + ks * 4096), 1);
#pragma unroll
                for (int ks = 0; ks < 4; ks++) wgmma_n128<1, -1>(acc, da + 512 + ks * dstep, desc_b<128>(hb + 16384 + ks * 4096), 1);
                wg_commit();
            }
            wg_wait<0>();
            if (lane == 0) mbar_arrive(BAR(B_AEMPTY + 7), 2);
            if (layer == 0) bar_arrive(9, 384);
            TS(12 + 12 * layer);
            {
                uint4 v[8];
                fetch_partial(g_P + (uint32_t)(((c * 8 + r) * 4 + ((pi_ - 3) & 3)) * 1024 + t2), ptag, v);
                TS(13 + 12 * layer);
                bar_sync(8, 384);
#pragma unroll 1
                for (int sidx = 0; sidx < 3; sidx++) {
#pragma unroll
                    for (int i = 0; i < 8; i++) {
                        acc[8 * i] += bf_lo(v[i].x); acc[8 * i + 1] += bf_hi(v[i].x);
                        acc[8 * i + 2] += bf_lo(v[i].y); acc[8 * i + 3] += bf_hi(v[i].y);
                        acc[8 * i + 4] += bf_lo(v[i].z); acc[8 * i + 5] += bf_hi(v[i].z);
                        acc[8 * i + 6] += bf_lo(v[i].w); acc[8 * i + 7] += bf_hi(v[i].w);
                        v[i] = *(const uint4*)(sm + SM_A + (sidx & 1) * 32768 + i * 2048 + t2 * 16);
                    }
                }
            }
            TS(14 + 12 * layer);
            if (layer == 0) {
                uint8_t* xd = g_X + 16 * 8 * 16384 + xoff;
                const float w0 = (own == 0 && m0 < 2) ? (m0 == 0 ? 0.f : 0.5f) : 1.f;
                float* sq = (float*)(sm + SM_A + 6 * 16384);
#pragma unroll
                for (int i = 0; i < 16; i++) {
                    uint32_t v0 = pack_bf16(acc[4 * i], acc[4 * i + 1]), v1 = pack_bf16(acc[4 * i + 2], acc[4 * i + 3]);
                    *(uint32_t*)(xd + i * 128) = v0;
                    *(uint32_t*)(xd + 2048 + i * 128) = v1;
                    float s0 = w0 * bf_lo(v0) * bf_lo(v0) + bf_lo(v1) * bf_lo(v1);
                    float s1 = w0 * bf_hi(v0) * bf_hi(v0) + bf_hi(v1) * bf_hi(v1);
                    *(float2*)(sq + (8 * w + g) * 128 + ((8 * i + 2 * q + 8 * g) & 127)) = make_float2(s0, s1);
                }
                bar_sync(3, 128);
                float tot = 0.f;
#pragma unroll 8
                for (int k = 0; k < 32; k++) tot += sq[k * 128 + ((t2 + 8 * (k & 7)) & 127)];
                atomicAdd(g_ssq + 2 * 2048 + 128 * c + t2, tot * (2.f / 512.f));
                fence_async_smem();
                bar_sync(3, 128);
                if (lane == 0) mbar_arrive(BAR(B_AEMPTY + 6), 2);
                if (t2 == 0) { fence_async(); red_release(&g_bar[2], 1); }
            } else {
                float* o = p.out + (uint32_t)((128 * c + 32 * q) * 512 + 64 * own + m0);
#pragma unroll
                for (int i = 0; i < 16; i++) {
                    o[(2 * i) * 512] = acc[4 * i];
                    o[(2 * i + 1) * 512] = acc[4 * i + 1];
                    o[(2 * i) * 512 + 8] = acc[4 * i + 2];
                    o[(2 * i + 1) * 512 + 8] = acc[4 * i + 3];
                }
            }
        }
        TS(15 + 12 * layer);
        if (wg == 0) TC(31);
    }
}

typedef CUresult (*EncFn)(CUtensorMap*, CUtensorMapDataType, cuuint32_t, void*, const cuuint64_t*, const cuuint64_t*,
                          const cuuint32_t*, const cuuint32_t*, CUtensorMapInterleave, CUtensorMapSwizzle,
                          CUtensorMapL2promotion, CUtensorMapFloatOOBfill);

void launch_impl(void* const* d_in, void* d_out, int stop) {
    static EncFn enc = nullptr;
    if (!enc) {
        void* fn = nullptr;
        cudaDriverEntryPointQueryResult qr;
        cudaGetDriverEntryPoint("cuTensorMapEncodeTiled", &fn, cudaEnableDefault, &qr);
        enc = (EncFn)fn;
        cudaFuncSetAttribute(fused_kernel, cudaFuncAttributeMaxDynamicSharedMemorySize, SM_TOTAL);
    }
    CUtensorMap tx, tbr, tbi, tcr, tci, tcol;
    {
        void* gx = nullptr;
        cudaGetSymbolAddress(&gx, g_X);
        cuuint64_t gd[5] = {64, 16, 64, 16, 2};
        cuuint64_t gs[4] = {128, 2048, 128 * 1024, 2048 * 1024};
        cuuint32_t bx[5] = {32, 16, 1, 16, 1};
        cuuint32_t es[5] = {1, 1, 1, 1, 1};
        enc(&tcol, CU_TENSOR_MAP_DATA_TYPE_BFLOAT16, 5, gx, gd, gs, bx, es, CU_TENSOR_MAP_INTERLEAVE_NONE,
            CU_TENSOR_MAP_SWIZZLE_64B, CU_TENSOR_MAP_L2_PROMOTION_NONE, CU_TENSOR_MAP_FLOAT_OOB_FILL_NONE);
    }
    {
        cuuint64_t gd[5] = {512, 2, 4, 16, 16};
        cuuint64_t gs[4] = {1024, 32 * 1024, 2 * 1024, 128 * 1024};
        cuuint32_t bx[5] = {64, 2, 4, 16, 1};
        cuuint32_t es[5] = {1, 1, 1, 1, 1};
        enc(&tx, CU_TENSOR_MAP_DATA_TYPE_BFLOAT16, 5, d_in[0], gd, gs, bx, es, CU_TENSOR_MAP_INTERLEAVE_NONE,
            CU_TENSOR_MAP_SWIZZLE_128B, CU_TENSOR_MAP_L2_PROMOTION_L2_128B, CU_TENSOR_MAP_FLOAT_OOB_FILL_NONE);
    }
    auto mk2 = [&](CUtensorMap* m, void* ptr, cuuint32_t rows) {
        cuuint64_t gd[2] = {512, 512};
        cuuint64_t gs[1] = {1024};
        cuuint32_t bx[2] = {64, rows};
        cuuint32_t es[2] = {1, 1};
        enc(m, CU_TENSOR_MAP_DATA_TYPE_BFLOAT16, 2, ptr, gd, gs, bx, es, CU_TENSOR_MAP_INTERLEAVE_NONE,
            CU_TENSOR_MAP_SWIZZLE_128B, CU_TENSOR_MAP_L2_PROMOTION_L2_128B, CU_TENSOR_MAP_FLOAT_OOB_FILL_NONE);
    };
    mk2(&tbr, d_in[6], 32);
    mk2(&tbi, d_in[7], 32);
    mk2(&tcr, d_in[8], 64);
    mk2(&tci, d_in[9], 64);
    Params p;
    p.x0 = (const __nv_bfloat16*)d_in[0];
    p.w_r = (const __nv_bfloat16*)d_in[1];
    p.w_i = (const __nv_bfloat16*)d_in[2];
    p.lam_re = (const __nv_bfloat16*)d_in[4];
    p.lam_im = (const __nv_bfloat16*)d_in[5];
    p.log_dt = (const __nv_bfloat16*)d_in[10];
    p.dskip = (const __nv_bfloat16*)d_in[11];
    p.out = (float*)d_out;
    p.stop = stop;
    cudaLaunchConfig_t cfg = {};
    cfg.gridDim = dim3(NCTA); cfg.blockDim = dim3(NTHREADS); cfg.dynamicSmemBytes = SM_TOTAL; cfg.stream = cudaStreamPerThread;
    cudaLaunchAttribute at[1];
    at[0].id = cudaLaunchAttributeClusterDimension;
    at[0].val.clusterDim.x = 2; at[0].val.clusterDim.y = 1; at[0].val.clusterDim.z = 1;
    cfg.attrs = at; cfg.numAttrs = 1;
    cudaLaunchKernelEx(&cfg, fused_kernel, tx, tbr, tbi, tcr, tci, tcol, p);
}

}

extern "C" void kernel_launch(void* const* d_in, const int* in_sizes, int n_in, void* d_out, int out_size) {
    (void)in_sizes; (void)n_in; (void)out_size;
    launch_impl(d_in, d_out, 100);
}
```

```cpp
#include <cuda_runtime.h>
#include <cuda_bf16.h>
#include <cuda.h>
#include <stdint.h>

namespace {

constexpr int NCTA = 128;
constexpr int NTHREADS = 512;
constexpr int SM_A = 0;
constexpr int SM_X = 131072;
constexpr int SM_H = 196608;
constexpr int SM_HH = SM_X + 32768;
constexpr int SM_M = 229376;
constexpr int SM_TOTAL = 232448;
constexpr int SM_BAR = SM_M;
constexpr int SM_TGT = SM_M + 352;
constexpr int SM_LAM = SM_M + 376;
constexpr int SM_TAB = SM_M + 896;
constexpr int SM_RSTD = SM_M + 1920;
constexpr int SM_MEAN = SM_TAB;
constexpr int SM_T64 = SM_M + 2944;
constexpr int SM_RAW = SM_X + 40960;
constexpr int SM_SSQ = SM_X + 57344;
constexpr int B_FULL0 = 0;
constexpr int B_EMPTY0 = 8;
constexpr int B_FULLC = 12;
constexpr int B_AFULL = 13;
constexpr int B_AEMPTY = 21;
constexpr int B_XFULL = 29;
constexpr int B_XEMPTY = 33;
constexpr int B_AFREE = 37;
constexpr int B_COL = 38;
constexpr int B_SSQ = 39;
constexpr int B_HPEER = 40;
constexpr int B_RFREE = 41;
constexpr int B_HDONE = 42;
constexpr int B_WRDY = 43;
constexpr int NBARS = 44;

__device__ __align__(1024) uint8_t g_X[2 * 16 * 8 * 16384];
__device__ __align__(1024) uint8_t g_A1[8 * 8 * 16384];
__device__ __align__(1024) uint8_t g_A2[8 * 8 * 16384];
__device__ __align__(1024) uint8_t g_E[2 * 8 * 8 * 8192];
__device__ __align__(16) float g_ssq[2 * 2048];
__device__ __align__(16) float g_ssqc[2 * 16 * 2048];
__device__ __align__(16) float g_Dh[512];
__device__ __align__(16) uint4 g_Wfrag[128 * 4 * 256];
__device__ __align__(16) float4 g_Ebuf[2 * 16 * 512];
__device__ __align__(16) uint4 g_P[16 * 8 * 4 * 1024];
__device__ unsigned g_bar[8];
__device__ unsigned g_err;
#define TX(i)
#define TS(i)
#define TC(i)

constexpr unsigned SPIN_LIMIT = 1u << 22;

__device__ __forceinline__ uint32_t s2u(const void* p) { return (uint32_t)__cvta_generic_to_shared(p); }
__device__ __forceinline__ void mbar_init(uint32_t a, uint32_t c) {
    asm volatile("mbarrier.init.shared::cta.b64 [%0], %1;" ::"r"(a), "r"(c) : "memory");
}
__device__ __forceinline__ void mbar_expect(uint32_t a, uint32_t bytes) {
    asm volatile("mbarrier.arrive.expect_tx.shared::cta.b64 _, [%0], %1;" ::"r"(a), "r"(bytes) : "memory");
}
__device__ __forceinline__ void mbar_arrive(uint32_t a, uint32_t cnt) {
    asm volatile("mbarrier.arrive.shared::cta.b64 _, [%0], %1;" ::"r"(a), "r"(cnt) : "memory");
}
__device__ __forceinline__ bool mbar_try(uint32_t a, uint32_t parity) {
    uint32_t ok;
    asm volatile("{\n.reg .pred p;\nmbarrier.try_wait.parity.shared::cta.b64 p, [%1], %2;\nselp.u32 %0, 1, 0, p;\n}"
                 : "=r"(ok) : "r"(a), "r"(parity) : "memory");
    return ok != 0;
}
__device__ __forceinline__ void mbar_wait(uint32_t a, uint32_t parity) {
    asm volatile("{\n.reg .pred p, q;\n.reg .u32 n;\nmov.u32 n, 0;\n"
                 "W_%=:\nmbarrier.try_wait.parity.shared::cta.b64 p, [%0], %1;\n@p bra D_%=;\n"
                 "add.u32 n, n, 1;\nsetp.lt.u32 q, n, 4194304;\n@q bra W_%=;\nD_%=:\n}" ::"r"(a), "r"(parity) : "memory");
}
__device__ __forceinline__ void bulk_g2s(uint32_t dst, const void* src, uint32_t bytes, uint32_t bar) {
    asm volatile("cp.async.bulk.shared::cluster.global.mbarrier::complete_tx::bytes [%0], [%1], %2, [%3];" ::"r"(dst),
                 "l"(src), "r"(bytes), "r"(bar) : "memory");
}
__device__ __forceinline__ void tma_2d(uint32_t dst, const CUtensorMap* m, int c0, int c1, uint32_t bar) {
    asm volatile("cp.async.bulk.tensor.2d.shared::cluster.global.mbarrier::complete_tx::bytes [%0], [%1, {%3,%4}], [%2];" ::"r"(dst),
                 "l"(m), "r"(bar), "r"(c0), "r"(c1) : "memory");
}
__device__ __forceinline__ void tma_5d(uint32_t dst, const CUtensorMap* m, int c0, int c1, int c2, int c3, int c4, uint32_t bar) {
    asm volatile("cp.async.bulk.tensor.5d.shared::cluster.global.mbarrier::complete_tx::bytes [%0], [%1, {%3,%4,%5,%6,%7}], [%2];" ::"r"(dst),
                 "l"(m), "r"(bar), "r"(c0), "r"(c1), "r"(c2), "r"(c3), "r"(c4) : "memory");
}
__device__ __forceinline__ void tma_2d_mc(uint32_t dst, const CUtensorMap* m, int c0, int c1, uint32_t bar) {
    asm volatile("cp.async.bulk.tensor.2d.shared::cluster.global.mbarrier::complete_tx::bytes.multicast::cluster [%0], [%1, {%3,%4}], [%2], %5;" ::"r"(dst),
                 "l"(m), "r"(bar), "r"(c0), "r"(c1), "h"((unsigned short)3) : "memory");
}
__device__ __forceinline__ void tma_5d_mc(uint32_t dst, const CUtensorMap* m, int c0, int c1, int c2, int c3, int c4, uint32_t bar) {
    asm volatile("cp.async.bulk.tensor.5d.shared::cluster.global.mbarrier::complete_tx::bytes.multicast::cluster [%0], [%1, {%3,%4,%5,%6,%7}], [%2], %8;" ::"r"(dst),
                 "l"(m), "r"(bar), "r"(c0), "r"(c1), "r"(c2), "r"(c3), "r"(c4), "h"((unsigned short)3) : "memory");
}
__device__ __forceinline__ void bulk_g2s_mc(uint32_t dst, const void* src, uint32_t bytes, uint32_t bar) {
    asm volatile("cp.async.bulk.shared::cluster.global.mbarrier::complete_tx::bytes.multicast::cluster [%0], [%1], %2, [%3], %4;" ::"r"(dst),
                 "l"(src), "r"(bytes), "r"(bar), "h"((unsigned short)3) : "memory");
}
__device__ __forceinline__ void tma_store_5d(const CUtensorMap* m, int c0, int c1, int c2, int c3, int c4, uint32_t src) {
    asm volatile("cp.async.bulk.tensor.5d.global.shared::cta.bulk_group [%0, {%2,%3,%4,%5,%6}], [%1];" ::"l"(m), "r"(src),
                 "r"(c0), "r"(c1), "r"(c2), "r"(c3), "r"(c4) : "memory");
}
__device__ __forceinline__ uint32_t lds32(uint32_t a) { uint32_t v; asm volatile("ld.shared.u32 %0, [%1];" : "=r"(v) : "r"(a) : "memory"); return v; }
__device__ __forceinline__ uint4 ld_relaxed_u4(const uint4* p) {
    uint4 v;
    asm volatile("ld.relaxed.gpu.global.v4.u32 {%0,%1,%2,%3}, [%4];" : "=r"(v.x), "=r"(v.y), "=r"(v.z), "=r"(v.w) : "l"(p) : "memory");
    return v;
}
__device__ __forceinline__ void fence_async() { asm volatile("fence.proxy.async.global;" ::: "memory"); }
__device__ __forceinline__ void red_relaxed(unsigned* p, unsigned v) {
    asm volatile("red.relaxed.gpu.global.add.u32 [%0], %1;" ::"l"(p), "r"(v) : "memory");
}
__device__ __forceinline__ uint32_t mapa(uint32_t a, uint32_t rank) {
    uint32_t d;
    asm("mapa.shared::cluster.u32 %0, %1, %2;" : "=r"(d) : "r"(a), "r"(rank));
    return d;
}
__device__ __forceinline__ void mbar_arrive_remote(uint32_t ra) {
    asm volatile("mbarrier.arrive.relaxed.cluster.shared::cluster.b64 _, [%0];" ::"r"(ra) : "memory");
}
__device__ __forceinline__ void mbar_wait_cluster(uint32_t a, uint32_t parity) {
    asm volatile("{\n.reg .pred p, q;\n.reg .u32 n;\nmov.u32 n, 0;\n"
                 "W_%=:\nmbarrier.try_wait.parity.acquire.cluster.shared::cta.b64 p, [%0], %1;\n@p bra D_%=;\n"
                 "add.u32 n, n, 1;\nsetp.lt.u32 q, n, 4194304;\n@q bra W_%=;\nD_%=:\n}" ::"r"(a), "r"(parity) : "memory");
}
__device__ __forceinline__ void bulk_s2peer(uint32_t rdst, uint32_t src, uint32_t bytes, uint32_t rbar) {
    asm volatile("cp.async.bulk.shared::cluster.shared::cta.mbarrier::complete_tx::bytes [%0], [%1], %2, [%3];" ::"r"(rdst),
                 "r"(src), "r"(bytes), "r"(rbar) : "memory");
}
__device__ __forceinline__ void fence_async_smem() { asm volatile("fence.proxy.async.shared::cta;" ::: "memory"); }
__device__ __forceinline__ void wg_fence() { asm volatile("wgmma.fence.sync.aligned;" ::: "memory"); }
__device__ __forceinline__ void wg_commit() { asm volatile("wgmma.commit_group.sync.aligned;" ::: "memory"); }
template <int N> __device__ __forceinline__ void wg_wait() { asm volatile("wgmma.wait_group.sync.aligned %0;" ::"n"(N) : "memory"); }
__device__ __forceinline__ void bar_sync(int id, int n) { asm volatile("bar.sync %0, %1;" ::"r"(id), "r"(n) : "memory"); }
__device__ __forceinline__ void bar_arrive(int id, int n) { asm volatile("bar.arrive %0, %1;" ::"r"(id), "r"(n) : "memory"); }
__device__ __forceinline__ unsigned ld_acquire(const unsigned* p) {
    unsigned v;
    asm volatile("ld.acquire.gpu.global.u32 %0, [%1];" : "=r"(v) : "l"(p) : "memory");
    return v;
}
__device__ __forceinline__ void red_release(unsigned* p, unsigned v) {
    asm volatile("red.release.gpu.global.add.u32 [%0], %1;" ::"l"(p), "r"(v) : "memory");
}
__device__ __forceinline__ void wait_count(const unsigned* p, unsigned target) {
    unsigned n = 0;
#pragma unroll 1
    while ((int)(ld_acquire(p) - target) < 0 && ++n < SPIN_LIMIT) {}
}
__device__ __forceinline__ float4 ld_relaxed_f4(const float4* p) {
    float4 v;
    asm volatile("ld.relaxed.gpu.global.v4.f32 {%0,%1,%2,%3}, [%4];" : "=f"(v.x), "=f"(v.y), "=f"(v.z), "=f"(v.w) : "l"(p) : "memory");
    return v;
}
__device__ __forceinline__ void st_relaxed_f4(float4* p, float4 v) {
    asm volatile("st.relaxed.gpu.global.v4.f32 [%0], {%1,%2,%3,%4};" ::"l"(p), "f"(v.x), "f"(v.y), "f"(v.z), "f"(v.w) : "memory");
}
__device__ __forceinline__ uint32_t pack_bf16(float lo, float hi) {
    uint32_t r;
    asm("cvt.rn.bf16x2.f32 %0, %1, %2;" : "=r"(r) : "f"(hi), "f"(lo));
    return r;
}
__device__ __forceinline__ float bf_lo(uint32_t v) { return __uint_as_float(v << 16); }
__device__ __forceinline__ float bf_hi(uint32_t v) { return __uint_as_float(v & 0xffff0000u); }
__device__ __forceinline__ void sts32(uint32_t a, uint32_t v) { asm volatile("st.shared.u32 [%0], %1;" ::"r"(a), "r"(v) : "memory"); }
__device__ __forceinline__ void sts128(uint32_t a, uint4 v) {
    asm volatile("st.shared.v4.u32 [%0], {%1,%2,%3,%4};" ::"r"(a), "r"(v.x), "r"(v.y), "r"(v.z), "r"(v.w) : "memory");
}

__device__ __forceinline__ uint64_t desc_ni(uint32_t addr, uint32_t lbo, uint32_t sbo) {
    return (uint64_t)((addr & 0x3FFFF) >> 4) | ((uint64_t)(lbo >> 4) << 16) | ((uint64_t)(sbo >> 4) << 32);
}
__device__ __forceinline__ uint64_t desc_a(uint32_t addr) { return desc_ni(addr, 128, 1024); }
template <int N> __device__ __forceinline__ uint64_t desc_b(uint32_t addr) { return desc_ni(addr, 16 * N, 128); }
__device__ __forceinline__ uint64_t desc_k(uint32_t addr) {
    return (uint64_t)((addr & 0x3FFFF) >> 4) | (1ull << 16) | (64ull << 32) | (1ull << 62);
}
__device__ __forceinline__ uint64_t desc_mn(uint32_t addr, uint32_t lbo) {
    return (uint64_t)((addr & 0x3FFFF) >> 4) | ((uint64_t)(lbo >> 4) << 16) | (64ull << 32) | (1ull << 62);
}

#define ACC8(d, o) "+f"(d[o + 0]), "+f"(d[o + 1]), "+f"(d[o + 2]), "+f"(d[o + 3]), "+f"(d[o + 4]), "+f"(d[o + 5]), "+f"(d[o + 6]), "+f"(d[o + 7])
template <int TB, int SA = 1>
__device__ __forceinline__ void wgmma_n128(float (&d)[64], uint64_t da, uint64_t db, int sd) {
    asm volatile(
        "{\n.reg .pred p;\nsetp.ne.b32 p, %66, 0;\n"
        "wgmma.mma_async.sync.aligned.m64n128k16.f32.bf16.bf16 "
        "{%0,%1,%2,%3,%4,%5,%6,%7,%8,%9,%10,%11,%12,%13,%14,%15,%16,%17,%18,%19,%20,%21,%22,%23,%24,%25,%26,%27,%28,%29,%30,%31,"
        "%32,%33,%34,%35,%36,%37,%38,%39,%40,%41,%42,%43,%44,%45,%46,%47,%48,%49,%50,%51,%52,%53,%54,%55,%56,%57,%58,%59,%60,%61,%62,%63},"
        " %64, %65, p, %68, 1, 0, %67;\n}"
        : ACC8(d, 0), ACC8(d, 8), ACC8(d, 16), ACC8(d, 24), ACC8(d, 32), ACC8(d, 40), ACC8(d, 48), ACC8(d, 56)
        : "l"(da), "l"(db), "r"(sd), "n"(TB), "n"(SA));
}
template <int N> __device__ __forceinline__ void acc_def(float (&d)[N]) {
#pragma unroll
    for (int i = 0; i < N; i++) d[i] = 0.f;
}
template <int TB>
__device__ __forceinline__ void wgmma_n64(float (&d)[32], uint64_t da, uint64_t db, int sd) {
    asm volatile(
        "{\n.reg .pred p;\nsetp.ne.b32 p, %34, 0;\n"
        "wgmma.mma_async.sync.aligned.m64n64k16.f32.bf16.bf16 "
        "{%0,%1,%2,%3,%4,%5,%6,%7,%8,%9,%10,%11,%12,%13,%14,%15,%16,%17,%18,%19,%20,%21,%22,%23,%24,%25,%26,%27,%28,%29,%30,%31},"
        " %32, %33, p, 1, 1, 0, %35;\n}"
        : ACC8(d, 0), ACC8(d, 8), ACC8(d, 16), ACC8(d, 24)
        : "l"(da), "l"(db), "r"(sd), "n"(TB));
}
template <int SA>
__device__ __forceinline__ void wgmma_n64s(float (&d)[32], uint64_t da, uint64_t db, int sd) {
    asm volatile(
        "{\n.reg .pred p;\nsetp.ne.b32 p, %34, 0;\n"
        "wgmma.mma_async.sync.aligned.m64n64k16.f32.bf16.bf16 "
        "{%0,%1,%2,%3,%4,%5,%6,%7,%8,%9,%10,%11,%12,%13,%14,%15,%16,%17,%18,%19,%20,%21,%22,%23,%24,%25,%26,%27,%28,%29,%30,%31},"
        " %32, %33, p, %35, 1, 0, 1;\n}"
        : ACC8(d, 0), ACC8(d, 8), ACC8(d, 16), ACC8(d, 24)
        : "l"(da), "l"(db), "r"(sd), "n"(SA));
}
__device__ __forceinline__ void wgmma_n64_rs(float (&d)[32], uint32_t a0, uint32_t a1, uint32_t a2, uint32_t a3, uint64_t db, int sd) {
    asm volatile(
        "{\n.reg .pred p;\nsetp.ne.b32 p, %37, 0;\n"
        "wgmma.mma_async.sync.aligned.m64n64k16.f32.bf16.bf16 "
        "{%0,%1,%2,%3,%4,%5,%6,%7,%8,%9,%10,%11,%12,%13,%14,%15,%16,%17,%18,%19,%20,%21,%22,%23,%24,%25,%26,%27,%28,%29,%30,%31},"
        " {%32,%33,%34,%35}, %36, p, 1, 1, 1;\n}"
        : ACC8(d, 0), ACC8(d, 8), ACC8(d, 16), ACC8(d, 24)
        : "r"(a0), "r"(a1), "r"(a2), "r"(a3), "l"(db), "r"(sd));
}

struct Params {
    const __nv_bfloat16* x0;
    const __nv_bfloat16* w_r;
    const __nv_bfloat16* w_i;
    const __nv_bfloat16* lam_re;
    const __nv_bfloat16* lam_im;
    const __nv_bfloat16* log_dt;
    const __nv_bfloat16* dskip;
    float* out;
    int stop;
};

__device__ __forceinline__ float ldbf(const __nv_bfloat16* p) { return __bfloat162float(*p); }

__device__ __forceinline__ void dft_fp(int j, int& f, int& ph) {
    int cs = j >> 1;
    if (j == 1) { f = 256; ph = 0; }
    else { f = cs; ph = (j & 1) ? 128 : 0; }
}

__device__ __forceinline__ void gen_col_consts(uint8_t* sm, int tid) {
    const unsigned short* t64 = (const unsigned short*)(sm + SM_T64);
    const uint32_t sb = s2u(sm);
#pragma unroll 1
    for (int ch = tid; ch < 2560; ch += 256) {
        int c8 = (ch >> 3) & 7, m = (ch & 7) | ((ch >> 3) & 56), po, pi, step, base;
        if (ch < 2048) {
            pi = (ch >> 9) & 1; po = (m >> 3) & 1;
            step = 32 * (ch >> 10) + 8 * (m >> 4) + (m & 7);
            base = c8 * 8;
        } else {
            pi = m >> 5; po = c8 >> 2;
            step = 2 * (m & 31);
            base = (c8 & 3) * 8;
        }
        int idx = base * step + ((po == pi) ? 0 : (po == 0 ? 48 : 16));
        uint32_t v[4];
#pragma unroll
        for (int e = 0; e < 4; e++) {
            uint32_t lo = t64[idx & 63], hi = t64[(idx + step) & 63];
            idx += 2 * step;
            v[e] = lo | (hi << 16);
        }
        sts128(sb + SM_X + ch * 16, make_uint4(v[0], v[1], v[2], v[3]));
    }
}

__device__ __forceinline__ void fetch_partial(const uint4* ps_, uint32_t ptag, uint4 (&v)[8]) {
    unsigned n = 0;
#pragma unroll 1
    while (true) {
        if ((threadIdx.x & 31) == 31) {
#pragma unroll 1
            while (true) {
                uint32_t t0, t1;
                asm volatile("ld.relaxed.gpu.global.u32 %0, [%1];" : "=r"(t0) : "l"(ps_ + 3 * 128) : "memory");
                asm volatile("ld.relaxed.gpu.global.u32 %0, [%1];" : "=r"(t1) : "l"(ps_ + 7 * 128) : "memory");
                if (!(((t0 ^ ptag) | (t1 ^ ptag)) & 0x00010001u) || ++n >= SPIN_LIMIT) break;
            }
        }
        __syncwarp();
        uint32_t bad = 0;
#pragma unroll
        for (int i = 0; i < 8; i++) { v[i] = ld_relaxed_u4(ps_ + i * 128); bad |= (v[i].x ^ ptag) & 0x00010001u; }
        if (!__any_sync(~0u, bad) || ++n >= SPIN_LIMIT) break;
    }
}

__global__ void __launch_bounds__(NTHREADS, 1)
fused_kernel(const __grid_constant__ CUtensorMap tm_x, const __grid_constant__ CUtensorMap tm_bre,
             const __grid_constant__ CUtensorMap tm_bim, const __grid_constant__ CUtensorMap tm_cre,
             const __grid_constant__ CUtensorMap tm_cim, const __grid_constant__ CUtensorMap tm_col, const Params p) {
    extern __shared__ __align__(1024) uint8_t sm[];
    const uint32_t sb = s2u(sm);
    const int tid = threadIdx.x, b = blockIdx.x;
    const int c = b >> 3, r = b & 7;
    const int par = r & 1, pi_ = r >> 1, own = 4 * par + pi_;
    const int wg = __shfl_sync(~0u, tid >> 7, 0), w = __shfl_sync(~0u, (tid >> 5) & 3, 0), lane = tid & 31, g = lane >> 2, q = lane & 3;
    auto BAR = [&](int i) { return sb + SM_BAR + 8 * i; };
    unsigned* s_tgt = (unsigned*)(sm + SM_TGT);

    if (tid < NBARS) {
        int cnt = 1;
        if ((tid >= B_EMPTY0 && tid < B_EMPTY0 + 4) || (tid >= B_XEMPTY && tid < B_XEMPTY + 4)) cnt = 24;
        if (tid == B_RFREE) cnt = 12;
        if (tid >= B_AEMPTY && tid < B_AEMPTY + 8) cnt = 8;
        if (tid == B_AFREE) cnt = 4;
        mbar_init(BAR(tid), cnt);
        asm volatile("fence.mbarrier_init.release.cluster;" ::: "memory");
    }
    asm volatile("barrier.cluster.arrive.release.aligned;" ::: "memory");
    if (tid >= 64 && tid < 69) {
        s_tgt[tid - 64] = ((ld_acquire(&g_bar[tid - 64]) >> 7) + 1u) << 7;
    } else if (tid >= 96 && tid < 112) {
        g_ssq[2048 + 16 * b + tid - 96] = 0.f;
    } else if (tid >= 128 && tid < 384) {
        int i = tid - 128;
        __nv_bfloat16 h = __float2bfloat16(cospif((float)i * (1.f / 256.f)));
        ((__nv_bfloat16*)(sm + SM_TAB))[i] = h;
        ((__nv_bfloat16*)(sm + SM_TAB))[i + 256] = __hneg(h);
        if ((i & 7) == 0) {
            ((__nv_bfloat16*)(sm + SM_T64))[i >> 3] = h;
            ((__nv_bfloat16*)(sm + SM_T64))[(i >> 3) + 32] = __hneg(h);
        }
        if (i < 128) ((float4*)g_ssqc)[b * 128 + i] = make_float4(0.f, 0.f, 0.f, 0.f);
    } else if (tid >= 416) {
        int i = tid - 416;
        int ps = i < 64 ? 64 * r + i : 32 * c + i - 64;
        float lr = ldbf(p.lam_re + ps), li = ldbf(p.lam_im + ps);
        float dt = __bfloat162float(__float2bfloat16(expf(ldbf(p.log_dt + ps))));
        float mag = expf(lr * dt), t = li * dt * 0.15915494309189535f, sn, cs;
        t -= rintf(t);
        sincospif(2.f * t, &sn, &cs);
        float er = mag * cs, ei = mag * sn;
        if (i < 64) {
            *(float2*)(sm + SM_LAM + i * 8) = make_float2(er, ei);
        } else {
            er -= 1.f;
            float inv = 1.f / (lr * lr + li * li);
            *(float2*)(sm + SM_RSTD + (i - 64) * 8) = make_float2((er * lr + ei * li) * inv, (ei * lr - er * li) * inv);
        }
    } else if (tid >= 384 && tid < 390) {
        const CUtensorMap* tm = tid == 384 ? &tm_x : tid == 385 ? &tm_bre : tid == 386 ? &tm_bim : tid == 387 ? &tm_cre : tid == 388 ? &tm_cim : &tm_col;
        asm volatile("prefetch.tensormap [%0];" ::"l"(tm) : "memory");
    }
    __syncwarp();
    asm volatile("barrier.cluster.wait.acquire.aligned;" ::: "memory");

    if (wg == 3) {
        asm volatile("setmaxnreg.dec.sync.aligned.u32 56;");
        if (w > 0) {
            bar_arrive(10, 480);
#pragma unroll 1
            for (int i = tid - 416; i < 1024 + 128; i += 96) {
                if (i < 1024) g_P[(uint32_t)(b * 4 + (i >> 8)) * 1024 + (3 + 4 * ((i >> 7) & 1)) * 128 + (i & 127)] = make_uint4(0, 0, 0, 0);
                else g_Ebuf[b * 128 + i - 1024] = make_float4(0.f, 0.f, 0.f, 0.f);
            }
#pragma unroll 1
            for (int task = tid - 416; task < 256; task += 96) {
                const int cb = task & 127, kq = 2 * b + (task >> 7), k1 = kq >> 2, qq = kq & 3;
                const unsigned short* wr_ = (const unsigned short*)p.w_r + (k1 + 128 * qq) * 257;
                const unsigned short* wi_ = (const unsigned short*)p.w_i + (k1 + 128 * qq) * 257;
                const int c0 = cb == 0 ? 256 : 2 * cb, c1 = 2 * cb + 1;
                uint32_t wf[16];
#pragma unroll
                for (int i = 0; i < 8; i++) {
                    int o = (512 * (i >> 1) + 64 * (i & 1)) * 257;
                    wf[i] = (uint32_t)__ldg(wr_ + o + c0) | ((uint32_t)__ldg(wi_ + o + c0) << 16);
                    wf[8 + i] = (uint32_t)__ldg(wr_ + o + c1) | ((uint32_t)__ldg(wi_ + o + c1) << 16);
                }
                uint4* wd = g_Wfrag + (uint32_t)(cb * 1024 + kq);
#pragma unroll
                for (int i = 0; i < 4; i++) wd[i * 256] = make_uint4(wf[4 * i], wf[4 * i + 1], wf[4 * i + 2], wf[4 * i + 3]);
            }
            __syncwarp();
            bar_sync(11, 96);
            if (w == 3) {
                if (lane == 0) red_release(&g_bar[4], 1);
                return;
            }
            if (w == 2) {
#pragma unroll 1
                for (int layer = 0; layer < 2; layer++) {
                    __syncwarp();
                    bar_sync(6, 416);
                    if (lane == 0) {
                        mbar_wait_cluster(BAR(B_RFREE), layer);
                        bulk_s2peer(mapa(sb + SM_HH + par * 32768, par ^ 1), sb + SM_HH + par * 32768, 32768, mapa(BAR(B_HPEER), par ^ 1));
                    }
                }
                return;
            }
            bar_sync(2, 416);
            if (lane == 0) { TX(5); fence_async(); red_release(&g_bar[0], 1); TX(6); }
#pragma unroll 1
            for (int layer = 0; layer < 2; layer++) {
                __syncwarp();
                bar_sync(5, 416);
                if (lane == 0) {
                    TX(0 + 8 * layer);
                    tma_store_5d(&tm_col, 32 * (b & 1), 0, b >> 1, 0, layer, sb + SM_RAW);
                    asm volatile("cp.reduce.async.bulk.global.shared::cta.bulk_group.add.f32 [%0], [%1], 8192;" ::"l"(g_ssqc + (layer * 16 + (b & 15)) * 2048),
                                 "r"(sb + SM_SSQ) : "memory");
                    asm volatile("cp.async.bulk.commit_group;" ::: "memory");
                    asm volatile("cp.async.bulk.wait_group 0;" ::: "memory");
                    TX(1 + 8 * layer);
                    fence_async();
                    red_release(&g_bar[1 + 2 * layer], 1);
                    TX(2 + 8 * layer);
                }
            }
        } else if (tid == 384) {
#pragma unroll 1
            for (int kb = 0; kb < 8; kb++) {
                int s = kb < 6 ? kb : kb - 4;
                uint32_t dst = s < 2 ? sb + SM_A + 65536 + s * 24576 : sb + SM_X + (s - 2) * 24576;
                if (kb >= 6) mbar_wait_cluster(BAR(B_EMPTY0 + s), 0);
                uint32_t fb = BAR(B_FULL0 + kb);
                mbar_expect(fb, 24576);
                tma_5d_mc(dst + par * 8192, &tm_x, kb * 64, 0, 0, 8 * par, c, fb);
                tma_2d_mc(dst + 16384 + par * 4096, par ? &tm_bim : &tm_bre, kb * 64, 32 * c, fb);
                if (kb == 5) {
#pragma unroll 1
                    for (int k2 = par; k2 < 8; k2 += 2) {
                        asm volatile("cp.async.bulk.prefetch.tensor.2d.L2.global [%0, {%1,%2}];" ::"l"((c & 1) ? &tm_cim : &tm_cre), "r"(64 * (c >> 1)), "r"(k2 * 64) : "memory");
                        if (k2 < 4) {
                            asm volatile("cp.async.bulk.prefetch.tensor.5d.L2.global [%0, {%1,%2,%3,%4,%5}];" ::"l"(&tm_x), "r"((6 + (k2 >> 1)) * 64), "r"(0), "r"(0), "r"(8 * par), "r"(c) : "memory");
                            asm volatile("cp.async.bulk.prefetch.tensor.2d.L2.global [%0, {%1,%2}];" ::"l"(par ? &tm_bim : &tm_bre), "r"((6 + (k2 >> 1)) * 64), "r"(32 * c) : "memory");
                        }
                    }
                }
                if (kb == 7) {
                    mbar_wait_cluster(BAR(B_EMPTY0 + 0), 0);
                    mbar_wait_cluster(BAR(B_EMPTY0 + 1), 0);
                    mbar_expect(BAR(B_FULLC), 65536);
#pragma unroll 1
                    for (int k2 = par; k2 < 8; k2 += 2)
                        tma_2d_mc(sb + SM_A + 65536 + k2 * 8192, (c & 1) ? &tm_cim : &tm_cre, 64 * (c >> 1), k2 * 64, BAR(B_FULLC));
                }
            }
#pragma unroll 1
            for (int layer = 0; layer < 2; layer++) {
                if (layer == 1) {
                    mbar_wait(BAR(B_AEMPTY + 6), 1);
#pragma unroll 1
                    for (int s = 0; s < 8; s++) {
                        mbar_wait(BAR(B_AEMPTY + s), 1);
                        mbar_expect(BAR(B_AFULL + s), 16384);
                        bulk_g2s(sb + SM_A + s * 16384, g_A1 + (uint32_t)(r * 8 + s) * 16384, 16384, BAR(B_AFULL + s));
                    }
                }
                wait_count(&g_bar[2 * layer], s_tgt[2 * layer]);
                TX(4 + 8 * layer);
                fence_async();
                mbar_expect(BAR(B_COL), 16384 + 8192);
                tma_5d(sb + SM_RAW, &tm_col, 32 * (b & 1), 0, b >> 1, 0, layer, BAR(B_COL));
                bulk_g2s(sb + SM_SSQ, g_ssq + layer * 2048, 8192, BAR(B_COL));
                if (layer == 0) {
                    wait_count(&g_bar[4], s_tgt[4]);
                    mbar_arrive(BAR(B_WRDY), 1);
                }
                if (layer == 0) {
                    mbar_wait(BAR(B_AFREE), 0);
                    mbar_wait(BAR(B_COL), 0);
#pragma unroll 1
                    for (int s = 0; s < 8; s++) {
                        mbar_expect(BAR(B_AFULL + s), 16384);
                        bulk_g2s(sb + SM_A + s * 16384, g_A1 + (uint32_t)(r * 8 + s) * 16384, 16384, BAR(B_AFULL + s));
                    }
                }
                wait_count(&g_bar[1 + 2 * layer], s_tgt[1 + 2 * layer]);
                TX(3 + 8 * layer);
                fence_async();
                const uint8_t* xsrc = g_X + (uint32_t)(layer * 16 + c) * 8 * 16384;
                const uint8_t* esrc = g_E + (uint32_t)(layer * 8 + own) * 8 * 8192;
                mbar_arrive(BAR(B_SSQ), 1);
                mbar_expect(BAR(B_HPEER), 32768);
#pragma unroll 1
                for (int it = 0; it < 12; it++) {
                    if (it < 8) {
                        int st = it & 3, f = layer * 2 + (it >> 2);
                        if (f > 0) mbar_wait_cluster(BAR(B_XEMPTY + st), (f - 1) & 1);
                        mbar_expect(BAR(B_XFULL + st), 24576);
                        bulk_g2s_mc(sb + SM_X + st * 24576 + par * 8192, xsrc + (uint32_t)it * 16384 + par * 8192, 8192, BAR(B_XFULL + st));
                        bulk_g2s(sb + SM_X + st * 24576 + 16384, esrc + (uint32_t)it * 8192, 8192, BAR(B_XFULL + st));
                    }
                    if (it >= 4) {
                        int s = it - 4, tile = 4 * par + ((pi_ + 1 + (s >> 1)) & 3), sl = r ^ (s & 1);
                        mbar_wait(BAR(B_AEMPTY + s), 0);
                        uint32_t fb = BAR(B_AFULL + s), dst = sb + SM_A + s * 16384;
                        mbar_expect(fb, 16384);
                        if (layer == 1) {
                            tma_2d(dst, &tm_cre, 64 * sl, 64 * tile, fb);
                            tma_2d(dst + 8192, &tm_cim, 64 * sl, 64 * tile, fb);
                        } else {
                            bulk_g2s(dst, g_A2 + (uint32_t)(sl * 8 + tile) * 16384, 16384, fb);
                        }
                    }
                }
            }
        }
        return;
    }

    asm volatile("setmaxnreg.inc.sync.aligned.u32 152;");
    TS(0);
    if (wg == 0) TC(30);
    {
        const int f = 32 * r + lane;
        float cd, sd;
        __sincosf((float)f * (6.283185307179586f / 512.f), &sd, &cd);
        const uint32_t dst = sb + SM_A + (lane >> 2) * 1024 + (lane & 3) * 32;
#pragma unroll 1
        for (int ch = tid >> 5; ch < 64; ch += 12) {
            int a = (8 * ch * f) & 511;
            a = a >= 256 ? a - 512 : a;
            float cs, sn;
            __sincosf((float)a * (6.283185307179586f / 512.f), &sn, &cs);
            float cv[8], sv[8];
#pragma unroll
            for (int e = 0; e < 8; e++) {
                cv[e] = cs; sv[e] = -sn;
                float t = cs * cd - sn * sd;
                sn = sn * cd + cs * sd;
                cs = t;
            }
            uint4 o1 = make_uint4(pack_bf16(sv[0], sv[1]), pack_bf16(sv[2], sv[3]), pack_bf16(sv[4], sv[5]), pack_bf16(sv[6], sv[7]));
            if (f == 0) o1 = make_uint4(0xbf803f80u, 0xbf803f80u, 0xbf803f80u, 0xbf803f80u);
            uint32_t a0 = dst + (ch >> 3) * 8192 + (ch & 7) * 128;
            sts128(a0, make_uint4(pack_bf16(cv[0], cv[1]), pack_bf16(cv[2], cv[3]), pack_bf16(cv[4], cv[5]), pack_bf16(cv[6], cv[7])));
            sts128(a0 + 16, o1);
        }
    }
    fence_async_smem();
    bar_sync(10, 480);
    TS(1);
    uint4 pre[4];
    if (wg < 2) {
        const uint4* src = (const uint4*)(p.x0 + (uint32_t)(128 * c + 16 * r + 8 * wg + 2 * w) * 512) + lane;
#pragma unroll
        for (int i = 0; i < 4; i++) pre[i] = __ldg(src + 32 * i);
    } else {
        pre[0] = __ldg((const uint4*)p.dskip + 2 * lane);
        pre[1] = __ldg((const uint4*)p.dskip + 2 * lane + 1);
        pre[2] = pre[0]; pre[3] = pre[0];
    }

    {
        float acc[32];
        acc_def(acc);
#pragma unroll 1
        for (int kb = 0; kb < 8; kb++) {
            int s = kb < 6 ? kb : kb - 4;
            uint32_t src = (s < 2 ? sb + SM_A + 65536 + s * 24576 : sb + SM_X + (s - 2) * 24576) + wg * 8192;
            mbar_wait(BAR(B_FULL0 + kb), 0);
            if (tid == 0) TX(24 + kb);
            __syncwarp();
            wg_fence();
#pragma unroll
            for (int ks = 0; ks < 4; ks++)
                wgmma_n64<0>(acc, desc_a(sb + SM_A + kb * 8192 + ks * 256), desc_k(src + ks * 32), 1);
            wg_commit();
            wg_wait<1>();
            if (kb > 0 && kb <= 4 && lane == 0) { mbar_arrive(BAR(B_EMPTY0 + kb - 1), 1); mbar_arrive_remote(mapa(BAR(B_EMPTY0 + kb - 1), par ^ 1)); }
        }
        wg_wait<0>();
        TS(2);
        if (wg < 2) {
            uint8_t* dst = g_X + (uint32_t)((c * 8 + r) * 16384 + w * 4096 + wg * 1024 + g * 16 + 4 * q);
#pragma unroll
            for (int i = 0; i < 8; i++) {
                *(uint32_t*)(dst + i * 128) = pack_bf16(acc[4 * i], acc[4 * i + 1]);
                *(uint32_t*)(dst + 2048 + i * 128) = pack_bf16(acc[4 * i + 2], acc[4 * i + 3]);
            }
#pragma unroll
            for (int rr = 0; rr < 2; rr++) {
                int t = 16 * r + 8 * wg + 2 * w + rr;
                uint32_t u[8] = {pre[2 * rr].x, pre[2 * rr].y, pre[2 * rr].z, pre[2 * rr].w, pre[2 * rr + 1].x, pre[2 * rr + 1].y, pre[2 * rr + 1].z, pre[2 * rr + 1].w};
                float s = 0.f;
#pragma unroll
                for (int i = 0; i < 8; i++) s += bf_lo(u[i]) + bf_hi(u[i]);
#pragma unroll
                for (int o = 16; o; o >>= 1) s += __shfl_xor_sync(~0u, s, o);
                float m = s * (1.f / 512.f), ss = 0.f;
#pragma unroll
                for (int i = 0; i < 8; i++) { float d0 = bf_lo(u[i]) - m, d1 = bf_hi(u[i]) - m; ss += d0 * d0 + d1 * d1; }
#pragma unroll
                for (int o = 16; o; o >>= 1) ss += __shfl_xor_sync(~0u, ss, o);
                if (lane == 0) g_ssq[128 * c + 8 * ((t >> 1) & 15) + 2 * (t >> 5) + (t & 1)] = ss;
            }
        } else {
            uint8_t* dst = g_A1 + (uint32_t)(((c >> 1) * 8 + r) * 16384 + (c & 1) * 8192 + w * 256 + q * 32 + g * 2);
            const float wj0 = (r == 0 && w == 0 && g < 2) ? (g == 0 ? 0.f : 1.f / 512.f) : 2.f / 512.f;
#pragma unroll
            for (int i = 0; i < 4; i++) {
#pragma unroll
                for (int e = 0; e < 2; e++) {
                    float2 cf = *(const float2*)(sm + SM_RSTD + (8 * i + 2 * q + e) * 8);
#pragma unroll
                    for (int h = 0; h < 2; h++) {
                        float wj = h == 0 ? wj0 : 2.f / 512.f;
                        float pr = acc[4 * i + 2 * h + e] * wj, pi = acc[16 + 4 * i + 2 * h + e] * wj;
                        uint8_t* d2 = dst + i * 2048 + h * 128 + e * 16;
                        *(__nv_bfloat16*)(d2) = __float2bfloat16(cf.x * pr - cf.y * pi);
                        *(__nv_bfloat16*)(d2 + 1024) = __float2bfloat16(cf.x * pi + cf.y * pr);
                    }
                }
            }
            int j = 64 * r + 4 * c + w, f, ph;
            dft_fp(j, f, ph);
            uint32_t u[8] = {pre[0].x, pre[0].y, pre[0].z, pre[0].w, pre[1].x, pre[1].y, pre[1].z, pre[1].w};
            float s = 0.f;
            int idx = 16 * lane * f + ph;
#pragma unroll
            for (int i = 0; i < 16; i++) {
                int a = idx & 511;
                idx += f;
                a = a >= 256 ? a - 512 : a;
                s += ((i & 1) ? bf_hi(u[i >> 1]) : bf_lo(u[i >> 1])) * __cosf((float)a * (6.283185307179586f / 512.f));
            }
#pragma unroll
            for (int o = 16; o; o >>= 1) s += __shfl_xor_sync(~0u, s, o);
            if (lane == 0) g_Dh[j] = s;
        }
        bar_sync(2, 416);
        TS(3);
    }

    if (wg == 2) {
        float acc[32];
        acc_def(acc);
        mbar_wait(BAR(B_FULLC), 0);
        wg_fence();
#pragma unroll 1
        for (int kb = 0; kb < 8; kb++) {
#pragma unroll
            for (int ks = 0; ks < 4; ks++)
                wgmma_n64<1>(acc, desc_a(sb + SM_A + kb * 8192 + ks * 256), desc_mn(sb + SM_A + 65536 + kb * 8192 + ks * 2048, 8192), 1);
            wg_commit();
        }
        wg_wait<0>();
        fence_async_smem();
        if (lane == 0) mbar_arrive(BAR(B_AFREE), 1);
        uint8_t* dst = g_A2 + (uint32_t)(((c >> 1) * 8 + r) * 16384 + (c & 1) * 8192 + w * 2048 + g * 16 + 4 * q);
#pragma unroll
        for (int i = 0; i < 8; i++) {
            *(uint32_t*)(dst + i * 128) = pack_bf16(acc[4 * i], acc[4 * i + 1]);
            *(uint32_t*)(dst + 1024 + i * 128) = pack_bf16(acc[4 * i + 2], acc[4 * i + 3]);
        }
        const int m = 4 * c + w, jp = 64 * r + m;
        int fp, php;
        dft_fp(jp, fp, php);
        const __nv_bfloat16* tab = (const __nv_bfloat16*)(sm + SM_TAB);
        const __nv_bfloat16* dh = (const __nv_bfloat16*)(sm + SM_RSTD);
#pragma unroll 1
        for (int it = 0; it < 4; it++) {
            if (it == 2) {
                if (tid == 256) wait_count(&g_bar[0], s_tgt[0]);
                bar_sync(3, 128);
                float4 d4 = __ldcg((const float4*)g_Dh + (tid - 256));
                *(uint2*)(sm + SM_RSTD + (tid - 256) * 8) = make_uint2(pack_bf16(d4.x, d4.y), pack_bf16(d4.z, d4.w));
                bar_sync(3, 128);
            }
            const int ch = lane + 32 * (it & 1);
            float v[8];
#pragma unroll
            for (int e = 0; e < 8; e++) {
                int j = 8 * ch + e, f, ph;
                dft_fp(j, f, ph);
                float wj = j == 0 ? 0.f : (j == 1 ? 1.f / 512.f : 2.f / 512.f);
                if (it < 2) {
                    v[e] = wj * __bfloat162float(tab[(jp * f + ph) & 511]);
                } else {
                    float gsum = 0.f;
#pragma unroll
                    for (int sgn = 0; sgn < 2; sgn++) {
                        int mm = (sgn ? f - fp : f + fp) & 511, pp = (sgn ? ph - php : ph + php) & 511;
                        if (mm > 256) { mm = 512 - mm; pp = (512 - pp) & 511; }
                        int odd = (pp >> 7) & 1;
                        float t = __bfloat162float(dh[mm == 256 ? 1 : 2 * mm + odd]);
                        if (odd && (mm & 255) == 0) t = 0.f;
                        gsum += (pp & 256) ? -t : t;
                    }
                    v[e] = 0.5f * wj * gsum;
                }
            }
            uint32_t off = (uint32_t)((it < 2 ? 64 : 0) + r * 8 + (ch >> 3)) * 8192 + (m >> 3) * 1024 + (ch & 7) * 128 + (m & 7) * 16;
            *(uint4*)(g_E + off) = make_uint4(pack_bf16(v[0], v[1]), pack_bf16(v[2], v[3]), pack_bf16(v[4], v[5]), pack_bf16(v[6], v[7]));
        }
        fence_async_smem();
    }

#pragma unroll 1
    for (int layer = 0; layer < 2; layer++) {
        if (wg < 2) {
            const int n1 = 32 * wg + 8 * w + g;
            const int ct = n1 >> 2;
            gen_col_consts(sm, tid);
            float twr[8], twi[8];
#pragma unroll
            for (int i = 0; i < 8; i++) {
                int n2 = 8 * (i >> 1) + 2 * q + (i & 1);
                int a = (n1 * n2) & 2047;
                a = a >= 1024 ? a - 2048 : a;
                float ang = (float)a * (-6.283185307179586f / 2048.f);
                twr[i] = __cosf(ang); twi[i] = __sinf(ang);
            }
            mbar_wait(BAR(B_COL), layer);
            TS(4 + 12 * layer);
            if (wg == 0) TC(0 + 10 * layer);
            const uint32_t rw0 = sb + SM_RAW + ct * 1024 + q * 64 + ((q >> 1) << 4) + (g & 3) * 4, rw1 = rw0 ^ 16;
            const int pos0 = 128 * ct + 8 * q + 2 * (g & 3);
            const int sw = b == 0 ? 1 : 0;
            uint32_t xr[4][4];
            const uint32_t st0 = sb + SM_H + (n1 >> 3) * 1024 + g * 16 + 4 * q;
#pragma unroll
            for (int i = 0; i < 4; i++) {
                float2 sq = *(const float2*)(sm + SM_SSQ + (pos0 + 32 * i) * 4);
                float r0 = rsqrtf(sq.x * (1.f / 512.f) + 1e-5f), r1 = rsqrtf(sq.y * (1.f / 512.f) + 1e-5f);
#pragma unroll
                for (int jj = 0; jj < 4; jj++) {
                    const int K = jj ^ (2 * (i & 1));
                    uint32_t a = ((K & 1) ? rw1 : rw0) + i * 256 + (K & 2) * 16;
                    if (jj < 2) a ^= sw << 4;
                    uint32_t v = lds32(a);
                    xr[jj][i] = v;
                    uint32_t o = pack_bf16(bf_lo(v) * r0, bf_hi(v) * r1);
                    if (jj == 1 && sw) o = 0u;
                    sts32(st0 + (jj & 1) * 8192 + (4 * (jj >> 1) + i) * 128, o);
                }
            }
            if (wg == 0) TC(1 + 10 * layer);
            fence_async_smem();
            bar_sync(1, 256);
            float acc[32];
            const uint32_t s1a = sb + SM_X + wg * 16384, s2b = sb + SM_X + 32768;
            wg_fence();
#pragma unroll
            for (int ks = 0; ks < 8; ks++)
                wgmma_n64<1>(acc, desc_a(s1a + (ks >> 2) * 8192 + (ks & 3) * 256), desc_b<64>(sb + SM_H + ks * 2048), ks != 0);
            wg_commit();
            mbar_wait(BAR(B_WRDY), 0);
            uint32_t wf[16];
            {
                const uint4* ws = g_Wfrag + (uint32_t)(b * 1024 + n1 * 4 + q);
#pragma unroll
                for (int i = 0; i < 4; i++) {
                    uint4 v = __ldcg(ws + i * 256);
                    wf[4 * i] = v.x; wf[4 * i + 1] = v.y; wf[4 * i + 2] = v.z; wf[4 * i + 3] = v.w;
                }
            }
            wg_wait<0>();
            if (wg == 0) TC(2 + 10 * layer);
            uint32_t are[2][4], aim[2][4];
#pragma unroll
            for (int col = 0; col < 2; col++) {
#pragma unroll
                for (int i = 0; i < 4; i++) {
                    int o = 4 * (4 * col + i);
                    float r0 = acc[o] * twr[2 * i] - acc[o + 2] * twi[2 * i], i0 = acc[o] * twi[2 * i] + acc[o + 2] * twr[2 * i];
                    float r1 = acc[o + 1] * twr[2 * i + 1] - acc[o + 3] * twi[2 * i + 1], i1 = acc[o + 1] * twi[2 * i + 1] + acc[o + 3] * twr[2 * i + 1];
                    are[col][i] = pack_bf16(r0, r1);
                    aim[col][i] = pack_bf16(i0, i1);
                }
            }
            wg_fence();
#pragma unroll
            for (int ks = 0; ks < 2; ks++)
                wgmma_n64_rs(acc, are[0][2 * ks], are[1][2 * ks], are[0][2 * ks + 1], are[1][2 * ks + 1], desc_b<64>(s2b + ks * 2048), ks != 0);
#pragma unroll
            for (int ks = 0; ks < 2; ks++)
                wgmma_n64_rs(acc, aim[0][2 * ks], aim[1][2 * ks], aim[0][2 * ks + 1], aim[1][2 * ks + 1], desc_b<64>(s2b + 4096 + ks * 2048), 1);
            wg_commit();
            wg_wait<0>();
            if (wg == 0) TC(3 + 10 * layer);
#pragma unroll
            for (int col = 0; col < 2; col++) {
#pragma unroll
                for (int i = 0; i < 4; i++) {
                    float gr[2], gi[2];
#pragma unroll
                    for (int e = 0; e < 2; e++) {
                        uint32_t wv = wf[col * 8 + 2 * i + e];
                        float wr = bf_lo(wv), wi = bf_hi(wv);
                        float zr = acc[4 * i + 2 * col + e], zi = acc[16 + 4 * i + 2 * col + e];
                        gr[e] = zr * wr - zi * wi;
                        gi[e] = -(zr * wi + zi * wr);
                    }
                    are[col][i] = pack_bf16(gr[0], gr[1]);
                    aim[col][i] = pack_bf16(gi[0], gi[1]);
                }
            }
            wg_fence();
#pragma unroll
            for (int ks = 0; ks < 2; ks++)
                wgmma_n64_rs(acc, are[0][2 * ks], are[1][2 * ks], are[0][2 * ks + 1], are[1][2 * ks + 1], desc_b<64>(s2b + ks * 2048), ks != 0);
#pragma unroll
            for (int ks = 0; ks < 2; ks++)
                wgmma_n64_rs(acc, aim[0][2 * ks], aim[1][2 * ks], aim[0][2 * ks + 1], aim[1][2 * ks + 1], desc_b<64>(s2b + 4096 + ks * 2048), 1);
            wg_commit();
            wg_wait<0>();
            if (wg == 0) TC(4 + 10 * layer);
#pragma unroll
            for (int col = 0; col < 2; col++) {
#pragma unroll
                for (int i = 0; i < 4; i++) {
                    float rr[2], im[2];
#pragma unroll
                    for (int e = 0; e < 2; e++) {
                        float zr = acc[4 * i + 2 * col + e], zi = acc[16 + 4 * i + 2 * col + e];
                        rr[e] = zr * twr[2 * i + e] - zi * twi[2 * i + e];
                        im[e] = zr * twi[2 * i + e] + zi * twr[2 * i + e];
                    }
                    sts32(st0 + 16384 + (4 * col + i) * 128, pack_bf16(rr[0], rr[1]));
                    sts32(st0 + 16384 + 8192 + (4 * col + i) * 128, pack_bf16(im[0], im[1]));
                }
            }
            if (wg == 0) TC(5 + 10 * layer);
            fence_async_smem();
            bar_sync(1, 256);
            wg_fence();
#pragma unroll
            for (int ks = 0; ks < 8; ks++)
                wgmma_n64<1>(acc, desc_a(s1a + (ks >> 2) * 8192 + (ks & 3) * 256), desc_b<64>(sb + SM_H + 16384 + ks * 2048), ks != 0);
            wg_commit();
            wg_wait<0>();
            if (wg == 0) TC(6 + 10 * layer);
            const float sc = 1.f / 2048.f;
            const float sci0 = sw ? 0.f : -sc;
            const float wr0 = sw ? 0.5f : 1.f, wi0 = sw ? 0.f : 1.f;
#pragma unroll
            for (int i = 0; i < 4; i++) {
                float ss0, ss1;
#pragma unroll
                for (int col = 0; col < 2; col++) {
                    int o = 4 * (4 * col + i);
                    uint32_t vr = xr[2 * col][i], vi = xr[2 * col + 1][i];
                    float si = col == 0 ? sci0 : -sc;
                    uint32_t nr = pack_bf16(fmaf(acc[o], sc, bf_lo(vr)), fmaf(acc[o + 1], sc, bf_hi(vr)));
                    uint32_t ni = pack_bf16(fmaf(acc[o + 2], si, bf_lo(vi)), fmaf(acc[o + 3], si, bf_hi(vi)));
                    float a0 = bf_lo(nr), a1 = bf_hi(nr), b0 = bf_lo(ni), b1 = bf_hi(ni);
                    if (col == 0) {
                        ss0 = wr0 * a0 * a0 + wi0 * b0 * b0;
                        ss1 = wr0 * a1 * a1 + wi0 * b1 * b1;
                    } else {
                        ss0 += a0 * a0 + b0 * b0;
                        ss1 += a1 * a1 + b1 * b1;
                    }
                    const int K = (2 * col) ^ (2 * (i & 1));
                    uint32_t a = rw0 + i * 256 + K * 16;
                    if (col == 0) a ^= sw << 4;
                    sts32(a, nr);
                    sts32(a ^ 16, ni);
                }
                *(float2*)(sm + SM_SSQ + (pos0 + 32 * i) * 4) = make_float2(ss0 * (2.f / 512.f), ss1 * (2.f / 512.f));
            }
            fence_async_smem();
        }
        TS(5 + 12 * layer);
        if (wg == 0) TC(7 + 10 * layer);
        bar_arrive(5, 416);

        float acc[64];
        float* s_rstd = (float*)(sm + SM_RSTD);
        float* s_mean = (float*)(sm + SM_MEAN);
        const unsigned epoch = s_tgt[0] >> 7;
        const uint32_t pt3 = 1u + (2u * epoch + layer) % 3u;
        const uint32_t ptag = (pt3 & 1u) | ((pt3 & 2u) << 15);
        const uint64_t dstep = layer == 0 ? 16 : 2;
        auto c_desc = [&](int s) { return layer == 0 ? desc_a(sb + SM_A + s * 16384) : desc_k(sb + SM_A + s * 16384); };
        if (wg < 2) {
            const int prow = 32 * wg + 8 * w + g;
            const float2 l1 = *(const float2*)(sm + SM_LAM + prow * 8);
            float lr32 = l1.x, li32 = l1.y;
#pragma unroll
            for (int i = 0; i < 5; i++) { float t = lr32 * lr32 - li32 * li32; li32 = 2.f * lr32 * li32; lr32 = t; }
            float lr128 = lr32, li128 = li32;
#pragma unroll
            for (int i = 0; i < 2; i++) { float t = lr128 * lr128 - li128 * li128; li128 = 2.f * lr128 * li128; lr128 = t; }
            const float lr1 = l1.x, li1 = l1.y;
            acc_def(acc);
#pragma unroll 1
            for (int kb = 0; kb < 8; kb++) {
                mbar_wait(BAR(B_AFULL + kb), 0);
                mbar_wait(BAR(B_XFULL + (kb & 3)), (kb >> 2) & 1);
                if (tid == 0 && layer == 0) TX(16 + kb);
                __syncwarp();
                wg_fence();
#pragma unroll
                for (int ks = 0; ks < 4; ks++)
                    wgmma_n128<1>(acc, desc_a(sb + SM_A + kb * 16384 + wg * 8192 + ks * 256),
                                  desc_b<128>(sb + SM_X + (kb & 3) * 24576 + ks * 4096), 1);
                wg_commit();
                wg_wait<1>();
                if (kb > 0 && lane == 0) {
                    mbar_arrive(BAR(B_AEMPTY + kb - 1), 1); mbar_arrive(BAR(B_XEMPTY + ((kb - 1) & 3)), 1);
                    mbar_arrive_remote(mapa(BAR(B_XEMPTY + ((kb - 1) & 3)), par ^ 1));
                }
            }
            wg_wait<0>();
            if (lane == 0) {
                mbar_arrive(BAR(B_AEMPTY + 7), 1); mbar_arrive(BAR(B_XEMPTY + 3), 1);
                mbar_arrive_remote(mapa(BAR(B_XEMPTY + 3), par ^ 1)); mbar_arrive_remote(mapa(BAR(B_RFREE), par ^ 1));
            }
            TS(6 + 12 * layer);
            bar_sync(4, 384);
            TS(7 + 12 * layer);
            float er = 0.f, ei = 0.f;
#pragma unroll
            for (int i = 0; i < 16; i++) {
                float2 rs = *(const float2*)(s_rstd + 128 + 8 * i + 2 * q);
                acc[4 * i] *= rs.x; acc[4 * i + 1] *= rs.y; acc[4 * i + 2] *= rs.x; acc[4 * i + 3] *= rs.y;
                float nr = lr1 * er - li1 * ei + acc[4 * i], ni = lr1 * ei + li1 * er + acc[4 * i + 2];
                er = lr1 * nr - li1 * ni + acc[4 * i + 1];
                ei = lr1 * ni + li1 * nr + acc[4 * i + 3];
            }
            float cr = 0.f, ci = 0.f, tr = 0.f, ti = 0.f;
#pragma unroll
            for (int qq = 0; qq < 4; qq++) {
                float xr_ = __shfl_sync(~0u, er, (lane & ~3) | qq), xi_ = __shfl_sync(~0u, ei, (lane & ~3) | qq);
                if (qq == q) { cr = tr; ci = ti; }
                float nr = lr32 * tr - li32 * ti + xr_, ni = lr32 * ti + li32 * tr + xi_;
                tr = nr; ti = ni;
            }
            float4* eb = g_Ebuf + (uint32_t)(layer * 16 * 512 + 64 * r + prow);
            if (q == 0 && c < 15) st_relaxed_f4(eb + c * 512, make_float4(tr, ti, __uint_as_float(epoch), 0.f));
            TS(8 + 12 * layer);
            float pr[4], pi[4];
            {
                unsigned n = 0;
                bool ok;
#pragma unroll 1
                do {
                    ok = true;
#pragma unroll
                    for (int k = 0; k < 4; k++) {
                        float4 v = make_float4(0.f, 0.f, __uint_as_float(epoch), 0.f);
                        if (4 * k + q < c) v = ld_relaxed_f4(eb + (4 * k + q) * 512);
                        pr[k] = v.x; pi[k] = v.y;
                        ok = ok && __float_as_uint(v.z) == epoch;
                    }
                } while (!ok && ++n < SPIN_LIMIT);
            }
            __syncwarp();
            TS(9 + 12 * layer);
            float hr = 0.f, hi = 0.f;
#pragma unroll
            for (int cc = 0; cc < 15; cc++) {
                float xr_ = __shfl_sync(~0u, pr[cc >> 2], (lane & ~3) | (cc & 3)), xi_ = __shfl_sync(~0u, pi[cc >> 2], (lane & ~3) | (cc & 3));
                if (cc < c) {
                    float nr = lr128 * hr - li128 * hi + xr_, ni = lr128 * hi + li128 * hr + xi_;
                    hr = nr; hi = ni;
                }
            }
#pragma unroll
            for (int qq = 0; qq < 3; qq++) {
                if (qq < q) { float nr = lr32 * hr - li32 * hi, ni = lr32 * hi + li32 * hr; hr = nr; hi = ni; }
            }
            er = cr + hr; ei = ci + hi;
            bar_sync(7, 384);
            const uint32_t ha = sb + SM_HH + par * 32768 + (prow >> 3) * 2048 + g * 16 + 4 * q;
#pragma unroll
            for (int i = 0; i < 16; i++) {
                float nr = lr1 * er - li1 * ei + acc[4 * i], ni = lr1 * ei + li1 * er + acc[4 * i + 2];
                er = lr1 * nr - li1 * ni + acc[4 * i + 1];
                ei = lr1 * ni + li1 * nr + acc[4 * i + 3];
                sts32(ha + i * 128, pack_bf16(nr, er));
                sts32(ha + 16384 + i * 128, pack_bf16(ni, ei));
            }
            fence_async_smem();
            float acc2[32];
            acc_def(acc2);
            TS(10 + 12 * layer);
            bar_sync(6, 416);
            TS(11 + 12 * layer);
#pragma unroll 1
            for (int k = 0; k < 2; k++) {
                const uint32_t hb = sb + SM_HH + (par ^ k) * 32768;
                if (k == 1) mbar_wait(BAR(B_HPEER), layer);
                mbar_wait(BAR(B_AFULL + 2 * wg + k), 1);
                mbar_wait(BAR(B_AFULL + 4 + k), 1);
                if (layer == 0) TS(28 + k);
                const uint64_t da = c_desc(2 * wg + k), da2 = c_desc(4 + k);
                wg_fence();
#pragma unroll
                for (int ks = 0; ks < 4; ks++) wgmma_n128<1, 1>(acc, da + ks * dstep, desc_b<128>(hb + ks * 4096), (ks | k) != 0);
#pragma unroll
                for (int ks = 0; ks < 4; ks++) wgmma_n128<1, -1>(acc, da + 512 + ks * dstep, desc_b<128>(hb + 16384 + ks * 4096), 1);
                wg_commit();
#pragma unroll
                for (int ks = 0; ks < 4; ks++) wgmma_n64s<1>(acc2, da2 + ks * dstep, desc_b<128>(hb + wg * 1024 + ks * 4096), 1);
#pragma unroll
                for (int ks = 0; ks < 4; ks++) wgmma_n64s<-1>(acc2, da2 + 512 + ks * dstep, desc_b<128>(hb + 16384 + wg * 1024 + ks * 4096), 1);
                wg_commit();
            }
            wg_wait<1>();
            bar_arrive(12, 384);
            TS(13 + 12 * layer);
            {
                uint4* dst = g_P + (uint32_t)(((c * 8 + 2 * ((pi_ + 1 + wg) & 3) + par) * 4 + pi_) * 1024 + (tid & 127));
#pragma unroll
                for (int i = 0; i < 8; i++)
                    dst[i * 128] = make_uint4((pack_bf16(acc[8 * i], acc[8 * i + 1]) & 0xfffefffeu) | ptag, pack_bf16(acc[8 * i + 2], acc[8 * i + 3]),
                                              pack_bf16(acc[8 * i + 4], acc[8 * i + 5]), pack_bf16(acc[8 * i + 6], acc[8 * i + 7]));
            }
            wg_wait<0>();
            TS(14 + 12 * layer);
            {
                uint4* dst = g_P + (uint32_t)(((c * 8 + 2 * ((pi_ + 3) & 3) + par) * 4 + pi_) * 1024 + wg * 512 + (tid & 127));
#pragma unroll
                for (int i = 0; i < 4; i++)
                    dst[i * 128] = make_uint4((pack_bf16(acc2[8 * i], acc2[8 * i + 1]) & 0xfffefffeu) | ptag, pack_bf16(acc2[8 * i + 2], acc2[8 * i + 3]),
                                              pack_bf16(acc2[8 * i + 4], acc2[8 * i + 5]), pack_bf16(acc2[8 * i + 6], acc2[8 * i + 7]));
            }
            if (layer == 0) TS(30);
            {
                uint4 v[8];
                fetch_partial(g_P + (uint32_t)(((c * 8 + r) * 4 + ((pi_ - 1 - wg) & 3)) * 1024 + (tid & 127)), ptag, v);
#pragma unroll
                for (int i = 0; i < 8; i++) *(uint4*)(sm + SM_A + wg * 32768 + i * 2048 + (tid & 127) * 16) = v[i];
                fence_async_smem();
                bar_arrive(8, 384);
            }
            if (lane == 0) {
                mbar_arrive(BAR(B_AEMPTY + 2 * wg), 2); mbar_arrive(BAR(B_AEMPTY + 2 * wg + 1), 2);
                mbar_arrive(BAR(B_AEMPTY + 4), 1); mbar_arrive(BAR(B_AEMPTY + 5), 1);
            }
            TS(12 + 12 * layer);
            mbar_wait_cluster(BAR(B_HDONE), layer);
            if (layer == 0) bar_sync(9, 384);
        } else {
            const int t2 = tid - 256;
            const uint8_t* ximg = g_X + (uint32_t)layer * 16 * 8 * 16384;
            mbar_wait(BAR(B_SSQ), layer);
            TS(6 + 12 * layer);
            {
                float tot = 0.f;
#pragma unroll
                for (int i = 0; i < 16; i++) tot += __ldcg(g_ssqc + (layer * 16 + i) * 2048 + 128 * c + t2);
                float rs = rsqrtf(tot * (1.f / 512.f) + 1e-5f);
                s_rstd[t2] = rs;
                s_rstd[128 + t2] = 2.f * rs;
                if (layer == 1) {
                    unsigned short u = __ldcg((const unsigned short*)(ximg + (uint32_t)(c * 8 * 16384 + (t2 >> 3) * 128 + (t2 & 7) * 2)));
                    s_mean[t2] = __uint_as_float((uint32_t)u << 16) * (1.f / 512.f);
                }
            }
            TS(7 + 12 * layer);
            bar_arrive(4, 384);
            acc_def(acc);
#pragma unroll 1
            for (int kb = 0; kb < 8; kb++) {
                mbar_wait(BAR(B_XFULL + (kb & 3)), (kb >> 2) & 1);
                wg_fence();
#pragma unroll
                for (int ks = 0; ks < 4; ks++)
                    wgmma_n128<1>(acc, desc_a(sb + SM_X + (kb & 3) * 24576 + 16384 + ks * 256), desc_b<128>(sb + SM_X + (kb & 3) * 24576 + ks * 4096), 1);
                wg_commit();
                wg_wait<1>();
                if (kb > 0 && lane == 0) { mbar_arrive(BAR(B_XEMPTY + ((kb - 1) & 3)), 1); mbar_arrive_remote(mapa(BAR(B_XEMPTY + ((kb - 1) & 3)), par ^ 1)); }
            }
            wg_wait<0>();
            if (lane == 0) { mbar_arrive(BAR(B_XEMPTY + 3), 1); mbar_arrive_remote(mapa(BAR(B_XEMPTY + 3), par ^ 1)); mbar_arrive_remote(mapa(BAR(B_RFREE), par ^ 1)); }
            bar_arrive(7, 384);
            bar_sync(3, 128);
            TS(9 + 12 * layer);
            const int m0 = 16 * w + g;
            const uint32_t xoff = (uint32_t)((c * 8 + own) * 16384 + w * 4096 + g * 16 + 4 * q);
            if (layer == 0) {
                const uint8_t* xs = g_X + xoff;
#pragma unroll
                for (int i = 0; i < 16; i++) {
                    float2 rs = *(const float2*)(s_rstd + 8 * i + 2 * q);
                    uint32_t x0v = __ldcg((const uint32_t*)(xs + i * 128)), x1v = __ldcg((const uint32_t*)(xs + 2048 + i * 128));
                    acc[4 * i] = acc[4 * i] * rs.x + bf_lo(x0v);
                    acc[4 * i + 1] = acc[4 * i + 1] * rs.y + bf_hi(x0v);
                    acc[4 * i + 2] = acc[4 * i + 2] * rs.x + bf_lo(x1v);
                    acc[4 * i + 3] = acc[4 * i + 3] * rs.y + bf_hi(x1v);
                }
            } else {
                float d0 = ldbf(p.dskip + 64 * own + m0), d1 = ldbf(p.dskip + 64 * own + m0 + 8);
#pragma unroll
                for (int i = 0; i < 16; i++) {
                    float2 rs = *(const float2*)(s_rstd + 8 * i + 2 * q);
                    float2 mn = *(const float2*)(s_mean + 8 * i + 2 * q);
                    acc[4 * i] = acc[4 * i] * (1.f + rs.x * d0) + mn.x;
                    acc[4 * i + 1] = acc[4 * i + 1] * (1.f + rs.y * d0) + mn.y;
                    acc[4 * i + 2] = acc[4 * i + 2] * (1.f + rs.x * d1) + mn.x;
                    acc[4 * i + 3] = acc[4 * i + 3] * (1.f + rs.y * d1) + mn.y;
                }
            }
            TS(10 + 12 * layer);
            bar_sync(6, 416);
            TS(11 + 12 * layer);
#pragma unroll 1
            for (int k = 0; k < 2; k++) {
                const uint32_t hb = sb + SM_HH + (par ^ k) * 32768;
                if (k == 1) {
                    mbar_wait(BAR(B_HPEER), layer);
                    if (t2 == 0) mbar_arrive_remote(mapa(BAR(B_HDONE), par ^ 1));
                    __syncwarp();
                    bar_sync(12, 384);
                }
                mbar_wait(BAR(B_AFULL + 6 + k), 1);
                const uint64_t da = c_desc(6 + k);
                wg_fence();
#pragma unroll
                for (int ks = 0; ks < 4; ks++) wgmma_n128<1, 1>(acc, da + ks * dstep, desc_b<128>(hb + ks * 4096), 1);
#pragma unroll
                for (int ks = 0; ks < 4; ks++) wgmma_n128<1, -1>(acc, da + 512 + ks * dstep, desc_b<128>(hb + 16384 + ks * 4096), 1);
                wg_commit();
            }
            wg_wait<0>();
            if (lane == 0) mbar_arrive(BAR(B_AEMPTY + 7), 2);
            if (layer == 0) bar_arrive(9, 384);
            TS(12 + 12 * layer);
            {
                uint4 v[8];
                fetch_partial(g_P + (uint32_t)(((c * 8 + r) * 4 + ((pi_ - 3) & 3)) * 1024 + t2), ptag, v);
                TS(13 + 12 * layer);
                bar_sync(8, 384);
#pragma unroll 1
                for (int sidx = 0; sidx < 3; sidx++) {
#pragma unroll
                    for (int i = 0; i < 8; i++) {
                        acc[8 * i] += bf_lo(v[i].x); acc[8 * i + 1] += bf_hi(v[i].x);
                        acc[8 * i + 2] += bf_lo(v[i].y); acc[8 * i + 3] += bf_hi(v[i].y);
                        acc[8 * i + 4] += bf_lo(v[i].z); acc[8 * i + 5] += bf_hi(v[i].z);
                        acc[8 * i + 6] += bf_lo(v[i].w); acc[8 * i + 7] += bf_hi(v[i].w);
                        v[i] = *(const uint4*)(sm + SM_A + (sidx & 1) * 32768 + i * 2048 + t2 * 16);
                    }
                }
            }
            TS(14 + 12 * layer);
            if (layer == 0) {
                uint8_t* xd = g_X + 16 * 8 * 16384 + xoff;
                const float w0 = (own == 0 && m0 < 2) ? (m0 == 0 ? 0.f : 0.5f) : 1.f;
                float* sq = (float*)(sm + SM_A + 6 * 16384);
#pragma unroll
                for (int i = 0; i < 16; i++) {
                    uint32_t v0 = pack_bf16(acc[4 * i], acc[4 * i + 1]), v1 = pack_bf16(acc[4 * i + 2], acc[4 * i + 3]);
                    *(uint32_t*)(xd + i * 128) = v0;
                    *(uint32_t*)(xd + 2048 + i * 128) = v1;
                    float s0 = w0 * bf_lo(v0) * bf_lo(v0) + bf_lo(v1) * bf_lo(v1);
                    float s1 = w0 * bf_hi(v0) * bf_hi(v0) + bf_hi(v1) * bf_hi(v1);
                    *(float2*)(sq + (8 * w + g) * 128 + ((8 * i + 2 * q + 8 * g) & 127)) = make_float2(s0, s1);
                }
                bar_sync(3, 128);
                float tot = 0.f;
#pragma unroll 8
                for (int k = 0; k < 32; k++) tot += sq[k * 128 + ((t2 + 8 * (k & 7)) & 127)];
                atomicAdd(g_ssq + 2048 + 128 * c + t2, tot * (2.f / 512.f));
                fence_async_smem();
                bar_sync(3, 128);
                if (lane == 0) mbar_arrive(BAR(B_AEMPTY + 6), 2);
                if (t2 == 0) { fence_async(); red_release(&g_bar[2], 1); }
            } else {
                float* o = p.out + (uint32_t)((128 * c + 32 * q) * 512 + 64 * own + m0);
#pragma unroll
                for (int i = 0; i < 16; i++) {
                    o[(2 * i) * 512] = acc[4 * i];
                    o[(2 * i + 1) * 512] = acc[4 * i + 1];
                    o[(2 * i) * 512 + 8] = acc[4 * i + 2];
                    o[(2 * i + 1) * 512 + 8] = acc[4 * i + 3];
                }
            }
        }
        TS(15 + 12 * layer);
        if (wg == 0) TC(31);
    }
}

typedef CUresult (*EncFn)(CUtensorMap*, CUtensorMapDataType, cuuint32_t, void*, const cuuint64_t*, const cuuint64_t*,
                          const cuuint32_t*, const cuuint32_t*, CUtensorMapInterleave, CUtensorMapSwizzle,
                          CUtensorMapL2promotion, CUtensorMapFloatOOBfill);

void launch_impl(void* const* d_in, void* d_out, int stop) {
    static EncFn enc = nullptr;
    if (!enc) {
        void* fn = nullptr;
        cudaDriverEntryPointQueryResult qr;
        cudaGetDriverEntryPoint("cuTensorMapEncodeTiled", &fn, cudaEnableDefault, &qr);
        enc = (EncFn)fn;
        cudaFuncSetAttribute(fused_kernel, cudaFuncAttributeMaxDynamicSharedMemorySize, SM_TOTAL);
    }
    CUtensorMap tx, tbr, tbi, tcr, tci, tcol;
    {
        void* gx = nullptr;
        cudaGetSymbolAddress(&gx, g_X);
        cuuint64_t gd[5] = {64, 16, 64, 16, 2};
        cuuint64_t gs[4] = {128, 2048, 128 * 1024, 2048 * 1024};
        cuuint32_t bx[5] = {32, 16, 1, 16, 1};
        cuuint32_t es[5] = {1, 1, 1, 1, 1};
        enc(&tcol, CU_TENSOR_MAP_DATA_TYPE_BFLOAT16, 5, gx, gd, gs, bx, es, CU_TENSOR_MAP_INTERLEAVE_NONE,
            CU_TENSOR_MAP_SWIZZLE_64B, CU_TENSOR_MAP_L2_PROMOTION_NONE, CU_TENSOR_MAP_FLOAT_OOB_FILL_NONE);
    }
    {
        cuuint64_t gd[5] = {512, 2, 4, 16, 16};
        cuuint64_t gs[4] = {1024, 32 * 1024, 2 * 1024, 128 * 1024};
        cuuint32_t bx[5] = {64, 2, 4, 8, 1};
        cuuint32_t es[5] = {1, 1, 1, 1, 1};
        enc(&tx, CU_TENSOR_MAP_DATA_TYPE_BFLOAT16, 5, d_in[0], gd, gs, bx, es, CU_TENSOR_MAP_INTERLEAVE_NONE,
            CU_TENSOR_MAP_SWIZZLE_128B, CU_TENSOR_MAP_L2_PROMOTION_L2_128B, CU_TENSOR_MAP_FLOAT_OOB_FILL_NONE);
    }
    auto mk2 = [&](CUtensorMap* m, void* ptr, cuuint32_t rows) {
        cuuint64_t gd[2] = {512, 512};
        cuuint64_t gs[1] = {1024};
        cuuint32_t bx[2] = {64, rows};
        cuuint32_t es[2] = {1, 1};
        enc(m, CU_TENSOR_MAP_DATA_TYPE_BFLOAT16, 2, ptr, gd, gs, bx, es, CU_TENSOR_MAP_INTERLEAVE_NONE,
            CU_TENSOR_MAP_SWIZZLE_128B, CU_TENSOR_MAP_L2_PROMOTION_L2_128B, CU_TENSOR_MAP_FLOAT_OOB_FILL_NONE);
    };
    mk2(&tbr, d_in[6], 32);
    mk2(&tbi, d_in[7], 32);
    mk2(&tcr, d_in[8], 64);
    mk2(&tci, d_in[9], 64);
    Params p;
    p.x0 = (const __nv_bfloat16*)d_in[0];
    p.w_r = (const __nv_bfloat16*)d_in[1];
    p.w_i = (const __nv_bfloat16*)d_in[2];
    p.lam_re = (const __nv_bfloat16*)d_in[4];
    p.lam_im = (const __nv_bfloat16*)d_in[5];
    p.log_dt = (const __nv_bfloat16*)d_in[10];
    p.dskip = (const __nv_bfloat16*)d_in[11];
    p.out = (float*)d_out;
    p.stop = stop;
    cudaLaunchConfig_t cfg = {};
    cfg.gridDim = dim3(NCTA); cfg.blockDim = dim3(NTHREADS); cfg.dynamicSmemBytes = SM_TOTAL; cfg.stream = cudaStreamPerThread;
    cudaLaunchAttribute at[1];
    at[0].id = cudaLaunchAttributeClusterDimension;
    at[0].val.clusterDim.x = 2; at[0].val.clusterDim.y = 1; at[0].val.clusterDim.z = 1;
    cfg.attrs = at; cfg.numAttrs = 1;
    cudaLaunchKernelEx(&cfg, fused_kernel, tx, tbr, tbi, tcr, tci, tcol, p);
}

}

extern "C" void kernel_launch(void* const* d_in, const int* in_sizes, int n_in, void* d_out, int out_size) {
    (void)in_sizes; (void)n_in; (void)out_size;
    launch_impl(d_in, d_out, 100);
}
```

```cpp
#include <cuda_runtime.h>
#include <cuda_bf16.h>
#include <cuda.h>
#include <stdint.h>

namespace {

constexpr int NCTA = 128;
constexpr int NTHREADS = 512;
constexpr int SM_A = 0;
constexpr int SM_X = 131072;
constexpr int SM_H = 196608;
constexpr int SM_HH = SM_X + 32768;
constexpr int SM_M = 229376;
constexpr int SM_TOTAL = 232448;
constexpr int SM_BAR = SM_M;
constexpr int SM_TGT = SM_M + 360;
constexpr int SM_LAM = SM_M + 384;
constexpr int SM_TAB = SM_M + 896;
constexpr int SM_RSTD = SM_M + 1920;
constexpr int SM_MEAN = SM_TAB;
constexpr int SM_T64 = SM_M + 2944;
constexpr int SM_B1ST = SM_H + 24576;
constexpr int SM_RAW = SM_X + 40960;
constexpr int SM_SSQ = SM_X + 57344;
constexpr int B_FULL0 = 0;
constexpr int B_EMPTY0 = 8;
constexpr int B_FULLC = 12;
constexpr int B_AFULL = 13;
constexpr int B_AEMPTY = 21;
constexpr int B_XFULL = 29;
constexpr int B_XEMPTY = 33;
constexpr int B_AFREE = 37;
constexpr int B_COL = 38;
constexpr int B_SSQ = 39;
constexpr int B_HPEER = 40;
constexpr int B_RFREE = 41;
constexpr int B_HDONE = 42;
constexpr int B_WRDY = 43;
constexpr int B_HPEER1 = 44;
constexpr int NBARS = 45;

__device__ __align__(1024) uint8_t g_X[2 * 16 * 8 * 16384];
__device__ __align__(1024) uint8_t g_A1[8 * 8 * 16384];
__device__ __align__(1024) uint8_t g_A2[8 * 8 * 16384];
__device__ __align__(1024) uint8_t g_E[2 * 8 * 8 * 8192];
__device__ __align__(16) float g_ssq[2 * 2048];
__device__ __align__(16) float g_ssqc[2 * 16 * 2048];
__device__ __align__(16) float g_Dh[512];
__device__ __align__(16) uint4 g_Wfrag[128 * 4 * 256];
__device__ __align__(16) float4 g_Ebuf[2 * 16 * 512];
__device__ __align__(16) uint4 g_P[16 * 8 * 4 * 1024];
__device__ unsigned g_bar[8];
__device__ unsigned g_err;
#define TX(i)
#define TQ(i)
#define TS(i)
#define TC(i)

constexpr unsigned SPIN_LIMIT = 1u << 22;

__device__ __forceinline__ uint32_t s2u(const void* p) { return (uint32_t)__cvta_generic_to_shared(p); }
__device__ __forceinline__ void mbar_init(uint32_t a, uint32_t c) {
    asm volatile("mbarrier.init.shared::cta.b64 [%0], %1;" ::"r"(a), "r"(c) : "memory");
}
__device__ __forceinline__ void mbar_expect(uint32_t a, uint32_t bytes) {
    asm volatile("mbarrier.arrive.expect_tx.shared::cta.b64 _, [%0], %1;" ::"r"(a), "r"(bytes) : "memory");
}
__device__ __forceinline__ void mbar_arrive(uint32_t a, uint32_t cnt) {
    asm volatile("mbarrier.arrive.shared::cta.b64 _, [%0], %1;" ::"r"(a), "r"(cnt) : "memory");
}
__device__ __forceinline__ bool mbar_try(uint32_t a, uint32_t parity) {
    uint32_t ok;
    asm volatile("{\n.reg .pred p;\nmbarrier.try_wait.parity.shared::cta.b64 p, [%1], %2;\nselp.u32 %0, 1, 0, p;\n}"
                 : "=r"(ok) : "r"(a), "r"(parity) : "memory");
    return ok != 0;
}
__device__ __forceinline__ void mbar_wait(uint32_t a, uint32_t parity) {
    asm volatile("{\n.reg .pred p, q;\n.reg .u32 n;\nmov.u32 n, 0;\n"
                 "W_%=:\nmbarrier.try_wait.parity.shared::cta.b64 p, [%0], %1;\n@p bra D_%=;\n"
                 "add.u32 n, n, 1;\nsetp.lt.u32 q, n, 4194304;\n@q bra W_%=;\nD_%=:\n}" ::"r"(a), "r"(parity) : "memory");
}
__device__ __forceinline__ void bulk_g2s(uint32_t dst, const void* src, uint32_t bytes, uint32_t bar) {
    asm volatile("cp.async.bulk.shared::cluster.global.mbarrier::complete_tx::bytes [%0], [%1], %2, [%3];" ::"r"(dst),
                 "l"(src), "r"(bytes), "r"(bar) : "memory");
}
__device__ __forceinline__ void tma_2d(uint32_t dst, const CUtensorMap* m, int c0, int c1, uint32_t bar) {
    asm volatile("cp.async.bulk.tensor.2d.shared::cluster.global.mbarrier::complete_tx::bytes [%0], [%1, {%3,%4}], [%2];" ::"r"(dst),
                 "l"(m), "r"(bar), "r"(c0), "r"(c1) : "memory");
}
__device__ __forceinline__ void tma_5d(uint32_t dst, const CUtensorMap* m, int c0, int c1, int c2, int c3, int c4, uint32_t bar) {
    asm volatile("cp.async.bulk.tensor.5d.shared::cluster.global.mbarrier::complete_tx::bytes [%0], [%1, {%3,%4,%5,%6,%7}], [%2];" ::"r"(dst),
                 "l"(m), "r"(bar), "r"(c0), "r"(c1), "r"(c2), "r"(c3), "r"(c4) : "memory");
}
__device__ __forceinline__ void tma_2d_mc(uint32_t dst, const CUtensorMap* m, int c0, int c1, uint32_t bar) {
    asm volatile("cp.async.bulk.tensor.2d.shared::cluster.global.mbarrier::complete_tx::bytes.multicast::cluster [%0], [%1, {%3,%4}], [%2], %5;" ::"r"(dst),
                 "l"(m), "r"(bar), "r"(c0), "r"(c1), "h"((unsigned short)3) : "memory");
}
__device__ __forceinline__ void tma_5d_mc(uint32_t dst, const CUtensorMap* m, int c0, int c1, int c2, int c3, int c4, uint32_t bar) {
    asm volatile("cp.async.bulk.tensor.5d.shared::cluster.global.mbarrier::complete_tx::bytes.multicast::cluster [%0], [%1, {%3,%4,%5,%6,%7}], [%2], %8;" ::"r"(dst),
                 "l"(m), "r"(bar), "r"(c0), "r"(c1), "r"(c2), "r"(c3), "r"(c4), "h"((unsigned short)3) : "memory");
}
__device__ __forceinline__ void bulk_g2s_mc(uint32_t dst, const void* src, uint32_t bytes, uint32_t bar) {
    asm volatile("cp.async.bulk.shared::cluster.global.mbarrier::complete_tx::bytes.multicast::cluster [%0], [%1], %2, [%3], %4;" ::"r"(dst),
                 "l"(src), "r"(bytes), "r"(bar), "h"((unsigned short)3) : "memory");
}
__device__ __forceinline__ void tma_store_5d(const CUtensorMap* m, int c0, int c1, int c2, int c3, int c4, uint32_t src) {
    asm volatile("cp.async.bulk.tensor.5d.global.shared::cta.bulk_group [%0, {%2,%3,%4,%5,%6}], [%1];" ::"l"(m), "r"(src),
                 "r"(c0), "r"(c1), "r"(c2), "r"(c3), "r"(c4) : "memory");
}
__device__ __forceinline__ uint32_t lds32(uint32_t a) { uint32_t v; asm volatile("ld.shared.u32 %0, [%1];" : "=r"(v) : "r"(a) : "memory"); return v; }
__device__ __forceinline__ uint4 ld_relaxed_u4(const uint4* p) {
    uint4 v;
    asm volatile("ld.relaxed.gpu.global.v4.u32 {%0,%1,%2,%3}, [%4];" : "=r"(v.x), "=r"(v.y), "=r"(v.z), "=r"(v.w) : "l"(p) : "memory");
    return v;
}
__device__ __forceinline__ void fence_async() { asm volatile("fence.proxy.async.global;" ::: "memory"); }
__device__ __forceinline__ void red_relaxed(unsigned* p, unsigned v) {
    asm volatile("red.relaxed.gpu.global.add.u32 [%0], %1;" ::"l"(p), "r"(v) : "memory");
}
__device__ __forceinline__ uint32_t mapa(uint32_t a, uint32_t rank) {
    uint32_t d;
    asm("mapa.shared::cluster.u32 %0, %1, %2;" : "=r"(d) : "r"(a), "r"(rank));
    return d;
}
__device__ __forceinline__ void mbar_arrive_remote(uint32_t ra) {
    asm volatile("mbarrier.arrive.relaxed.cluster.shared::cluster.b64 _, [%0];" ::"r"(ra) : "memory");
}
__device__ __forceinline__ void mbar_wait_cluster(uint32_t a, uint32_t parity) {
    asm volatile("{\n.reg .pred p, q;\n.reg .u32 n;\nmov.u32 n, 0;\n"
                 "W_%=:\nmbarrier.try_wait.parity.acquire.cluster.shared::cta.b64 p, [%0], %1;\n@p bra D_%=;\n"
                 "add.u32 n, n, 1;\nsetp.lt.u32 q, n, 4194304;\n@q bra W_%=;\nD_%=:\n}" ::"r"(a), "r"(parity) : "memory");
}
__device__ __forceinline__ void bulk_s2peer(uint32_t rdst, uint32_t src, uint32_t bytes, uint32_t rbar) {
    asm volatile("cp.async.bulk.shared::cluster.shared::cta.mbarrier::complete_tx::bytes [%0], [%1], %2, [%3];" ::"r"(rdst),
                 "r"(src), "r"(bytes), "r"(rbar) : "memory");
}
__device__ __forceinline__ void fence_async_smem() { asm volatile("fence.proxy.async.shared::cta;" ::: "memory"); }
__device__ __forceinline__ void wg_fence() { asm volatile("wgmma.fence.sync.aligned;" ::: "memory"); }
__device__ __forceinline__ void wg_commit() { asm volatile("wgmma.commit_group.sync.aligned;" ::: "memory"); }
template <int N> __device__ __forceinline__ void wg_wait() { asm volatile("wgmma.wait_group.sync.aligned %0;" ::"n"(N) : "memory"); }
__device__ __forceinline__ void bar_sync(int id, int n) { asm volatile("bar.sync %0, %1;" ::"r"(id), "r"(n) : "memory"); }
__device__ __forceinline__ void bar_arrive(int id, int n) { asm volatile("bar.arrive %0, %1;" ::"r"(id), "r"(n) : "memory"); }
__device__ __forceinline__ unsigned ld_acquire(const unsigned* p) {
    unsigned v;
    asm volatile("ld.acquire.gpu.global.u32 %0, [%1];" : "=r"(v) : "l"(p) : "memory");
    return v;
}
__device__ __forceinline__ void red_release(unsigned* p, unsigned v) {
    asm volatile("red.release.gpu.global.add.u32 [%0], %1;" ::"l"(p), "r"(v) : "memory");
}
__device__ __forceinline__ void wait_count(const unsigned* p, unsigned target) {
    unsigned n = 0;
#pragma unroll 1
    while ((int)(ld_acquire(p) - target) < 0 && ++n < SPIN_LIMIT) {}
}
__device__ __forceinline__ float4 ld_relaxed_f4(const float4* p) {
    float4 v;
    asm volatile("ld.relaxed.gpu.global.v4.f32 {%0,%1,%2,%3}, [%4];" : "=f"(v.x), "=f"(v.y), "=f"(v.z), "=f"(v.w) : "l"(p) : "memory");
    return v;
}
__device__ __forceinline__ void st_relaxed_f4(float4* p, float4 v) {
    asm volatile("st.relaxed.gpu.global.v4.f32 [%0], {%1,%2,%3,%4};" ::"l"(p), "f"(v.x), "f"(v.y), "f"(v.z), "f"(v.w) : "memory");
}
__device__ __forceinline__ uint32_t pack_bf16(float lo, float hi) {
    uint32_t r;
    asm("cvt.rn.bf16x2.f32 %0, %1, %2;" : "=r"(r) : "f"(hi), "f"(lo));
    return r;
}
__device__ __forceinline__ float bf_lo(uint32_t v) { return __uint_as_float(v << 16); }
__device__ __forceinline__ float bf_hi(uint32_t v) { return __uint_as_float(v & 0xffff0000u); }
__device__ __forceinline__ void sts32(uint32_t a, uint32_t v) { asm volatile("st.shared.u32 [%0], %1;" ::"r"(a), "r"(v) : "memory"); }
__device__ __forceinline__ void sts128(uint32_t a, uint4 v) {
    asm volatile("st.shared.v4.u32 [%0], {%1,%2,%3,%4};" ::"r"(a), "r"(v.x), "r"(v.y), "r"(v.z), "r"(v.w) : "memory");
}

__device__ __forceinline__ uint64_t desc_ni(uint32_t addr, uint32_t lbo, uint32_t sbo) {
    return (uint64_t)((addr & 0x3FFFF) >> 4) | ((uint64_t)(lbo >> 4) << 16) | ((uint64_t)(sbo >> 4) << 32);
}
__device__ __forceinline__ uint64_t desc_a(uint32_t addr) { return desc_ni(addr, 128, 1024); }
template <int N> __device__ __forceinline__ uint64_t desc_b(uint32_t addr) { return desc_ni(addr, 16 * N, 128); }
__device__ __forceinline__ uint64_t desc_k(uint32_t addr) {
    return (uint64_t)((addr & 0x3FFFF) >> 4) | (1ull << 16) | (64ull << 32) | (1ull << 62);
}
__device__ __forceinline__ uint64_t desc_mn(uint32_t addr, uint32_t lbo) {
    return (uint64_t)((addr & 0x3FFFF) >> 4) | ((uint64_t)(lbo >> 4) << 16) | (64ull << 32) | (1ull << 62);
}

#define ACC8(d, o) "+f"(d[o + 0]), "+f"(d[o + 1]), "+f"(d[o + 2]), "+f"(d[o + 3]), "+f"(d[o + 4]), "+f"(d[o + 5]), "+f"(d[o + 6]), "+f"(d[o + 7])
template <int TB, int SA = 1>
__device__ __forceinline__ void wgmma_n128(float (&d)[64], uint64_t da, uint64_t db, int sd) {
    asm volatile(
        "{\n.reg .pred p;\nsetp.ne.b32 p, %66, 0;\n"
        "wgmma.mma_async.sync.aligned.m64n128k16.f32.bf16.bf16 "
        "{%0,%1,%2,%3,%4,%5,%6,%7,%8,%9,%10,%11,%12,%13,%14,%15,%16,%17,%18,%19,%20,%21,%22,%23,%24,%25,%26,%27,%28,%29,%30,%31,"
        "%32,%33,%34,%35,%36,%37,%38,%39,%40,%41,%42,%43,%44,%45,%46,%47,%48,%49,%50,%51,%52,%53,%54,%55,%56,%57,%58,%59,%60,%61,%62,%63},"
        " %64, %65, p, %68, 1, 0, %67;\n}"
        : ACC8(d, 0), ACC8(d, 8), ACC8(d, 16), ACC8(d, 24), ACC8(d, 32), ACC8(d, 40), ACC8(d, 48), ACC8(d, 56)
        : "l"(da), "l"(db), "r"(sd), "n"(TB), "n"(SA));
}
template <int N> __device__ __forceinline__ void acc_def(float (&d)[N]) {
#pragma unroll
    for (int i = 0; i < N; i++) d[i] = 0.f;
}
template <int TB>
__device__ __forceinline__ void wgmma_n64(float (&d)[32], uint64_t da, uint64_t db, int sd) {
    asm volatile(
        "{\n.reg .pred p;\nsetp.ne.b32 p, %34, 0;\n"
        "wgmma.mma_async.sync.aligned.m64n64k16.f32.bf16.bf16 "
        "{%0,%1,%2,%3,%4,%5,%6,%7,%8,%9,%10,%11,%12,%13,%14,%15,%16,%17,%18,%19,%20,%21,%22,%23,%24,%25,%26,%27,%28,%29,%30,%31},"
        " %32, %33, p, 1, 1, 0, %35;\n}"
        : ACC8(d, 0), ACC8(d, 8), ACC8(d, 16), ACC8(d, 24)
        : "l"(da), "l"(db), "r"(sd), "n"(TB));
}
template <int SA>
__device__ __forceinline__ void wgmma_n64s(float (&d)[32], uint64_t da, uint64_t db, int sd) {
    asm volatile(
        "{\n.reg .pred p;\nsetp.ne.b32 p, %34, 0;\n"
        "wgmma.mma_async.sync.aligned.m64n64k16.f32.bf16.bf16 "
        "{%0,%1,%2,%3,%4,%5,%6,%7,%8,%9,%10,%11,%12,%13,%14,%15,%16,%17,%18,%19,%20,%21,%22,%23,%24,%25,%26,%27,%28,%29,%30,%31},"
        " %32, %33, p, %35, 1, 0, 1;\n}"
        : ACC8(d, 0), ACC8(d, 8), ACC8(d, 16), ACC8(d, 24)
        : "l"(da), "l"(db), "r"(sd), "n"(SA));
}
__device__ __forceinline__ void wgmma_n64_rs(float (&d)[32], uint32_t a0, uint32_t a1, uint32_t a2, uint32_t a3, uint64_t db, int sd) {
    asm volatile(
        "{\n.reg .pred p;\nsetp.ne.b32 p, %37, 0;\n"
        "wgmma.mma_async.sync.aligned.m64n64k16.f32.bf16.bf16 "
        "{%0,%1,%2,%3,%4,%5,%6,%7,%8,%9,%10,%11,%12,%13,%14,%15,%16,%17,%18,%19,%20,%21,%22,%23,%24,%25,%26,%27,%28,%29,%30,%31},"
        " {%32,%33,%34,%35}, %36, p, 1, 1, 1;\n}"
        : ACC8(d, 0), ACC8(d, 8), ACC8(d, 16), ACC8(d, 24)
        : "r"(a0), "r"(a1), "r"(a2), "r"(a3), "l"(db), "r"(sd));
}

struct Params {
    const __nv_bfloat16* x0;
    const __nv_bfloat16* w_r;
    const __nv_bfloat16* w_i;
    const __nv_bfloat16* lam_re;
    const __nv_bfloat16* lam_im;
    const __nv_bfloat16* log_dt;
    const __nv_bfloat16* dskip;
    float* out;
    int stop;
};

__device__ __forceinline__ float ldbf(const __nv_bfloat16* p) { return __bfloat162float(*p); }

__device__ __forceinline__ void dft_fp(int j, int& f, int& ph) {
    int cs = j >> 1;
    if (j == 1) { f = 256; ph = 0; }
    else { f = cs; ph = (j & 1) ? 128 : 0; }
}

__device__ __forceinline__ void gen_col_consts(uint8_t* sm, int tid) {
    const unsigned short* t64 = (const unsigned short*)(sm + SM_T64);
    const uint32_t sb = s2u(sm);
#pragma unroll 1
    for (int ch = tid; ch < 2560; ch += 256) {
        int c8 = (ch >> 3) & 7, m = (ch & 7) | ((ch >> 3) & 56), po, pi, step, base;
        if (ch < 2048) {
            pi = (ch >> 9) & 1; po = (m >> 3) & 1;
            step = 32 * (ch >> 10) + 8 * (m >> 4) + (m & 7);
            base = c8 * 8;
        } else {
            pi = m >> 5; po = c8 >> 2;
            step = 2 * (m & 31);
            base = (c8 & 3) * 8;
        }
        int idx = base * step + ((po == pi) ? 0 : (po == 0 ? 48 : 16));
        uint32_t v[4];
#pragma unroll
        for (int e = 0; e < 4; e++) {
            uint32_t lo = t64[idx & 63], hi = t64[(idx + step) & 63];
            idx += 2 * step;
            v[e] = lo | (hi << 16);
        }
        sts128(sb + SM_X + ch * 16, make_uint4(v[0], v[1], v[2], v[3]));
    }
}

__global__ void __launch_bounds__(NTHREADS, 1)
fused_kernel(const __grid_constant__ CUtensorMap tm_x, const __grid_constant__ CUtensorMap tm_bre,
             const __grid_constant__ CUtensorMap tm_bim, const __grid_constant__ CUtensorMap tm_cre,
             const __grid_constant__ CUtensorMap tm_cim, const __grid_constant__ CUtensorMap tm_col, const Params p) {
    extern __shared__ __align__(1024) uint8_t sm[];
    const uint32_t sb = s2u(sm);
    const int tid = threadIdx.x, b = blockIdx.x;
    const int c = b >> 3, r = b & 7;
    const int par = r & 1, pi_ = r >> 1, own = 4 * par + pi_;
    const int wg = __shfl_sync(~0u, tid >> 7, 0), w = __shfl_sync(~0u, (tid >> 5) & 3, 0), lane = tid & 31, g = lane >> 2, q = lane & 3;
    auto BAR = [&](int i) { return sb + SM_BAR + 8 * i; };
    unsigned* s_tgt = (unsigned*)(sm + SM_TGT);

    if (tid < NBARS) {
        int cnt = 1;
        if ((tid >= B_EMPTY0 && tid < B_EMPTY0 + 4) || (tid >= B_XEMPTY && tid < B_XEMPTY + 4)) cnt = 24;
        if (tid == B_RFREE) cnt = 12;
        if (tid == B_HDONE) cnt = 2;
        if (tid >= B_AEMPTY && tid < B_AEMPTY + 8) cnt = 8;
        if (tid == B_AFREE) cnt = 4;
        mbar_init(BAR(tid), cnt);
        asm volatile("fence.mbarrier_init.release.cluster;" ::: "memory");
    }
    asm volatile("barrier.cluster.arrive.release.aligned;" ::: "memory");
    if (tid >= 64 && tid < 70) {
        s_tgt[tid - 64] = ((ld_acquire(&g_bar[tid - 64]) >> 7) + 1u) << 7;
    } else if (tid >= 96 && tid < 112) {
        g_ssq[2048 + 16 * b + tid - 96] = 0.f;
    } else if (tid >= 128 && tid < 384) {
        int i = tid - 128;
        __nv_bfloat16 h = __float2bfloat16(cospif((float)i * (1.f / 256.f)));
        ((__nv_bfloat16*)(sm + SM_TAB))[i] = h;
        ((__nv_bfloat16*)(sm + SM_TAB))[i + 256] = __hneg(h);
        if ((i & 7) == 0) {
            ((__nv_bfloat16*)(sm + SM_T64))[i >> 3] = h;
            ((__nv_bfloat16*)(sm + SM_T64))[(i >> 3) + 32] = __hneg(h);
        }
        if (i < 128) ((float4*)g_ssqc)[b * 128 + i] = make_float4(0.f, 0.f, 0.f, 0.f);
    } else if (tid >= 416) {
        int i = tid - 416;
        int ps = i < 64 ? 64 * r + i : 32 * c + i - 64;
        float lr = ldbf(p.lam_re + ps), li = ldbf(p.lam_im + ps);
        float dt = __bfloat162float(__float2bfloat16(expf(ldbf(p.log_dt + ps))));
        float mag = expf(lr * dt), t = li * dt * 0.15915494309189535f, sn, cs;
        t -= rintf(t);
        sincospif(2.f * t, &sn, &cs);
        float er = mag * cs, ei = mag * sn;
        if (i < 64) {
            *(float2*)(sm + SM_LAM + i * 8) = make_float2(er, ei);
        } else {
            er -= 1.f;
            float inv = 1.f / (lr * lr + li * li);
            *(float2*)(sm + SM_RSTD + (i - 64) * 8) = make_float2((er * lr + ei * li) * inv, (ei * lr - er * li) * inv);
        }
    } else if (tid >= 384 && tid < 390) {
        const CUtensorMap* tm = tid == 384 ? &tm_x : tid == 385 ? &tm_bre : tid == 386 ? &tm_bim : tid == 387 ? &tm_cre : tid == 388 ? &tm_cim : &tm_col;
        asm volatile("prefetch.tensormap [%0];" ::"l"(tm) : "memory");
    }
    __syncwarp();
    asm volatile("barrier.cluster.wait.acquire.aligned;" ::: "memory");

    if (wg == 3) {
        asm volatile("setmaxnreg.dec.sync.aligned.u32 56;");
        if (w > 0) {
            bar_arrive(10, 480);
            if (w == 2) {
                const int kq = 2 * b + (lane >> 4), row = (kq >> 2) + 128 * (kq & 3) + 512 * ((lane >> 1) & 3) + 64 * (lane & 1);
                const char* src = (const char*)(((lane >> 3) & 1) ? p.w_i : p.w_r) + (size_t)row * 514;
                size_t a0 = (size_t)src & ~(size_t)15;
                int bytes = row == 2047 ? 512 : 544;
                asm volatile("cp.async.bulk.prefetch.L2.global [%0], %1;" ::"l"(a0), "r"(bytes) : "memory");
            }
#pragma unroll 1
            for (int i = tid - 448; i < 1536 + 128 && w > 1; i += 64) {
                if (i < 1536) g_P[(uint32_t)(b * 4 + i / 384) * 1024 + 640 + i % 384] = make_uint4(0, 0, 0, 0);
                else g_Ebuf[b * 128 + i - 1536] = make_float4(0.f, 0.f, 0.f, 0.f);
            }
#pragma unroll 1
            for (int task = tid - 448; task < 256 && w > 1; task += 64) {
                const int cb = task & 127, kq = 2 * b + (task >> 7), k1 = kq >> 2, qq = kq & 3;
                const unsigned short* wr_ = (const unsigned short*)p.w_r + (k1 + 128 * qq) * 257;
                const unsigned short* wi_ = (const unsigned short*)p.w_i + (k1 + 128 * qq) * 257;
                const int c0 = cb == 0 ? 256 : 2 * cb, c1 = 2 * cb + 1;
                uint32_t wf[16];
#pragma unroll
                for (int i = 0; i < 8; i++) {
                    int o = (512 * (i >> 1) + 64 * (i & 1)) * 257;
                    wf[i] = (uint32_t)__ldg(wr_ + o + c0) | ((uint32_t)__ldg(wi_ + o + c0) << 16);
                    wf[8 + i] = (uint32_t)__ldg(wr_ + o + c1) | ((uint32_t)__ldg(wi_ + o + c1) << 16);
                }
                uint4* wd = g_Wfrag + (uint32_t)(cb * 1024 + kq);
#pragma unroll
                for (int i = 0; i < 4; i++) wd[i * 256] = make_uint4(wf[4 * i], wf[4 * i + 1], wf[4 * i + 2], wf[4 * i + 3]);
            }
            __syncwarp();
            if (w > 1) bar_arrive(11, 96);
            if (w == 3) return;
            if (w == 2) {
#pragma unroll 1
                for (int it = 0; it < 4; it++) {
                    const int hf = it & 1;
                    __syncwarp();
                    if (hf == 0) bar_sync(13, 288); else bar_sync(6, 416);
                    if (lane == 0) {
                        const uint32_t src = sb + SM_HH + par * 32768 + hf * 16384;
                        bulk_s2peer(mapa(src, par ^ 1), src, 16384, mapa(BAR(hf ? B_HPEER1 : B_HPEER), par ^ 1));
                    }
                }
                return;
            }
            {
                uint4 p0 = __ldg((const uint4*)p.dskip + 2 * lane), p1 = __ldg((const uint4*)p.dskip + 2 * lane + 1);
                uint32_t u[8] = {p0.x, p0.y, p0.z, p0.w, p1.x, p1.y, p1.z, p1.w};
#pragma unroll 1
                for (int jj = 0; jj < 4; jj++) {
                    int j = 64 * r + 4 * c + jj, f, ph;
                    dft_fp(j, f, ph);
                    float s = 0.f;
                    int idx = 16 * lane * f + ph;
#pragma unroll
                    for (int i = 0; i < 16; i++) {
                        int a = idx & 511;
                        idx += f;
                        a = a >= 256 ? a - 512 : a;
                        s += ((i & 1) ? bf_hi(u[i >> 1]) : bf_lo(u[i >> 1])) * __cosf((float)a * (6.283185307179586f / 512.f));
                    }
#pragma unroll
                    for (int o = 16; o; o >>= 1) s += __shfl_xor_sync(~0u, s, o);
                    if (lane == 0) g_Dh[j] = s;
                }
                if (lane == 0) red_release(&g_bar[5], 1);
                __syncwarp();
            }
            bar_sync(2, 416);
            if (lane == 0) {
                TX(5);
                asm volatile("cp.async.bulk.global.shared::cta.bulk_group [%0], [%1], 8192;" ::"l"(g_A1 + (uint32_t)(((c >> 1) * 8 + r) * 16384 + (c & 1) * 8192)),
                             "r"(sb + SM_B1ST) : "memory");
                asm volatile("cp.async.bulk.commit_group;" ::: "memory");
                fence_async();
                red_release(&g_bar[0], 1);
                TX(6);
                asm volatile("cp.async.bulk.wait_group 0;" ::: "memory");
                fence_async();
            }
            __syncwarp();
            bar_sync(11, 96);
            if (lane == 0) red_release(&g_bar[4], 1);
#pragma unroll 1
            for (int layer = 0; layer < 2; layer++) {
                __syncwarp();
                bar_sync(5, 416);
                if (lane == 0) {
                    TX(0 + 8 * layer);
                    tma_store_5d(&tm_col, 32 * (b & 1), 0, b >> 1, 0, layer, sb + SM_RAW);
                    asm volatile("cp.reduce.async.bulk.global.shared::cta.bulk_group.add.f32 [%0], [%1], 8192;" ::"l"(g_ssqc + (layer * 16 + (b & 15)) * 2048),
                                 "r"(sb + SM_SSQ) : "memory");
                    asm volatile("cp.async.bulk.commit_group;" ::: "memory");
                    asm volatile("cp.async.bulk.wait_group 0;" ::: "memory");
                    TX(1 + 8 * layer);
                    fence_async();
                    red_release(&g_bar[1 + 2 * layer], 1);
                    TX(2 + 8 * layer);
                }
            }
        } else if (tid == 384) {
#pragma unroll 1
            for (int kb = 0; kb < 8; kb++) {
                int s = kb < 6 ? kb : kb - 4;
                uint32_t dst = s < 2 ? sb + SM_A + 65536 + s * 24576 : sb + SM_X + (s - 2) * 24576;
                if (kb >= 6) mbar_wait_cluster(BAR(B_EMPTY0 + s), 0);
                uint32_t fb = BAR(B_FULL0 + kb);
                mbar_expect(fb, 24576);
                tma_5d_mc(dst + par * 8192, &tm_x, kb * 64, 0, 0, 8 * par, c, fb);
                tma_2d_mc(dst + 16384 + par * 4096, par ? &tm_bim : &tm_bre, kb * 64, 32 * c, fb);
                if (kb == 5) {
#pragma unroll 1
                    for (int k2 = par; k2 < 8; k2 += 2) {
                        asm volatile("cp.async.bulk.prefetch.tensor.2d.L2.global [%0, {%1,%2}];" ::"l"((c & 1) ? &tm_cim : &tm_cre), "r"(64 * (c >> 1)), "r"(k2 * 64) : "memory");
                        if (k2 < 4) {
                            asm volatile("cp.async.bulk.prefetch.tensor.5d.L2.global [%0, {%1,%2,%3,%4,%5}];" ::"l"(&tm_x), "r"((6 + (k2 >> 1)) * 64), "r"(0), "r"(0), "r"(8 * par), "r"(c) : "memory");
                            asm volatile("cp.async.bulk.prefetch.tensor.2d.L2.global [%0, {%1,%2}];" ::"l"(par ? &tm_bim : &tm_bre), "r"((6 + (k2 >> 1)) * 64), "r"(32 * c) : "memory");
                        }
                    }
                }
                if (kb == 7) {
                    mbar_wait_cluster(BAR(B_EMPTY0 + 0), 0);
                    mbar_wait_cluster(BAR(B_EMPTY0 + 1), 0);
                    mbar_expect(BAR(B_FULLC), 65536);
#pragma unroll 1
                    for (int k2 = par; k2 < 8; k2 += 2)
                        tma_2d_mc(sb + SM_A + 65536 + k2 * 8192, (c & 1) ? &tm_cim : &tm_cre, 64 * (c >> 1), k2 * 64, BAR(B_FULLC));
                }
            }
#pragma unroll 1
            for (int layer = 0; layer < 2; layer++) {
                if (layer == 1) {
                    mbar_wait(BAR(B_AEMPTY + 6), 1);
#pragma unroll 1
                    for (int s = 0; s < 8; s++) {
                        mbar_wait(BAR(B_AEMPTY + s), 1);
                        mbar_expect(BAR(B_AFULL + s), 16384);
                        bulk_g2s(sb + SM_A + s * 16384, g_A1 + (uint32_t)(r * 8 + s) * 16384, 16384, BAR(B_AFULL + s));
                    }
                }
                wait_count(&g_bar[2 * layer], s_tgt[2 * layer]);
                TX(4 + 8 * layer);
                fence_async();
                mbar_expect(BAR(B_COL), 16384 + 8192);
                tma_5d(sb + SM_RAW, &tm_col, 32 * (b & 1), 0, b >> 1, 0, layer, BAR(B_COL));
                bulk_g2s(sb + SM_SSQ, g_ssq + layer * 2048, 8192, BAR(B_COL));
                if (layer == 0) {
                    wait_count(&g_bar[4], s_tgt[4]);
                    mbar_arrive(BAR(B_WRDY), 1);
                }
                if (layer == 0) {
                    mbar_wait(BAR(B_AFREE), 0);
                    mbar_wait(BAR(B_COL), 0);
#pragma unroll 1
                    for (int s = 0; s < 8; s++) {
                        mbar_expect(BAR(B_AFULL + s), 16384);
                        bulk_g2s(sb + SM_A + s * 16384, g_A1 + (uint32_t)(r * 8 + s) * 16384, 16384, BAR(B_AFULL + s));
                    }
                }
                wait_count(&g_bar[1 + 2 * layer], s_tgt[1 + 2 * layer]);
                TX(3 + 8 * layer);
                fence_async();
                const uint8_t* xsrc = g_X + (uint32_t)(layer * 16 + c) * 8 * 16384;
                const uint8_t* esrc = g_E + (uint32_t)(layer * 8 + own) * 8 * 8192;
                mbar_arrive(BAR(B_SSQ), 1);
                mbar_expect(BAR(B_HPEER), 16384);
                mbar_expect(BAR(B_HPEER1), 16384);
#pragma unroll 1
                for (int it = 0; it < 12; it++) {
                    if (it < 8) {
                        int st = it & 3, f = layer * 2 + (it >> 2);
                        if (f > 0) mbar_wait_cluster(BAR(B_XEMPTY + st), (f - 1) & 1);
                        mbar_expect(BAR(B_XFULL + st), 24576);
                        bulk_g2s_mc(sb + SM_X + st * 24576 + par * 8192, xsrc + (uint32_t)it * 16384 + par * 8192, 8192, BAR(B_XFULL + st));
                        bulk_g2s(sb + SM_X + st * 24576 + 16384, esrc + (uint32_t)it * 8192, 8192, BAR(B_XFULL + st));
                    }
                    if (it >= 4) {
                        int s = it - 4, tile = 4 * par + ((pi_ + 1 + (s >> 1)) & 3), sl = r ^ (s & 1);
                        mbar_wait(BAR(B_AEMPTY + s), 0);
                        uint32_t fb = BAR(B_AFULL + s), dst = sb + SM_A + s * 16384;
                        mbar_expect(fb, 16384);
                        if (layer == 1) {
                            tma_2d(dst, &tm_cre, 64 * sl, 64 * tile, fb);
                            tma_2d(dst + 8192, &tm_cim, 64 * sl, 64 * tile, fb);
                        } else {
                            bulk_g2s(dst, g_A2 + (uint32_t)(sl * 8 + tile) * 16384, 16384, fb);
                        }
                    }
                }
            }
        }
        return;
    }

    asm volatile("setmaxnreg.inc.sync.aligned.u32 152;");
    TS(0);
    if (wg == 0) TC(30);
    {
        const int f = 32 * r + lane;
        float cd, sd;
        __sincosf((float)f * (6.283185307179586f / 512.f), &sd, &cd);
        const uint32_t dst = sb + SM_A + (lane >> 2) * 1024 + (lane & 3) * 32;
#pragma unroll 1
        for (int ch = tid >> 5; ch < 64; ch += 12) {
            int a = (8 * ch * f) & 511;
            a = a >= 256 ? a - 512 : a;
            float cs, sn;
            __sincosf((float)a * (6.283185307179586f / 512.f), &sn, &cs);
            float cv[8], sv[8];
#pragma unroll
            for (int e = 0; e < 8; e++) {
                cv[e] = cs; sv[e] = -sn;
                float t = cs * cd - sn * sd;
                sn = sn * cd + cs * sd;
                cs = t;
            }
            uint4 o1 = make_uint4(pack_bf16(sv[0], sv[1]), pack_bf16(sv[2], sv[3]), pack_bf16(sv[4], sv[5]), pack_bf16(sv[6], sv[7]));
            if (f == 0) o1 = make_uint4(0xbf803f80u, 0xbf803f80u, 0xbf803f80u, 0xbf803f80u);
            uint32_t a0 = dst + (ch >> 3) * 8192 + (ch & 7) * 128;
            sts128(a0, make_uint4(pack_bf16(cv[0], cv[1]), pack_bf16(cv[2], cv[3]), pack_bf16(cv[4], cv[5]), pack_bf16(cv[6], cv[7])));
            sts128(a0 + 16, o1);
        }
    }
    fence_async_smem();
    bar_sync(10, 480);
    TS(1);
    uint4 pre[4];
    if (wg < 2) {
        const uint4* src = (const uint4*)(p.x0 + (uint32_t)(128 * c + 16 * r + 8 * wg + 2 * w) * 512) + lane;
#pragma unroll
        for (int i = 0; i < 4; i++) pre[i] = __ldg(src + 32 * i);
    } else {
        pre[0] = pre[1] = pre[2] = pre[3] = make_uint4(0, 0, 0, 0);
    }

    {
        float acc[32];
        acc_def(acc);
#pragma unroll 1
        for (int kb = 0; kb < 8; kb++) {
            int s = kb < 6 ? kb : kb - 4;
            uint32_t src = (s < 2 ? sb + SM_A + 65536 + s * 24576 : sb + SM_X + (s - 2) * 24576) + wg * 8192;
            mbar_wait(BAR(B_FULL0 + kb), 0);
            wg_fence();
#pragma unroll
            for (int ks = 0; ks < 4; ks++)
                wgmma_n64<0>(acc, desc_a(sb + SM_A + kb * 8192 + ks * 256), desc_k(src + ks * 32), 1);
            wg_commit();
            wg_wait<1>();
            if (kb > 0 && kb <= 4 && lane == 0) { mbar_arrive(BAR(B_EMPTY0 + kb - 1), 1); mbar_arrive_remote(mapa(BAR(B_EMPTY0 + kb - 1), par ^ 1)); }
        }
        wg_wait<0>();
        TS(2);
        if (wg < 2) {
            uint8_t* dst = g_X + (uint32_t)((c * 8 + r) * 16384 + w * 4096 + wg * 1024 + g * 16 + 4 * q);
#pragma unroll
            for (int i = 0; i < 8; i++) {
                *(uint32_t*)(dst + i * 128) = pack_bf16(acc[4 * i], acc[4 * i + 1]);
                *(uint32_t*)(dst + 2048 + i * 128) = pack_bf16(acc[4 * i + 2], acc[4 * i + 3]);
            }
#pragma unroll
            for (int rr = 0; rr < 2; rr++) {
                int t = 16 * r + 8 * wg + 2 * w + rr;
                uint32_t u[8] = {pre[2 * rr].x, pre[2 * rr].y, pre[2 * rr].z, pre[2 * rr].w, pre[2 * rr + 1].x, pre[2 * rr + 1].y, pre[2 * rr + 1].z, pre[2 * rr + 1].w};
                float s = 0.f;
#pragma unroll
                for (int i = 0; i < 8; i++) s += bf_lo(u[i]) + bf_hi(u[i]);
#pragma unroll
                for (int o = 16; o; o >>= 1) s += __shfl_xor_sync(~0u, s, o);
                float m = s * (1.f / 512.f), ss = 0.f;
#pragma unroll
                for (int i = 0; i < 8; i++) { float d0 = bf_lo(u[i]) - m, d1 = bf_hi(u[i]) - m; ss += d0 * d0 + d1 * d1; }
#pragma unroll
                for (int o = 16; o; o >>= 1) ss += __shfl_xor_sync(~0u, ss, o);
                if (lane == 0) g_ssq[128 * c + 8 * ((t >> 1) & 15) + 2 * (t >> 5) + (t & 1)] = ss;
            }
        } else {
            uint8_t* dst = sm + SM_B1ST + w * 256 + q * 32 + g * 2;
            const float wj0 = (r == 0 && w == 0 && g < 2) ? (g == 0 ? 0.f : 1.f / 512.f) : 2.f / 512.f;
#pragma unroll
            for (int i = 0; i < 4; i++) {
#pragma unroll
                for (int e = 0; e < 2; e++) {
                    float2 cf = *(const float2*)(sm + SM_RSTD + (8 * i + 2 * q + e) * 8);
#pragma unroll
                    for (int h = 0; h < 2; h++) {
                        float wj = h == 0 ? wj0 : 2.f / 512.f;
                        float pr = acc[4 * i + 2 * h + e] * wj, pi = acc[16 + 4 * i + 2 * h + e] * wj;
                        uint8_t* d2 = dst + i * 2048 + h * 128 + e * 16;
                        *(__nv_bfloat16*)(d2) = __float2bfloat16(cf.x * pr - cf.y * pi);
                        *(__nv_bfloat16*)(d2 + 1024) = __float2bfloat16(cf.x * pi + cf.y * pr);
                    }
                }
            }
            fence_async_smem();
        }
        bar_sync(2, 416);
        TS(3);
    }

    if (wg == 2) {
        float acc[32];
        acc_def(acc);
        mbar_wait(BAR(B_FULLC), 0);
        wg_fence();
#pragma unroll 1
        for (int kb = 0; kb < 8; kb++) {
#pragma unroll
            for (int ks = 0; ks < 4; ks++)
                wgmma_n64<1>(acc, desc_a(sb + SM_A + kb * 8192 + ks * 256), desc_mn(sb + SM_A + 65536 + kb * 8192 + ks * 2048, 8192), 1);
            wg_commit();
        }
        wg_wait<0>();
        fence_async_smem();
        if (lane == 0) mbar_arrive(BAR(B_AFREE), 1);
        uint8_t* dst = g_A2 + (uint32_t)(((c >> 1) * 8 + r) * 16384 + (c & 1) * 8192 + w * 2048 + g * 16 + 4 * q);
#pragma unroll
        for (int i = 0; i < 8; i++) {
            *(uint32_t*)(dst + i * 128) = pack_bf16(acc[4 * i], acc[4 * i + 1]);
            *(uint32_t*)(dst + 1024 + i * 128) = pack_bf16(acc[4 * i + 2], acc[4 * i + 3]);
        }
        const int m = 4 * c + w, jp = 64 * r + m;
        int fp, php;
        dft_fp(jp, fp, php);
        const __nv_bfloat16* tab = (const __nv_bfloat16*)(sm + SM_TAB);
        const __nv_bfloat16* dh = (const __nv_bfloat16*)(sm + SM_RSTD);
#pragma unroll 1
        for (int it = 0; it < 4; it++) {
            if (it == 2) {
                if (tid == 256) wait_count(&g_bar[5], s_tgt[5]);
                bar_sync(3, 128);
                float4 d4 = __ldcg((const float4*)g_Dh + (tid - 256));
                *(uint2*)(sm + SM_RSTD + (tid - 256) * 8) = make_uint2(pack_bf16(d4.x, d4.y), pack_bf16(d4.z, d4.w));
                bar_sync(3, 128);
            }
            const int ch = lane + 32 * (it & 1);
            float v[8];
#pragma unroll
            for (int e = 0; e < 8; e++) {
                int j = 8 * ch + e, f, ph;
                dft_fp(j, f, ph);
                float wj = j == 0 ? 0.f : (j == 1 ? 1.f / 512.f : 2.f / 512.f);
                if (it < 2) {
                    v[e] = wj * __bfloat162float(tab[(jp * f + ph) & 511]);
                } else {
                    float gsum = 0.f;
#pragma unroll
                    for (int sgn = 0; sgn < 2; sgn++) {
                        int mm = (sgn ? f - fp : f + fp) & 511, pp = (sgn ? ph - php : ph + php) & 511;
                        if (mm > 256) { mm = 512 - mm; pp = (512 - pp) & 511; }
                        int odd = (pp >> 7) & 1;
                        float t = __bfloat162float(dh[mm == 256 ? 1 : 2 * mm + odd]);
                        if (odd && (mm & 255) == 0) t = 0.f;
                        gsum += (pp & 256) ? -t : t;
                    }
                    v[e] = 0.5f * wj * gsum;
                }
            }
            uint32_t off = (uint32_t)((it < 2 ? 64 : 0) + r * 8 + (ch >> 3)) * 8192 + (m >> 3) * 1024 + (ch & 7) * 128 + (m & 7) * 16;
            *(uint4*)(g_E + off) = make_uint4(pack_bf16(v[0], v[1]), pack_bf16(v[2], v[3]), pack_bf16(v[4], v[5]), pack_bf16(v[6], v[7]));
        }
        fence_async_smem();
    }

#pragma unroll 1
    for (int layer = 0; layer < 2; layer++) {
        if (wg < 2) {
            const int n1 = 32 * wg + 8 * w + g;
            const int ct = n1 >> 2;
            gen_col_consts(sm, tid);
            float twr[8], twi[8];
#pragma unroll
            for (int i = 0; i < 8; i++) {
                int n2 = 8 * (i >> 1) + 2 * q + (i & 1);
                int a = (n1 * n2) & 2047;
                a = a >= 1024 ? a - 2048 : a;
                float ang = (float)a * (-6.283185307179586f / 2048.f);
                twr[i] = __cosf(ang); twi[i] = __sinf(ang);
            }
            mbar_wait(BAR(B_COL), layer);
            TS(4 + 12 * layer);
            if (wg == 0) TC(0 + 10 * layer);
            const uint32_t rw0 = sb + SM_RAW + ct * 1024 + q * 64 + ((q >> 1) << 4) + (g & 3) * 4, rw1 = rw0 ^ 16;
            const int pos0 = 128 * ct + 8 * q + 2 * (g & 3);
            const int sw = b == 0 ? 1 : 0;
            uint32_t xr[4][4];
            const uint32_t st0 = sb + SM_H + (n1 >> 3) * 1024 + g * 16 + 4 * q;
#pragma unroll
            for (int i = 0; i < 4; i++) {
                float2 sq = *(const float2*)(sm + SM_SSQ + (pos0 + 32 * i) * 4);
                float r0 = rsqrtf(sq.x * (1.f / 512.f) + 1e-5f), r1 = rsqrtf(sq.y * (1.f / 512.f) + 1e-5f);
#pragma unroll
                for (int jj = 0; jj < 4; jj++) {
                    const int K = jj ^ (2 * (i & 1));
                    uint32_t a = ((K & 1) ? rw1 : rw0) + i * 256 + (K & 2) * 16;
                    if (jj < 2) a ^= sw << 4;
                    uint32_t v = lds32(a);
                    xr[jj][i] = v;
                    uint32_t o = pack_bf16(bf_lo(v) * r0, bf_hi(v) * r1);
                    if (jj == 1 && sw) o = 0u;
                    sts32(st0 + (jj & 1) * 8192 + (4 * (jj >> 1) + i) * 128, o);
                }
            }
            if (wg == 0) TC(1 + 10 * layer);
            fence_async_smem();
            bar_sync(1, 256);
            float acc[32];
            const uint32_t s1a = sb + SM_X + wg * 16384, s2b = sb + SM_X + 32768;
            wg_fence();
#pragma unroll
            for (int ks = 0; ks < 8; ks++)
                wgmma_n64<1>(acc, desc_a(s1a + (ks >> 2) * 8192 + (ks & 3) * 256), desc_b<64>(sb + SM_H + ks * 2048), ks != 0);
            wg_commit();
            mbar_wait(BAR(B_WRDY), 0);
            uint32_t wf[16];
            {
                const uint4* ws = g_Wfrag + (uint32_t)(b * 1024 + n1 * 4 + q);
#pragma unroll
                for (int i = 0; i < 4; i++) {
                    uint4 v = __ldcg(ws + i * 256);
                    wf[4 * i] = v.x; wf[4 * i + 1] = v.y; wf[4 * i + 2] = v.z; wf[4 * i + 3] = v.w;
                }
            }
            wg_wait<0>();
            if (wg == 0) TC(2 + 10 * layer);
            uint32_t are[2][4], aim[2][4];
#pragma unroll
            for (int col = 0; col < 2; col++) {
#pragma unroll
                for (int i = 0; i < 4; i++) {
                    int o = 4 * (4 * col + i);
                    float r0 = acc[o] * twr[2 * i] - acc[o + 2] * twi[2 * i], i0 = acc[o] * twi[2 * i] + acc[o + 2] * twr[2 * i];
                    float r1 = acc[o + 1] * twr[2 * i + 1] - acc[o + 3] * twi[2 * i + 1], i1 = acc[o + 1] * twi[2 * i + 1] + acc[o + 3] * twr[2 * i + 1];
                    are[col][i] = pack_bf16(r0, r1);
                    aim[col][i] = pack_bf16(i0, i1);
                }
            }
            wg_fence();
#pragma unroll
            for (int ks = 0; ks < 2; ks++)
                wgmma_n64_rs(acc, are[0][2 * ks], are[1][2 * ks], are[0][2 * ks + 1], are[1][2 * ks + 1], desc_b<64>(s2b + ks * 2048), ks != 0);
#pragma unroll
            for (int ks = 0; ks < 2; ks++)
                wgmma_n64_rs(acc, aim[0][2 * ks], aim[1][2 * ks], aim[0][2 * ks + 1], aim[1][2 * ks + 1], desc_b<64>(s2b + 4096 + ks * 2048), 1);
            wg_commit();
            wg_wait<0>();
            if (wg == 0) TC(3 + 10 * layer);
#pragma unroll
            for (int col = 0; col < 2; col++) {
#pragma unroll
                for (int i = 0; i < 4; i++) {
                    float gr[2], gi[2];
#pragma unroll
                    for (int e = 0; e < 2; e++) {
                        uint32_t wv = wf[col * 8 + 2 * i + e];
                        float wr = bf_lo(wv), wi = bf_hi(wv);
                        float zr = acc[4 * i + 2 * col + e], zi = acc[16 + 4 * i + 2 * col + e];
                        gr[e] = zr * wr - zi * wi;
                        gi[e] = -(zr * wi + zi * wr);
                    }
                    are[col][i] = pack_bf16(gr[0], gr[1]);
                    aim[col][i] = pack_bf16(gi[0], gi[1]);
                }
            }
            wg_fence();
#pragma unroll
            for (int ks = 0; ks < 2; ks++)
                wgmma_n64_rs(acc, are[0][2 * ks], are[1][2 * ks], are[0][2 * ks + 1], are[1][2 * ks + 1], desc_b<64>(s2b + ks * 2048), ks != 0);
#pragma unroll
            for (int ks = 0; ks < 2; ks++)
                wgmma_n64_rs(acc, aim[0][2 * ks], aim[1][2 * ks], aim[0][2 * ks + 1], aim[1][2 * ks + 1], desc_b<64>(s2b + 4096 + ks * 2048), 1);
            wg_commit();
            wg_wait<0>();
            if (wg == 0) TC(4 + 10 * layer);
#pragma unroll
            for (int col = 0; col < 2; col++) {
#pragma unroll
                for (int i = 0; i < 4; i++) {
                    float rr[2], im[2];
#pragma unroll
                    for (int e = 0; e < 2; e++) {
                        float zr = acc[4 * i + 2 * col + e], zi = acc[16 + 4 * i + 2 * col + e];
                        rr[e] = zr * twr[2 * i + e] - zi * twi[2 * i + e];
                        im[e] = zr * twi[2 * i + e] + zi * twr[2 * i + e];
                    }
                    sts32(st0 + 16384 + (4 * col + i) * 128, pack_bf16(rr[0], rr[1]));
                    sts32(st0 + 16384 + 8192 + (4 * col + i) * 128, pack_bf16(im[0], im[1]));
                }
            }
            if (wg == 0) TC(5 + 10 * layer);
            fence_async_smem();
            bar_sync(1, 256);
            wg_fence();
#pragma unroll
            for (int ks = 0; ks < 8; ks++)
                wgmma_n64<1>(acc, desc_a(s1a + (ks >> 2) * 8192 + (ks & 3) * 256), desc_b<64>(sb + SM_H + 16384 + ks * 2048), ks != 0);
            wg_commit();
            wg_wait<0>();
            if (wg == 0) TC(6 + 10 * layer);
            const float sc = 1.f / 2048.f;
            const float sci0 = sw ? 0.f : -sc;
            const float wr0 = sw ? 0.5f : 1.f, wi0 = sw ? 0.f : 1.f;
#pragma unroll
            for (int i = 0; i < 4; i++) {
                float ss0, ss1;
#pragma unroll
                for (int col = 0; col < 2; col++) {
                    int o = 4 * (4 * col + i);
                    uint32_t vr = xr[2 * col][i], vi = xr[2 * col + 1][i];
                    float si = col == 0 ? sci0 : -sc;
                    uint32_t nr = pack_bf16(fmaf(acc[o], sc, bf_lo(vr)), fmaf(acc[o + 1], sc, bf_hi(vr)));
                    uint32_t ni = pack_bf16(fmaf(acc[o + 2], si, bf_lo(vi)), fmaf(acc[o + 3], si, bf_hi(vi)));
                    float a0 = bf_lo(nr), a1 = bf_hi(nr), b0 = bf_lo(ni), b1 = bf_hi(ni);
                    if (col == 0) {
                        ss0 = wr0 * a0 * a0 + wi0 * b0 * b0;
                        ss1 = wr0 * a1 * a1 + wi0 * b1 * b1;
                    } else {
                        ss0 += a0 * a0 + b0 * b0;
                        ss1 += a1 * a1 + b1 * b1;
                    }
                    const int K = (2 * col) ^ (2 * (i & 1));
                    uint32_t a = rw0 + i * 256 + K * 16;
                    if (col == 0) a ^= sw << 4;
                    sts32(a, nr);
                    sts32(a ^ 16, ni);
                }
                *(float2*)(sm + SM_SSQ + (pos0 + 32 * i) * 4) = make_float2(ss0 * (2.f / 512.f), ss1 * (2.f / 512.f));
            }
            fence_async_smem();
        }
        TS(5 + 12 * layer);
        if (wg == 0) TC(7 + 10 * layer);
        bar_arrive(5, 416);

        float acc[64];
        float* s_rstd = (float*)(sm + SM_RSTD);
        float* s_mean = (float*)(sm + SM_MEAN);
        const unsigned epoch = s_tgt[0] >> 7;
        const uint32_t pt3 = 1u + (2u * epoch + layer) % 3u;
        const uint32_t ptag = (pt3 & 1u) | ((pt3 & 2u) << 15);
        const uint64_t dstep = layer == 0 ? 16 : 2;
        auto c_desc = [&](int s) { return layer == 0 ? desc_a(sb + SM_A + s * 16384) : desc_k(sb + SM_A + s * 16384); };
        if (wg < 2) {
            const int prow = 32 * wg + 8 * w + g;
            const float2 l1 = *(const float2*)(sm + SM_LAM + prow * 8);
            float lr32 = l1.x, li32 = l1.y;
#pragma unroll
            for (int i = 0; i < 5; i++) { float t = lr32 * lr32 - li32 * li32; li32 = 2.f * lr32 * li32; lr32 = t; }
            float lr128 = lr32, li128 = li32;
#pragma unroll
            for (int i = 0; i < 2; i++) { float t = lr128 * lr128 - li128 * li128; li128 = 2.f * lr128 * li128; lr128 = t; }
            const float lr1 = l1.x, li1 = l1.y;
            acc_def(acc);
#pragma unroll 1
            for (int kb = 0; kb < 8; kb++) {
                mbar_wait(BAR(B_AFULL + kb), 0);
                mbar_wait(BAR(B_XFULL + (kb & 3)), (kb >> 2) & 1);
                wg_fence();
#pragma unroll
                for (int ks = 0; ks < 4; ks++)
                    wgmma_n128<1>(acc, desc_a(sb + SM_A + kb * 16384 + wg * 8192 + ks * 256),
                                  desc_b<128>(sb + SM_X + (kb & 3) * 24576 + ks * 4096), 1);
                wg_commit();
                wg_wait<1>();
                if (kb > 0 && lane == 0) {
                    mbar_arrive(BAR(B_AEMPTY + kb - 1), 1); mbar_arrive(BAR(B_XEMPTY + ((kb - 1) & 3)), 1);
                    mbar_arrive_remote(mapa(BAR(B_XEMPTY + ((kb - 1) & 3)), par ^ 1));
                }
            }
            wg_wait<0>();
            if (lane == 0) {
                mbar_arrive(BAR(B_AEMPTY + 7), 1); mbar_arrive(BAR(B_XEMPTY + 3), 1);
                mbar_arrive_remote(mapa(BAR(B_XEMPTY + 3), par ^ 1)); mbar_arrive_remote(mapa(BAR(B_RFREE), par ^ 1));
            }
            bar_arrive(14, 384);
            TS(6 + 12 * layer);
            bar_sync(4, 384);
            TS(7 + 12 * layer);
            float er = 0.f, ei = 0.f;
#pragma unroll
            for (int i = 0; i < 16; i++) {
                float2 rs = *(const float2*)(s_rstd + 128 + 8 * i + 2 * q);
                acc[4 * i] *= rs.x; acc[4 * i + 1] *= rs.y; acc[4 * i + 2] *= rs.x; acc[4 * i + 3] *= rs.y;
                float nr = lr1 * er - li1 * ei + acc[4 * i], ni = lr1 * ei + li1 * er + acc[4 * i + 2];
                er = lr1 * nr - li1 * ni + acc[4 * i + 1];
                ei = lr1 * ni + li1 * nr + acc[4 * i + 3];
            }
            float cr = 0.f, ci = 0.f, tr = 0.f, ti = 0.f;
#pragma unroll
            for (int qq = 0; qq < 4; qq++) {
                float xr_ = __shfl_sync(~0u, er, (lane & ~3) | qq), xi_ = __shfl_sync(~0u, ei, (lane & ~3) | qq);
                if (qq == q) { cr = tr; ci = ti; }
                float nr = lr32 * tr - li32 * ti + xr_, ni = lr32 * ti + li32 * tr + xi_;
                tr = nr; ti = ni;
            }
            float4* eb = g_Ebuf + (uint32_t)(layer * 16 * 512 + 64 * r + prow);
            if (q == 0 && c < 15) st_relaxed_f4(eb + c * 512, make_float4(tr, ti, __uint_as_float(epoch), 0.f));
            TS(8 + 12 * layer);
            float pr[4], pi[4];
            {
                unsigned n = 0;
                bool ok;
#pragma unroll 1
                do {
                    ok = true;
#pragma unroll
                    for (int k = 0; k < 4; k++) {
                        float4 v = make_float4(0.f, 0.f, __uint_as_float(epoch), 0.f);
                        if (4 * k + q < c) v = ld_relaxed_f4(eb + (4 * k + q) * 512);
                        pr[k] = v.x; pi[k] = v.y;
                        ok = ok && __float_as_uint(v.z) == epoch;
                    }
                } while (!ok && ++n < SPIN_LIMIT);
            }
            __syncwarp();
            TS(9 + 12 * layer);
            float hr = 0.f, hi = 0.f;
#pragma unroll
            for (int cc = 0; cc < 15; cc++) {
                float xr_ = __shfl_sync(~0u, pr[cc >> 2], (lane & ~3) | (cc & 3)), xi_ = __shfl_sync(~0u, pi[cc >> 2], (lane & ~3) | (cc & 3));
                if (cc < c) {
                    float nr = lr128 * hr - li128 * hi + xr_, ni = lr128 * hi + li128 * hr + xi_;
                    hr = nr; hi = ni;
                }
            }
#pragma unroll
            for (int qq = 0; qq < 3; qq++) {
                if (qq < q) { float nr = lr32 * hr - li32 * hi, ni = lr32 * hi + li32 * hr; hr = nr; hi = ni; }
            }
            er = cr + hr; ei = ci + hi;
            bar_sync(7, 384);
            mbar_wait_cluster(BAR(B_RFREE), layer);
            const uint32_t ha = sb + SM_HH + par * 32768 + (prow >> 3) * 1024 + g * 16 + 4 * q;
#pragma unroll
            for (int i = 0; i < 16; i++) {
                float nr = lr1 * er - li1 * ei + acc[4 * i], ni = lr1 * ei + li1 * er + acc[4 * i + 2];
                er = lr1 * nr - li1 * ni + acc[4 * i + 1];
                ei = lr1 * ni + li1 * nr + acc[4 * i + 3];
                sts32(ha + (i >> 3) * 16384 + (i & 7) * 128, pack_bf16(nr, er));
                sts32(ha + (i >> 3) * 16384 + 8192 + (i & 7) * 128, pack_bf16(ni, ei));
                if (i == 7) { fence_async_smem(); bar_arrive(13, 288); }
            }
            fence_async_smem();
            acc_def(acc);
            float acc2[32];
            acc_def(acc2);
            TS(10 + 12 * layer);
            bar_sync(6, 416);
            TS(11 + 12 * layer);
            float (&a0)[32] = *reinterpret_cast<float (*)[32]>(&acc[0]);
            float (&a1)[32] = *reinterpret_cast<float (*)[32]>(&acc[32]);
            auto tile_mma = [&](float (&d)[32], int u, int k) {
                const uint32_t hb = sb + SM_HH + (par ^ k) * 32768 + wg * 16384;
                mbar_wait(BAR(B_AFULL + 2 * u + k), 1);
                const uint64_t da = c_desc(2 * u + k);
                wg_fence();
#pragma unroll
                for (int ks = 0; ks < 4; ks++) wgmma_n64s<1>(d, da + ks * dstep, desc_b<64>(hb + ks * 2048), 1);
#pragma unroll
                for (int ks = 0; ks < 4; ks++) wgmma_n64s<-1>(d, da + 512 + ks * dstep, desc_b<64>(hb + 8192 + ks * 2048), 1);
                wg_commit();
            };
            auto tile_ship = [&](float (&d)[32], int u) {
                uint4* dst = g_P + (uint32_t)(((c * 8 + 2 * ((pi_ + 1 + u) & 3) + par) * 4 + pi_) * 1024 + wg * 512 + (tid & 127));
#pragma unroll
                for (int i = 0; i < 4; i++)
                    dst[i * 128] = make_uint4((pack_bf16(d[8 * i], d[8 * i + 1]) & 0xfffefffeu) | ptag, pack_bf16(d[8 * i + 2], d[8 * i + 3]),
                                              pack_bf16(d[8 * i + 4], d[8 * i + 5]), pack_bf16(d[8 * i + 6], d[8 * i + 7]));
            };
#pragma unroll 1
            for (int k = 0; k < 2; k++) {
                if (k == 1) {
                    mbar_wait(BAR(wg ? B_HPEER1 : B_HPEER), layer);
                    if ((tid & 127) == 0) mbar_arrive_remote(mapa(BAR(B_HDONE), par ^ 1));
                    __syncwarp();
                }
                tile_mma(a0, 0, k);
                tile_mma(a1, 1, k);
                tile_mma(acc2, 2, k);
            }
            wg_wait<2>();
            tile_ship(a0, 0);
            wg_wait<1>();
            bar_arrive(12, 384);
            tile_ship(a1, 1);
            wg_wait<0>();
            tile_ship(acc2, 2);
            if (lane < 6) mbar_arrive(BAR(B_AEMPTY + lane), 1);
            TS(12 + 12 * layer);
        } else {
            const int t2 = tid - 256;
            const uint8_t* ximg = g_X + (uint32_t)layer * 16 * 8 * 16384;
            mbar_wait(BAR(B_SSQ), layer);
            TS(6 + 12 * layer);
            {
                float tot = 0.f;
#pragma unroll
                for (int i = 0; i < 16; i++) tot += __ldcg(g_ssqc + (layer * 16 + i) * 2048 + 128 * c + t2);
                float rs = rsqrtf(tot * (1.f / 512.f) + 1e-5f);
                s_rstd[t2] = rs;
                s_rstd[128 + t2] = 2.f * rs;
                if (layer == 0) s_mean[t2] = 0.f;
                if (layer == 1) {
                    unsigned short u = __ldcg((const unsigned short*)(ximg + (uint32_t)(c * 8 * 16384 + (t2 >> 3) * 128 + (t2 & 7) * 2)));
                    s_mean[t2] = __uint_as_float((uint32_t)u << 16) * (1.f / 512.f);
                }
            }
            TS(7 + 12 * layer);
            bar_arrive(4, 384);
            acc_def(acc);
#pragma unroll 1
            for (int kb = 0; kb < 8; kb++) {
                if (kb == 4) {
                    wg_wait<0>();
                    if (lane == 0) { mbar_arrive(BAR(B_XEMPTY + 3), 1); mbar_arrive_remote(mapa(BAR(B_XEMPTY + 3), par ^ 1)); }
                    bar_sync(14, 384);
                }
                mbar_wait(BAR(B_XFULL + (kb & 3)), (kb >> 2) & 1);
                wg_fence();
#pragma unroll
                for (int ks = 0; ks < 4; ks++)
                    wgmma_n128<1>(acc, desc_a(sb + SM_X + (kb & 3) * 24576 + 16384 + ks * 256), desc_b<128>(sb + SM_X + (kb & 3) * 24576 + ks * 4096), 1);
                wg_commit();
                wg_wait<1>();
                if ((kb & 3) != 0 && lane == 0) { mbar_arrive(BAR(B_XEMPTY + ((kb - 1) & 3)), 1); mbar_arrive_remote(mapa(BAR(B_XEMPTY + ((kb - 1) & 3)), par ^ 1)); }
            }
            wg_wait<0>();
            if (lane == 0) { mbar_arrive(BAR(B_XEMPTY + 3), 1); mbar_arrive_remote(mapa(BAR(B_XEMPTY + 3), par ^ 1)); mbar_arrive_remote(mapa(BAR(B_RFREE), par ^ 1)); }
            bar_arrive(7, 384);
            bar_sync(3, 128);
            TS(9 + 12 * layer);
            const int m0 = 16 * w + g;
            const uint32_t xoff = (uint32_t)((c * 8 + own) * 16384 + w * 4096 + g * 16 + 4 * q);
            if (layer == 0) {
                const uint8_t* xs = g_X + xoff;
#pragma unroll
                for (int i = 0; i < 16; i++) {
                    float2 rs = *(const float2*)(s_rstd + 8 * i + 2 * q);
                    uint32_t x0v = __ldcg((const uint32_t*)(xs + i * 128)), x1v = __ldcg((const uint32_t*)(xs + 2048 + i * 128));
                    acc[4 * i] = acc[4 * i] * rs.x + bf_lo(x0v);
                    acc[4 * i + 1] = acc[4 * i + 1] * rs.y + bf_hi(x0v);
                    acc[4 * i + 2] = acc[4 * i + 2] * rs.x + bf_lo(x1v);
                    acc[4 * i + 3] = acc[4 * i + 3] * rs.y + bf_hi(x1v);
                }
            } else {
                float d0 = ldbf(p.dskip + 64 * own + m0), d1 = ldbf(p.dskip + 64 * own + m0 + 8);
#pragma unroll
                for (int i = 0; i < 16; i++) {
                    float2 rs = *(const float2*)(s_rstd + 8 * i + 2 * q);
                    float2 mn = *(const float2*)(s_mean + 8 * i + 2 * q);
                    acc[4 * i] = acc[4 * i] * (1.f + rs.x * d0) + mn.x;
                    acc[4 * i + 1] = acc[4 * i + 1] * (1.f + rs.y * d0) + mn.y;
                    acc[4 * i + 2] = acc[4 * i + 2] * (1.f + rs.x * d1) + mn.x;
                    acc[4 * i + 3] = acc[4 * i + 3] * (1.f + rs.y * d1) + mn.y;
                }
            }
            TS(10 + 12 * layer);
            bar_sync(6, 416);
            TS(11 + 12 * layer);
            {
                float (&a0)[32] = *reinterpret_cast<float (*)[32]>(&acc[0]);
                float (&a1)[32] = *reinterpret_cast<float (*)[32]>(&acc[32]);
#pragma unroll 1
                for (int k = 0; k < 2; k++) {
                    const uint32_t hb = sb + SM_HH + (par ^ k) * 32768;
                    if (k == 1) {
                        mbar_wait(BAR(B_HPEER), layer);
                        mbar_wait(BAR(B_HPEER1), layer);
                        bar_sync(12, 384);
                    }
                    mbar_wait(BAR(B_AFULL + 6 + k), 1);
                    const uint64_t da = c_desc(6 + k);
                    wg_fence();
#pragma unroll
                    for (int ks = 0; ks < 4; ks++) {
                        wgmma_n64s<1>(a0, da + ks * dstep, desc_b<64>(hb + ks * 2048), 1);
                        wgmma_n64s<1>(a1, da + ks * dstep, desc_b<64>(hb + 16384 + ks * 2048), 1);
                    }
#pragma unroll
                    for (int ks = 0; ks < 4; ks++) {
                        wgmma_n64s<-1>(a0, da + 512 + ks * dstep, desc_b<64>(hb + 8192 + ks * 2048), 1);
                        wgmma_n64s<-1>(a1, da + 512 + ks * dstep, desc_b<64>(hb + 16384 + 8192 + ks * 2048), 1);
                    }
                    wg_commit();
                }
                wg_wait<0>();
            }
#pragma unroll
            for (int i = 0; i < 16; i++)
                *(float4*)(sm + SM_A + 6 * 16384 + i * 2048 + t2 * 16) = make_float4(acc[4 * i], acc[4 * i + 1], acc[4 * i + 2], acc[4 * i + 3]);
            TS(12 + 12 * layer);
        }
        {
            const int t = tid & 127;
            const int nch = wg == 2 ? 2 : 3;
            const uint4* pb = g_P + (uint32_t)((c * 8 + r) * 4 * 1024 + wg * 128 + t);
            uint4 v[3][3];
            unsigned n = 0;
#pragma unroll 1
            while (true) {
                if (lane == 31) {
#pragma unroll 1
                    while (true) {
                        uint32_t bad = 0;
#pragma unroll
                        for (int sx = 0; sx < 3; sx++) {
                            uint32_t t0;
                            asm volatile("ld.relaxed.gpu.global.u32 %0, [%1];" : "=r"(t0) : "l"(pb + ((pi_ + 1 + sx) & 3) * 1024 + (nch - 1) * 384) : "memory");
                            bad |= t0 ^ ptag;
                        }
                        if (!(bad & 0x00010001u) || ++n >= SPIN_LIMIT) break;
                    }
                }
                __syncwarp();
                uint32_t bad = 0;
#pragma unroll
                for (int k = 0; k < 3; k++)
#pragma unroll
                    for (int sx = 0; sx < 3; sx++) {
                        v[k][sx] = make_uint4(ptag, 0, 0, 0);
                        if (k < nch) v[k][sx] = ld_relaxed_u4(pb + ((pi_ + 1 + sx) & 3) * 1024 + k * 384);
                        bad |= v[k][sx].x ^ ptag;
                    }
                if (!__any_sync(~0u, bad & 0x00010001u) || ++n >= SPIN_LIMIT) break;
            }
            bar_sync(8, 384);
            TS(13 + 12 * layer);
            const int m0 = 16 * w + g;
            const float w0 = (own == 0 && m0 < 2) ? (m0 == 0 ? 0.f : 0.5f) : 1.f;
#pragma unroll
            for (int k = 0; k < 3; k++) {
                if (k < nch) {
                    const int i = wg + 3 * k;
                    float4 a = *(const float4*)(sm + SM_A + 6 * 16384 + (2 * i) * 2048 + t * 16);
                    float4 bq = *(const float4*)(sm + SM_A + 6 * 16384 + (2 * i + 1) * 2048 + t * 16);
#pragma unroll
                    for (int sx = 0; sx < 3; sx++) {
                        a.x += bf_lo(v[k][sx].x); a.y += bf_hi(v[k][sx].x); a.z += bf_lo(v[k][sx].y); a.w += bf_hi(v[k][sx].y);
                        bq.x += bf_lo(v[k][sx].z); bq.y += bf_hi(v[k][sx].z); bq.z += bf_lo(v[k][sx].w); bq.w += bf_hi(v[k][sx].w);
                    }
                    if (layer == 0) {
                        uint8_t* xd = g_X + (uint32_t)((16 * 8 + c * 8 + own) * 16384 + w * 4096 + g * 16 + 4 * q + i * 256);
                        uint32_t v0 = pack_bf16(a.x, a.y), v1 = pack_bf16(a.z, a.w), v2 = pack_bf16(bq.x, bq.y), v3 = pack_bf16(bq.z, bq.w);
                        *(uint32_t*)(xd) = v0; *(uint32_t*)(xd + 2048) = v1; *(uint32_t*)(xd + 128) = v2; *(uint32_t*)(xd + 2048 + 128) = v3;
                        float sq[4];
                        sq[0] = w0 * bf_lo(v0) * bf_lo(v0) + bf_lo(v1) * bf_lo(v1);
                        sq[1] = w0 * bf_hi(v0) * bf_hi(v0) + bf_hi(v1) * bf_hi(v1);
                        sq[2] = w0 * bf_lo(v2) * bf_lo(v2) + bf_lo(v3) * bf_lo(v3);
                        sq[3] = w0 * bf_hi(v2) * bf_hi(v2) + bf_hi(v3) * bf_hi(v3);
                        float u0 = (g & 1) ? sq[2] : sq[0], u1 = (g & 1) ? sq[3] : sq[1];
                        u0 += __shfl_xor_sync(~0u, (g & 1) ? sq[0] : sq[2], 4);
                        u1 += __shfl_xor_sync(~0u, (g & 1) ? sq[1] : sq[3], 4);
                        float z = (g & 2) ? u1 : u0;
                        z += __shfl_xor_sync(~0u, (g & 2) ? u0 : u1, 8);
                        z += __shfl_xor_sync(~0u, z, 16);
                        if (g < 4) atomicAdd(s_mean + 16 * i + 8 * (g & 1) + 2 * q + (g >> 1), z);
                    } else {
                        float* o = p.out + (uint32_t)((128 * c + 32 * q + 4 * i) * 512 + 64 * own + m0);
                        o[0] = a.x; o[512] = a.y; o[8] = a.z; o[512 + 8] = a.w;
                        o[1024] = bq.x; o[1536] = bq.y; o[1024 + 8] = bq.z; o[1536 + 8] = bq.w;
                    }
                }
            }
            if (wg < 2) mbar_wait_cluster(BAR(B_HDONE), layer);
            if (layer == 0) {
                fence_async_smem();
                bar_sync(9, 384);
                TS(14 + 12 * layer);
                if (wg == 2) {
                    atomicAdd(g_ssq + 2048 + 128 * c + t, s_mean[t] * (2.f / 512.f));
                    bar_sync(3, 128);
                    if (lane == 0) { mbar_arrive(BAR(B_AEMPTY + 6), 2); mbar_arrive(BAR(B_AEMPTY + 7), 2); }
                    if (t == 0) { fence_async(); red_release(&g_bar[2], 1); }
                }
            }
        }
        TS(15 + 12 * layer);
        if (wg == 0) TC(31);
    }
}

typedef CUresult (*EncFn)(CUtensorMap*, CUtensorMapDataType, cuuint32_t, void*, const cuuint64_t*, const cuuint64_t*,
                          const cuuint32_t*, const cuuint32_t*, CUtensorMapInterleave, CUtensorMapSwizzle,
                          CUtensorMapL2promotion, CUtensorMapFloatOOBfill);

void launch_impl(void* const* d_in, void* d_out, int stop) {
    static EncFn enc = nullptr;
    if (!enc) {
        void* fn = nullptr;
        cudaDriverEntryPointQueryResult qr;
        cudaGetDriverEntryPoint("cuTensorMapEncodeTiled", &fn, cudaEnableDefault, &qr);
        enc = (EncFn)fn;
        cudaFuncSetAttribute(fused_kernel, cudaFuncAttributeMaxDynamicSharedMemorySize, SM_TOTAL);
    }
    CUtensorMap tx, tbr, tbi, tcr, tci, tcol;
    {
        void* gx = nullptr;
        cudaGetSymbolAddress(&gx, g_X);
        cuuint64_t gd[5] = {64, 16, 64, 16, 2};
        cuuint64_t gs[4] = {128, 2048, 128 * 1024, 2048 * 1024};
        cuuint32_t bx[5] = {32, 16, 1, 16, 1};
        cuuint32_t es[5] = {1, 1, 1, 1, 1};
        enc(&tcol, CU_TENSOR_MAP_DATA_TYPE_BFLOAT16, 5, gx, gd, gs, bx, es, CU_TENSOR_MAP_INTERLEAVE_NONE,
            CU_TENSOR_MAP_SWIZZLE_64B, CU_TENSOR_MAP_L2_PROMOTION_NONE, CU_TENSOR_MAP_FLOAT_OOB_FILL_NONE);
    }
    {
        cuuint64_t gd[5] = {512, 2, 4, 16, 16};
        cuuint64_t gs[4] = {1024, 32 * 1024, 2 * 1024, 128 * 1024};
        cuuint32_t bx[5] = {64, 2, 4, 8, 1};
        cuuint32_t es[5] = {1, 1, 1, 1, 1};
        enc(&tx, CU_TENSOR_MAP_DATA_TYPE_BFLOAT16, 5, d_in[0], gd, gs, bx, es, CU_TENSOR_MAP_INTERLEAVE_NONE,
            CU_TENSOR_MAP_SWIZZLE_128B, CU_TENSOR_MAP_L2_PROMOTION_L2_128B, CU_TENSOR_MAP_FLOAT_OOB_FILL_NONE);
    }
    auto mk2 = [&](CUtensorMap* m, void* ptr, cuuint32_t rows) {
        cuuint64_t gd[2] = {512, 512};
        cuuint64_t gs[1] = {1024};
        cuuint32_t bx[2] = {64, rows};
        cuuint32_t es[2] = {1, 1};
        enc(m, CU_TENSOR_MAP_DATA_TYPE_BFLOAT16, 2, ptr, gd, gs, bx, es, CU_TENSOR_MAP_INTERLEAVE_NONE,
            CU_TENSOR_MAP_SWIZZLE_128B, CU_TENSOR_MAP_L2_PROMOTION_L2_128B, CU_TENSOR_MAP_FLOAT_OOB_FILL_NONE);
    };
    mk2(&tbr, d_in[6], 32);
    mk2(&tbi, d_in[7], 32);
    mk2(&tcr, d_in[8], 64);
    mk2(&tci, d_in[9], 64);
    Params p;
    p.x0 = (const __nv_bfloat16*)d_in[0];
    p.w_r = (const __nv_bfloat16*)d_in[1];
    p.w_i = (const __nv_bfloat16*)d_in[2];
    p.lam_re = (const __nv_bfloat16*)d_in[4];
    p.lam_im = (const __nv_bfloat16*)d_in[5];
    p.log_dt = (const __nv_bfloat16*)d_in[10];
    p.dskip = (const __nv_bfloat16*)d_in[11];
    p.out = (float*)d_out;
    p.stop = stop;
    cudaLaunchConfig_t cfg = {};
    cfg.gridDim = dim3(NCTA); cfg.blockDim = dim3(NTHREADS); cfg.dynamicSmemBytes = SM_TOTAL; cfg.stream = cudaStreamPerThread;
    cudaLaunchAttribute at[1];
    at[0].id = cudaLaunchAttributeClusterDimension;
    at[0].val.clusterDim.x = 2; at[0].val.clusterDim.y = 1; at[0].val.clusterDim.z = 1;
    cfg.attrs = at; cfg.numAttrs = 1;
    cudaLaunchKernelEx(&cfg, fused_kernel, tx, tbr, tbi, tcr, tci, tcol, p);
}

}

extern "C" void kernel_launch(void* const* d_in, const int* in_sizes, int n_in, void* d_out, int out_size) {
    (void)in_sizes; (void)n_in; (void)out_size;
    launch_impl(d_in, d_out, 100);
}
```

```cpp
#include <cuda_runtime.h>
#include <cuda_bf16.h>
#include <cuda.h>
#include <stdint.h>

namespace {

constexpr int NCTA = 128;
constexpr int NTHREADS = 512;
constexpr int SM_A = 0;
constexpr int SM_X = 131072;
constexpr int SM_H = 196608;
constexpr int SM_HH = SM_X + 32768;
constexpr int SM_M = 229376;
constexpr int SM_TOTAL = 232448;
constexpr int SM_BAR = SM_M;
constexpr int SM_TGT = SM_M + 360;
constexpr int SM_LAM = SM_M + 384;
constexpr int SM_TAB = SM_M + 896;
constexpr int SM_RSTD = SM_M + 1920;
constexpr int SM_MEAN = SM_TAB;
constexpr int SM_T64 = SM_M + 2944;
constexpr int SM_B1ST = SM_H + 24576;
constexpr int SM_RAW = SM_X + 40960;
constexpr int SM_SSQ = SM_X + 57344;
constexpr int B_FULL0 = 0;
constexpr int B_EMPTY0 = 8;
constexpr int B_FULLC = 12;
constexpr int B_AFULL = 13;
constexpr int B_AEMPTY = 21;
constexpr int B_XFULL = 29;
constexpr int B_XEMPTY = 33;
constexpr int B_AFREE = 37;
constexpr int B_COL = 38;
constexpr int B_SSQ = 39;
constexpr int B_HPEER = 40;
constexpr int B_RFREE = 41;
constexpr int B_HDONE = 42;
constexpr int B_WRDY = 43;
constexpr int B_HPEER1 = 44;
constexpr int NBARS = 45;

__device__ __align__(1024) uint8_t g_X[2 * 16 * 8 * 16384];
__device__ __align__(1024) uint8_t g_A1[8 * 8 * 16384];
__device__ __align__(1024) uint8_t g_A2[8 * 8 * 16384];
__device__ __align__(1024) uint8_t g_E[2 * 8 * 8 * 8192];
__device__ __align__(16) float g_ssq[2 * 2048];
__device__ __align__(16) float g_ssqc[2 * 16 * 2048];
__device__ __align__(16) float g_Dh[512];
__device__ __align__(16) uint4 g_Wfrag[128 * 4 * 256];
__device__ __align__(16) float4 g_Ebuf[2 * 16 * 512];
__device__ __align__(16) uint4 g_P[16 * 8 * 4 * 1024];
__device__ unsigned g_bar[8];
__device__ unsigned g_err;
#define TX(i)
#define TQ(i)
#define TS(i)
#define TC(i)

constexpr unsigned SPIN_LIMIT = 1u << 22;

__device__ __forceinline__ uint32_t s2u(const void* p) { return (uint32_t)__cvta_generic_to_shared(p); }
__device__ __forceinline__ void mbar_init(uint32_t a, uint32_t c) {
    asm volatile("mbarrier.init.shared::cta.b64 [%0], %1;" ::"r"(a), "r"(c) : "memory");
}
__device__ __forceinline__ void mbar_expect(uint32_t a, uint32_t bytes) {
    asm volatile("mbarrier.arrive.expect_tx.shared::cta.b64 _, [%0], %1;" ::"r"(a), "r"(bytes) : "memory");
}
__device__ __forceinline__ void mbar_arrive(uint32_t a, uint32_t cnt) {
    asm volatile("mbarrier.arrive.shared::cta.b64 _, [%0], %1;" ::"r"(a), "r"(cnt) : "memory");
}
__device__ __forceinline__ bool mbar_try(uint32_t a, uint32_t parity) {
    uint32_t ok;
    asm volatile("{\n.reg .pred p;\nmbarrier.try_wait.parity.shared::cta.b64 p, [%1], %2;\nselp.u32 %0, 1, 0, p;\n}"
                 : "=r"(ok) : "r"(a), "r"(parity) : "memory");
    return ok != 0;
}
__device__ __forceinline__ void mbar_wait(uint32_t a, uint32_t parity) {
    asm volatile("{\n.reg .pred p, q;\n.reg .u32 n;\nmov.u32 n, 0;\n"
                 "W_%=:\nmbarrier.try_wait.parity.shared::cta.b64 p, [%0], %1;\n@p bra D_%=;\n"
                 "add.u32 n, n, 1;\nsetp.lt.u32 q, n, 4194304;\n@q bra W_%=;\nD_%=:\n}" ::"r"(a), "r"(parity) : "memory");
}
__device__ __forceinline__ void bulk_g2s(uint32_t dst, const void* src, uint32_t bytes, uint32_t bar) {
    asm volatile("cp.async.bulk.shared::cluster.global.mbarrier::complete_tx::bytes [%0], [%1], %2, [%3];" ::"r"(dst),
                 "l"(src), "r"(bytes), "r"(bar) : "memory");
}
__device__ __forceinline__ void tma_2d(uint32_t dst, const CUtensorMap* m, int c0, int c1, uint32_t bar) {
    asm volatile("cp.async.bulk.tensor.2d.shared::cluster.global.mbarrier::complete_tx::bytes [%0], [%1, {%3,%4}], [%2];" ::"r"(dst),
                 "l"(m), "r"(bar), "r"(c0), "r"(c1) : "memory");
}
__device__ __forceinline__ void tma_5d(uint32_t dst, const CUtensorMap* m, int c0, int c1, int c2, int c3, int c4, uint32_t bar) {
    asm volatile("cp.async.bulk.tensor.5d.shared::cluster.global.mbarrier::complete_tx::bytes [%0], [%1, {%3,%4,%5,%6,%7}], [%2];" ::"r"(dst),
                 "l"(m), "r"(bar), "r"(c0), "r"(c1), "r"(c2), "r"(c3), "r"(c4) : "memory");
}
__device__ __forceinline__ void tma_2d_mc(uint32_t dst, const CUtensorMap* m, int c0, int c1, uint32_t bar) {
    asm volatile("cp.async.bulk.tensor.2d.shared::cluster.global.mbarrier::complete_tx::bytes.multicast::cluster [%0], [%1, {%3,%4}], [%2], %5;" ::"r"(dst),
                 "l"(m), "r"(bar), "r"(c0), "r"(c1), "h"((unsigned short)3) : "memory");
}
__device__ __forceinline__ void tma_5d_mc(uint32_t dst, const CUtensorMap* m, int c0, int c1, int c2, int c3, int c4, uint32_t bar) {
    asm volatile("cp.async.bulk.tensor.5d.shared::cluster.global.mbarrier::complete_tx::bytes.multicast::cluster [%0], [%1, {%3,%4,%5,%6,%7}], [%2], %8;" ::"r"(dst),
                 "l"(m), "r"(bar), "r"(c0), "r"(c1), "r"(c2), "r"(c3), "r"(c4), "h"((unsigned short)3) : "memory");
}
__device__ __forceinline__ void bulk_g2s_mc(uint32_t dst, const void* src, uint32_t bytes, uint32_t bar) {
    asm volatile("cp.async.bulk.shared::cluster.global.mbarrier::complete_tx::bytes.multicast::cluster [%0], [%1], %2, [%3], %4;" ::"r"(dst),
                 "l"(src), "r"(bytes), "r"(bar), "h"((unsigned short)3) : "memory");
}
__device__ __forceinline__ void tma_store_5d(const CUtensorMap* m, int c0, int c1, int c2, int c3, int c4, uint32_t src) {
    asm volatile("cp.async.bulk.tensor.5d.global.shared::cta.bulk_group [%0, {%2,%3,%4,%5,%6}], [%1];" ::"l"(m), "r"(src),
                 "r"(c0), "r"(c1), "r"(c2), "r"(c3), "r"(c4) : "memory");
}
__device__ __forceinline__ uint32_t lds32(uint32_t a) { uint32_t v; asm volatile("ld.shared.u32 %0, [%1];" : "=r"(v) : "r"(a) : "memory"); return v; }
__device__ __forceinline__ uint4 ld_relaxed_u4(const uint4* p) {
    uint4 v;
    asm volatile("ld.relaxed.gpu.global.v4.u32 {%0,%1,%2,%3}, [%4];" : "=r"(v.x), "=r"(v.y), "=r"(v.z), "=r"(v.w) : "l"(p) : "memory");
    return v;
}
__device__ __forceinline__ void fence_async() { asm volatile("fence.proxy.async.global;" ::: "memory"); }
__device__ __forceinline__ void red_relaxed(unsigned* p, unsigned v) {
    asm volatile("red.relaxed.gpu.global.add.u32 [%0], %1;" ::"l"(p), "r"(v) : "memory");
}
__device__ __forceinline__ uint32_t mapa(uint32_t a, uint32_t rank) {
    uint32_t d;
    asm("mapa.shared::cluster.u32 %0, %1, %2;" : "=r"(d) : "r"(a), "r"(rank));
    return d;
}
__device__ __forceinline__ void mbar_arrive_remote(uint32_t ra) {
    asm volatile("mbarrier.arrive.relaxed.cluster.shared::cluster.b64 _, [%0];" ::"r"(ra) : "memory");
}
__device__ __forceinline__ void mbar_wait_cluster(uint32_t a, uint32_t parity) {
    asm volatile("{\n.reg .pred p, q;\n.reg .u32 n;\nmov.u32 n, 0;\n"
                 "W_%=:\nmbarrier.try_wait.parity.acquire.cluster.shared::cta.b64 p, [%0], %1;\n@p bra D_%=;\n"
                 "add.u32 n, n, 1;\nsetp.lt.u32 q, n, 4194304;\n@q bra W_%=;\nD_%=:\n}" ::"r"(a), "r"(parity) : "memory");
}
__device__ __forceinline__ void bulk_s2peer(uint32_t rdst, uint32_t src, uint32_t bytes, uint32_t rbar) {
    asm volatile("cp.async.bulk.shared::cluster.shared::cta.mbarrier::complete_tx::bytes [%0], [%1], %2, [%3];" ::"r"(rdst),
                 "r"(src), "r"(bytes), "r"(rbar) : "memory");
}
__device__ __forceinline__ void fence_async_smem() { asm volatile("fence.proxy.async.shared::cta;" ::: "memory"); }
__device__ __forceinline__ void wg_fence() { asm volatile("wgmma.fence.sync.aligned;" ::: "memory"); }
__device__ __forceinline__ void wg_commit() { asm volatile("wgmma.commit_group.sync.aligned;" ::: "memory"); }
template <int N> __device__ __forceinline__ void wg_wait() { asm volatile("wgmma.wait_group.sync.aligned %0;" ::"n"(N) : "memory"); }
__device__ __forceinline__ void bar_sync(int id, int n) { asm volatile("bar.sync %0, %1;" ::"r"(id), "r"(n) : "memory"); }
__device__ __forceinline__ void bar_arrive(int id, int n) { asm volatile("bar.arrive %0, %1;" ::"r"(id), "r"(n) : "memory"); }
__device__ __forceinline__ unsigned ld_acquire(const unsigned* p) {
    unsigned v;
    asm volatile("ld.acquire.gpu.global.u32 %0, [%1];" : "=r"(v) : "l"(p) : "memory");
    return v;
}
__device__ __forceinline__ void red_release(unsigned* p, unsigned v) {
    asm volatile("red.release.gpu.global.add.u32 [%0], %1;" ::"l"(p), "r"(v) : "memory");
}
__device__ __forceinline__ void wait_count(const unsigned* p, unsigned target) {
    unsigned n = 0;
#pragma unroll 1
    while ((int)(ld_acquire(p) - target) < 0 && ++n < SPIN_LIMIT) {}
}
__device__ __forceinline__ float4 ld_relaxed_f4(const float4* p) {
    float4 v;
    asm volatile("ld.relaxed.gpu.global.v4.f32 {%0,%1,%2,%3}, [%4];" : "=f"(v.x), "=f"(v.y), "=f"(v.z), "=f"(v.w) : "l"(p) : "memory");
    return v;
}
__device__ __forceinline__ void st_relaxed_f4(float4* p, float4 v) {
    asm volatile("st.relaxed.gpu.global.v4.f32 [%0], {%1,%2,%3,%4};" ::"l"(p), "f"(v.x), "f"(v.y), "f"(v.z), "f"(v.w) : "memory");
}
__device__ __forceinline__ uint32_t pack_bf16(float lo, float hi) {
    uint32_t r;
    asm("cvt.rn.bf16x2.f32 %0, %1, %2;" : "=r"(r) : "f"(hi), "f"(lo));
    return r;
}
__device__ __forceinline__ float bf_lo(uint32_t v) { return __uint_as_float(v << 16); }
__device__ __forceinline__ float bf_hi(uint32_t v) { return __uint_as_float(v & 0xffff0000u); }
__device__ __forceinline__ void sts32(uint32_t a, uint32_t v) { asm volatile("st.shared.u32 [%0], %1;" ::"r"(a), "r"(v) : "memory"); }
__device__ __forceinline__ void sts128(uint32_t a, uint4 v) {
    asm volatile("st.shared.v4.u32 [%0], {%1,%2,%3,%4};" ::"r"(a), "r"(v.x), "r"(v.y), "r"(v.z), "r"(v.w) : "memory");
}

__device__ __forceinline__ uint64_t desc_ni(uint32_t addr, uint32_t lbo, uint32_t sbo) {
    return (uint64_t)((addr & 0x3FFFF) >> 4) | ((uint64_t)(lbo >> 4) << 16) | ((uint64_t)(sbo >> 4) << 32);
}
__device__ __forceinline__ uint64_t desc_a(uint32_t addr) { return desc_ni(addr, 128, 1024); }
template <int N> __device__ __forceinline__ uint64_t desc_b(uint32_t addr) { return desc_ni(addr, 16 * N, 128); }
__device__ __forceinline__ uint64_t desc_k(uint32_t addr) {
    return (uint64_t)((addr & 0x3FFFF) >> 4) | (1ull << 16) | (64ull << 32) | (1ull << 62);
}
__device__ __forceinline__ uint64_t desc_mn(uint32_t addr, uint32_t lbo) {
    return (uint64_t)((addr & 0x3FFFF) >> 4) | ((uint64_t)(lbo >> 4) << 16) | (64ull << 32) | (1ull << 62);
}

#define ACC8(d, o) "+f"(d[o + 0]), "+f"(d[o + 1]), "+f"(d[o + 2]), "+f"(d[o + 3]), "+f"(d[o + 4]), "+f"(d[o + 5]), "+f"(d[o + 6]), "+f"(d[o + 7])
template <int TB, int SA = 1>
__device__ __forceinline__ void wgmma_n128(float (&d)[64], uint64_t da, uint64_t db, int sd) {
    asm volatile(
        "{\n.reg .pred p;\nsetp.ne.b32 p, %66, 0;\n"
        "wgmma.mma_async.sync.aligned.m64n128k16.f32.bf16.bf16 "
        "{%0,%1,%2,%3,%4,%5,%6,%7,%8,%9,%10,%11,%12,%13,%14,%15,%16,%17,%18,%19,%20,%21,%22,%23,%24,%25,%26,%27,%28,%29,%30,%31,"
        "%32,%33,%34,%35,%36,%37,%38,%39,%40,%41,%42,%43,%44,%45,%46,%47,%48,%49,%50,%51,%52,%53,%54,%55,%56,%57,%58,%59,%60,%61,%62,%63},"
        " %64, %65, p, %68, 1, 0, %67;\n}"
        : ACC8(d, 0), ACC8(d, 8), ACC8(d, 16), ACC8(d, 24), ACC8(d, 32), ACC8(d, 40), ACC8(d, 48), ACC8(d, 56)
        : "l"(da), "l"(db), "r"(sd), "n"(TB), "n"(SA));
}
template <int N> __device__ __forceinline__ void acc_def(float (&d)[N]) {
#pragma unroll
    for (int i = 0; i < N; i++) d[i] = 0.f;
}
template <int TB>
__device__ __forceinline__ void wgmma_n64(float (&d)[32], uint64_t da, uint64_t db, int sd) {
    asm volatile(
        "{\n.reg .pred p;\nsetp.ne.b32 p, %34, 0;\n"
        "wgmma.mma_async.sync.aligned.m64n64k16.f32.bf16.bf16 "
        "{%0,%1,%2,%3,%4,%5,%6,%7,%8,%9,%10,%11,%12,%13,%14,%15,%16,%17,%18,%19,%20,%21,%22,%23,%24,%25,%26,%27,%28,%29,%30,%31},"
        " %32, %33, p, 1, 1, 0, %35;\n}"
        : ACC8(d, 0), ACC8(d, 8), ACC8(d, 16), ACC8(d, 24)
        : "l"(da), "l"(db), "r"(sd), "n"(TB));
}
template <int SA>
__device__ __forceinline__ void wgmma_n64s(float (&d)[32], uint64_t da, uint64_t db, int sd) {
    asm volatile(
        "{\n.reg .pred p;\nsetp.ne.b32 p, %34, 0;\n"
        "wgmma.mma_async.sync.aligned.m64n64k16.f32.bf16.bf16 "
        "{%0,%1,%2,%3,%4,%5,%6,%7,%8,%9,%10,%11,%12,%13,%14,%15,%16,%17,%18,%19,%20,%21,%22,%23,%24,%25,%26,%27,%28,%29,%30,%31},"
        " %32, %33, p, %35, 1, 0, 1;\n}"
        : ACC8(d, 0), ACC8(d, 8), ACC8(d, 16), ACC8(d, 24)
        : "l"(da), "l"(db), "r"(sd), "n"(SA));
}
__device__ __forceinline__ void wgmma_n64_rs(float (&d)[32], uint32_t a0, uint32_t a1, uint32_t a2, uint32_t a3, uint64_t db, int sd) {
    asm volatile(
        "{\n.reg .pred p;\nsetp.ne.b32 p, %37, 0;\n"
        "wgmma.mma_async.sync.aligned.m64n64k16.f32.bf16.bf16 "
        "{%0,%1,%2,%3,%4,%5,%6,%7,%8,%9,%10,%11,%12,%13,%14,%15,%16,%17,%18,%19,%20,%21,%22,%23,%24,%25,%26,%27,%28,%29,%30,%31},"
        " {%32,%33,%34,%35}, %36, p, 1, 1, 1;\n}"
        : ACC8(d, 0), ACC8(d, 8), ACC8(d, 16), ACC8(d, 24)
        : "r"(a0), "r"(a1), "r"(a2), "r"(a3), "l"(db), "r"(sd));
}

struct Params {
    const __nv_bfloat16* x0;
    const __nv_bfloat16* w_r;
    const __nv_bfloat16* w_i;
    const __nv_bfloat16* lam_re;
    const __nv_bfloat16* lam_im;
    const __nv_bfloat16* log_dt;
    const __nv_bfloat16* dskip;
    float* out;
    int stop;
};

__device__ __forceinline__ float ldbf(const __nv_bfloat16* p) { return __bfloat162float(*p); }

__device__ __forceinline__ void dft_fp(int j, int& f, int& ph) {
    int cs = j >> 1;
    if (j == 1) { f = 256; ph = 0; }
    else { f = cs; ph = (j & 1) ? 128 : 0; }
}

__device__ __forceinline__ void gen_col_consts(uint32_t sb, int tid) {
#pragma unroll 1
    for (int task = tid; task < 640; task += 256) {
        int f, c8;
        uint32_t a_cc, d_pi, d_po;
        if (task < 512) {
            f = task & 63; c8 = task >> 6;
            a_cc = sb + SM_X + (f >> 5) * 16384 + ((f >> 3) & 3) * 2048 + c8 * 128 + (f & 7) * 16;
            d_pi = 8192; d_po = 1024;
        } else {
            int n2 = task & 31;
            f = 2 * n2; c8 = (task >> 5) & 3;
            a_cc = sb + SM_X + 32768 + (n2 >> 3) * 1024 + c8 * 128 + (n2 & 7) * 16;
            d_pi = 4096; d_po = 512;
        }
        float cd, sd, cs, sn;
        __sincosf((float)(f >= 32 ? f - 64 : f) * (6.283185307179586f / 64.f), &sd, &cd);
        int a = (8 * c8 * f) & 63;
        __sincosf((float)(a >= 32 ? a - 64 : a) * (6.283185307179586f / 64.f), &sn, &cs);
        float cv[8], sv[8];
#pragma unroll
        for (int e = 0; e < 8; e++) {
            cv[e] = cs; sv[e] = sn;
            float t = cs * cd - sn * sd;
            sn = sn * cd + cs * sd;
            cs = t;
        }
        uint4 oc = make_uint4(pack_bf16(cv[0], cv[1]), pack_bf16(cv[2], cv[3]), pack_bf16(cv[4], cv[5]), pack_bf16(cv[6], cv[7]));
        uint4 os = make_uint4(pack_bf16(sv[0], sv[1]), pack_bf16(sv[2], sv[3]), pack_bf16(sv[4], sv[5]), pack_bf16(sv[6], sv[7]));
        sts128(a_cc, oc);
        sts128(a_cc + d_pi, os);
        sts128(a_cc + d_po, make_uint4(os.x ^ 0x80008000u, os.y ^ 0x80008000u, os.z ^ 0x80008000u, os.w ^ 0x80008000u));
        sts128(a_cc + d_pi + d_po, oc);
    }
}

__global__ void __launch_bounds__(NTHREADS, 1)
fused_kernel(const __grid_constant__ CUtensorMap tm_x, const __grid_constant__ CUtensorMap tm_bre,
             const __grid_constant__ CUtensorMap tm_bim, const __grid_constant__ CUtensorMap tm_cre,
             const __grid_constant__ CUtensorMap tm_cim, const __grid_constant__ CUtensorMap tm_col, const Params p) {
    extern __shared__ __align__(1024) uint8_t sm[];
    const uint32_t sb = s2u(sm);
    const int tid = threadIdx.x, b = blockIdx.x;
    const int c = b >> 3, r = b & 7;
    const int par = r & 1, pi_ = r >> 1, own = 4 * par + pi_;
    const int wg = __shfl_sync(~0u, tid >> 7, 0), w = __shfl_sync(~0u, (tid >> 5) & 3, 0), lane = tid & 31, g = lane >> 2, q = lane & 3;
    auto BAR = [&](int i) { return sb + SM_BAR + 8 * i; };
    unsigned* s_tgt = (unsigned*)(sm + SM_TGT);

    if (tid < NBARS) {
        int cnt = 1;
        if ((tid >= B_EMPTY0 && tid < B_EMPTY0 + 4) || (tid >= B_XEMPTY && tid < B_XEMPTY + 4)) cnt = 24;
        if (tid == B_RFREE) cnt = 12;
        if (tid == B_HDONE) cnt = 2;
        if (tid >= B_AEMPTY && tid < B_AEMPTY + 8) cnt = 8;
        if (tid == B_AFREE) cnt = 4;
        mbar_init(BAR(tid), cnt);
        asm volatile("fence.mbarrier_init.release.cluster;" ::: "memory");
    }
    asm volatile("barrier.cluster.arrive.release.aligned;" ::: "memory");
    if (tid >= 64 && tid < 70) {
        s_tgt[tid - 64] = ((ld_acquire(&g_bar[tid - 64]) >> 7) + 1u) << 7;
    } else if (tid >= 96 && tid < 112) {
        g_ssq[2048 + 16 * b + tid - 96] = 0.f;
    } else if (tid >= 128 && tid < 384) {
        int i = tid - 128;
        if (i < 128) ((float4*)g_ssqc)[b * 128 + i] = make_float4(0.f, 0.f, 0.f, 0.f);
    } else if (tid >= 416) {
        int i = tid - 416;
        int ps = i < 64 ? 64 * r + i : 32 * c + i - 64;
        float lr = ldbf(p.lam_re + ps), li = ldbf(p.lam_im + ps);
        float dt = __bfloat162float(__float2bfloat16(expf(ldbf(p.log_dt + ps))));
        float mag = expf(lr * dt), t = li * dt * 0.15915494309189535f, sn, cs;
        t -= rintf(t);
        sincospif(2.f * t, &sn, &cs);
        float er = mag * cs, ei = mag * sn;
        if (i < 64) {
            *(float2*)(sm + SM_LAM + i * 8) = make_float2(er, ei);
        } else {
            er -= 1.f;
            float inv = 1.f / (lr * lr + li * li);
            *(float2*)(sm + SM_RSTD + (i - 64) * 8) = make_float2((er * lr + ei * li) * inv, (ei * lr - er * li) * inv);
        }
    } else if (tid >= 384 && tid < 390) {
        const CUtensorMap* tm = tid == 384 ? &tm_x : tid == 385 ? &tm_bre : tid == 386 ? &tm_bim : tid == 387 ? &tm_cre : tid == 388 ? &tm_cim : &tm_col;
        asm volatile("prefetch.tensormap [%0];" ::"l"(tm) : "memory");
    }
    __syncwarp();
    asm volatile("barrier.cluster.wait.acquire.aligned;" ::: "memory");

    if (wg == 3) {
        asm volatile("setmaxnreg.dec.sync.aligned.u32 56;");
        if (w > 0) {
            bar_arrive(10, 480);
            if (w == 2) {
                const int kq = 2 * b + (lane >> 4), row = (kq >> 2) + 128 * (kq & 3) + 512 * ((lane >> 1) & 3) + 64 * (lane & 1);
                const char* src = (const char*)(((lane >> 3) & 1) ? p.w_i : p.w_r) + (size_t)row * 514;
                size_t a0 = (size_t)src & ~(size_t)15;
                int bytes = row == 2047 ? 512 : 544;
                asm volatile("cp.async.bulk.prefetch.L2.global [%0], %1;" ::"l"(a0), "r"(bytes) : "memory");
            }
#pragma unroll 1
            for (int i = tid - 448; i < 1536 + 128 && w > 1; i += 64) {
                if (i < 1536) g_P[(uint32_t)(b * 4 + i / 384) * 1024 + 640 + i % 384] = make_uint4(0, 0, 0, 0);
                else g_Ebuf[b * 128 + i - 1536] = make_float4(0.f, 0.f, 0.f, 0.f);
            }
#pragma unroll 1
            for (int task = tid - 448; task < 256 && w > 1; task += 64) {
                const int cb = task & 127, kq = 2 * b + (task >> 7), k1 = kq >> 2, qq = kq & 3;
                const unsigned short* wr_ = (const unsigned short*)p.w_r + (k1 + 128 * qq) * 257;
                const unsigned short* wi_ = (const unsigned short*)p.w_i + (k1 + 128 * qq) * 257;
                const int c0 = cb == 0 ? 256 : 2 * cb, c1 = 2 * cb + 1;
                uint32_t wf[16];
#pragma unroll
                for (int i = 0; i < 8; i++) {
                    int o = (512 * (i >> 1) + 64 * (i & 1)) * 257;
                    wf[i] = (uint32_t)__ldg(wr_ + o + c0) | ((uint32_t)__ldg(wi_ + o + c0) << 16);
                    wf[8 + i] = (uint32_t)__ldg(wr_ + o + c1) | ((uint32_t)__ldg(wi_ + o + c1) << 16);
                }
                uint4* wd = g_Wfrag + (uint32_t)(cb * 1024 + kq);
#pragma unroll
                for (int i = 0; i < 4; i++) wd[i * 256] = make_uint4(wf[4 * i], wf[4 * i + 1], wf[4 * i + 2], wf[4 * i + 3]);
            }
            __syncwarp();
            if (w > 1) bar_arrive(11, 96);
            if (w == 3) {
#pragma unroll 1
                for (int it = 0; it < 8; it++) {
                    const int m = 4 * c + (it >> 1), d = 64 * r + m, ch = lane + 32 * (it & 1);
                    float v[8];
#pragma unroll
                    for (int e = 0; e < 8; e++) {
                        int j = 8 * ch + e, f, ph;
                        dft_fp(j, f, ph);
                        int a = (d * f + ph) & 511;
                        a = a >= 256 ? a - 512 : a;
                        float wj = j == 0 ? 0.f : (j == 1 ? 1.f / 512.f : 2.f / 512.f);
                        v[e] = wj * __cosf((float)a * (6.283185307179586f / 512.f));
                    }
                    uint32_t off = (uint32_t)(64 + r * 8 + (ch >> 3)) * 8192 + (m >> 3) * 1024 + (ch & 7) * 128 + (m & 7) * 16;
                    *(uint4*)(g_E + off) = make_uint4(pack_bf16(v[0], v[1]), pack_bf16(v[2], v[3]), pack_bf16(v[4], v[5]), pack_bf16(v[6], v[7]));
                }
                __syncwarp();
                if (lane == 0) { fence_async(); red_release(&g_bar[6], 1); }
                return;
            }
            if (w == 2) {
#pragma unroll 1
                for (int it = 0; it < 4; it++) {
                    const int hf = it & 1;
                    __syncwarp();
                    if (hf == 0) bar_sync(13, 288); else bar_sync(6, 416);
                    if (lane == 0) {
                        const uint32_t src = sb + SM_HH + par * 32768 + hf * 16384;
                        bulk_s2peer(mapa(src, par ^ 1), src, 16384, mapa(BAR(hf ? B_HPEER1 : B_HPEER), par ^ 1));
                    }
                }
                return;
            }
            {
                uint4 p0 = __ldg((const uint4*)p.dskip + 2 * lane), p1 = __ldg((const uint4*)p.dskip + 2 * lane + 1);
                uint32_t u[8] = {p0.x, p0.y, p0.z, p0.w, p1.x, p1.y, p1.z, p1.w};
#pragma unroll 1
                for (int jj = 0; jj < 4; jj++) {
                    int j = 64 * r + 4 * c + jj, f, ph;
                    dft_fp(j, f, ph);
                    float s = 0.f;
                    int idx = 16 * lane * f + ph;
#pragma unroll
                    for (int i = 0; i < 16; i++) {
                        int a = idx & 511;
                        idx += f;
                        a = a >= 256 ? a - 512 : a;
                        s += ((i & 1) ? bf_hi(u[i >> 1]) : bf_lo(u[i >> 1])) * __cosf((float)a * (6.283185307179586f / 512.f));
                    }
#pragma unroll
                    for (int o = 16; o; o >>= 1) s += __shfl_xor_sync(~0u, s, o);
                    if (lane == 0) g_Dh[j] = s;
                }
                if (lane == 0) red_release(&g_bar[5], 1);
                __syncwarp();
            }
            bar_sync(2, 416);
            if (lane == 0) {
                TX(5);
                asm volatile("cp.async.bulk.global.shared::cta.bulk_group [%0], [%1], 8192;" ::"l"(g_A1 + (uint32_t)(((c >> 1) * 8 + r) * 16384 + (c & 1) * 8192)),
                             "r"(sb + SM_B1ST) : "memory");
                asm volatile("cp.async.bulk.commit_group;" ::: "memory");
                fence_async();
                red_release(&g_bar[0], 1);
                TX(6);
                asm volatile("cp.async.bulk.wait_group 0;" ::: "memory");
                fence_async();
            }
            __syncwarp();
            bar_sync(11, 96);
            if (lane == 0) red_release(&g_bar[4], 1);
#pragma unroll 1
            for (int layer = 0; layer < 2; layer++) {
                __syncwarp();
                bar_sync(5, 416);
                if (lane == 0) {
                    TX(0 + 8 * layer);
                    tma_store_5d(&tm_col, 32 * (b & 1), 0, b >> 1, 0, layer, sb + SM_RAW);
                    asm volatile("cp.reduce.async.bulk.global.shared::cta.bulk_group.add.f32 [%0], [%1], 8192;" ::"l"(g_ssqc + (layer * 16 + (b & 15)) * 2048),
                                 "r"(sb + SM_SSQ) : "memory");
                    asm volatile("cp.async.bulk.commit_group;" ::: "memory");
                    asm volatile("cp.async.bulk.wait_group 0;" ::: "memory");
                    TX(1 + 8 * layer);
                    fence_async();
                    red_release(&g_bar[1 + 2 * layer], 1);
                    TX(2 + 8 * layer);
                }
            }
        } else if (tid == 384) {
#pragma unroll 1
            for (int kb = 0; kb < 8; kb++) {
                int s = kb < 6 ? kb : kb - 4;
                uint32_t dst = s < 2 ? sb + SM_A + 65536 + s * 24576 : sb + SM_X + (s - 2) * 24576;
                if (kb >= 6) mbar_wait_cluster(BAR(B_EMPTY0 + s), 0);
                uint32_t fb = BAR(B_FULL0 + kb);
                mbar_expect(fb, 24576);
                tma_5d_mc(dst + par * 8192, &tm_x, kb * 64, 0, 0, 8 * par, c, fb);
                tma_2d_mc(dst + 16384 + par * 4096, par ? &tm_bim : &tm_bre, kb * 64, 32 * c, fb);
                if (kb == 5) {
#pragma unroll 1
                    for (int k2 = par; k2 < 8; k2 += 2) {
                        asm volatile("cp.async.bulk.prefetch.tensor.2d.L2.global [%0, {%1,%2}];" ::"l"((c & 1) ? &tm_cim : &tm_cre), "r"(64 * (c >> 1)), "r"(k2 * 64) : "memory");
                        if (k2 < 4) {
                            asm volatile("cp.async.bulk.prefetch.tensor.5d.L2.global [%0, {%1,%2,%3,%4,%5}];" ::"l"(&tm_x), "r"((6 + (k2 >> 1)) * 64), "r"(0), "r"(0), "r"(8 * par), "r"(c) : "memory");
                            asm volatile("cp.async.bulk.prefetch.tensor.2d.L2.global [%0, {%1,%2}];" ::"l"(par ? &tm_bim : &tm_bre), "r"((6 + (k2 >> 1)) * 64), "r"(32 * c) : "memory");
                        }
                    }
                }
                if (kb == 7) {
                    mbar_wait_cluster(BAR(B_EMPTY0 + 0), 0);
                    mbar_wait_cluster(BAR(B_EMPTY0 + 1), 0);
                    mbar_expect(BAR(B_FULLC), 65536);
#pragma unroll 1
                    for (int k2 = par; k2 < 8; k2 += 2)
                        tma_2d_mc(sb + SM_A + 65536 + k2 * 8192, (c & 1) ? &tm_cim : &tm_cre, 64 * (c >> 1), k2 * 64, BAR(B_FULLC));
                }
            }
#pragma unroll 1
            for (int layer = 0; layer < 2; layer++) {
                wait_count(&g_bar[2 * layer], s_tgt[2 * layer]);
                TX(4 + 8 * layer);
                fence_async();
                mbar_expect(BAR(B_COL), 16384 + 8192);
                tma_5d(sb + SM_RAW, &tm_col, 32 * (b & 1), 0, b >> 1, 0, layer, BAR(B_COL));
                bulk_g2s(sb + SM_SSQ, g_ssq + layer * 2048, 8192, BAR(B_COL));
                if (layer == 0) {
                    wait_count(&g_bar[4], s_tgt[4]);
                    mbar_arrive(BAR(B_WRDY), 1);
                    fence_async();
                }
                if (layer == 0) mbar_wait(BAR(B_AFREE), 0);
                mbar_wait(BAR(B_COL), layer);
#pragma unroll 1
                for (int s = 0; s < 8; s++) {
                    if (layer == 1) mbar_wait(BAR(B_AEMPTY + s), 1);
                    mbar_expect(BAR(B_AFULL + s), 16384);
                    bulk_g2s(sb + SM_A + s * 16384, g_A1 + (uint32_t)(r * 8 + s) * 16384, 16384, BAR(B_AFULL + s));
                }
                if (layer == 1) wait_count(&g_bar[6], s_tgt[5]);
                wait_count(&g_bar[1 + 2 * layer], s_tgt[1 + 2 * layer]);
                TX(3 + 8 * layer);
                fence_async();
                const uint8_t* xsrc = g_X + (uint32_t)(layer * 16 + c) * 8 * 16384;
                const uint8_t* esrc = g_E + (uint32_t)(layer * 8 + own) * 8 * 8192;
                mbar_arrive(BAR(B_SSQ), 1);
                mbar_expect(BAR(B_HPEER), 16384);
                mbar_expect(BAR(B_HPEER1), 16384);
#pragma unroll 1
                for (int it = 0; it < 12; it++) {
                    if (it < 8) {
                        int st = it & 3, f = layer * 2 + (it >> 2);
                        if (f > 0) mbar_wait_cluster(BAR(B_XEMPTY + st), (f - 1) & 1);
                        mbar_expect(BAR(B_XFULL + st), 24576);
                        bulk_g2s_mc(sb + SM_X + st * 24576 + par * 8192, xsrc + (uint32_t)it * 16384 + par * 8192, 8192, BAR(B_XFULL + st));
                        bulk_g2s(sb + SM_X + st * 24576 + 16384, esrc + (uint32_t)it * 8192, 8192, BAR(B_XFULL + st));
                    }
                    if (it >= 4) {
                        int s = it - 4, tile = 4 * par + ((pi_ + 1 + (s >> 1)) & 3), sl = r ^ (s & 1);
                        mbar_wait(BAR(B_AEMPTY + s), 0);
                        uint32_t fb = BAR(B_AFULL + s), dst = sb + SM_A + s * 16384;
                        mbar_expect(fb, 16384);
                        if (layer == 1) {
                            tma_2d(dst, &tm_cre, 64 * sl, 64 * tile, fb);
                            tma_2d(dst + 8192, &tm_cim, 64 * sl, 64 * tile, fb);
                        } else {
                            bulk_g2s(dst, g_A2 + (uint32_t)(sl * 8 + tile) * 16384, 16384, fb);
                        }
                    }
                }
            }
        }
        return;
    }

    asm volatile("setmaxnreg.inc.sync.aligned.u32 152;");
    TS(0);
    if (wg == 0) TC(30);
    {
        const int f = 32 * r + lane;
        float cd, sd;
        __sincosf((float)f * (6.283185307179586f / 512.f), &sd, &cd);
        const uint32_t dst = sb + SM_A + (lane >> 2) * 1024 + (lane & 3) * 32;
#pragma unroll 1
        for (int ch = tid >> 5; ch < 64; ch += 12) {
            int a = (8 * ch * f) & 511;
            a = a >= 256 ? a - 512 : a;
            float cs, sn;
            __sincosf((float)a * (6.283185307179586f / 512.f), &sn, &cs);
            float cv[8], sv[8];
#pragma unroll
            for (int e = 0; e < 8; e++) {
                cv[e] = cs; sv[e] = -sn;
                float t = cs * cd - sn * sd;
                sn = sn * cd + cs * sd;
                cs = t;
            }
            uint4 o1 = make_uint4(pack_bf16(sv[0], sv[1]), pack_bf16(sv[2], sv[3]), pack_bf16(sv[4], sv[5]), pack_bf16(sv[6], sv[7]));
            if (f == 0) o1 = make_uint4(0xbf803f80u, 0xbf803f80u, 0xbf803f80u, 0xbf803f80u);
            uint32_t a0 = dst + (ch >> 3) * 8192 + (ch & 7) * 128;
            sts128(a0, make_uint4(pack_bf16(cv[0], cv[1]), pack_bf16(cv[2], cv[3]), pack_bf16(cv[4], cv[5]), pack_bf16(cv[6], cv[7])));
            sts128(a0 + 16, o1);
        }
    }
    fence_async_smem();
    bar_sync(10, 480);
    TS(1);
    uint4 pre[4];
    if (wg < 2) {
        const uint4* src = (const uint4*)(p.x0 + (uint32_t)(128 * c + 16 * r + 8 * wg + 2 * w) * 512) + lane;
#pragma unroll
        for (int i = 0; i < 4; i++) pre[i] = __ldg(src + 32 * i);
    } else {
        pre[0] = pre[1] = pre[2] = pre[3] = make_uint4(0, 0, 0, 0);
    }

    {
        float acc[32];
        acc_def(acc);
#pragma unroll 1
        for (int kb = 0; kb < 8; kb++) {
            int s = kb < 6 ? kb : kb - 4;
            uint32_t src = (s < 2 ? sb + SM_A + 65536 + s * 24576 : sb + SM_X + (s - 2) * 24576) + wg * 8192;
            mbar_wait(BAR(B_FULL0 + kb), 0);
            wg_fence();
#pragma unroll
            for (int ks = 0; ks < 4; ks++)
                wgmma_n64<0>(acc, desc_a(sb + SM_A + kb * 8192 + ks * 256), desc_k(src + ks * 32), 1);
            wg_commit();
            wg_wait<1>();
            if (kb > 0 && kb <= 4 && lane == 0) { mbar_arrive(BAR(B_EMPTY0 + kb - 1), 1); mbar_arrive_remote(mapa(BAR(B_EMPTY0 + kb - 1), par ^ 1)); }
        }
        wg_wait<0>();
        TS(2);
        if (wg < 2) {
            uint8_t* dst = g_X + (uint32_t)((c * 8 + r) * 16384 + w * 4096 + wg * 1024 + g * 16 + 4 * q);
#pragma unroll
            for (int i = 0; i < 8; i++) {
                *(uint32_t*)(dst + i * 128) = pack_bf16(acc[4 * i], acc[4 * i + 1]);
                *(uint32_t*)(dst + 2048 + i * 128) = pack_bf16(acc[4 * i + 2], acc[4 * i + 3]);
            }
#pragma unroll
            for (int rr = 0; rr < 2; rr++) {
                int t = 16 * r + 8 * wg + 2 * w + rr;
                uint32_t u[8] = {pre[2 * rr].x, pre[2 * rr].y, pre[2 * rr].z, pre[2 * rr].w, pre[2 * rr + 1].x, pre[2 * rr + 1].y, pre[2 * rr + 1].z, pre[2 * rr + 1].w};
                float s = 0.f;
#pragma unroll
                for (int i = 0; i < 8; i++) s += bf_lo(u[i]) + bf_hi(u[i]);
#pragma unroll
                for (int o = 16; o; o >>= 1) s += __shfl_xor_sync(~0u, s, o);
                float m = s * (1.f / 512.f), ss = 0.f;
#pragma unroll
                for (int i = 0; i < 8; i++) { float d0 = bf_lo(u[i]) - m, d1 = bf_hi(u[i]) - m; ss += d0 * d0 + d1 * d1; }
#pragma unroll
                for (int o = 16; o; o >>= 1) ss += __shfl_xor_sync(~0u, ss, o);
                if (lane == 0) g_ssq[128 * c + 8 * ((t >> 1) & 15) + 2 * (t >> 5) + (t & 1)] = ss;
            }
        } else {
            uint8_t* dst = sm + SM_B1ST + w * 256 + q * 32 + g * 2;
            const float wj0 = (r == 0 && w == 0 && g < 2) ? (g == 0 ? 0.f : 1.f / 512.f) : 2.f / 512.f;
#pragma unroll
            for (int i = 0; i < 4; i++) {
#pragma unroll
                for (int e = 0; e < 2; e++) {
                    float2 cf = *(const float2*)(sm + SM_RSTD + (8 * i + 2 * q + e) * 8);
#pragma unroll
                    for (int h = 0; h < 2; h++) {
                        float wj = h == 0 ? wj0 : 2.f / 512.f;
                        float pr = acc[4 * i + 2 * h + e] * wj, pi = acc[16 + 4 * i + 2 * h + e] * wj;
                        uint8_t* d2 = dst + i * 2048 + h * 128 + e * 16;
                        *(__nv_bfloat16*)(d2) = __float2bfloat16(cf.x * pr - cf.y * pi);
                        *(__nv_bfloat16*)(d2 + 1024) = __float2bfloat16(cf.x * pi + cf.y * pr);
                    }
                }
            }
            fence_async_smem();
        }
        bar_sync(2, 416);
        TS(3);
    }

    if (wg == 2) {
        {
            const int m = 4 * c + w, jp = 64 * r + m;
            int fp, php;
            dft_fp(jp, fp, php);
            const __nv_bfloat16* dh = (const __nv_bfloat16*)(sm + SM_RSTD);
            if (tid == 256) wait_count(&g_bar[5], s_tgt[5]);
            bar_sync(3, 128);
            float4 d4 = __ldcg((const float4*)g_Dh + (tid - 256));
            *(uint2*)(sm + SM_RSTD + (tid - 256) * 8) = make_uint2(pack_bf16(d4.x, d4.y), pack_bf16(d4.z, d4.w));
            bar_sync(3, 128);
#pragma unroll 1
            for (int it = 0; it < 2; it++) {
                const int ch = lane + 32 * it;
                float v[8];
#pragma unroll
                for (int e = 0; e < 8; e++) {
                    int j = 8 * ch + e, f, ph;
                    dft_fp(j, f, ph);
                    float wj = j == 0 ? 0.f : (j == 1 ? 1.f / 512.f : 2.f / 512.f);
                    float gsum = 0.f;
#pragma unroll
                    for (int sgn = 0; sgn < 2; sgn++) {
                        int mm = (sgn ? f - fp : f + fp) & 511, pp = (sgn ? ph - php : ph + php) & 511;
                        if (mm > 256) { mm = 512 - mm; pp = (512 - pp) & 511; }
                        int odd = (pp >> 7) & 1;
                        float t = __bfloat162float(dh[mm == 256 ? 1 : 2 * mm + odd]);
                        if (odd && (mm & 255) == 0) t = 0.f;
                        gsum += (pp & 256) ? -t : t;
                    }
                    v[e] = 0.5f * wj * gsum;
                }
                uint32_t off = (uint32_t)(r * 8 + (ch >> 3)) * 8192 + (m >> 3) * 1024 + (ch & 7) * 128 + (m & 7) * 16;
                *(uint4*)(g_E + off) = make_uint4(pack_bf16(v[0], v[1]), pack_bf16(v[2], v[3]), pack_bf16(v[4], v[5]), pack_bf16(v[6], v[7]));
            }
        }
        float acc[32];
        acc_def(acc);
        mbar_wait(BAR(B_FULLC), 0);
        wg_fence();
#pragma unroll 1
        for (int kb = 0; kb < 8; kb++) {
#pragma unroll
            for (int ks = 0; ks < 4; ks++)
                wgmma_n64<1>(acc, desc_a(sb + SM_A + kb * 8192 + ks * 256), desc_mn(sb + SM_A + 65536 + kb * 8192 + ks * 2048, 8192), 1);
            wg_commit();
        }
        wg_wait<0>();
        fence_async_smem();
        if (lane == 0) mbar_arrive(BAR(B_AFREE), 1);
        uint8_t* dst = g_A2 + (uint32_t)(((c >> 1) * 8 + r) * 16384 + (c & 1) * 8192 + w * 2048 + g * 16 + 4 * q);
#pragma unroll
        for (int i = 0; i < 8; i++) {
            *(uint32_t*)(dst + i * 128) = pack_bf16(acc[4 * i], acc[4 * i + 1]);
            *(uint32_t*)(dst + 1024 + i * 128) = pack_bf16(acc[4 * i + 2], acc[4 * i + 3]);
        }
    }

#pragma unroll 1
    for (int layer = 0; layer < 2; layer++) {
        if (wg < 2) {
            const int n1 = 32 * wg + 8 * w + g;
            const int ct = n1 >> 2;
            gen_col_consts(sb, tid);
            float twr[8], twi[8];
#pragma unroll
            for (int i = 0; i < 8; i++) {
                int n2 = 8 * (i >> 1) + 2 * q + (i & 1);
                int a = (n1 * n2) & 2047;
                a = a >= 1024 ? a - 2048 : a;
                float ang = (float)a * (-6.283185307179586f / 2048.f);
                twr[i] = __cosf(ang); twi[i] = __sinf(ang);
            }
            mbar_wait(BAR(B_COL), layer);
            TS(4 + 12 * layer);
            if (wg == 0) TC(0 + 10 * layer);
            const uint32_t rw0 = sb + SM_RAW + ct * 1024 + q * 64 + ((q >> 1) << 4) + (g & 3) * 4, rw1 = rw0 ^ 16;
            const int pos0 = 128 * ct + 8 * q + 2 * (g & 3);
            const int sw = b == 0 ? 1 : 0;
            uint32_t xr[4][4];
            const uint32_t st0 = sb + SM_H + (n1 >> 3) * 1024 + g * 16 + 4 * q;
#pragma unroll
            for (int i = 0; i < 4; i++) {
                float2 sq = *(const float2*)(sm + SM_SSQ + (pos0 + 32 * i) * 4);
                float r0 = rsqrtf(sq.x * (1.f / 512.f) + 1e-5f), r1 = rsqrtf(sq.y * (1.f / 512.f) + 1e-5f);
#pragma unroll
                for (int jj = 0; jj < 4; jj++) {
                    const int K = jj ^ (2 * (i & 1));
                    uint32_t a = ((K & 1) ? rw1 : rw0) + i * 256 + (K & 2) * 16;
                    if (jj < 2) a ^= sw << 4;
                    uint32_t v = lds32(a);
                    xr[jj][i] = v;
                    uint32_t o = pack_bf16(bf_lo(v) * r0, bf_hi(v) * r1);
                    if (jj == 1 && sw) o = 0u;
                    sts32(st0 + (jj & 1) * 8192 + (4 * (jj >> 1) + i) * 128, o);
                }
            }
            if (wg == 0) TC(1 + 10 * layer);
            fence_async_smem();
            bar_sync(1, 256);
            float acc[32];
            const uint32_t s1a = sb + SM_X + wg * 16384, s2b = sb + SM_X + 32768;
            wg_fence();
#pragma unroll
            for (int ks = 0; ks < 8; ks++)
                wgmma_n64<1>(acc, desc_a(s1a + (ks >> 2) * 8192 + (ks & 3) * 256), desc_b<64>(sb + SM_H + ks * 2048), ks != 0);
            wg_commit();
            mbar_wait(BAR(B_WRDY), 0);
            uint32_t wf[16];
            {
                const uint4* ws = g_Wfrag + (uint32_t)(b * 1024 + n1 * 4 + q);
#pragma unroll
                for (int i = 0; i < 4; i++) {
                    uint4 v = __ldcg(ws + i * 256);
                    wf[4 * i] = v.x; wf[4 * i + 1] = v.y; wf[4 * i + 2] = v.z; wf[4 * i + 3] = v.w;
                }
            }
            wg_wait<0>();
            if (wg == 0) TC(2 + 10 * layer);
            uint32_t are[2][4], aim[2][4];
#pragma unroll
            for (int col = 0; col < 2; col++) {
#pragma unroll
                for (int i = 0; i < 4; i++) {
                    int o = 4 * (4 * col + i);
                    float r0 = acc[o] * twr[2 * i] - acc[o + 2] * twi[2 * i], i0 = acc[o] * twi[2 * i] + acc[o + 2] * twr[2 * i];
                    float r1 = acc[o + 1] * twr[2 * i + 1] - acc[o + 3] * twi[2 * i + 1], i1 = acc[o + 1] * twi[2 * i + 1] + acc[o + 3] * twr[2 * i + 1];
                    are[col][i] = pack_bf16(r0, r1);
                    aim[col][i] = pack_bf16(i0, i1);
                }
            }
            wg_fence();
#pragma unroll
            for (int ks = 0; ks < 2; ks++)
                wgmma_n64_rs(acc, are[0][2 * ks], are[1][2 * ks], are[0][2 * ks + 1], are[1][2 * ks + 1], desc_b<64>(s2b + ks * 2048), ks != 0);
#pragma unroll
            for (int ks = 0; ks < 2; ks++)
                wgmma_n64_rs(acc, aim[0][2 * ks], aim[1][2 * ks], aim[0][2 * ks + 1], aim[1][2 * ks + 1], desc_b<64>(s2b + 4096 + ks * 2048), 1);
            wg_commit();
            wg_wait<0>();
            if (wg == 0) TC(3 + 10 * layer);
#pragma unroll
            for (int col = 0; col < 2; col++) {
#pragma unroll
                for (int i = 0; i < 4; i++) {
                    float gr[2], gi[2];
#pragma unroll
                    for (int e = 0; e < 2; e++) {
                        uint32_t wv = wf[col * 8 + 2 * i + e];
                        float wr = bf_lo(wv), wi = bf_hi(wv);
                        float zr = acc[4 * i + 2 * col + e], zi = acc[16 + 4 * i + 2 * col + e];
                        gr[e] = zr * wr - zi * wi;
                        gi[e] = -(zr * wi + zi * wr);
                    }
                    are[col][i] = pack_bf16(gr[0], gr[1]);
                    aim[col][i] = pack_bf16(gi[0], gi[1]);
                }
            }
            wg_fence();
#pragma unroll
            for (int ks = 0; ks < 2; ks++)
                wgmma_n64_rs(acc, are[0][2 * ks], are[1][2 * ks], are[0][2 * ks + 1], are[1][2 * ks + 1], desc_b<64>(s2b + ks * 2048), ks != 0);
#pragma unroll
            for (int ks = 0; ks < 2; ks++)
                wgmma_n64_rs(acc, aim[0][2 * ks], aim[1][2 * ks], aim[0][2 * ks + 1], aim[1][2 * ks + 1], desc_b<64>(s2b + 4096 + ks * 2048), 1);
            wg_commit();
            wg_wait<0>();
            if (wg == 0) TC(4 + 10 * layer);
#pragma unroll
            for (int col = 0; col < 2; col++) {
#pragma unroll
                for (int i = 0; i < 4; i++) {
                    float rr[2], im[2];
#pragma unroll
                    for (int e = 0; e < 2; e++) {
                        float zr = acc[4 * i + 2 * col + e], zi = acc[16 + 4 * i + 2 * col + e];
                        rr[e] = zr * twr[2 * i + e] - zi * twi[2 * i + e];
                        im[e] = zr * twi[2 * i + e] + zi * twr[2 * i + e];
                    }
                    sts32(st0 + 16384 + (4 * col + i) * 128, pack_bf16(rr[0], rr[1]));
                    sts32(st0 + 16384 + 8192 + (4 * col + i) * 128, pack_bf16(im[0], im[1]));
                }
            }
            if (wg == 0) TC(5 + 10 * layer);
            fence_async_smem();
            bar_sync(1, 256);
            wg_fence();
#pragma unroll
            for (int ks = 0; ks < 8; ks++)
                wgmma_n64<1>(acc, desc_a(s1a + (ks >> 2) * 8192 + (ks & 3) * 256), desc_b<64>(sb + SM_H + 16384 + ks * 2048), ks != 0);
            wg_commit();
            wg_wait<0>();
            if (wg == 0) TC(6 + 10 * layer);
            const float sc = 1.f / 2048.f;
            const float sci0 = sw ? 0.f : -sc;
            const float wr0 = sw ? 0.5f : 1.f, wi0 = sw ? 0.f : 1.f;
#pragma unroll
            for (int i = 0; i < 4; i++) {
                float ss0, ss1;
#pragma unroll
                for (int col = 0; col < 2; col++) {
                    int o = 4 * (4 * col + i);
                    uint32_t vr = xr[2 * col][i], vi = xr[2 * col + 1][i];
                    float si = col == 0 ? sci0 : -sc;
                    uint32_t nr = pack_bf16(fmaf(acc[o], sc, bf_lo(vr)), fmaf(acc[o + 1], sc, bf_hi(vr)));
                    uint32_t ni = pack_bf16(fmaf(acc[o + 2], si, bf_lo(vi)), fmaf(acc[o + 3], si, bf_hi(vi)));
                    float a0 = bf_lo(nr), a1 = bf_hi(nr), b0 = bf_lo(ni), b1 = bf_hi(ni);
                    if (col == 0) {
                        ss0 = wr0 * a0 * a0 + wi0 * b0 * b0;
                        ss1 = wr0 * a1 * a1 + wi0 * b1 * b1;
                    } else {
                        ss0 += a0 * a0 + b0 * b0;
                        ss1 += a1 * a1 + b1 * b1;
                    }
                    const int K = (2 * col) ^ (2 * (i & 1));
                    uint32_t a = rw0 + i * 256 + K * 16;
                    if (col == 0) a ^= sw << 4;
                    sts32(a, nr);
                    sts32(a ^ 16, ni);
                }
                *(float2*)(sm + SM_SSQ + (pos0 + 32 * i) * 4) = make_float2(ss0 * (2.f / 512.f), ss1 * (2.f / 512.f));
            }
            fence_async_smem();
        }
        TS(5 + 12 * layer);
        if (wg == 0) TC(7 + 10 * layer);
        bar_arrive(5, 416);

        float acc[64];
        float* s_rstd = (float*)(sm + SM_RSTD);
        float* s_mean = (float*)(sm + SM_MEAN);
        const unsigned epoch = s_tgt[0] >> 7;
        const uint32_t pt3 = 1u + (2u * epoch + layer) % 3u;
        const uint32_t ptag = (pt3 & 1u) | ((pt3 & 2u) << 15);
        const uint64_t dstep = layer == 0 ? 16 : 2;
        auto c_desc = [&](int s) { return layer == 0 ? desc_a(sb + SM_A + s * 16384) : desc_k(sb + SM_A + s * 16384); };
        if (wg < 2) {
            const int prow = 32 * wg + 8 * w + g;
            const float2 l1 = *(const float2*)(sm + SM_LAM + prow * 8);
            float lr32 = l1.x, li32 = l1.y;
#pragma unroll
            for (int i = 0; i < 5; i++) { float t = lr32 * lr32 - li32 * li32; li32 = 2.f * lr32 * li32; lr32 = t; }
            float lr128 = lr32, li128 = li32;
#pragma unroll
            for (int i = 0; i < 2; i++) { float t = lr128 * lr128 - li128 * li128; li128 = 2.f * lr128 * li128; lr128 = t; }
            const float lr1 = l1.x, li1 = l1.y;
            acc_def(acc);
#pragma unroll 1
            for (int kb = 0; kb < 8; kb++) {
                mbar_wait(BAR(B_AFULL + kb), 0);
                mbar_wait(BAR(B_XFULL + (kb & 3)), (kb >> 2) & 1);
                wg_fence();
#pragma unroll
                for (int ks = 0; ks < 4; ks++)
                    wgmma_n128<1>(acc, desc_a(sb + SM_A + kb * 16384 + wg * 8192 + ks * 256),
                                  desc_b<128>(sb + SM_X + (kb & 3) * 24576 + ks * 4096), 1);
                wg_commit();
                wg_wait<1>();
                if (kb > 0 && lane == 0) {
                    mbar_arrive(BAR(B_AEMPTY + kb - 1), 1); mbar_arrive(BAR(B_XEMPTY + ((kb - 1) & 3)), 1);
                    mbar_arrive_remote(mapa(BAR(B_XEMPTY + ((kb - 1) & 3)), par ^ 1));
                }
            }
            wg_wait<0>();
            if (lane == 0) {
                mbar_arrive(BAR(B_AEMPTY + 7), 1); mbar_arrive(BAR(B_XEMPTY + 3), 1);
                mbar_arrive_remote(mapa(BAR(B_XEMPTY + 3), par ^ 1)); mbar_arrive_remote(mapa(BAR(B_RFREE), par ^ 1));
            }
            bar_arrive(14, 384);
            TS(6 + 12 * layer);
            bar_sync(4, 384);
            TS(7 + 12 * layer);
            float er = 0.f, ei = 0.f;
#pragma unroll
            for (int i = 0; i < 16; i++) {
                float2 rs = *(const float2*)(s_rstd + 128 + 8 * i + 2 * q);
                acc[4 * i] *= rs.x; acc[4 * i + 1] *= rs.y; acc[4 * i + 2] *= rs.x; acc[4 * i + 3] *= rs.y;
                float nr = lr1 * er - li1 * ei + acc[4 * i], ni = lr1 * ei + li1 * er + acc[4 * i + 2];
                er = lr1 * nr - li1 * ni + acc[4 * i + 1];
                ei = lr1 * ni + li1 * nr + acc[4 * i + 3];
            }
            float cr = 0.f, ci = 0.f, tr = 0.f, ti = 0.f;
#pragma unroll
            for (int qq = 0; qq < 4; qq++) {
                float xr_ = __shfl_sync(~0u, er, (lane & ~3) | qq), xi_ = __shfl_sync(~0u, ei, (lane & ~3) | qq);
                if (qq == q) { cr = tr; ci = ti; }
                float nr = lr32 * tr - li32 * ti + xr_, ni = lr32 * ti + li32 * tr + xi_;
                tr = nr; ti = ni;
            }
            float4* eb = g_Ebuf + (uint32_t)(layer * 16 * 512 + 64 * r + prow);
            if (q == 0 && c < 15) st_relaxed_f4(eb + c * 512, make_float4(tr, ti, __uint_as_float(epoch), 0.f));
            TS(8 + 12 * layer);
            float pr[4], pi[4];
            {
                unsigned n = 0;
                bool ok;
#pragma unroll 1
                do {
                    ok = true;
#pragma unroll
                    for (int k = 0; k < 4; k++) {
                        float4 v = make_float4(0.f, 0.f, __uint_as_float(epoch), 0.f);
                        if (4 * k + q < c) v = ld_relaxed_f4(eb + (4 * k + q) * 512);
                        pr[k] = v.x; pi[k] = v.y;
                        ok = ok && __float_as_uint(v.z) == epoch;
                    }
                } while (!ok && ++n < SPIN_LIMIT);
            }
            __syncwarp();
            TS(9 + 12 * layer);
            float hr = 0.f, hi = 0.f;
#pragma unroll
            for (int cc = 0; cc < 15; cc++) {
                float xr_ = __shfl_sync(~0u, pr[cc >> 2], (lane & ~3) | (cc & 3)), xi_ = __shfl_sync(~0u, pi[cc >> 2], (lane & ~3) | (cc & 3));
                if (cc < c) {
                    float nr = lr128 * hr - li128 * hi + xr_, ni = lr128 * hi + li128 * hr + xi_;
                    hr = nr; hi = ni;
                }
            }
#pragma unroll
            for (int qq = 0; qq < 3; qq++) {
                if (qq < q) { float nr = lr32 * hr - li32 * hi, ni = lr32 * hi + li32 * hr; hr = nr; hi = ni; }
            }
            er = cr + hr; ei = ci + hi;
            bar_sync(7, 384);
            mbar_wait_cluster(BAR(B_RFREE), layer);
            const uint32_t ha = sb + SM_HH + par * 32768 + (prow >> 3) * 1024 + g * 16 + 4 * q;
#pragma unroll
            for (int i = 0; i < 16; i++) {
                float nr = lr1 * er - li1 * ei + acc[4 * i], ni = lr1 * ei + li1 * er + acc[4 * i + 2];
                er = lr1 * nr - li1 * ni + acc[4 * i + 1];
                ei = lr1 * ni + li1 * nr + acc[4 * i + 3];
                sts32(ha + (i >> 3) * 16384 + (i & 7) * 128, pack_bf16(nr, er));
                sts32(ha + (i >> 3) * 16384 + 8192 + (i & 7) * 128, pack_bf16(ni, ei));
                if (i == 7) { fence_async_smem(); bar_arrive(13, 288); }
            }
            fence_async_smem();
            acc_def(acc);
            float acc2[32];
            acc_def(acc2);
            TS(10 + 12 * layer);
            bar_sync(6, 416);
            TS(11 + 12 * layer);
            float (&a0)[32] = *reinterpret_cast<float (*)[32]>(&acc[0]);
            float (&a1)[32] = *reinterpret_cast<float (*)[32]>(&acc[32]);
            auto tile_mma = [&](float (&d)[32], int u) {
#pragma unroll 1
                for (int k = 0; k < 2; k++) {
                    const uint32_t hb = sb + SM_HH + (par ^ k) * 32768 + wg * 16384;
                    if (k == 1) mbar_wait(BAR(wg ? B_HPEER1 : B_HPEER), layer);
                    mbar_wait(BAR(B_AFULL + 2 * u + k), 1);
                    const uint64_t da = c_desc(2 * u + k);
                    wg_fence();
#pragma unroll
                    for (int ks = 0; ks < 4; ks++) wgmma_n64s<1>(d, da + ks * dstep, desc_b<64>(hb + ks * 2048), 1);
#pragma unroll
                    for (int ks = 0; ks < 4; ks++) wgmma_n64s<-1>(d, da + 512 + ks * dstep, desc_b<64>(hb + 8192 + ks * 2048), 1);
                }
                wg_commit();
            };
            auto tile_ship = [&](float (&d)[32], int u) {
                uint4* dst = g_P + (uint32_t)(((c * 8 + 2 * ((pi_ + 1 + u) & 3) + par) * 4 + pi_) * 1024 + wg * 512 + (tid & 127));
#pragma unroll
                for (int i = 0; i < 4; i++)
                    dst[i * 128] = make_uint4((pack_bf16(d[8 * i], d[8 * i + 1]) & 0xfffefffeu) | ptag, pack_bf16(d[8 * i + 2], d[8 * i + 3]),
                                              pack_bf16(d[8 * i + 4], d[8 * i + 5]), pack_bf16(d[8 * i + 6], d[8 * i + 7]));
            };
            tile_mma(a0, 0);
            if ((tid & 127) == 0) mbar_arrive_remote(mapa(BAR(B_HDONE), par ^ 1));
            __syncwarp();
            tile_mma(a1, 1);
            wg_wait<1>();
            tile_ship(a0, 0);
            tile_mma(acc2, 2);
            bar_arrive(12, 384);
            wg_wait<1>();
            tile_ship(a1, 1);
            wg_wait<0>();
            tile_ship(acc2, 2);
            if (lane < 6) mbar_arrive(BAR(B_AEMPTY + lane), 1);
            TS(12 + 12 * layer);
        } else {
            const int t2 = tid - 256;
            const uint8_t* ximg = g_X + (uint32_t)layer * 16 * 8 * 16384;
            mbar_wait(BAR(B_SSQ), layer);
            TS(6 + 12 * layer);
            {
                float tot = 0.f;
#pragma unroll
                for (int i = 0; i < 16; i++) tot += __ldcg(g_ssqc + (layer * 16 + i) * 2048 + 128 * c + t2);
                float rs = rsqrtf(tot * (1.f / 512.f) + 1e-5f);
                s_rstd[t2] = rs;
                s_rstd[128 + t2] = 2.f * rs;
                if (layer == 0) s_mean[t2] = 0.f;
                if (layer == 1) {
                    unsigned short u = __ldcg((const unsigned short*)(ximg + (uint32_t)(c * 8 * 16384 + (t2 >> 3) * 128 + (t2 & 7) * 2)));
                    s_mean[t2] = __uint_as_float((uint32_t)u << 16) * (1.f / 512.f);
                }
            }
            TS(7 + 12 * layer);
            bar_arrive(4, 384);
            acc_def(acc);
#pragma unroll 1
            for (int kb = 0; kb < 8; kb++) {
                if (kb == 4) {
                    wg_wait<0>();
                    if (lane == 0) { mbar_arrive(BAR(B_XEMPTY + 3), 1); mbar_arrive_remote(mapa(BAR(B_XEMPTY + 3), par ^ 1)); }
                    bar_sync(14, 384);
                }
                mbar_wait(BAR(B_XFULL + (kb & 3)), (kb >> 2) & 1);
                wg_fence();
#pragma unroll
                for (int ks = 0; ks < 4; ks++)
                    wgmma_n128<1>(acc, desc_a(sb + SM_X + (kb & 3) * 24576 + 16384 + ks * 256), desc_b<128>(sb + SM_X + (kb & 3) * 24576 + ks * 4096), 1);
                wg_commit();
                wg_wait<1>();
                if ((kb & 3) != 0 && lane == 0) { mbar_arrive(BAR(B_XEMPTY + ((kb - 1) & 3)), 1); mbar_arrive_remote(mapa(BAR(B_XEMPTY + ((kb - 1) & 3)), par ^ 1)); }
            }
            wg_wait<0>();
            if (lane == 0) { mbar_arrive(BAR(B_XEMPTY + 3), 1); mbar_arrive_remote(mapa(BAR(B_XEMPTY + 3), par ^ 1)); mbar_arrive_remote(mapa(BAR(B_RFREE), par ^ 1)); }
            bar_arrive(7, 384);
            bar_sync(3, 128);
            TS(9 + 12 * layer);
            const int m0 = 16 * w + g;
            const uint32_t xoff = (uint32_t)((c * 8 + own) * 16384 + w * 4096 + g * 16 + 4 * q);
            if (layer == 0) {
                const uint8_t* xs = g_X + xoff;
#pragma unroll
                for (int i = 0; i < 16; i++) {
                    float2 rs = *(const float2*)(s_rstd + 8 * i + 2 * q);
                    uint32_t x0v = __ldcg((const uint32_t*)(xs + i * 128)), x1v = __ldcg((const uint32_t*)(xs + 2048 + i * 128));
                    acc[4 * i] = acc[4 * i] * rs.x + bf_lo(x0v);
                    acc[4 * i + 1] = acc[4 * i + 1] * rs.y + bf_hi(x0v);
                    acc[4 * i + 2] = acc[4 * i + 2] * rs.x + bf_lo(x1v);
                    acc[4 * i + 3] = acc[4 * i + 3] * rs.y + bf_hi(x1v);
                }
            } else {
                float d0 = ldbf(p.dskip + 64 * own + m0), d1 = ldbf(p.dskip + 64 * own + m0 + 8);
#pragma unroll
                for (int i = 0; i < 16; i++) {
                    float2 rs = *(const float2*)(s_rstd + 8 * i + 2 * q);
                    float2 mn = *(const float2*)(s_mean + 8 * i + 2 * q);
                    acc[4 * i] = acc[4 * i] * (1.f + rs.x * d0) + mn.x;
                    acc[4 * i + 1] = acc[4 * i + 1] * (1.f + rs.y * d0) + mn.y;
                    acc[4 * i + 2] = acc[4 * i + 2] * (1.f + rs.x * d1) + mn.x;
                    acc[4 * i + 3] = acc[4 * i + 3] * (1.f + rs.y * d1) + mn.y;
                }
            }
            TS(10 + 12 * layer);
            bar_sync(6, 416);
            TS(11 + 12 * layer);
            {
                float (&a0)[32] = *reinterpret_cast<float (*)[32]>(&acc[0]);
                float (&a1)[32] = *reinterpret_cast<float (*)[32]>(&acc[32]);
#pragma unroll 1
                for (int k = 0; k < 2; k++) {
                    const uint32_t hb = sb + SM_HH + (par ^ k) * 32768;
                    if (k == 1) {
                        mbar_wait(BAR(B_HPEER), layer);
                        mbar_wait(BAR(B_HPEER1), layer);
                        bar_sync(12, 384);
                    }
                    mbar_wait(BAR(B_AFULL + 6 + k), 1);
                    const uint64_t da = c_desc(6 + k);
                    wg_fence();
#pragma unroll
                    for (int ks = 0; ks < 4; ks++) {
                        wgmma_n64s<1>(a0, da + ks * dstep, desc_b<64>(hb + ks * 2048), 1);
                        wgmma_n64s<1>(a1, da + ks * dstep, desc_b<64>(hb + 16384 + ks * 2048), 1);
                    }
#pragma unroll
                    for (int ks = 0; ks < 4; ks++) {
                        wgmma_n64s<-1>(a0, da + 512 + ks * dstep, desc_b<64>(hb + 8192 + ks * 2048), 1);
                        wgmma_n64s<-1>(a1, da + 512 + ks * dstep, desc_b<64>(hb + 16384 + 8192 + ks * 2048), 1);
                    }
                    wg_commit();
                }
                wg_wait<0>();
            }
#pragma unroll
            for (int i = 0; i < 16; i++)
                *(float4*)(sm + SM_A + 6 * 16384 + i * 2048 + t2 * 16) = make_float4(acc[4 * i], acc[4 * i + 1], acc[4 * i + 2], acc[4 * i + 3]);
            TS(12 + 12 * layer);
        }
        {
            const int t = tid & 127;
            const int nch = wg == 2 ? 2 : 3;
            const uint4* pb = g_P + (uint32_t)((c * 8 + r) * 4 * 1024 + wg * 128 + t);
            uint4 v[3][3];
            unsigned n = 0;
#pragma unroll 1
            while (true) {
                if (lane == 31) {
#pragma unroll 1
                    while (true) {
                        uint32_t bad = 0;
#pragma unroll
                        for (int sx = 0; sx < 3; sx++) {
                            uint32_t t0;
                            asm volatile("ld.relaxed.gpu.global.u32 %0, [%1];" : "=r"(t0) : "l"(pb + ((pi_ + 1 + sx) & 3) * 1024 + (nch - 1) * 384) : "memory");
                            bad |= t0 ^ ptag;
                        }
                        if (!(bad & 0x00010001u) || ++n >= SPIN_LIMIT) break;
                    }
                }
                __syncwarp();
                uint32_t bad = 0;
#pragma unroll
                for (int k = 0; k < 3; k++)
#pragma unroll
                    for (int sx = 0; sx < 3; sx++) {
                        v[k][sx] = make_uint4(ptag, 0, 0, 0);
                        if (k < nch) v[k][sx] = ld_relaxed_u4(pb + ((pi_ + 1 + sx) & 3) * 1024 + k * 384);
                        bad |= v[k][sx].x ^ ptag;
                    }
                if (!__any_sync(~0u, bad & 0x00010001u) || ++n >= SPIN_LIMIT) break;
            }
            bar_sync(8, 384);
            TS(13 + 12 * layer);
            const int m0 = 16 * w + g;
            const float w0 = (own == 0 && m0 < 2) ? (m0 == 0 ? 0.f : 0.5f) : 1.f;
#pragma unroll
            for (int k = 0; k < 3; k++) {
                if (k < nch) {
                    const int i = wg + 3 * k;
                    float4 a = *(const float4*)(sm + SM_A + 6 * 16384 + (2 * i) * 2048 + t * 16);
                    float4 bq = *(const float4*)(sm + SM_A + 6 * 16384 + (2 * i + 1) * 2048 + t * 16);
#pragma unroll
                    for (int sx = 0; sx < 3; sx++) {
                        a.x += bf_lo(v[k][sx].x); a.y += bf_hi(v[k][sx].x); a.z += bf_lo(v[k][sx].y); a.w += bf_hi(v[k][sx].y);
                        bq.x += bf_lo(v[k][sx].z); bq.y += bf_hi(v[k][sx].z); bq.z += bf_lo(v[k][sx].w); bq.w += bf_hi(v[k][sx].w);
                    }
                    if (layer == 0) {
                        uint8_t* xd = g_X + (uint32_t)((16 * 8 + c * 8 + own) * 16384 + w * 4096 + g * 16 + 4 * q + i * 256);
                        uint32_t v0 = pack_bf16(a.x, a.y), v1 = pack_bf16(a.z, a.w), v2 = pack_bf16(bq.x, bq.y), v3 = pack_bf16(bq.z, bq.w);
                        *(uint32_t*)(xd) = v0; *(uint32_t*)(xd + 2048) = v1; *(uint32_t*)(xd + 128) = v2; *(uint32_t*)(xd + 2048 + 128) = v3;
                        float sq[4];
                        sq[0] = w0 * bf_lo(v0) * bf_lo(v0) + bf_lo(v1) * bf_lo(v1);
                        sq[1] = w0 * bf_hi(v0) * bf_hi(v0) + bf_hi(v1) * bf_hi(v1);
                        sq[2] = w0 * bf_lo(v2) * bf_lo(v2) + bf_lo(v3) * bf_lo(v3);
                        sq[3] = w0 * bf_hi(v2) * bf_hi(v2) + bf_hi(v3) * bf_hi(v3);
                        float u0 = (g & 1) ? sq[2] : sq[0], u1 = (g & 1) ? sq[3] : sq[1];
                        u0 += __shfl_xor_sync(~0u, (g & 1) ? sq[0] : sq[2], 4);
                        u1 += __shfl_xor_sync(~0u, (g & 1) ? sq[1] : sq[3], 4);
                        float z = (g & 2) ? u1 : u0;
                        z += __shfl_xor_sync(~0u, (g & 2) ? u0 : u1, 8);
                        z += __shfl_xor_sync(~0u, z, 16);
                        if (g < 4) atomicAdd(s_mean + 16 * i + 8 * (g & 1) + 2 * q + (g >> 1), z);
                    } else {
                        float* o = p.out + (uint32_t)((128 * c + 32 * q + 4 * i) * 512 + 64 * own + m0);
                        o[0] = a.x; o[512] = a.y; o[8] = a.z; o[512 + 8] = a.w;
                        o[1024] = bq.x; o[1536] = bq.y; o[1024 + 8] = bq.z; o[1536 + 8] = bq.w;
                    }
                }
            }
            if (wg < 2) mbar_wait_cluster(BAR(B_HDONE), layer);
            if (layer == 0) {
                fence_async_smem();
                bar_sync(9, 384);
                TS(14 + 12 * layer);
                if (wg == 2) {
                    atomicAdd(g_ssq + 2048 + 128 * c + t, s_mean[t] * (2.f / 512.f));
                    bar_sync(3, 128);
                    if (lane == 0) { mbar_arrive(BAR(B_AEMPTY + 6), 2); mbar_arrive(BAR(B_AEMPTY + 7), 2); }
                    if (t == 0) { fence_async(); red_release(&g_bar[2], 1); }
                }
            }
        }
        TS(15 + 12 * layer);
        if (wg == 0) TC(31);
    }
}

typedef CUresult (*EncFn)(CUtensorMap*, CUtensorMapDataType, cuuint32_t, void*, const cuuint64_t*, const cuuint64_t*,
                          const cuuint32_t*, const cuuint32_t*, CUtensorMapInterleave, CUtensorMapSwizzle,
                          CUtensorMapL2promotion, CUtensorMapFloatOOBfill);

void launch_impl(void* const* d_in, void* d_out, int stop) {
    static EncFn enc = nullptr;
    if (!enc) {
        void* fn = nullptr;
        cudaDriverEntryPointQueryResult qr;
        cudaGetDriverEntryPoint("cuTensorMapEncodeTiled", &fn, cudaEnableDefault, &qr);
        enc = (EncFn)fn;
        cudaFuncSetAttribute(fused_kernel, cudaFuncAttributeMaxDynamicSharedMemorySize, SM_TOTAL);
    }
    CUtensorMap tx, tbr, tbi, tcr, tci, tcol;
    {
        void* gx = nullptr;
        cudaGetSymbolAddress(&gx, g_X);
        cuuint64_t gd[5] = {64, 16, 64, 16, 2};
        cuuint64_t gs[4] = {128, 2048, 128 * 1024, 2048 * 1024};
        cuuint32_t bx[5] = {32, 16, 1, 16, 1};
        cuuint32_t es[5] = {1, 1, 1, 1, 1};
        enc(&tcol, CU_TENSOR_MAP_DATA_TYPE_BFLOAT16, 5, gx, gd, gs, bx, es, CU_TENSOR_MAP_INTERLEAVE_NONE,
            CU_TENSOR_MAP_SWIZZLE_64B, CU_TENSOR_MAP_L2_PROMOTION_NONE, CU_TENSOR_MAP_FLOAT_OOB_FILL_NONE);
    }
    {
        cuuint64_t gd[5] = {512, 2, 4, 16, 16};
        cuuint64_t gs[4] = {1024, 32 * 1024, 2 * 1024, 128 * 1024};
        cuuint32_t bx[5] = {64, 2, 4, 8, 1};
        cuuint32_t es[5] = {1, 1, 1, 1, 1};
        enc(&tx, CU_TENSOR_MAP_DATA_TYPE_BFLOAT16, 5, d_in[0], gd, gs, bx, es, CU_TENSOR_MAP_INTERLEAVE_NONE,
            CU_TENSOR_MAP_SWIZZLE_128B, CU_TENSOR_MAP_L2_PROMOTION_L2_128B, CU_TENSOR_MAP_FLOAT_OOB_FILL_NONE);
    }
    auto mk2 = [&](CUtensorMap* m, void* ptr, cuuint32_t rows) {
        cuuint64_t gd[2] = {512, 512};
        cuuint64_t gs[1] = {1024};
        cuuint32_t bx[2] = {64, rows};
        cuuint32_t es[2] = {1, 1};
        enc(m, CU_TENSOR_MAP_DATA_TYPE_BFLOAT16, 2, ptr, gd, gs, bx, es, CU_TENSOR_MAP_INTERLEAVE_NONE,
            CU_TENSOR_MAP_SWIZZLE_128B, CU_TENSOR_MAP_L2_PROMOTION_L2_128B, CU_TENSOR_MAP_FLOAT_OOB_FILL_NONE);
    };
    mk2(&tbr, d_in[6], 32);
    mk2(&tbi, d_in[7], 32);
    mk2(&tcr, d_in[8], 64);
    mk2(&tci, d_in[9], 64);
    Params p;
    p.x0 = (const __nv_bfloat16*)d_in[0];
    p.w_r = (const __nv_bfloat16*)d_in[1];
    p.w_i = (const __nv_bfloat16*)d_in[2];
    p.lam_re = (const __nv_bfloat16*)d_in[4];
    p.lam_im = (const __nv_bfloat16*)d_in[5];
    p.log_dt = (const __nv_bfloat16*)d_in[10];
    p.dskip = (const __nv_bfloat16*)d_in[11];
    p.out = (float*)d_out;
    p.stop = stop;
    cudaLaunchConfig_t cfg = {};
    cfg.gridDim = dim3(NCTA); cfg.blockDim = dim3(NTHREADS); cfg.dynamicSmemBytes = SM_TOTAL; cfg.stream = cudaStreamPerThread;
    cudaLaunchAttribute at[1];
    at[0].id = cudaLaunchAttributeClusterDimension;
    at[0].val.clusterDim.x = 2; at[0].val.clusterDim.y = 1; at[0].val.clusterDim.z = 1;
    cfg.attrs = at; cfg.numAttrs = 1;
    cudaLaunchKernelEx(&cfg, fused_kernel, tx, tbr, tbi, tcr, tci, tcol, p);
}

}

extern "C" void kernel_launch(void* const* d_in, const int* in_sizes, int n_in, void* d_out, int out_size) {
    (void)in_sizes; (void)n_in; (void)out_size;
    launch_impl(d_in, d_out, 100);
}
```

```cpp
#include <cuda_runtime.h>
#include <cuda_bf16.h>
#include <cuda.h>
#include <stdint.h>

namespace {

constexpr int NCTA = 128;
constexpr int NTHREADS = 512;
constexpr int SM_A = 0;
constexpr int SM_X = 131072;
constexpr int SM_H = 196608;
constexpr int SM_HH = SM_X + 32768;
constexpr int SM_M = 229376;
constexpr int SM_TOTAL = 232448;
constexpr int SM_BAR = SM_M;
constexpr int SM_TGT = SM_M + 360;
constexpr int SM_LAM = SM_M + 384;
constexpr int SM_TAB = SM_M + 896;
constexpr int SM_RSTD = SM_M + 1920;
constexpr int SM_MEAN = SM_TAB;
constexpr int SM_T64 = SM_M + 2944;
constexpr int SM_B1ST = SM_H + 24576;
constexpr int SM_RAW = SM_X + 40960;
constexpr int SM_SSQ = SM_X + 57344;
constexpr int B_FULL0 = 0;
constexpr int B_EMPTY0 = 8;
constexpr int B_FULLC = 12;
constexpr int B_AFULL = 13;
constexpr int B_AEMPTY = 21;
constexpr int B_XFULL = 29;
constexpr int B_XEMPTY = 33;
constexpr int B_AFREE = 37;
constexpr int B_COL = 38;
constexpr int B_SSQ = 39;
constexpr int B_HPEER = 40;
constexpr int B_RFREE = 41;
constexpr int B_HDONE = 42;
constexpr int B_WRDY = 43;
constexpr int B_HPEER1 = 44;
constexpr int NBARS = 45;

__device__ __align__(1024) uint8_t g_X[2 * 16 * 8 * 16384];
__device__ __align__(1024) uint8_t g_A1[8 * 8 * 16384];
__device__ __align__(1024) uint8_t g_A2[8 * 8 * 16384];
__device__ __align__(1024) uint8_t g_E[2 * 8 * 8 * 8192];
__device__ __align__(16) float g_ssq[2 * 2048];
__device__ __align__(16) float g_ssqc[2 * 16 * 2048];
__device__ __align__(16) float g_Dh[512];
__device__ __align__(16) uint4 g_Wfrag[128 * 4 * 256];
__device__ __align__(16) float4 g_Ebuf[2 * 16 * 512];
__device__ __align__(16) uint4 g_P[16 * 8 * 4 * 1024];
__device__ unsigned g_bar[8];
__device__ unsigned g_err;
#define TX(i)
#define TQ(i)
#define TS(i)
#define TC(i)

constexpr unsigned SPIN_LIMIT = 1u << 22;

__device__ __forceinline__ uint32_t s2u(const void* p) { return (uint32_t)__cvta_generic_to_shared(p); }
__device__ __forceinline__ void mbar_init(uint32_t a, uint32_t c) {
    asm volatile("mbarrier.init.shared::cta.b64 [%0], %1;" ::"r"(a), "r"(c) : "memory");
}
__device__ __forceinline__ void mbar_expect(uint32_t a, uint32_t bytes) {
    asm volatile("mbarrier.arrive.expect_tx.shared::cta.b64 _, [%0], %1;" ::"r"(a), "r"(bytes) : "memory");
}
__device__ __forceinline__ void mbar_arrive(uint32_t a, uint32_t cnt) {
    asm volatile("mbarrier.arrive.shared::cta.b64 _, [%0], %1;" ::"r"(a), "r"(cnt) : "memory");
}
__device__ __forceinline__ bool mbar_try(uint32_t a, uint32_t parity) {
    uint32_t ok;
    asm volatile("{\n.reg .pred p;\nmbarrier.try_wait.parity.shared::cta.b64 p, [%1], %2;\nselp.u32 %0, 1, 0, p;\n}"
                 : "=r"(ok) : "r"(a), "r"(parity) : "memory");
    return ok != 0;
}
__device__ __forceinline__ void mbar_wait(uint32_t a, uint32_t parity) {
    asm volatile("{\n.reg .pred p, q;\n.reg .u32 n;\nmov.u32 n, 0;\n"
                 "W_%=:\nmbarrier.try_wait.parity.shared::cta.b64 p, [%0], %1;\n@p bra D_%=;\n"
                 "add.u32 n, n, 1;\nsetp.lt.u32 q, n, 4194304;\n@q bra W_%=;\nD_%=:\n}" ::"r"(a), "r"(parity) : "memory");
}
__device__ __forceinline__ void bulk_g2s(uint32_t dst, const void* src, uint32_t bytes, uint32_t bar) {
    asm volatile("cp.async.bulk.shared::cluster.global.mbarrier::complete_tx::bytes [%0], [%1], %2, [%3];" ::"r"(dst),
                 "l"(src), "r"(bytes), "r"(bar) : "memory");
}
__device__ __forceinline__ void tma_2d(uint32_t dst, const CUtensorMap* m, int c0, int c1, uint32_t bar) {
    asm volatile("cp.async.bulk.tensor.2d.shared::cluster.global.mbarrier::complete_tx::bytes [%0], [%1, {%3,%4}], [%2];" ::"r"(dst),
                 "l"(m), "r"(bar), "r"(c0), "r"(c1) : "memory");
}
__device__ __forceinline__ void tma_5d(uint32_t dst, const CUtensorMap* m, int c0, int c1, int c2, int c3, int c4, uint32_t bar) {
    asm volatile("cp.async.bulk.tensor.5d.shared::cluster.global.mbarrier::complete_tx::bytes [%0], [%1, {%3,%4,%5,%6,%7}], [%2];" ::"r"(dst),
                 "l"(m), "r"(bar), "r"(c0), "r"(c1), "r"(c2), "r"(c3), "r"(c4) : "memory");
}
__device__ __forceinline__ void tma_2d_mc(uint32_t dst, const CUtensorMap* m, int c0, int c1, uint32_t bar) {
    asm volatile("cp.async.bulk.tensor.2d.shared::cluster.global.mbarrier::complete_tx::bytes.multicast::cluster [%0], [%1, {%3,%4}], [%2], %5;" ::"r"(dst),
                 "l"(m), "r"(bar), "r"(c0), "r"(c1), "h"((unsigned short)3) : "memory");
}
__device__ __forceinline__ void tma_5d_mc(uint32_t dst, const CUtensorMap* m, int c0, int c1, int c2, int c3, int c4, uint32_t bar) {
    asm volatile("cp.async.bulk.tensor.5d.shared::cluster.global.mbarrier::complete_tx::bytes.multicast::cluster [%0], [%1, {%3,%4,%5,%6,%7}], [%2], %8;" ::"r"(dst),
                 "l"(m), "r"(bar), "r"(c0), "r"(c1), "r"(c2), "r"(c3), "r"(c4), "h"((unsigned short)3) : "memory");
}
__device__ __forceinline__ void bulk_g2s_mc(uint32_t dst, const void* src, uint32_t bytes, uint32_t bar) {
    asm volatile("cp.async.bulk.shared::cluster.global.mbarrier::complete_tx::bytes.multicast::cluster [%0], [%1], %2, [%3], %4;" ::"r"(dst),
                 "l"(src), "r"(bytes), "r"(bar), "h"((unsigned short)3) : "memory");
}
__device__ __forceinline__ void tma_store_5d(const CUtensorMap* m, int c0, int c1, int c2, int c3, int c4, uint32_t src) {
    asm volatile("cp.async.bulk.tensor.5d.global.shared::cta.bulk_group [%0, {%2,%3,%4,%5,%6}], [%1];" ::"l"(m), "r"(src),
                 "r"(c0), "r"(c1), "r"(c2), "r"(c3), "r"(c4) : "memory");
}
__device__ __forceinline__ uint32_t lds32(uint32_t a) { uint32_t v; asm volatile("ld.shared.u32 %0, [%1];" : "=r"(v) : "r"(a) : "memory"); return v; }
__device__ __forceinline__ uint4 ld_relaxed_u4(const uint4* p) {
    uint4 v;
    asm volatile("ld.relaxed.gpu.global.v4.u32 {%0,%1,%2,%3}, [%4];" : "=r"(v.x), "=r"(v.y), "=r"(v.z), "=r"(v.w) : "l"(p) : "memory");
    return v;
}
__device__ __forceinline__ void fence_async() { asm volatile("fence.proxy.async.global;" ::: "memory"); }
__device__ __forceinline__ void red_relaxed(unsigned* p, unsigned v) {
    asm volatile("red.relaxed.gpu.global.add.u32 [%0], %1;" ::"l"(p), "r"(v) : "memory");
}
__device__ __forceinline__ uint32_t mapa(uint32_t a, uint32_t rank) {
    uint32_t d;
    asm("mapa.shared::cluster.u32 %0, %1, %2;" : "=r"(d) : "r"(a), "r"(rank));
    return d;
}
__device__ __forceinline__ void mbar_arrive_remote(uint32_t ra) {
    asm volatile("mbarrier.arrive.relaxed.cluster.shared::cluster.b64 _, [%0];" ::"r"(ra) : "memory");
}
__device__ __forceinline__ void mbar_wait_cluster(uint32_t a, uint32_t parity) {
    asm volatile("{\n.reg .pred p, q;\n.reg .u32 n;\nmov.u32 n, 0;\n"
                 "W_%=:\nmbarrier.try_wait.parity.acquire.cluster.shared::cta.b64 p, [%0], %1;\n@p bra D_%=;\n"
                 "add.u32 n, n, 1;\nsetp.lt.u32 q, n, 4194304;\n@q bra W_%=;\nD_%=:\n}" ::"r"(a), "r"(parity) : "memory");
}
__device__ __forceinline__ void bulk_s2peer(uint32_t rdst, uint32_t src, uint32_t bytes, uint32_t rbar) {
    asm volatile("cp.async.bulk.shared::cluster.shared::cta.mbarrier::complete_tx::bytes [%0], [%1], %2, [%3];" ::"r"(rdst),
                 "r"(src), "r"(bytes), "r"(rbar) : "memory");
}
__device__ __forceinline__ void fence_async_smem() { asm volatile("fence.proxy.async.shared::cta;" ::: "memory"); }
__device__ __forceinline__ void wg_fence() { asm volatile("wgmma.fence.sync.aligned;" ::: "memory"); }
__device__ __forceinline__ void wg_commit() { asm volatile("wgmma.commit_group.sync.aligned;" ::: "memory"); }
template <int N> __device__ __forceinline__ void wg_wait() { asm volatile("wgmma.wait_group.sync.aligned %0;" ::"n"(N) : "memory"); }
__device__ __forceinline__ void bar_sync(int id, int n) { asm volatile("bar.sync %0, %1;" ::"r"(id), "r"(n) : "memory"); }
__device__ __forceinline__ void bar_arrive(int id, int n) { asm volatile("bar.arrive %0, %1;" ::"r"(id), "r"(n) : "memory"); }
__device__ __forceinline__ unsigned ld_acquire(const unsigned* p) {
    unsigned v;
    asm volatile("ld.acquire.gpu.global.u32 %0, [%1];" : "=r"(v) : "l"(p) : "memory");
    return v;
}
__device__ __forceinline__ void red_release(unsigned* p, unsigned v) {
    asm volatile("red.release.gpu.global.add.u32 [%0], %1;" ::"l"(p), "r"(v) : "memory");
}
__device__ __forceinline__ void wait_count(const unsigned* p, unsigned target) {
    unsigned n = 0;
#pragma unroll 1
    while ((int)(ld_acquire(p) - target) < 0 && ++n < SPIN_LIMIT) {}
}
__device__ __forceinline__ float4 ld_relaxed_f4(const float4* p) {
    float4 v;
    asm volatile("ld.relaxed.gpu.global.v4.f32 {%0,%1,%2,%3}, [%4];" : "=f"(v.x), "=f"(v.y), "=f"(v.z), "=f"(v.w) : "l"(p) : "memory");
    return v;
}
__device__ __forceinline__ void st_relaxed_f4(float4* p, float4 v) {
    asm volatile("st.relaxed.gpu.global.v4.f32 [%0], {%1,%2,%3,%4};" ::"l"(p), "f"(v.x), "f"(v.y), "f"(v.z), "f"(v.w) : "memory");
}
__device__ __forceinline__ uint32_t pack_bf16(float lo, float hi) {
    uint32_t r;
    asm("cvt.rn.bf16x2.f32 %0, %1, %2;" : "=r"(r) : "f"(hi), "f"(lo));
    return r;
}
__device__ __forceinline__ uint32_t hmul2(uint32_t a, uint32_t b) {
    uint32_t r;
    asm("mul.rn.bf16x2 %0, %1, %2;" : "=r"(r) : "r"(a), "r"(b));
    return r;
}
__device__ __forceinline__ uint32_t hfma2(uint32_t a, uint32_t b, uint32_t c) {
    uint32_t r;
    asm("fma.rn.bf16x2 %0, %1, %2, %3;" : "=r"(r) : "r"(a), "r"(b), "r"(c));
    return r;
}
__device__ __forceinline__ float bf_lo(uint32_t v) { return __uint_as_float(v << 16); }
__device__ __forceinline__ float bf_hi(uint32_t v) { return __uint_as_float(v & 0xffff0000u); }
__device__ __forceinline__ void sts32(uint32_t a, uint32_t v) { asm volatile("st.shared.u32 [%0], %1;" ::"r"(a), "r"(v) : "memory"); }
__device__ __forceinline__ void sts128(uint32_t a, uint4 v) {
    asm volatile("st.shared.v4.u32 [%0], {%1,%2,%3,%4};" ::"r"(a), "r"(v.x), "r"(v.y), "r"(v.z), "r"(v.w) : "memory");
}

__device__ __forceinline__ uint64_t desc_ni(uint32_t addr, uint32_t lbo, uint32_t sbo) {
    return (uint64_t)((addr & 0x3FFFF) >> 4) | ((uint64_t)(lbo >> 4) << 16) | ((uint64_t)(sbo >> 4) << 32);
}
__device__ __forceinline__ uint64_t desc_a(uint32_t addr) { return desc_ni(addr, 128, 1024); }
template <int N> __device__ __forceinline__ uint64_t desc_b(uint32_t addr) { return desc_ni(addr, 16 * N, 128); }
__device__ __forceinline__ uint64_t desc_k(uint32_t addr) {
    return (uint64_t)((addr & 0x3FFFF) >> 4) | (1ull << 16) | (64ull << 32) | (1ull << 62);
}
__device__ __forceinline__ uint64_t desc_mn(uint32_t addr, uint32_t lbo) {
    return (uint64_t)((addr & 0x3FFFF) >> 4) | ((uint64_t)(lbo >> 4) << 16) | (64ull << 32) | (1ull << 62);
}

#define ACC8(d, o) "+f"(d[o + 0]), "+f"(d[o + 1]), "+f"(d[o + 2]), "+f"(d[o + 3]), "+f"(d[o + 4]), "+f"(d[o + 5]), "+f"(d[o + 6]), "+f"(d[o + 7])
template <int TB, int SA = 1>
__device__ __forceinline__ void wgmma_n128(float (&d)[64], uint64_t da, uint64_t db, int sd) {
    asm volatile(
        "{\n.reg .pred p;\nsetp.ne.b32 p, %66, 0;\n"
        "wgmma.mma_async.sync.aligned.m64n128k16.f32.bf16.bf16 "
        "{%0,%1,%2,%3,%4,%5,%6,%7,%8,%9,%10,%11,%12,%13,%14,%15,%16,%17,%18,%19,%20,%21,%22,%23,%24,%25,%26,%27,%28,%29,%30,%31,"
        "%32,%33,%34,%35,%36,%37,%38,%39,%40,%41,%42,%43,%44,%45,%46,%47,%48,%49,%50,%51,%52,%53,%54,%55,%56,%57,%58,%59,%60,%61,%62,%63},"
        " %64, %65, p, %68, 1, 0, %67;\n}"
        : ACC8(d, 0), ACC8(d, 8), ACC8(d, 16), ACC8(d, 24), ACC8(d, 32), ACC8(d, 40), ACC8(d, 48), ACC8(d, 56)
        : "l"(da), "l"(db), "r"(sd), "n"(TB), "n"(SA));
}
template <int N> __device__ __forceinline__ void acc_def(float (&d)[N]) {
#pragma unroll
    for (int i = 0; i < N; i++) d[i] = 0.f;
}
template <int TB>
__device__ __forceinline__ void wgmma_n64(float (&d)[32], uint64_t da, uint64_t db, int sd) {
    asm volatile(
        "{\n.reg .pred p;\nsetp.ne.b32 p, %34, 0;\n"
        "wgmma.mma_async.sync.aligned.m64n64k16.f32.bf16.bf16 "
        "{%0,%1,%2,%3,%4,%5,%6,%7,%8,%9,%10,%11,%12,%13,%14,%15,%16,%17,%18,%19,%20,%21,%22,%23,%24,%25,%26,%27,%28,%29,%30,%31},"
        " %32, %33, p, 1, 1, 0, %35;\n}"
        : ACC8(d, 0), ACC8(d, 8), ACC8(d, 16), ACC8(d, 24)
        : "l"(da), "l"(db), "r"(sd), "n"(TB));
}
template <int SA>
__device__ __forceinline__ void wgmma_n64s(float (&d)[32], uint64_t da, uint64_t db, int sd) {
    asm volatile(
        "{\n.reg .pred p;\nsetp.ne.b32 p, %34, 0;\n"
        "wgmma.mma_async.sync.aligned.m64n64k16.f32.bf16.bf16 "
        "{%0,%1,%2,%3,%4,%5,%6,%7,%8,%9,%10,%11,%12,%13,%14,%15,%16,%17,%18,%19,%20,%21,%22,%23,%24,%25,%26,%27,%28,%29,%30,%31},"
        " %32, %33, p, %35, 1, 0, 1;\n}"
        : ACC8(d, 0), ACC8(d, 8), ACC8(d, 16), ACC8(d, 24)
        : "l"(da), "l"(db), "r"(sd), "n"(SA));
}
__device__ __forceinline__ void wgmma_n64_rs(float (&d)[32], uint32_t a0, uint32_t a1, uint32_t a2, uint32_t a3, uint64_t db, int sd) {
    asm volatile(
        "{\n.reg .pred p;\nsetp.ne.b32 p, %37, 0;\n"
        "wgmma.mma_async.sync.aligned.m64n64k16.f32.bf16.bf16 "
        "{%0,%1,%2,%3,%4,%5,%6,%7,%8,%9,%10,%11,%12,%13,%14,%15,%16,%17,%18,%19,%20,%21,%22,%23,%24,%25,%26,%27,%28,%29,%30,%31},"
        " {%32,%33,%34,%35}, %36, p, 1, 1, 1;\n}"
        : ACC8(d, 0), ACC8(d, 8), ACC8(d, 16), ACC8(d, 24)
        : "r"(a0), "r"(a1), "r"(a2), "r"(a3), "l"(db), "r"(sd));
}

struct Params {
    const __nv_bfloat16* x0;
    const __nv_bfloat16* w_r;
    const __nv_bfloat16* w_i;
    const __nv_bfloat16* lam_re;
    const __nv_bfloat16* lam_im;
    const __nv_bfloat16* log_dt;
    const __nv_bfloat16* dskip;
    float* out;
    int stop;
};

__device__ __forceinline__ float ldbf(const __nv_bfloat16* p) { return __bfloat162float(*p); }

__device__ __forceinline__ void dft_fp(int j, int& f, int& ph) {
    int cs = j >> 1;
    if (j == 1) { f = 256; ph = 0; }
    else { f = cs; ph = (j & 1) ? 128 : 0; }
}

__device__ __forceinline__ void gen_col_consts(uint32_t sb, int tid) {
#pragma unroll 1
    for (int task = tid; task < 640; task += 256) {
        int f, c8;
        uint32_t a_cc, d_pi, d_po;
        if (task < 512) {
            f = task & 63; c8 = task >> 6;
            a_cc = sb + SM_X + (f >> 5) * 16384 + ((f >> 3) & 3) * 2048 + c8 * 128 + (f & 7) * 16;
            d_pi = 8192; d_po = 1024;
        } else {
            int n2 = task & 31;
            f = 2 * n2; c8 = (task >> 5) & 3;
            a_cc = sb + SM_X + 32768 + (n2 >> 3) * 1024 + c8 * 128 + (n2 & 7) * 16;
            d_pi = 4096; d_po = 512;
        }
        float cd, sd, cs, sn;
        __sincosf((float)(f >= 32 ? f - 64 : f) * (6.283185307179586f / 64.f), &sd, &cd);
        int a = (8 * c8 * f) & 63;
        __sincosf((float)(a >= 32 ? a - 64 : a) * (6.283185307179586f / 64.f), &sn, &cs);
        float cv[8], sv[8];
#pragma unroll
        for (int e = 0; e < 8; e++) {
            cv[e] = cs; sv[e] = sn;
            float t = cs * cd - sn * sd;
            sn = sn * cd + cs * sd;
            cs = t;
        }
        uint4 oc = make_uint4(pack_bf16(cv[0], cv[1]), pack_bf16(cv[2], cv[3]), pack_bf16(cv[4], cv[5]), pack_bf16(cv[6], cv[7]));
        uint4 os = make_uint4(pack_bf16(sv[0], sv[1]), pack_bf16(sv[2], sv[3]), pack_bf16(sv[4], sv[5]), pack_bf16(sv[6], sv[7]));
        sts128(a_cc, oc);
        sts128(a_cc + d_pi, os);
        sts128(a_cc + d_po, make_uint4(os.x ^ 0x80008000u, os.y ^ 0x80008000u, os.z ^ 0x80008000u, os.w ^ 0x80008000u));
        sts128(a_cc + d_pi + d_po, oc);
    }
}

__global__ void __launch_bounds__(NTHREADS, 1)
fused_kernel(const __grid_constant__ CUtensorMap tm_x, const __grid_constant__ CUtensorMap tm_bre,
             const __grid_constant__ CUtensorMap tm_bim, const __grid_constant__ CUtensorMap tm_cre,
             const __grid_constant__ CUtensorMap tm_cim, const __grid_constant__ CUtensorMap tm_col, const Params p) {
    extern __shared__ __align__(1024) uint8_t sm[];
    const uint32_t sb = s2u(sm);
    const int tid = threadIdx.x, b = blockIdx.x;
    const int c = b >> 3, r = b & 7;
    const int par = r & 1, pi_ = r >> 1, own = 4 * par + pi_;
    const int wg = __shfl_sync(~0u, tid >> 7, 0), w = __shfl_sync(~0u, (tid >> 5) & 3, 0), lane = tid & 31, g = lane >> 2, q = lane & 3;
    auto BAR = [&](int i) { return sb + SM_BAR + 8 * i; };
    unsigned* s_tgt = (unsigned*)(sm + SM_TGT);

    if (tid < NBARS) {
        int cnt = 1;
        if ((tid >= B_EMPTY0 && tid < B_EMPTY0 + 4) || (tid >= B_XEMPTY && tid < B_XEMPTY + 4)) cnt = 24;
        if (tid == B_RFREE) cnt = 12;
        if (tid == B_HDONE) cnt = 2;
        if (tid >= B_AEMPTY && tid < B_AEMPTY + 8) cnt = 8;
        if (tid == B_AFREE) cnt = 4;
        mbar_init(BAR(tid), cnt);
        asm volatile("fence.mbarrier_init.release.cluster;" ::: "memory");
    }
    asm volatile("barrier.cluster.arrive.release.aligned;" ::: "memory");
    if (tid >= 64 && tid < 70) {
        s_tgt[tid - 64] = ((ld_acquire(&g_bar[tid - 64]) >> 7) + 1u) << 7;
    } else if (tid >= 96 && tid < 112) {
        g_ssq[2048 + 16 * b + tid - 96] = 0.f;
    } else if (tid >= 128 && tid < 384) {
        int i = tid - 128;
        if (i < 128) ((float4*)g_ssqc)[b * 128 + i] = make_float4(0.f, 0.f, 0.f, 0.f);
    } else if (tid >= 416) {
        int i = tid - 416;
        int ps = i < 64 ? 64 * r + i : 32 * c + i - 64;
        float lr = ldbf(p.lam_re + ps), li = ldbf(p.lam_im + ps);
        float dt = __bfloat162float(__float2bfloat16(expf(ldbf(p.log_dt + ps))));
        float mag = expf(lr * dt), t = li * dt * 0.15915494309189535f, sn, cs;
        t -= rintf(t);
        sincospif(2.f * t, &sn, &cs);
        float er = mag * cs, ei = mag * sn;
        if (i < 64) {
            *(float2*)(sm + SM_LAM + i * 8) = make_float2(er, ei);
        } else {
            er -= 1.f;
            float inv = 1.f / (lr * lr + li * li);
            *(float2*)(sm + SM_RSTD + (i - 64) * 8) = make_float2((er * lr + ei * li) * inv, (ei * lr - er * li) * inv);
        }
    } else if (tid >= 384 && tid < 390) {
        const CUtensorMap* tm = tid == 384 ? &tm_x : tid == 385 ? &tm_bre : tid == 386 ? &tm_bim : tid == 387 ? &tm_cre : tid == 388 ? &tm_cim : &tm_col;
        asm volatile("prefetch.tensormap [%0];" ::"l"(tm) : "memory");
    }
    __syncwarp();
    asm volatile("barrier.cluster.wait.acquire.aligned;" ::: "memory");

    if (wg == 3) {
        asm volatile("setmaxnreg.dec.sync.aligned.u32 56;");
        if (w > 0) {
            bar_arrive(10, 480);
            if (w == 2) {
                const int kq = 2 * b + (lane >> 4), row = (kq >> 2) + 128 * (kq & 3) + 512 * ((lane >> 1) & 3) + 64 * (lane & 1);
                const char* src = (const char*)(((lane >> 3) & 1) ? p.w_i : p.w_r) + (size_t)row * 514;
                size_t a0 = (size_t)src & ~(size_t)15;
                int bytes = row == 2047 ? 512 : 544;
                asm volatile("cp.async.bulk.prefetch.L2.global [%0], %1;" ::"l"(a0), "r"(bytes) : "memory");
            }
#pragma unroll 1
            for (int i = tid - 448; i < 1536 + 128 && w > 1; i += 64) {
                if (i < 1536) g_P[(uint32_t)(b * 4 + i / 384) * 1024 + 640 + i % 384] = make_uint4(0, 0, 0, 0);
                else g_Ebuf[b * 128 + i - 1536] = make_float4(0.f, 0.f, 0.f, 0.f);
            }
#pragma unroll 1
            for (int task = tid - 448; task < 256 && w > 1; task += 64) {
                const int cb = task & 127, kq = 2 * b + (task >> 7), k1 = kq >> 2, qq = kq & 3;
                const unsigned short* wr_ = (const unsigned short*)p.w_r + (k1 + 128 * qq) * 257;
                const unsigned short* wi_ = (const unsigned short*)p.w_i + (k1 + 128 * qq) * 257;
                const int c0 = cb == 0 ? 256 : 2 * cb, c1 = 2 * cb + 1;
                uint32_t wf[16];
#pragma unroll
                for (int i = 0; i < 4; i++) {
                    int o = 512 * i * 257;
                    wf[2 * i] = (uint32_t)__ldg(wr_ + o + c0) | ((uint32_t)__ldg(wr_ + o + 64 * 257 + c0) << 16);
                    wf[2 * i + 1] = ((uint32_t)__ldg(wi_ + o + c0) | ((uint32_t)__ldg(wi_ + o + 64 * 257 + c0) << 16)) ^ 0x80008000u;
                    wf[8 + 2 * i] = (uint32_t)__ldg(wr_ + o + c1) | ((uint32_t)__ldg(wr_ + o + 64 * 257 + c1) << 16);
                    wf[8 + 2 * i + 1] = ((uint32_t)__ldg(wi_ + o + c1) | ((uint32_t)__ldg(wi_ + o + 64 * 257 + c1) << 16)) ^ 0x80008000u;
                }
                uint4* wd = g_Wfrag + (uint32_t)(cb * 1024 + kq);
#pragma unroll
                for (int i = 0; i < 4; i++) wd[i * 256] = make_uint4(wf[4 * i], wf[4 * i + 1], wf[4 * i + 2], wf[4 * i + 3]);
            }
            __syncwarp();
            if (w > 1) bar_arrive(11, 96);
            if (w == 3) {
#pragma unroll 1
                for (int it = 0; it < 8; it++) {
                    const int m = 4 * c + (it >> 1), d = 64 * r + m, ch = lane + 32 * (it & 1);
                    float v[8];
#pragma unroll
                    for (int e = 0; e < 8; e++) {
                        int j = 8 * ch + e, f, ph;
                        dft_fp(j, f, ph);
                        int a = (d * f + ph) & 511;
                        a = a >= 256 ? a - 512 : a;
                        float wj = j == 0 ? 0.f : (j == 1 ? 1.f / 512.f : 2.f / 512.f);
                        v[e] = wj * __cosf((float)a * (6.283185307179586f / 512.f));
                    }
                    uint32_t off = (uint32_t)(64 + r * 8 + (ch >> 3)) * 8192 + (m >> 3) * 1024 + (ch & 7) * 128 + (m & 7) * 16;
                    *(uint4*)(g_E + off) = make_uint4(pack_bf16(v[0], v[1]), pack_bf16(v[2], v[3]), pack_bf16(v[4], v[5]), pack_bf16(v[6], v[7]));
                }
                __syncwarp();
                if (lane == 0) { fence_async(); red_release(&g_bar[6], 1); }
                return;
            }
            if (w == 2) {
#pragma unroll 1
                for (int it = 0; it < 4; it++) {
                    const int hf = it & 1;
                    __syncwarp();
                    if (hf == 0) bar_sync(13, 288); else bar_sync(6, 416);
                    if (lane == 0) {
                        const uint32_t src = sb + SM_HH + par * 32768 + hf * 16384;
                        bulk_s2peer(mapa(src, par ^ 1), src, 16384, mapa(BAR(hf ? B_HPEER1 : B_HPEER), par ^ 1));
                    }
                }
                return;
            }
            {
                uint4 p0 = __ldg((const uint4*)p.dskip + 2 * lane), p1 = __ldg((const uint4*)p.dskip + 2 * lane + 1);
                uint32_t u[8] = {p0.x, p0.y, p0.z, p0.w, p1.x, p1.y, p1.z, p1.w};
#pragma unroll 1
                for (int jj = 0; jj < 4; jj++) {
                    int j = 64 * r + 4 * c + jj, f, ph;
                    dft_fp(j, f, ph);
                    float s = 0.f;
                    int idx = 16 * lane * f + ph;
#pragma unroll
                    for (int i = 0; i < 16; i++) {
                        int a = idx & 511;
                        idx += f;
                        a = a >= 256 ? a - 512 : a;
                        s += ((i & 1) ? bf_hi(u[i >> 1]) : bf_lo(u[i >> 1])) * __cosf((float)a * (6.283185307179586f / 512.f));
                    }
#pragma unroll
                    for (int o = 16; o; o >>= 1) s += __shfl_xor_sync(~0u, s, o);
                    if (lane == 0) g_Dh[j] = s;
                }
                if (lane == 0) red_release(&g_bar[5], 1);
                __syncwarp();
            }
            bar_sync(2, 416);
            if (lane == 0) {
                TX(5);
                asm volatile("cp.async.bulk.global.shared::cta.bulk_group [%0], [%1], 8192;" ::"l"(g_A1 + (uint32_t)(((c >> 1) * 8 + r) * 16384 + (c & 1) * 8192)),
                             "r"(sb + SM_B1ST) : "memory");
                asm volatile("cp.async.bulk.commit_group;" ::: "memory");
                fence_async();
                red_release(&g_bar[0], 1);
                TX(6);
                asm volatile("cp.async.bulk.wait_group 0;" ::: "memory");
                fence_async();
            }
            __syncwarp();
            bar_sync(11, 96);
            if (lane == 0) red_release(&g_bar[4], 1);
#pragma unroll 1
            for (int layer = 0; layer < 2; layer++) {
                __syncwarp();
                bar_sync(5, 416);
                if (lane == 0) {
                    TX(0 + 8 * layer);
                    tma_store_5d(&tm_col, 32 * (b & 1), 0, b >> 1, 0, layer, sb + SM_RAW);
                    asm volatile("cp.reduce.async.bulk.global.shared::cta.bulk_group.add.f32 [%0], [%1], 8192;" ::"l"(g_ssqc + (layer * 16 + (b & 15)) * 2048),
                                 "r"(sb + SM_SSQ) : "memory");
                    asm volatile("cp.async.bulk.commit_group;" ::: "memory");
                    asm volatile("cp.async.bulk.wait_group 0;" ::: "memory");
                    TX(1 + 8 * layer);
                    fence_async();
                    red_release(&g_bar[1 + 2 * layer], 1);
                    TX(2 + 8 * layer);
                }
            }
        } else if (tid == 384) {
#pragma unroll 1
            for (int kb = 0; kb < 8; kb++) {
                int s = kb < 6 ? kb : kb - 4;
                uint32_t dst = s < 2 ? sb + SM_A + 65536 + s * 24576 : sb + SM_X + (s - 2) * 24576;
                if (kb >= 6) mbar_wait_cluster(BAR(B_EMPTY0 + s), 0);
                uint32_t fb = BAR(B_FULL0 + kb);
                mbar_expect(fb, 24576);
                tma_5d_mc(dst + par * 8192, &tm_x, kb * 64, 0, 0, 8 * par, c, fb);
                tma_2d_mc(dst + 16384 + par * 4096, par ? &tm_bim : &tm_bre, kb * 64, 32 * c, fb);
                if (kb == 5) {
#pragma unroll 1
                    for (int k2 = par; k2 < 8; k2 += 2) {
                        asm volatile("cp.async.bulk.prefetch.tensor.2d.L2.global [%0, {%1,%2}];" ::"l"((c & 1) ? &tm_cim : &tm_cre), "r"(64 * (c >> 1)), "r"(k2 * 64) : "memory");
                        if (k2 < 4) {
                            asm volatile("cp.async.bulk.prefetch.tensor.5d.L2.global [%0, {%1,%2,%3,%4,%5}];" ::"l"(&tm_x), "r"((6 + (k2 >> 1)) * 64), "r"(0), "r"(0), "r"(8 * par), "r"(c) : "memory");
                            asm volatile("cp.async.bulk.prefetch.tensor.2d.L2.global [%0, {%1,%2}];" ::"l"(par ? &tm_bim : &tm_bre), "r"((6 + (k2 >> 1)) * 64), "r"(32 * c) : "memory");
                        }
                    }
                }
                if (kb == 7) {
                    mbar_wait_cluster(BAR(B_EMPTY0 + 0), 0);
                    mbar_wait_cluster(BAR(B_EMPTY0 + 1), 0);
                    mbar_expect(BAR(B_FULLC), 65536);
#pragma unroll 1
                    for (int k2 = par; k2 < 8; k2 += 2)
                        tma_2d_mc(sb + SM_A + 65536 + k2 * 8192, (c & 1) ? &tm_cim : &tm_cre, 64 * (c >> 1), k2 * 64, BAR(B_FULLC));
                }
            }
#pragma unroll 1
            for (int layer = 0; layer < 2; layer++) {
                wait_count(&g_bar[2 * layer], s_tgt[2 * layer]);
                TX(4 + 8 * layer);
                fence_async();
                mbar_expect(BAR(B_COL), 16384 + 8192);
                tma_5d(sb + SM_RAW, &tm_col, 32 * (b & 1), 0, b >> 1, 0, layer, BAR(B_COL));
                bulk_g2s(sb + SM_SSQ, g_ssq + layer * 2048, 8192, BAR(B_COL));
                if (layer == 0) {
                    wait_count(&g_bar[4], s_tgt[4]);
                    mbar_arrive(BAR(B_WRDY), 1);
                    fence_async();
                }
                if (layer == 0) mbar_wait(BAR(B_AFREE), 0);
                mbar_wait(BAR(B_COL), layer);
#pragma unroll 1
                for (int s = 0; s < 8; s++) {
                    if (layer == 1) mbar_wait(BAR(B_AEMPTY + s), 1);
                    mbar_expect(BAR(B_AFULL + s), 16384);
                    bulk_g2s(sb + SM_A + s * 16384, g_A1 + (uint32_t)(r * 8 + s) * 16384, 16384, BAR(B_AFULL + s));
                }
                if (layer == 1) wait_count(&g_bar[6], s_tgt[5]);
                wait_count(&g_bar[1 + 2 * layer], s_tgt[1 + 2 * layer]);
                TX(3 + 8 * layer);
                fence_async();
                const uint8_t* xsrc = g_X + (uint32_t)(layer * 16 + c) * 8 * 16384;
                const uint8_t* esrc = g_E + (uint32_t)(layer * 8 + own) * 8 * 8192;
                mbar_arrive(BAR(B_SSQ), 1);
                mbar_expect(BAR(B_HPEER), 16384);
                mbar_expect(BAR(B_HPEER1), 16384);
#pragma unroll 1
                for (int it = 0; it < 12; it++) {
                    if (it < 8) {
                        int st = it & 3, f = layer * 2 + (it >> 2);
                        if (f > 0) mbar_wait_cluster(BAR(B_XEMPTY + st), (f - 1) & 1);
                        mbar_expect(BAR(B_XFULL + st), 24576);
                        bulk_g2s_mc(sb + SM_X + st * 24576 + par * 8192, xsrc + (uint32_t)it * 16384 + par * 8192, 8192, BAR(B_XFULL + st));
                        bulk_g2s(sb + SM_X + st * 24576 + 16384, esrc + (uint32_t)it * 8192, 8192, BAR(B_XFULL + st));
                    }
                    if (it >= 4) {
                        int s = it - 4, tile = 4 * par + ((pi_ + 1 + (s >> 1)) & 3), sl = r ^ (s & 1);
                        mbar_wait(BAR(B_AEMPTY + s), 0);
                        uint32_t fb = BAR(B_AFULL + s), dst = sb + SM_A + s * 16384;
                        mbar_expect(fb, 16384);
                        if (layer == 1) {
                            tma_2d(dst, &tm_cre, 64 * sl, 64 * tile, fb);
                            tma_2d(dst + 8192, &tm_cim, 64 * sl, 64 * tile, fb);
                        } else {
                            bulk_g2s(dst, g_A2 + (uint32_t)(sl * 8 + tile) * 16384, 16384, fb);
                        }
                    }
                }
            }
        }
        return;
    }

    asm volatile("setmaxnreg.inc.sync.aligned.u32 152;");
    TS(0);
    if (wg == 0) TC(30);
    {
        const int f = 32 * r + lane;
        float cd, sd;
        __sincosf((float)f * (6.283185307179586f / 512.f), &sd, &cd);
        const uint32_t dst = sb + SM_A + (lane >> 2) * 1024 + (lane & 3) * 32;
#pragma unroll 1
        for (int ch = tid >> 5; ch < 64; ch += 12) {
            int a = (8 * ch * f) & 511;
            a = a >= 256 ? a - 512 : a;
            float cs, sn;
            __sincosf((float)a * (6.283185307179586f / 512.f), &sn, &cs);
            float cv[8], sv[8];
#pragma unroll
            for (int e = 0; e < 8; e++) {
                cv[e] = cs; sv[e] = -sn;
                float t = cs * cd - sn * sd;
                sn = sn * cd + cs * sd;
                cs = t;
            }
            uint4 o1 = make_uint4(pack_bf16(sv[0], sv[1]), pack_bf16(sv[2], sv[3]), pack_bf16(sv[4], sv[5]), pack_bf16(sv[6], sv[7]));
            if (f == 0) o1 = make_uint4(0xbf803f80u, 0xbf803f80u, 0xbf803f80u, 0xbf803f80u);
            uint32_t a0 = dst + (ch >> 3) * 8192 + (ch & 7) * 128;
            sts128(a0, make_uint4(pack_bf16(cv[0], cv[1]), pack_bf16(cv[2], cv[3]), pack_bf16(cv[4], cv[5]), pack_bf16(cv[6], cv[7])));
            sts128(a0 + 16, o1);
        }
    }
    fence_async_smem();
    bar_sync(10, 480);
    TS(1);
    uint4 pre[4];
    if (wg < 2) {
        const uint4* src = (const uint4*)(p.x0 + (uint32_t)(128 * c + 16 * r + 8 * wg + 2 * w) * 512) + lane;
#pragma unroll
        for (int i = 0; i < 4; i++) pre[i] = __ldg(src + 32 * i);
    } else {
        pre[0] = pre[1] = pre[2] = pre[3] = make_uint4(0, 0, 0, 0);
    }

    {
        float acc[32];
        acc_def(acc);
#pragma unroll 1
        for (int kb = 0; kb < 8; kb++) {
            int s = kb < 6 ? kb : kb - 4;
            uint32_t src = (s < 2 ? sb + SM_A + 65536 + s * 24576 : sb + SM_X + (s - 2) * 24576) + wg * 8192;
            mbar_wait(BAR(B_FULL0 + kb), 0);
            wg_fence();
#pragma unroll
            for (int ks = 0; ks < 4; ks++)
                wgmma_n64<0>(acc, desc_a(sb + SM_A + kb * 8192 + ks * 256), desc_k(src + ks * 32), 1);
            wg_commit();
            wg_wait<1>();
            if (kb > 0 && kb <= 4 && lane == 0) { mbar_arrive(BAR(B_EMPTY0 + kb - 1), 1); mbar_arrive_remote(mapa(BAR(B_EMPTY0 + kb - 1), par ^ 1)); }
            if (kb == 5 && wg < 2) {
#pragma unroll
            for (int rr = 0; rr < 2; rr++) {
                int t = 16 * r + 8 * wg + 2 * w + rr;
                uint32_t u[8] = {pre[2 * rr].x, pre[2 * rr].y, pre[2 * rr].z, pre[2 * rr].w, pre[2 * rr + 1].x, pre[2 * rr + 1].y, pre[2 * rr + 1].z, pre[2 * rr + 1].w};
                float s = 0.f;
#pragma unroll
                for (int i = 0; i < 8; i++) s += bf_lo(u[i]) + bf_hi(u[i]);
#pragma unroll
                for (int o = 16; o; o >>= 1) s += __shfl_xor_sync(~0u, s, o);
                float m = s * (1.f / 512.f), ss = 0.f;
#pragma unroll
                for (int i = 0; i < 8; i++) { float d0 = bf_lo(u[i]) - m, d1 = bf_hi(u[i]) - m; ss += d0 * d0 + d1 * d1; }
#pragma unroll
                for (int o = 16; o; o >>= 1) ss += __shfl_xor_sync(~0u, ss, o);
                if (lane == 0) g_ssq[128 * c + 8 * ((t >> 1) & 15) + 2 * (t >> 5) + (t & 1)] = ss;
            }
            }
        }
        wg_wait<0>();
        TS(2);
        if (wg < 2) {
            uint8_t* dst = g_X + (uint32_t)((c * 8 + r) * 16384 + w * 4096 + wg * 1024 + g * 16 + 4 * q);
#pragma unroll
            for (int i = 0; i < 8; i++) {
                *(uint32_t*)(dst + i * 128) = pack_bf16(acc[4 * i], acc[4 * i + 1]);
                *(uint32_t*)(dst + 2048 + i * 128) = pack_bf16(acc[4 * i + 2], acc[4 * i + 3]);
            }
        } else {
            uint8_t* dst = sm + SM_B1ST + w * 256 + q * 32 + g * 2;
            const float wj0 = (r == 0 && w == 0 && g < 2) ? (g == 0 ? 0.f : 1.f / 512.f) : 2.f / 512.f;
#pragma unroll
            for (int i = 0; i < 4; i++) {
#pragma unroll
                for (int e = 0; e < 2; e++) {
                    float2 cf = *(const float2*)(sm + SM_RSTD + (8 * i + 2 * q + e) * 8);
#pragma unroll
                    for (int h = 0; h < 2; h++) {
                        float wj = h == 0 ? wj0 : 2.f / 512.f;
                        float pr = acc[4 * i + 2 * h + e] * wj, pi = acc[16 + 4 * i + 2 * h + e] * wj;
                        uint8_t* d2 = dst + i * 2048 + h * 128 + e * 16;
                        *(__nv_bfloat16*)(d2) = __float2bfloat16(cf.x * pr - cf.y * pi);
                        *(__nv_bfloat16*)(d2 + 1024) = __float2bfloat16(cf.x * pi + cf.y * pr);
                    }
                }
            }
            fence_async_smem();
        }
        bar_sync(2, 416);
        TS(3);
    }

    if (wg == 2) {
        {
            const int m = 4 * c + w, jp = 64 * r + m;
            int fp, php;
            dft_fp(jp, fp, php);
            const __nv_bfloat16* dh = (const __nv_bfloat16*)(sm + SM_RSTD);
            if (tid == 256) wait_count(&g_bar[5], s_tgt[5]);
            bar_sync(3, 128);
            float4 d4 = __ldcg((const float4*)g_Dh + (tid - 256));
            *(uint2*)(sm + SM_RSTD + (tid - 256) * 8) = make_uint2(pack_bf16(d4.x, d4.y), pack_bf16(d4.z, d4.w));
            bar_sync(3, 128);
#pragma unroll 1
            for (int it = 0; it < 2; it++) {
                const int ch = lane + 32 * it;
                float v[8];
#pragma unroll
                for (int e = 0; e < 8; e++) {
                    int j = 8 * ch + e, f, ph;
                    dft_fp(j, f, ph);
                    float wj = j == 0 ? 0.f : (j == 1 ? 1.f / 512.f : 2.f / 512.f);
                    float gsum = 0.f;
#pragma unroll
                    for (int sgn = 0; sgn < 2; sgn++) {
                        int mm = (sgn ? f - fp : f + fp) & 511, pp = (sgn ? ph - php : ph + php) & 511;
                        if (mm > 256) { mm = 512 - mm; pp = (512 - pp) & 511; }
                        int odd = (pp >> 7) & 1;
                        float t = __bfloat162float(dh[mm == 256 ? 1 : 2 * mm + odd]);
                        if (odd && (mm & 255) == 0) t = 0.f;
                        gsum += (pp & 256) ? -t : t;
                    }
                    v[e] = 0.5f * wj * gsum;
                }
                uint32_t off = (uint32_t)(r * 8 + (ch >> 3)) * 8192 + (m >> 3) * 1024 + (ch & 7) * 128 + (m & 7) * 16;
                *(uint4*)(g_E + off) = make_uint4(pack_bf16(v[0], v[1]), pack_bf16(v[2], v[3]), pack_bf16(v[4], v[5]), pack_bf16(v[6], v[7]));
            }
        }
        float acc[32];
        acc_def(acc);
        mbar_wait(BAR(B_FULLC), 0);
        wg_fence();
#pragma unroll 1
        for (int kb = 0; kb < 8; kb++) {
#pragma unroll
            for (int ks = 0; ks < 4; ks++)
                wgmma_n64<1>(acc, desc_a(sb + SM_A + kb * 8192 + ks * 256), desc_mn(sb + SM_A + 65536 + kb * 8192 + ks * 2048, 8192), 1);
            wg_commit();
        }
        wg_wait<0>();
        fence_async_smem();
        if (lane == 0) mbar_arrive(BAR(B_AFREE), 1);
        uint8_t* dst = g_A2 + (uint32_t)(((c >> 1) * 8 + r) * 16384 + (c & 1) * 8192 + w * 2048 + g * 16 + 4 * q);
#pragma unroll
        for (int i = 0; i < 8; i++) {
            *(uint32_t*)(dst + i * 128) = pack_bf16(acc[4 * i], acc[4 * i + 1]);
            *(uint32_t*)(dst + 1024 + i * 128) = pack_bf16(acc[4 * i + 2], acc[4 * i + 3]);
        }
    }

#pragma unroll 1
    for (int layer = 0; layer < 2; layer++) {
        if (wg < 2) {
            const int n1 = 32 * wg + 8 * w + g;
            const int ct = n1 >> 2;
            gen_col_consts(sb, tid);
            uint32_t tr2[4], ti2[4], tn2[4];
#pragma unroll
            for (int i = 0; i < 4; i++) {
                float cr[2], ci[2];
#pragma unroll
                for (int e = 0; e < 2; e++) {
                    int a = (n1 * (8 * i + 2 * q + e)) & 2047;
                    a = a >= 1024 ? a - 2048 : a;
                    float ang = (float)a * (-6.283185307179586f / 2048.f);
                    cr[e] = __cosf(ang); ci[e] = __sinf(ang);
                }
                tr2[i] = pack_bf16(cr[0], cr[1]); ti2[i] = pack_bf16(ci[0], ci[1]); tn2[i] = ti2[i] ^ 0x80008000u;
            }
            mbar_wait(BAR(B_COL), layer);
            TS(4 + 12 * layer);
            if (wg == 0) TC(0 + 10 * layer);
            const uint32_t rw0 = sb + SM_RAW + ct * 1024 + q * 64 + ((q >> 1) << 4) + (g & 3) * 4, rw1 = rw0 ^ 16;
            const int pos0 = 128 * ct + 8 * q + 2 * (g & 3);
            const int sw = b == 0 ? 1 : 0;
            uint32_t xr[4][4];
            const uint32_t st0 = sb + SM_H + (n1 >> 3) * 1024 + g * 16 + 4 * q;
#pragma unroll
            for (int i = 0; i < 4; i++) {
                float2 sq = *(const float2*)(sm + SM_SSQ + (pos0 + 32 * i) * 4);
                const uint32_t rs2 = pack_bf16(rsqrtf(sq.x * (1.f / 512.f) + 1e-5f), rsqrtf(sq.y * (1.f / 512.f) + 1e-5f));
#pragma unroll
                for (int jj = 0; jj < 4; jj++) {
                    const int K = jj ^ (2 * (i & 1));
                    uint32_t a = ((K & 1) ? rw1 : rw0) + i * 256 + (K & 2) * 16;
                    if (jj < 2) a ^= sw << 4;
                    uint32_t v = lds32(a);
                    xr[jj][i] = v;
                    uint32_t o = hmul2(v, rs2);
                    if (jj == 1 && sw) o = 0u;
                    sts32(st0 + (jj & 1) * 8192 + (4 * (jj >> 1) + i) * 128, o);
                }
            }
            if (wg == 0) TC(1 + 10 * layer);
            fence_async_smem();
            bar_sync(1, 256);
            float acc[32];
            const uint32_t s1a = sb + SM_X + wg * 16384, s2b = sb + SM_X + 32768;
            wg_fence();
#pragma unroll
            for (int ks = 0; ks < 8; ks++)
                wgmma_n64<1>(acc, desc_a(s1a + (ks >> 2) * 8192 + (ks & 3) * 256), desc_b<64>(sb + SM_H + ks * 2048), ks != 0);
            wg_commit();
            mbar_wait(BAR(B_WRDY), 0);
            uint32_t wf[16];
            {
                const uint4* ws = g_Wfrag + (uint32_t)(b * 1024 + n1 * 4 + q);
#pragma unroll
                for (int i = 0; i < 4; i++) {
                    uint4 v = __ldcg(ws + i * 256);
                    wf[4 * i] = v.x; wf[4 * i + 1] = v.y; wf[4 * i + 2] = v.z; wf[4 * i + 3] = v.w;
                }
            }
            wg_wait<0>();
            if (wg == 0) TC(2 + 10 * layer);
            uint32_t are[2][4], aim[2][4];
#pragma unroll
            for (int col = 0; col < 2; col++) {
#pragma unroll
                for (int i = 0; i < 4; i++) {
                    int o = 4 * (4 * col + i);
                    uint32_t zr = pack_bf16(acc[o], acc[o + 1]), zi = pack_bf16(acc[o + 2], acc[o + 3]);
                    are[col][i] = hfma2(zr, tr2[i], hmul2(zi, tn2[i]));
                    aim[col][i] = hfma2(zr, ti2[i], hmul2(zi, tr2[i]));
                }
            }
            wg_fence();
#pragma unroll
            for (int ks = 0; ks < 2; ks++)
                wgmma_n64_rs(acc, are[0][2 * ks], are[1][2 * ks], are[0][2 * ks + 1], are[1][2 * ks + 1], desc_b<64>(s2b + ks * 2048), ks != 0);
#pragma unroll
            for (int ks = 0; ks < 2; ks++)
                wgmma_n64_rs(acc, aim[0][2 * ks], aim[1][2 * ks], aim[0][2 * ks + 1], aim[1][2 * ks + 1], desc_b<64>(s2b + 4096 + ks * 2048), 1);
            wg_commit();
            wg_wait<0>();
            if (wg == 0) TC(3 + 10 * layer);
#pragma unroll
            for (int col = 0; col < 2; col++) {
#pragma unroll
                for (int i = 0; i < 4; i++) {
                    uint32_t wr = wf[col * 8 + 2 * i], wn = wf[col * 8 + 2 * i + 1];
                    uint32_t zr = pack_bf16(acc[4 * i + 2 * col], acc[4 * i + 2 * col + 1]);
                    uint32_t zi = pack_bf16(acc[16 + 4 * i + 2 * col], acc[16 + 4 * i + 2 * col + 1]);
                    are[col][i] = hfma2(zr, wr, hmul2(zi, wn));
                    aim[col][i] = hfma2(zr, wn, hmul2(zi ^ 0x80008000u, wr));
                }
            }
            wg_fence();
#pragma unroll
            for (int ks = 0; ks < 2; ks++)
                wgmma_n64_rs(acc, are[0][2 * ks], are[1][2 * ks], are[0][2 * ks + 1], are[1][2 * ks + 1], desc_b<64>(s2b + ks * 2048), ks != 0);
#pragma unroll
            for (int ks = 0; ks < 2; ks++)
                wgmma_n64_rs(acc, aim[0][2 * ks], aim[1][2 * ks], aim[0][2 * ks + 1], aim[1][2 * ks + 1], desc_b<64>(s2b + 4096 + ks * 2048), 1);
            wg_commit();
            wg_wait<0>();
            if (wg == 0) TC(4 + 10 * layer);
#pragma unroll
            for (int col = 0; col < 2; col++) {
#pragma unroll
                for (int i = 0; i < 4; i++) {
                    uint32_t zr = pack_bf16(acc[4 * i + 2 * col], acc[4 * i + 2 * col + 1]);
                    uint32_t zi = pack_bf16(acc[16 + 4 * i + 2 * col], acc[16 + 4 * i + 2 * col + 1]);
                    sts32(st0 + 16384 + (4 * col + i) * 128, hfma2(zr, tr2[i], hmul2(zi, tn2[i])));
                    sts32(st0 + 16384 + 8192 + (4 * col + i) * 128, hfma2(zr, ti2[i], hmul2(zi, tr2[i])));
                }
            }
            if (wg == 0) TC(5 + 10 * layer);
            fence_async_smem();
            bar_sync(1, 256);
            wg_fence();
#pragma unroll
            for (int ks = 0; ks < 8; ks++)
                wgmma_n64<1>(acc, desc_a(s1a + (ks >> 2) * 8192 + (ks & 3) * 256), desc_b<64>(sb + SM_H + 16384 + ks * 2048), ks != 0);
            wg_commit();
            wg_wait<0>();
            if (wg == 0) TC(6 + 10 * layer);
            const float sc = 1.f / 2048.f;
            const float sci0 = sw ? 0.f : -sc;
            const float wr0 = sw ? 0.5f : 1.f, wi0 = sw ? 0.f : 1.f;
#pragma unroll
            for (int i = 0; i < 4; i++) {
                float ss0, ss1;
#pragma unroll
                for (int col = 0; col < 2; col++) {
                    int o = 4 * (4 * col + i);
                    uint32_t vr = xr[2 * col][i], vi = xr[2 * col + 1][i];
                    float si = col == 0 ? sci0 : -sc;
                    uint32_t nr = pack_bf16(fmaf(acc[o], sc, bf_lo(vr)), fmaf(acc[o + 1], sc, bf_hi(vr)));
                    uint32_t ni = pack_bf16(fmaf(acc[o + 2], si, bf_lo(vi)), fmaf(acc[o + 3], si, bf_hi(vi)));
                    float a0 = bf_lo(nr), a1 = bf_hi(nr), b0 = bf_lo(ni), b1 = bf_hi(ni);
                    if (col == 0) {
                        ss0 = wr0 * a0 * a0 + wi0 * b0 * b0;
                        ss1 = wr0 * a1 * a1 + wi0 * b1 * b1;
                    } else {
                        ss0 += a0 * a0 + b0 * b0;
                        ss1 += a1 * a1 + b1 * b1;
                    }
                    const int K = (2 * col) ^ (2 * (i & 1));
                    uint32_t a = rw0 + i * 256 + K * 16;
                    if (col == 0) a ^= sw << 4;
                    sts32(a, nr);
                    sts32(a ^ 16, ni);
                }
                *(float2*)(sm + SM_SSQ + (pos0 + 32 * i) * 4) = make_float2(ss0 * (2.f / 512.f), ss1 * (2.f / 512.f));
            }
            fence_async_smem();
        }
        TS(5 + 12 * layer);
        if (wg == 0) TC(7 + 10 * layer);
        bar_arrive(5, 416);

        float acc[64];
        float* s_rstd = (float*)(sm + SM_RSTD);
        float* s_mean = (float*)(sm + SM_MEAN);
        const unsigned epoch = s_tgt[0] >> 7;
        const uint32_t pt3 = 1u + (2u * epoch + layer) % 3u;
        const uint32_t ptag = (pt3 & 1u) | ((pt3 & 2u) << 15);
        const uint64_t dstep = layer == 0 ? 16 : 2;
        auto c_desc = [&](int s) { return layer == 0 ? desc_a(sb + SM_A + s * 16384) : desc_k(sb + SM_A + s * 16384); };
        if (wg < 2) {
            const int prow = 32 * wg + 8 * w + g;
            const float2 l1 = *(const float2*)(sm + SM_LAM + prow * 8);
            float lr32 = l1.x, li32 = l1.y;
#pragma unroll
            for (int i = 0; i < 5; i++) { float t = lr32 * lr32 - li32 * li32; li32 = 2.f * lr32 * li32; lr32 = t; }
            float lr128 = lr32, li128 = li32;
#pragma unroll
            for (int i = 0; i < 2; i++) { float t = lr128 * lr128 - li128 * li128; li128 = 2.f * lr128 * li128; lr128 = t; }
            const float lr1 = l1.x, li1 = l1.y;
            acc_def(acc);
#pragma unroll 1
            for (int kb = 0; kb < 8; kb++) {
                mbar_wait(BAR(B_AFULL + kb), 0);
                mbar_wait(BAR(B_XFULL + (kb & 3)), (kb >> 2) & 1);
                wg_fence();
#pragma unroll
                for (int ks = 0; ks < 4; ks++)
                    wgmma_n128<1>(acc, desc_a(sb + SM_A + kb * 16384 + wg * 8192 + ks * 256),
                                  desc_b<128>(sb + SM_X + (kb & 3) * 24576 + ks * 4096), 1);
                wg_commit();
                wg_wait<1>();
                if (kb > 0 && lane == 0) {
                    mbar_arrive(BAR(B_AEMPTY + kb - 1), 1); mbar_arrive(BAR(B_XEMPTY + ((kb - 1) & 3)), 1);
                    mbar_arrive_remote(mapa(BAR(B_XEMPTY + ((kb - 1) & 3)), par ^ 1));
                }
            }
            wg_wait<0>();
            if (lane == 0) {
                mbar_arrive(BAR(B_AEMPTY + 7), 1); mbar_arrive(BAR(B_XEMPTY + 3), 1);
                mbar_arrive_remote(mapa(BAR(B_XEMPTY + 3), par ^ 1)); mbar_arrive_remote(mapa(BAR(B_RFREE), par ^ 1));
            }
            bar_arrive(14, 384);
            TS(6 + 12 * layer);
            bar_sync(4, 384);
            TS(7 + 12 * layer);
            float er = 0.f, ei = 0.f;
#pragma unroll
            for (int i = 0; i < 16; i++) {
                float2 rs = *(const float2*)(s_rstd + 128 + 8 * i + 2 * q);
                acc[4 * i] *= rs.x; acc[4 * i + 1] *= rs.y; acc[4 * i + 2] *= rs.x; acc[4 * i + 3] *= rs.y;
                float nr = lr1 * er - li1 * ei + acc[4 * i], ni = lr1 * ei + li1 * er + acc[4 * i + 2];
                er = lr1 * nr - li1 * ni + acc[4 * i + 1];
                ei = lr1 * ni + li1 * nr + acc[4 * i + 3];
            }
            float cr = 0.f, ci = 0.f, tr = 0.f, ti = 0.f;
#pragma unroll
            for (int qq = 0; qq < 4; qq++) {
                float xr_ = __shfl_sync(~0u, er, (lane & ~3) | qq), xi_ = __shfl_sync(~0u, ei, (lane & ~3) | qq);
                if (qq == q) { cr = tr; ci = ti; }
                float nr = lr32 * tr - li32 * ti + xr_, ni = lr32 * ti + li32 * tr + xi_;
                tr = nr; ti = ni;
            }
            float4* eb = g_Ebuf + (uint32_t)(layer * 16 * 512 + 64 * r + prow);
            if (q == 0 && c < 15) st_relaxed_f4(eb + c * 512, make_float4(tr, ti, __uint_as_float(epoch), 0.f));
            TS(8 + 12 * layer);
            float pr[4], pi[4];
            {
                unsigned n = 0;
                bool ok;
#pragma unroll 1
                do {
                    ok = true;
#pragma unroll
                    for (int k = 0; k < 4; k++) {
                        float4 v = make_float4(0.f, 0.f, __uint_as_float(epoch), 0.f);
                        if (4 * k + q < c) v = ld_relaxed_f4(eb + (4 * k + q) * 512);
                        pr[k] = v.x; pi[k] = v.y;
                        ok = ok && __float_as_uint(v.z) == epoch;
                    }
                } while (!ok && ++n < SPIN_LIMIT);
            }
            __syncwarp();
            TS(9 + 12 * layer);
            float hr = 0.f, hi = 0.f;
#pragma unroll
            for (int cc = 0; cc < 15; cc++) {
                float xr_ = __shfl_sync(~0u, pr[cc >> 2], (lane & ~3) | (cc & 3)), xi_ = __shfl_sync(~0u, pi[cc >> 2], (lane & ~3) | (cc & 3));
                if (cc < c) {
                    float nr = lr128 * hr - li128 * hi + xr_, ni = lr128 * hi + li128 * hr + xi_;
                    hr = nr; hi = ni;
                }
            }
#pragma unroll
            for (int qq = 0; qq < 3; qq++) {
                if (qq < q) { float nr = lr32 * hr - li32 * hi, ni = lr32 * hi + li32 * hr; hr = nr; hi = ni; }
            }
            er = cr + hr; ei = ci + hi;
            bar_sync(7, 384);
            mbar_wait_cluster(BAR(B_RFREE), layer);
            const uint32_t ha = sb + SM_HH + par * 32768 + (prow >> 3) * 1024 + g * 16 + 4 * q;
#pragma unroll
            for (int i = 0; i < 16; i++) {
                float nr = lr1 * er - li1 * ei + acc[4 * i], ni = lr1 * ei + li1 * er + acc[4 * i + 2];
                er = lr1 * nr - li1 * ni + acc[4 * i + 1];
                ei = lr1 * ni + li1 * nr + acc[4 * i + 3];
                sts32(ha + (i >> 3) * 16384 + (i & 7) * 128, pack_bf16(nr, er));
                sts32(ha + (i >> 3) * 16384 + 8192 + (i & 7) * 128, pack_bf16(ni, ei));
                if (i == 7) { fence_async_smem(); bar_arrive(13, 288); }
            }
            fence_async_smem();
            acc_def(acc);
            float acc2[32];
            acc_def(acc2);
            TS(10 + 12 * layer);
            bar_sync(6, 416);
            TS(11 + 12 * layer);
            float (&a0)[32] = *reinterpret_cast<float (*)[32]>(&acc[0]);
            float (&a1)[32] = *reinterpret_cast<float (*)[32]>(&acc[32]);
            auto tile_mma = [&](float (&d)[32], int u) {
#pragma unroll 1
                for (int k = 0; k < 2; k++) {
                    const uint32_t hb = sb + SM_HH + (par ^ k) * 32768 + wg * 16384;
                    if (k == 1) mbar_wait(BAR(wg ? B_HPEER1 : B_HPEER), layer);
                    mbar_wait(BAR(B_AFULL + 2 * u + k), 1);
                    const uint64_t da = c_desc(2 * u + k);
                    wg_fence();
#pragma unroll
                    for (int ks = 0; ks < 4; ks++) wgmma_n64s<1>(d, da + ks * dstep, desc_b<64>(hb + ks * 2048), 1);
#pragma unroll
                    for (int ks = 0; ks < 4; ks++) wgmma_n64s<-1>(d, da + 512 + ks * dstep, desc_b<64>(hb + 8192 + ks * 2048), 1);
                }
                wg_commit();
            };
            auto tile_ship = [&](float (&d)[32], int u) {
                uint4* dst = g_P + (uint32_t)(((c * 8 + 2 * ((pi_ + 1 + u) & 3) + par) * 4 + pi_) * 1024 + wg * 512 + (tid & 127));
#pragma unroll
                for (int i = 0; i < 4; i++)
                    dst[i * 128] = make_uint4((pack_bf16(d[8 * i], d[8 * i + 1]) & 0xfffefffeu) | ptag, pack_bf16(d[8 * i + 2], d[8 * i + 3]),
                                              pack_bf16(d[8 * i + 4], d[8 * i + 5]), pack_bf16(d[8 * i + 6], d[8 * i + 7]));
            };
            tile_mma(a0, 0);
            if ((tid & 127) == 0) mbar_arrive_remote(mapa(BAR(B_HDONE), par ^ 1));
            __syncwarp();
            tile_mma(a1, 1);
            wg_wait<1>();
            tile_ship(a0, 0);
            tile_mma(acc2, 2);
            bar_arrive(12, 384);
            wg_wait<1>();
            tile_ship(a1, 1);
            wg_wait<0>();
            tile_ship(acc2, 2);
            if (lane < 6) mbar_arrive(BAR(B_AEMPTY + lane), 1);
            TS(12 + 12 * layer);
        } else {
            const int t2 = tid - 256;
            const uint8_t* ximg = g_X + (uint32_t)layer * 16 * 8 * 16384;
            mbar_wait(BAR(B_SSQ), layer);
            TS(6 + 12 * layer);
            {
                float tot = 0.f;
#pragma unroll
                for (int i = 0; i < 16; i++) tot += __ldcg(g_ssqc + (layer * 16 + i) * 2048 + 128 * c + t2);
                float rs = rsqrtf(tot * (1.f / 512.f) + 1e-5f);
                s_rstd[t2] = rs;
                s_rstd[128 + t2] = 2.f * rs;
                if (layer == 0) s_mean[t2] = 0.f;
                if (layer == 1) {
                    unsigned short u = __ldcg((const unsigned short*)(ximg + (uint32_t)(c * 8 * 16384 + (t2 >> 3) * 128 + (t2 & 7) * 2)));
                    s_mean[t2] = __uint_as_float((uint32_t)u << 16) * (1.f / 512.f);
                }
            }
            TS(7 + 12 * layer);
            bar_arrive(4, 384);
            acc_def(acc);
#pragma unroll 1
            for (int kb = 0; kb < 8; kb++) {
                if (kb == 4) {
                    wg_wait<0>();
                    if (lane == 0) { mbar_arrive(BAR(B_XEMPTY + 3), 1); mbar_arrive_remote(mapa(BAR(B_XEMPTY + 3), par ^ 1)); }
                    bar_sync(14, 384);
                }
                mbar_wait(BAR(B_XFULL + (kb & 3)), (kb >> 2) & 1);
                wg_fence();
#pragma unroll
                for (int ks = 0; ks < 4; ks++)
                    wgmma_n128<1>(acc, desc_a(sb + SM_X + (kb & 3) * 24576 + 16384 + ks * 256), desc_b<128>(sb + SM_X + (kb & 3) * 24576 + ks * 4096), 1);
                wg_commit();
                wg_wait<1>();
                if ((kb & 3) != 0 && lane == 0) { mbar_arrive(BAR(B_XEMPTY + ((kb - 1) & 3)), 1); mbar_arrive_remote(mapa(BAR(B_XEMPTY + ((kb - 1) & 3)), par ^ 1)); }
            }
            wg_wait<0>();
            if (lane == 0) { mbar_arrive(BAR(B_XEMPTY + 3), 1); mbar_arrive_remote(mapa(BAR(B_XEMPTY + 3), par ^ 1)); mbar_arrive_remote(mapa(BAR(B_RFREE), par ^ 1)); }
            bar_arrive(7, 384);
            bar_sync(3, 128);
            TS(9 + 12 * layer);
            const int m0 = 16 * w + g;
            const uint32_t xoff = (uint32_t)((c * 8 + own) * 16384 + w * 4096 + g * 16 + 4 * q);
            if (layer == 0) {
                const uint8_t* xs = g_X + xoff;
#pragma unroll
                for (int i = 0; i < 16; i++) {
                    float2 rs = *(const float2*)(s_rstd + 8 * i + 2 * q);
                    uint32_t x0v = __ldcg((const uint32_t*)(xs + i * 128)), x1v = __ldcg((const uint32_t*)(xs + 2048 + i * 128));
                    acc[4 * i] = acc[4 * i] * rs.x + bf_lo(x0v);
                    acc[4 * i + 1] = acc[4 * i + 1] * rs.y + bf_hi(x0v);
                    acc[4 * i + 2] = acc[4 * i + 2] * rs.x + bf_lo(x1v);
                    acc[4 * i + 3] = acc[4 * i + 3] * rs.y + bf_hi(x1v);
                }
            } else {
                float d0 = ldbf(p.dskip + 64 * own + m0), d1 = ldbf(p.dskip + 64 * own + m0 + 8);
#pragma unroll
                for (int i = 0; i < 16; i++) {
                    float2 rs = *(const float2*)(s_rstd + 8 * i + 2 * q);
                    float2 mn = *(const float2*)(s_mean + 8 * i + 2 * q);
                    acc[4 * i] = acc[4 * i] * (1.f + rs.x * d0) + mn.x;
                    acc[4 * i + 1] = acc[4 * i + 1] * (1.f + rs.y * d0) + mn.y;
                    acc[4 * i + 2] = acc[4 * i + 2] * (1.f + rs.x * d1) + mn.x;
                    acc[4 * i + 3] = acc[4 * i + 3] * (1.f + rs.y * d1) + mn.y;
                }
            }
            TS(10 + 12 * layer);
            bar_sync(6, 416);
            TS(11 + 12 * layer);
            {
                float (&a0)[32] = *reinterpret_cast<float (*)[32]>(&acc[0]);
                float (&a1)[32] = *reinterpret_cast<float (*)[32]>(&acc[32]);
#pragma unroll 1
                for (int k = 0; k < 2; k++) {
                    const uint32_t hb = sb + SM_HH + (par ^ k) * 32768;
                    if (k == 1) {
                        mbar_wait(BAR(B_HPEER), layer);
                        mbar_wait(BAR(B_HPEER1), layer);
                        bar_sync(12, 384);
                    }
                    mbar_wait(BAR(B_AFULL + 6 + k), 1);
                    const uint64_t da = c_desc(6 + k);
                    wg_fence();
#pragma unroll
                    for (int ks = 0; ks < 4; ks++) {
                        wgmma_n64s<1>(a0, da + ks * dstep, desc_b<64>(hb + ks * 2048), 1);
                        wgmma_n64s<1>(a1, da + ks * dstep, desc_b<64>(hb + 16384 + ks * 2048), 1);
                    }
#pragma unroll
                    for (int ks = 0; ks < 4; ks++) {
                        wgmma_n64s<-1>(a0, da + 512 + ks * dstep, desc_b<64>(hb + 8192 + ks * 2048), 1);
                        wgmma_n64s<-1>(a1, da + 512 + ks * dstep, desc_b<64>(hb + 16384 + 8192 + ks * 2048), 1);
                    }
                    wg_commit();
                }
                wg_wait<0>();
            }
#pragma unroll
            for (int i = 0; i < 16; i++)
                *(float4*)(sm + SM_A + 6 * 16384 + i * 2048 + t2 * 16) = make_float4(acc[4 * i], acc[4 * i + 1], acc[4 * i + 2], acc[4 * i + 3]);
            TS(12 + 12 * layer);
        }
        {
            const int t = tid & 127;
            const int nch = wg == 2 ? 2 : 3;
            const uint4* pb = g_P + (uint32_t)((c * 8 + r) * 4 * 1024 + wg * 128 + t);
            uint4 v[3][3];
            unsigned n = 0;
#pragma unroll 1
            while (true) {
                if (lane == 31) {
#pragma unroll 1
                    while (true) {
                        uint32_t bad = 0;
#pragma unroll
                        for (int sx = 0; sx < 3; sx++) {
                            uint32_t t0;
                            asm volatile("ld.relaxed.gpu.global.u32 %0, [%1];" : "=r"(t0) : "l"(pb + ((pi_ + 1 + sx) & 3) * 1024 + (nch - 1) * 384) : "memory");
                            bad |= t0 ^ ptag;
                        }
                        if (!(bad & 0x00010001u) || ++n >= SPIN_LIMIT) break;
                    }
                }
                __syncwarp();
                uint32_t bad = 0;
#pragma unroll
                for (int k = 0; k < 3; k++)
#pragma unroll
                    for (int sx = 0; sx < 3; sx++) {
                        v[k][sx] = make_uint4(ptag, 0, 0, 0);
                        if (k < nch) v[k][sx] = ld_relaxed_u4(pb + ((pi_ + 1 + sx) & 3) * 1024 + k * 384);
                        bad |= v[k][sx].x ^ ptag;
                    }
                if (!__any_sync(~0u, bad & 0x00010001u) || ++n >= SPIN_LIMIT) break;
            }
            bar_sync(8, 384);
            TS(13 + 12 * layer);
            const int m0 = 16 * w + g;
            const float w0 = (own == 0 && m0 < 2) ? (m0 == 0 ? 0.f : 0.5f) : 1.f;
#pragma unroll
            for (int k = 0; k < 3; k++) {
                if (k < nch) {
                    const int i = wg + 3 * k;
                    float4 a = *(const float4*)(sm + SM_A + 6 * 16384 + (2 * i) * 2048 + t * 16);
                    float4 bq = *(const float4*)(sm + SM_A + 6 * 16384 + (2 * i + 1) * 2048 + t * 16);
#pragma unroll
                    for (int sx = 0; sx < 3; sx++) {
                        a.x += bf_lo(v[k][sx].x); a.y += bf_hi(v[k][sx].x); a.z += bf_lo(v[k][sx].y); a.w += bf_hi(v[k][sx].y);
                        bq.x += bf_lo(v[k][sx].z); bq.y += bf_hi(v[k][sx].z); bq.z += bf_lo(v[k][sx].w); bq.w += bf_hi(v[k][sx].w);
                    }
                    if (layer == 0) {
                        uint8_t* xd = g_X + (uint32_t)((16 * 8 + c * 8 + own) * 16384 + w * 4096 + g * 16 + 4 * q + i * 256);
                        uint32_t v0 = pack_bf16(a.x, a.y), v1 = pack_bf16(a.z, a.w), v2 = pack_bf16(bq.x, bq.y), v3 = pack_bf16(bq.z, bq.w);
                        *(uint32_t*)(xd) = v0; *(uint32_t*)(xd + 2048) = v1; *(uint32_t*)(xd + 128) = v2; *(uint32_t*)(xd + 2048 + 128) = v3;
                        float sq[4];
                        sq[0] = w0 * bf_lo(v0) * bf_lo(v0) + bf_lo(v1) * bf_lo(v1);
                        sq[1] = w0 * bf_hi(v0) * bf_hi(v0) + bf_hi(v1) * bf_hi(v1);
                        sq[2] = w0 * bf_lo(v2) * bf_lo(v2) + bf_lo(v3) * bf_lo(v3);
                        sq[3] = w0 * bf_hi(v2) * bf_hi(v2) + bf_hi(v3) * bf_hi(v3);
                        float u0 = (g & 1) ? sq[2] : sq[0], u1 = (g & 1) ? sq[3] : sq[1];
                        u0 += __shfl_xor_sync(~0u, (g & 1) ? sq[0] : sq[2], 4);
                        u1 += __shfl_xor_sync(~0u, (g & 1) ? sq[1] : sq[3], 4);
                        float z = (g & 2) ? u1 : u0;
                        z += __shfl_xor_sync(~0u, (g & 2) ? u0 : u1, 8);
                        z += __shfl_xor_sync(~0u, z, 16);
                        if (g < 4) atomicAdd(s_mean + 16 * i + 8 * (g & 1) + 2 * q + (g >> 1), z);
                    } else {
                        float* o = p.out + (uint32_t)((128 * c + 32 * q + 4 * i) * 512 + 64 * own + m0);
                        o[0] = a.x; o[512] = a.y; o[8] = a.z; o[512 + 8] = a.w;
                        o[1024] = bq.x; o[1536] = bq.y; o[1024 + 8] = bq.z; o[1536 + 8] = bq.w;
                    }
                }
            }
            if (wg < 2) mbar_wait_cluster(BAR(B_HDONE), layer);
            if (layer == 0) {
                fence_async_smem();
                bar_sync(9, 384);
                TS(14 + 12 * layer);
                if (wg == 2) {
                    atomicAdd(g_ssq + 2048 + 128 * c + t, s_mean[t] * (2.f / 512.f));
                    bar_sync(3, 128);
                    if (lane == 0) { mbar_arrive(BAR(B_AEMPTY + 6), 2); mbar_arrive(BAR(B_AEMPTY + 7), 2); }
                    if (t == 0) { fence_async(); red_release(&g_bar[2], 1); }
                }
            }
        }
        TS(15 + 12 * layer);
        if (wg == 0) TC(31);
    }
}

typedef CUresult (*EncFn)(CUtensorMap*, CUtensorMapDataType, cuuint32_t, void*, const cuuint64_t*, const cuuint64_t*,
                          const cuuint32_t*, const cuuint32_t*, CUtensorMapInterleave, CUtensorMapSwizzle,
                          CUtensorMapL2promotion, CUtensorMapFloatOOBfill);

void launch_impl(void* const* d_in, void* d_out, int stop) {
    static EncFn enc = nullptr;
    if (!enc) {
        void* fn = nullptr;
        cudaDriverEntryPointQueryResult qr;
        cudaGetDriverEntryPoint("cuTensorMapEncodeTiled", &fn, cudaEnableDefault, &qr);
        enc = (EncFn)fn;
        cudaFuncSetAttribute(fused_kernel, cudaFuncAttributeMaxDynamicSharedMemorySize, SM_TOTAL);
    }
    CUtensorMap tx, tbr, tbi, tcr, tci, tcol;
    {
        void* gx = nullptr;
        cudaGetSymbolAddress(&gx, g_X);
        cuuint64_t gd[5] = {64, 16, 64, 16, 2};
        cuuint64_t gs[4] = {128, 2048, 128 * 1024, 2048 * 1024};
        cuuint32_t bx[5] = {32, 16, 1, 16, 1};
        cuuint32_t es[5] = {1, 1, 1, 1, 1};
        enc(&tcol, CU_TENSOR_MAP_DATA_TYPE_BFLOAT16, 5, gx, gd, gs, bx, es, CU_TENSOR_MAP_INTERLEAVE_NONE,
            CU_TENSOR_MAP_SWIZZLE_64B, CU_TENSOR_MAP_L2_PROMOTION_NONE, CU_TENSOR_MAP_FLOAT_OOB_FILL_NONE);
    }
    {
        cuuint64_t gd[5] = {512, 2, 4, 16, 16};
        cuuint64_t gs[4] = {1024, 32 * 1024, 2 * 1024, 128 * 1024};
        cuuint32_t bx[5] = {64, 2, 4, 8, 1};
        cuuint32_t es[5] = {1, 1, 1, 1, 1};
        enc(&tx, CU_TENSOR_MAP_DATA_TYPE_BFLOAT16, 5, d_in[0], gd, gs, bx, es, CU_TENSOR_MAP_INTERLEAVE_NONE,
            CU_TENSOR_MAP_SWIZZLE_128B, CU_TENSOR_MAP_L2_PROMOTION_L2_128B, CU_TENSOR_MAP_FLOAT_OOB_FILL_NONE);
    }
    auto mk2 = [&](CUtensorMap* m, void* ptr, cuuint32_t rows) {
        cuuint64_t gd[2] = {512, 512};
        cuuint64_t gs[1] = {1024};
        cuuint32_t bx[2] = {64, rows};
        cuuint32_t es[2] = {1, 1};
        enc(m, CU_TENSOR_MAP_DATA_TYPE_BFLOAT16, 2, ptr, gd, gs, bx, es, CU_TENSOR_MAP_INTERLEAVE_NONE,
            CU_TENSOR_MAP_SWIZZLE_128B, CU_TENSOR_MAP_L2_PROMOTION_L2_128B, CU_TENSOR_MAP_FLOAT_OOB_FILL_NONE);
    };
    mk2(&tbr, d_in[6], 32);
    mk2(&tbi, d_in[7], 32);
    mk2(&tcr, d_in[8], 64);
    mk2(&tci, d_in[9], 64);
    Params p;
    p.x0 = (const __nv_bfloat16*)d_in[0];
    p.w_r = (const __nv_bfloat16*)d_in[1];
    p.w_i = (const __nv_bfloat16*)d_in[2];
    p.lam_re = (const __nv_bfloat16*)d_in[4];
    p.lam_im = (const __nv_bfloat16*)d_in[5];
    p.log_dt = (const __nv_bfloat16*)d_in[10];
    p.dskip = (const __nv_bfloat16*)d_in[11];
    p.out = (float*)d_out;
    p.stop = stop;
    cudaLaunchConfig_t cfg = {};
    cfg.gridDim = dim3(NCTA); cfg.blockDim = dim3(NTHREADS); cfg.dynamicSmemBytes = SM_TOTAL; cfg.stream = cudaStreamPerThread;
    cudaLaunchAttribute at[1];
    at[0].id = cudaLaunchAttributeClusterDimension;
    at[0].val.clusterDim.x = 2; at[0].val.clusterDim.y = 1; at[0].val.clusterDim.z = 1;
    cfg.attrs = at; cfg.numAttrs = 1;
    cudaLaunchKernelEx(&cfg, fused_kernel, tx, tbr, tbi, tcr, tci, tcol, p);
}

}

extern "C" void kernel_launch(void* const* d_in, const int* in_sizes, int n_in, void* d_out, int out_size) {
    (void)in_sizes; (void)n_in; (void)out_size;
    launch_impl(d_in, d_out, 100);
}
```

```cpp
#include <cuda_runtime.h>
#include <cuda_bf16.h>
#include <cuda.h>
#include <stdint.h>

namespace {

constexpr int NCTA = 128;
constexpr int NTHREADS = 512;
constexpr int SM_A = 0;
constexpr int SM_X = 131072;
constexpr int SM_H = 196608;
constexpr int SM_HH = SM_X + 32768;
constexpr int SM_M = 229376;
constexpr int SM_TOTAL = 232448;
constexpr int SM_BAR = SM_M;
constexpr int SM_TGT = SM_M + 360;
constexpr int SM_LAM = SM_M + 384;
constexpr int SM_TAB = SM_M + 896;
constexpr int SM_RSTD = SM_M + 1920;
constexpr int SM_MEAN = SM_TAB;
constexpr int SM_T64 = SM_M + 2944;
constexpr int SM_B1ST = SM_H + 24576;
constexpr int SM_RAW = SM_X + 40960;
constexpr int SM_SSQ = SM_X + 57344;
constexpr int B_FULL0 = 0;
constexpr int B_EMPTY0 = 8;
constexpr int B_FULLC = 12;
constexpr int B_AFULL = 13;
constexpr int B_AEMPTY = 21;
constexpr int B_XFULL = 29;
constexpr int B_XEMPTY = 33;
constexpr int B_AFREE = 37;
constexpr int B_COL = 38;
constexpr int B_SSQ = 39;
constexpr int B_HPEER = 40;
constexpr int B_RFREE = 41;
constexpr int B_HDONE = 42;
constexpr int B_WRDY = 43;
constexpr int B_HPEER1 = 44;
constexpr int NBARS = 45;

__device__ __align__(1024) uint8_t g_X[2 * 16 * 8 * 16384];
__device__ __align__(1024) uint8_t g_A1[8 * 8 * 16384];
__device__ __align__(1024) uint8_t g_A2[8 * 8 * 16384];
__device__ __align__(1024) uint8_t g_E[2 * 8 * 8 * 8192];
__device__ __align__(16) float g_ssq[2 * 2048];
__device__ __align__(16) float g_ssqc[2 * 16 * 2048];
__device__ __align__(16) float g_Dh[512];
__device__ __align__(16) uint4 g_Wfrag[128 * 4 * 256];
__device__ __align__(16) float4 g_Ebuf[2 * 16 * 512];
__device__ __align__(16) uint4 g_P[16 * 8 * 4 * 1024];
__device__ unsigned g_bar[8];
__device__ unsigned g_err;
#define TX(i)
#define TQ(i)
#define TS(i)
#define TC(i)

constexpr unsigned SPIN_LIMIT = 1u << 22;

__device__ __forceinline__ uint32_t s2u(const void* p) { return (uint32_t)__cvta_generic_to_shared(p); }
__device__ __forceinline__ void mbar_init(uint32_t a, uint32_t c) {
    asm volatile("mbarrier.init.shared::cta.b64 [%0], %1;" ::"r"(a), "r"(c) : "memory");
}
__device__ __forceinline__ void mbar_expect(uint32_t a, uint32_t bytes) {
    asm volatile("mbarrier.arrive.expect_tx.shared::cta.b64 _, [%0], %1;" ::"r"(a), "r"(bytes) : "memory");
}
__device__ __forceinline__ void mbar_arrive(uint32_t a, uint32_t cnt) {
    asm volatile("mbarrier.arrive.shared::cta.b64 _, [%0], %1;" ::"r"(a), "r"(cnt) : "memory");
}
__device__ __forceinline__ bool mbar_try(uint32_t a, uint32_t parity) {
    uint32_t ok;
    asm volatile("{\n.reg .pred p;\nmbarrier.try_wait.parity.shared::cta.b64 p, [%1], %2;\nselp.u32 %0, 1, 0, p;\n}"
                 : "=r"(ok) : "r"(a), "r"(parity) : "memory");
    return ok != 0;
}
__device__ __forceinline__ void mbar_wait(uint32_t a, uint32_t parity) {
    asm volatile("{\n.reg .pred p, q;\n.reg .u32 n;\nmov.u32 n, 0;\n"
                 "W_%=:\nmbarrier.try_wait.parity.shared::cta.b64 p, [%0], %1;\n@p bra D_%=;\n"
                 "add.u32 n, n, 1;\nsetp.lt.u32 q, n, 4194304;\n@q bra W_%=;\nD_%=:\n}" ::"r"(a), "r"(parity) : "memory");
}
__device__ __forceinline__ void bulk_g2s(uint32_t dst, const void* src, uint32_t bytes, uint32_t bar) {
    asm volatile("cp.async.bulk.shared::cluster.global.mbarrier::complete_tx::bytes [%0], [%1], %2, [%3];" ::"r"(dst),
                 "l"(src), "r"(bytes), "r"(bar) : "memory");
}
__device__ __forceinline__ void tma_2d(uint32_t dst, const CUtensorMap* m, int c0, int c1, uint32_t bar) {
    asm volatile("cp.async.bulk.tensor.2d.shared::cluster.global.mbarrier::complete_tx::bytes [%0], [%1, {%3,%4}], [%2];" ::"r"(dst),
                 "l"(m), "r"(bar), "r"(c0), "r"(c1) : "memory");
}
__device__ __forceinline__ void tma_5d(uint32_t dst, const CUtensorMap* m, int c0, int c1, int c2, int c3, int c4, uint32_t bar) {
    asm volatile("cp.async.bulk.tensor.5d.shared::cluster.global.mbarrier::complete_tx::bytes [%0], [%1, {%3,%4,%5,%6,%7}], [%2];" ::"r"(dst),
                 "l"(m), "r"(bar), "r"(c0), "r"(c1), "r"(c2), "r"(c3), "r"(c4) : "memory");
}
__device__ __forceinline__ void tma_2d_mc(uint32_t dst, const CUtensorMap* m, int c0, int c1, uint32_t bar) {
    asm volatile("cp.async.bulk.tensor.2d.shared::cluster.global.mbarrier::complete_tx::bytes.multicast::cluster [%0], [%1, {%3,%4}], [%2], %5;" ::"r"(dst),
                 "l"(m), "r"(bar), "r"(c0), "r"(c1), "h"((unsigned short)3) : "memory");
}
__device__ __forceinline__ void tma_5d_mc(uint32_t dst, const CUtensorMap* m, int c0, int c1, int c2, int c3, int c4, uint32_t bar) {
    asm volatile("cp.async.bulk.tensor.5d.shared::cluster.global.mbarrier::complete_tx::bytes.multicast::cluster [%0], [%1, {%3,%4,%5,%6,%7}], [%2], %8;" ::"r"(dst),
                 "l"(m), "r"(bar), "r"(c0), "r"(c1), "r"(c2), "r"(c3), "r"(c4), "h"((unsigned short)3) : "memory");
}
__device__ __forceinline__ void bulk_g2s_mc(uint32_t dst, const void* src, uint32_t bytes, uint32_t bar) {
    asm volatile("cp.async.bulk.shared::cluster.global.mbarrier::complete_tx::bytes.multicast::cluster [%0], [%1], %2, [%3], %4;" ::"r"(dst),
                 "l"(src), "r"(bytes), "r"(bar), "h"((unsigned short)3) : "memory");
}
__device__ __forceinline__ void tma_store_5d(const CUtensorMap* m, int c0, int c1, int c2, int c3, int c4, uint32_t src) {
    asm volatile("cp.async.bulk.tensor.5d.global.shared::cta.bulk_group [%0, {%2,%3,%4,%5,%6}], [%1];" ::"l"(m), "r"(src),
                 "r"(c0), "r"(c1), "r"(c2), "r"(c3), "r"(c4) : "memory");
}
__device__ __forceinline__ uint32_t lds32(uint32_t a) { uint32_t v; asm volatile("ld.shared.u32 %0, [%1];" : "=r"(v) : "r"(a) : "memory"); return v; }
__device__ __forceinline__ uint4 ld_relaxed_u4(const uint4* p) {
    uint4 v;
    asm volatile("ld.relaxed.gpu.global.v4.u32 {%0,%1,%2,%3}, [%4];" : "=r"(v.x), "=r"(v.y), "=r"(v.z), "=r"(v.w) : "l"(p) : "memory");
    return v;
}
__device__ __forceinline__ void fence_async() { asm volatile("fence.proxy.async.global;" ::: "memory"); }
__device__ __forceinline__ void red_relaxed(unsigned* p, unsigned v) {
    asm volatile("red.relaxed.gpu.global.add.u32 [%0], %1;" ::"l"(p), "r"(v) : "memory");
}
__device__ __forceinline__ uint32_t mapa(uint32_t a, uint32_t rank) {
    uint32_t d;
    asm("mapa.shared::cluster.u32 %0, %1, %2;" : "=r"(d) : "r"(a), "r"(rank));
    return d;
}
__device__ __forceinline__ void mbar_arrive_remote(uint32_t ra) {
    asm volatile("mbarrier.arrive.relaxed.cluster.shared::cluster.b64 _, [%0];" ::"r"(ra) : "memory");
}
__device__ __forceinline__ void mbar_wait_cluster(uint32_t a, uint32_t parity) {
    asm volatile("{\n.reg .pred p, q;\n.reg .u32 n;\nmov.u32 n, 0;\n"
                 "W_%=:\nmbarrier.try_wait.parity.acquire.cluster.shared::cta.b64 p, [%0], %1;\n@p bra D_%=;\n"
                 "add.u32 n, n, 1;\nsetp.lt.u32 q, n, 4194304;\n@q bra W_%=;\nD_%=:\n}" ::"r"(a), "r"(parity) : "memory");
}
__device__ __forceinline__ void bulk_s2peer(uint32_t rdst, uint32_t src, uint32_t bytes, uint32_t rbar) {
    asm volatile("cp.async.bulk.shared::cluster.shared::cta.mbarrier::complete_tx::bytes [%0], [%1], %2, [%3];" ::"r"(rdst),
                 "r"(src), "r"(bytes), "r"(rbar) : "memory");
}
__device__ __forceinline__ void fence_async_smem() { asm volatile("fence.proxy.async.shared::cta;" ::: "memory"); }
__device__ __forceinline__ void wg_fence() { asm volatile("wgmma.fence.sync.aligned;" ::: "memory"); }
__device__ __forceinline__ void wg_commit() { asm volatile("wgmma.commit_group.sync.aligned;" ::: "memory"); }
template <int N> __device__ __forceinline__ void wg_wait() { asm volatile("wgmma.wait_group.sync.aligned %0;" ::"n"(N) : "memory"); }
__device__ __forceinline__ void bar_sync(int id, int n) { asm volatile("bar.sync %0, %1;" ::"r"(id), "r"(n) : "memory"); }
__device__ __forceinline__ void bar_arrive(int id, int n) { asm volatile("bar.arrive %0, %1;" ::"r"(id), "r"(n) : "memory"); }
__device__ __forceinline__ unsigned ld_acquire(const unsigned* p) {
    unsigned v;
    asm volatile("ld.acquire.gpu.global.u32 %0, [%1];" : "=r"(v) : "l"(p) : "memory");
    return v;
}
__device__ __forceinline__ void red_release(unsigned* p, unsigned v) {
    asm volatile("red.release.gpu.global.add.u32 [%0], %1;" ::"l"(p), "r"(v) : "memory");
}
__device__ __forceinline__ void wait_count(const unsigned* p, unsigned target) {
    unsigned n = 0;
#pragma unroll 1
    while ((int)(ld_acquire(p) - target) < 0 && ++n < SPIN_LIMIT) {}
}
__device__ __forceinline__ float4 ld_relaxed_f4(const float4* p) {
    float4 v;
    asm volatile("ld.relaxed.gpu.global.v4.f32 {%0,%1,%2,%3}, [%4];" : "=f"(v.x), "=f"(v.y), "=f"(v.z), "=f"(v.w) : "l"(p) : "memory");
    return v;
}
__device__ __forceinline__ void st_relaxed_f4(float4* p, float4 v) {
    asm volatile("st.relaxed.gpu.global.v4.f32 [%0], {%1,%2,%3,%4};" ::"l"(p), "f"(v.x), "f"(v.y), "f"(v.z), "f"(v.w) : "memory");
}
__device__ __forceinline__ uint32_t pack_bf16(float lo, float hi) {
    uint32_t r;
    asm("cvt.rn.bf16x2.f32 %0, %1, %2;" : "=r"(r) : "f"(hi), "f"(lo));
    return r;
}
__device__ __forceinline__ uint32_t hmul2(uint32_t a, uint32_t b) {
    uint32_t r;
    asm("mul.rn.bf16x2 %0, %1, %2;" : "=r"(r) : "r"(a), "r"(b));
    return r;
}
__device__ __forceinline__ uint32_t hfma2(uint32_t a, uint32_t b, uint32_t c) {
    uint32_t r;
    asm("fma.rn.bf16x2 %0, %1, %2, %3;" : "=r"(r) : "r"(a), "r"(b), "r"(c));
    return r;
}
__device__ __forceinline__ float bf_lo(uint32_t v) { return __uint_as_float(v << 16); }
__device__ __forceinline__ float bf_hi(uint32_t v) { return __uint_as_float(v & 0xffff0000u); }
__device__ __forceinline__ void sts32(uint32_t a, uint32_t v) { asm volatile("st.shared.u32 [%0], %1;" ::"r"(a), "r"(v) : "memory"); }
__device__ __forceinline__ void sts128(uint32_t a, uint4 v) {
    asm volatile("st.shared.v4.u32 [%0], {%1,%2,%3,%4};" ::"r"(a), "r"(v.x), "r"(v.y), "r"(v.z), "r"(v.w) : "memory");
}

__device__ __forceinline__ uint64_t desc_ni(uint32_t addr, uint32_t lbo, uint32_t sbo) {
    return (uint64_t)((addr & 0x3FFFF) >> 4) | ((uint64_t)(lbo >> 4) << 16) | ((uint64_t)(sbo >> 4) << 32);
}
__device__ __forceinline__ uint64_t desc_a(uint32_t addr) { return desc_ni(addr, 128, 1024); }
template <int N> __device__ __forceinline__ uint64_t desc_b(uint32_t addr) { return desc_ni(addr, 16 * N, 128); }
__device__ __forceinline__ uint64_t desc_k(uint32_t addr) {
    return (uint64_t)((addr & 0x3FFFF) >> 4) | (1ull << 16) | (64ull << 32) | (1ull << 62);
}
__device__ __forceinline__ uint64_t desc_mn(uint32_t addr, uint32_t lbo) {
    return (uint64_t)((addr & 0x3FFFF) >> 4) | ((uint64_t)(lbo >> 4) << 16) | (64ull << 32) | (1ull << 62);
}

#define ACC8(d, o) "+f"(d[o + 0]), "+f"(d[o + 1]), "+f"(d[o + 2]), "+f"(d[o + 3]), "+f"(d[o + 4]), "+f"(d[o + 5]), "+f"(d[o + 6]), "+f"(d[o + 7])
template <int TB, int SA = 1>
__device__ __forceinline__ void wgmma_n128(float (&d)[64], uint64_t da, uint64_t db, int sd) {
    asm volatile(
        "{\n.reg .pred p;\nsetp.ne.b32 p, %66, 0;\n"
        "wgmma.mma_async.sync.aligned.m64n128k16.f32.bf16.bf16 "
        "{%0,%1,%2,%3,%4,%5,%6,%7,%8,%9,%10,%11,%12,%13,%14,%15,%16,%17,%18,%19,%20,%21,%22,%23,%24,%25,%26,%27,%28,%29,%30,%31,"
        "%32,%33,%34,%35,%36,%37,%38,%39,%40,%41,%42,%43,%44,%45,%46,%47,%48,%49,%50,%51,%52,%53,%54,%55,%56,%57,%58,%59,%60,%61,%62,%63},"
        " %64, %65, p, %68, 1, 0, %67;\n}"
        : ACC8(d, 0), ACC8(d, 8), ACC8(d, 16), ACC8(d, 24), ACC8(d, 32), ACC8(d, 40), ACC8(d, 48), ACC8(d, 56)
        : "l"(da), "l"(db), "r"(sd), "n"(TB), "n"(SA));
}
template <int N> __device__ __forceinline__ void acc_def(float (&d)[N]) {
#pragma unroll
    for (int i = 0; i < N; i++) d[i] = 0.f;
}
template <int TB>
__device__ __forceinline__ void wgmma_n64(float (&d)[32], uint64_t da, uint64_t db, int sd) {
    asm volatile(
        "{\n.reg .pred p;\nsetp.ne.b32 p, %34, 0;\n"
        "wgmma.mma_async.sync.aligned.m64n64k16.f32.bf16.bf16 "
        "{%0,%1,%2,%3,%4,%5,%6,%7,%8,%9,%10,%11,%12,%13,%14,%15,%16,%17,%18,%19,%20,%21,%22,%23,%24,%25,%26,%27,%28,%29,%30,%31},"
        " %32, %33, p, 1, 1, 0, %35;\n}"
        : ACC8(d, 0), ACC8(d, 8), ACC8(d, 16), ACC8(d, 24)
        : "l"(da), "l"(db), "r"(sd), "n"(TB));
}
template <int SA>
__device__ __forceinline__ void wgmma_n64s(float (&d)[32], uint64_t da, uint64_t db, int sd) {
    asm volatile(
        "{\n.reg .pred p;\nsetp.ne.b32 p, %34, 0;\n"
        "wgmma.mma_async.sync.aligned.m64n64k16.f32.bf16.bf16 "
        "{%0,%1,%2,%3,%4,%5,%6,%7,%8,%9,%10,%11,%12,%13,%14,%15,%16,%17,%18,%19,%20,%21,%22,%23,%24,%25,%26,%27,%28,%29,%30,%31},"
        " %32, %33, p, %35, 1, 0, 1;\n}"
        : ACC8(d, 0), ACC8(d, 8), ACC8(d, 16), ACC8(d, 24)
        : "l"(da), "l"(db), "r"(sd), "n"(SA));
}
__device__ __forceinline__ void wgmma_n64_rs(float (&d)[32], uint32_t a0, uint32_t a1, uint32_t a2, uint32_t a3, uint64_t db, int sd) {
    asm volatile(
        "{\n.reg .pred p;\nsetp.ne.b32 p, %37, 0;\n"
        "wgmma.mma_async.sync.aligned.m64n64k16.f32.bf16.bf16 "
        "{%0,%1,%2,%3,%4,%5,%6,%7,%8,%9,%10,%11,%12,%13,%14,%15,%16,%17,%18,%19,%20,%21,%22,%23,%24,%25,%26,%27,%28,%29,%30,%31},"
        " {%32,%33,%34,%35}, %36, p, 1, 1, 1;\n}"
        : ACC8(d, 0), ACC8(d, 8), ACC8(d, 16), ACC8(d, 24)
        : "r"(a0), "r"(a1), "r"(a2), "r"(a3), "l"(db), "r"(sd));
}

struct Params {
    const __nv_bfloat16* x0;
    const __nv_bfloat16* w_r;
    const __nv_bfloat16* w_i;
    const __nv_bfloat16* lam_re;
    const __nv_bfloat16* lam_im;
    const __nv_bfloat16* log_dt;
    const __nv_bfloat16* dskip;
    float* out;
    int stop;
};

__device__ __forceinline__ float ldbf(const __nv_bfloat16* p) { return __bfloat162float(*p); }

__device__ __forceinline__ void dft_fp(int j, int& f, int& ph) {
    int cs = j >> 1;
    if (j == 1) { f = 256; ph = 0; }
    else { f = cs; ph = (j & 1) ? 128 : 0; }
}

__device__ __forceinline__ void gen_col_consts(uint32_t sb, int tid) {
#pragma unroll 1
    for (int task = tid; task < 640; task += 256) {
        int f, c8;
        uint32_t a_cc, d_pi, d_po;
        if (task < 512) {
            f = task & 63; c8 = task >> 6;
            a_cc = sb + SM_X + (f >> 5) * 16384 + ((f >> 3) & 3) * 2048 + c8 * 128 + (f & 7) * 16;
            d_pi = 8192; d_po = 1024;
        } else {
            int n2 = task & 31;
            f = 2 * n2; c8 = (task >> 5) & 3;
            a_cc = sb + SM_X + 32768 + (n2 >> 3) * 1024 + c8 * 128 + (n2 & 7) * 16;
            d_pi = 4096; d_po = 512;
        }
        float cd, sd, cs, sn;
        __sincosf((float)(f >= 32 ? f - 64 : f) * (6.283185307179586f / 64.f), &sd, &cd);
        int a = (8 * c8 * f) & 63;
        __sincosf((float)(a >= 32 ? a - 64 : a) * (6.283185307179586f / 64.f), &sn, &cs);
        float cv[8], sv[8];
#pragma unroll
        for (int e = 0; e < 8; e++) {
            cv[e] = cs; sv[e] = sn;
            float t = cs * cd - sn * sd;
            sn = sn * cd + cs * sd;
            cs = t;
        }
        uint4 oc = make_uint4(pack_bf16(cv[0], cv[1]), pack_bf16(cv[2], cv[3]), pack_bf16(cv[4], cv[5]), pack_bf16(cv[6], cv[7]));
        uint4 os = make_uint4(pack_bf16(sv[0], sv[1]), pack_bf16(sv[2], sv[3]), pack_bf16(sv[4], sv[5]), pack_bf16(sv[6], sv[7]));
        sts128(a_cc, oc);
        sts128(a_cc + d_pi, os);
        sts128(a_cc + d_po, make_uint4(os.x ^ 0x80008000u, os.y ^ 0x80008000u, os.z ^ 0x80008000u, os.w ^ 0x80008000u));
        sts128(a_cc + d_pi + d_po, oc);
    }
}

__global__ void __launch_bounds__(NTHREADS, 1)
fused_kernel(const __grid_constant__ CUtensorMap tm_x, const __grid_constant__ CUtensorMap tm_bre,
             const __grid_constant__ CUtensorMap tm_bim, const __grid_constant__ CUtensorMap tm_cre,
             const __grid_constant__ CUtensorMap tm_cim, const __grid_constant__ CUtensorMap tm_col, const Params p) {
    extern __shared__ __align__(1024) uint8_t sm[];
    const uint32_t sb = s2u(sm);
    const int tid = threadIdx.x, b = blockIdx.x;
    const int c = b >> 3, r = b & 7;
    const int par = r & 1, pi_ = r >> 1, own = 4 * par + pi_;
    const int wg = __shfl_sync(~0u, tid >> 7, 0), w = __shfl_sync(~0u, (tid >> 5) & 3, 0), lane = tid & 31, g = lane >> 2, q = lane & 3;
    auto BAR = [&](int i) { return sb + SM_BAR + 8 * i; };
    unsigned* s_tgt = (unsigned*)(sm + SM_TGT);

    if (tid < NBARS) {
        int cnt = 1;
        if ((tid >= B_EMPTY0 && tid < B_EMPTY0 + 4) || (tid >= B_XEMPTY && tid < B_XEMPTY + 4)) cnt = 24;
        if (tid == B_RFREE) cnt = 12;
        if (tid == B_HDONE) cnt = 2;
        if (tid >= B_AEMPTY && tid < B_AEMPTY + 8) cnt = 8;
        if (tid == B_AFREE) cnt = 4;
        mbar_init(BAR(tid), cnt);
        asm volatile("fence.mbarrier_init.release.cluster;" ::: "memory");
    }
    asm volatile("barrier.cluster.arrive.release.aligned;" ::: "memory");
    if (tid >= 64 && tid < 70) {
        s_tgt[tid - 64] = ((ld_acquire(&g_bar[tid - 64]) >> 7) + 1u) << 7;
    } else if (tid >= 96 && tid < 112) {
        g_ssq[2048 + 16 * b + tid - 96] = 0.f;
    } else if (tid >= 128 && tid < 384) {
        int i = tid - 128;
        if (i < 128) ((float4*)g_ssqc)[b * 128 + i] = make_float4(0.f, 0.f, 0.f, 0.f);
    } else if (tid >= 416) {
        int i = tid - 416;
        int ps = i < 64 ? 64 * r + i : 32 * c + i - 64;
        float lr = ldbf(p.lam_re + ps), li = ldbf(p.lam_im + ps);
        float dt = __bfloat162float(__float2bfloat16(expf(ldbf(p.log_dt + ps))));
        float mag = expf(lr * dt), t = li * dt * 0.15915494309189535f, sn, cs;
        t -= rintf(t);
        sincospif(2.f * t, &sn, &cs);
        float er = mag * cs, ei = mag * sn;
        if (i < 64) {
            *(float2*)(sm + SM_LAM + i * 8) = make_float2(er, ei);
        } else {
            er -= 1.f;
            float inv = 1.f / (lr * lr + li * li);
            *(float2*)(sm + SM_RSTD + (i - 64) * 8) = make_float2((er * lr + ei * li) * inv, (ei * lr - er * li) * inv);
        }
    } else if (tid >= 384 && tid < 390) {
        const CUtensorMap* tm = tid == 384 ? &tm_x : tid == 385 ? &tm_bre : tid == 386 ? &tm_bim : tid == 387 ? &tm_cre : tid == 388 ? &tm_cim : &tm_col;
        asm volatile("prefetch.tensormap [%0];" ::"l"(tm) : "memory");
    }
    __syncwarp();
    asm volatile("barrier.cluster.wait.acquire.aligned;" ::: "memory");

    if (wg == 3) {
        asm volatile("setmaxnreg.dec.sync.aligned.u32 56;");
        if (w > 0) {
            bar_arrive(10, 480);
            if (w == 2) {
                const int kq = 2 * b + (lane >> 4), row = (kq >> 2) + 128 * (kq & 3) + 512 * ((lane >> 1) & 3) + 64 * (lane & 1);
                const char* src = (const char*)(((lane >> 3) & 1) ? p.w_i : p.w_r) + (size_t)row * 514;
                size_t a0 = (size_t)src & ~(size_t)15;
                int bytes = row == 2047 ? 512 : 544;
                asm volatile("cp.async.bulk.prefetch.L2.global [%0], %1;" ::"l"(a0), "r"(bytes) : "memory");
            }
#pragma unroll 1
            for (int i = tid - 448; i < 1536 + 128 && w > 1; i += 64) {
                if (i < 1536) g_P[(uint32_t)(b * 4 + i / 384) * 1024 + 640 + i % 384] = make_uint4(0, 0, 0, 0);
                else g_Ebuf[b * 128 + i - 1536] = make_float4(0.f, 0.f, 0.f, 0.f);
            }
#pragma unroll 1
            for (int task = tid - 448; task < 256 && w > 1; task += 64) {
                const int cb = task & 127, kq = 2 * b + (task >> 7), k1 = kq >> 2, qq = kq & 3;
                const unsigned short* wr_ = (const unsigned short*)p.w_r + (k1 + 128 * qq) * 257;
                const unsigned short* wi_ = (const unsigned short*)p.w_i + (k1 + 128 * qq) * 257;
                const int c0 = cb == 0 ? 256 : 2 * cb, c1 = 2 * cb + 1;
                uint32_t wf[16];
#pragma unroll
                for (int i = 0; i < 4; i++) {
                    int o = 512 * i * 257;
                    wf[2 * i] = (uint32_t)__ldg(wr_ + o + c0) | ((uint32_t)__ldg(wr_ + o + 64 * 257 + c0) << 16);
                    wf[2 * i + 1] = ((uint32_t)__ldg(wi_ + o + c0) | ((uint32_t)__ldg(wi_ + o + 64 * 257 + c0) << 16)) ^ 0x80008000u;
                    wf[8 + 2 * i] = (uint32_t)__ldg(wr_ + o + c1) | ((uint32_t)__ldg(wr_ + o + 64 * 257 + c1) << 16);
                    wf[8 + 2 * i + 1] = ((uint32_t)__ldg(wi_ + o + c1) | ((uint32_t)__ldg(wi_ + o + 64 * 257 + c1) << 16)) ^ 0x80008000u;
                }
                uint4* wd = g_Wfrag + (uint32_t)(cb * 1024 + kq);
#pragma unroll
                for (int i = 0; i < 4; i++) wd[i * 256] = make_uint4(wf[4 * i], wf[4 * i + 1], wf[4 * i + 2], wf[4 * i + 3]);
            }
            __syncwarp();
            if (w > 1) bar_arrive(11, 96);
            if (w == 3) {
#pragma unroll 1
                for (int it = 0; it < 8; it++) {
                    const int m = 4 * c + (it >> 1), d = 64 * r + m, ch = lane + 32 * (it & 1);
                    float v[8];
#pragma unroll
                    for (int e = 0; e < 8; e++) {
                        int j = 8 * ch + e, f, ph;
                        dft_fp(j, f, ph);
                        int a = (d * f + ph) & 511;
                        a = a >= 256 ? a - 512 : a;
                        float wj = j == 0 ? 0.f : (j == 1 ? 1.f / 512.f : 2.f / 512.f);
                        v[e] = wj * __cosf((float)a * (6.283185307179586f / 512.f));
                    }
                    uint32_t off = (uint32_t)(64 + r * 8 + (ch >> 3)) * 8192 + (m >> 3) * 1024 + (ch & 7) * 128 + (m & 7) * 16;
                    *(uint4*)(g_E + off) = make_uint4(pack_bf16(v[0], v[1]), pack_bf16(v[2], v[3]), pack_bf16(v[4], v[5]), pack_bf16(v[6], v[7]));
                }
                __syncwarp();
                if (lane == 0) { fence_async(); red_release(&g_bar[6], 1); }
                return;
            }
            if (w == 2) {
#pragma unroll 1
                for (int it = 0; it < 4; it++) {
                    const int hf = it & 1;
                    __syncwarp();
                    if (hf == 0) bar_sync(13, 288); else bar_sync(6, 416);
                    if (lane == 0) {
                        const uint32_t src = sb + SM_HH + par * 32768 + hf * 16384;
                        bulk_s2peer(mapa(src, par ^ 1), src, 16384, mapa(BAR(hf ? B_HPEER1 : B_HPEER), par ^ 1));
                    }
                }
                return;
            }
            {
                uint4 p0 = __ldg((const uint4*)p.dskip + 2 * lane), p1 = __ldg((const uint4*)p.dskip + 2 * lane + 1);
                uint32_t u[8] = {p0.x, p0.y, p0.z, p0.w, p1.x, p1.y, p1.z, p1.w};
#pragma unroll 1
                for (int jj = 0; jj < 4; jj++) {
                    int j = 64 * r + 4 * c + jj, f, ph;
                    dft_fp(j, f, ph);
                    float s = 0.f;
                    int idx = 16 * lane * f + ph;
#pragma unroll
                    for (int i = 0; i < 16; i++) {
                        int a = idx & 511;
                        idx += f;
                        a = a >= 256 ? a - 512 : a;
                        s += ((i & 1) ? bf_hi(u[i >> 1]) : bf_lo(u[i >> 1])) * __cosf((float)a * (6.283185307179586f / 512.f));
                    }
#pragma unroll
                    for (int o = 16; o; o >>= 1) s += __shfl_xor_sync(~0u, s, o);
                    if (lane == 0) g_Dh[j] = s;
                }
                if (lane == 0) red_release(&g_bar[5], 1);
                __syncwarp();
            }
            bar_sync(2, 416);
            if (lane == 0) {
                TX(5);
                asm volatile("cp.async.bulk.global.shared::cta.bulk_group [%0], [%1], 8192;" ::"l"(g_A1 + (uint32_t)(((c >> 1) * 8 + r) * 16384 + (c & 1) * 8192)),
                             "r"(sb + SM_B1ST) : "memory");
                asm volatile("cp.async.bulk.commit_group;" ::: "memory");
                fence_async();
                red_release(&g_bar[0], 1);
                TX(6);
                asm volatile("cp.async.bulk.wait_group 0;" ::: "memory");
                fence_async();
            }
            __syncwarp();
            bar_sync(11, 96);
            if (lane == 0) red_release(&g_bar[4], 1);
#pragma unroll 1
            for (int layer = 0; layer < 2; layer++) {
                __syncwarp();
                bar_sync(5, 416);
                if (lane == 0) {
                    TX(0 + 8 * layer);
                    tma_store_5d(&tm_col, 32 * (b & 1), 0, b >> 1, 0, layer, sb + SM_RAW);
                    asm volatile("cp.reduce.async.bulk.global.shared::cta.bulk_group.add.f32 [%0], [%1], 8192;" ::"l"(g_ssqc + (layer * 16 + (b & 15)) * 2048),
                                 "r"(sb + SM_SSQ) : "memory");
                    asm volatile("cp.async.bulk.commit_group;" ::: "memory");
                    asm volatile("cp.async.bulk.wait_group 0;" ::: "memory");
                    TX(1 + 8 * layer);
                    fence_async();
                    red_release(&g_bar[1 + 2 * layer], 1);
                    TX(2 + 8 * layer);
                }
            }
        } else if (tid == 384) {
#pragma unroll 1
            for (int kb = 0; kb < 8; kb++) {
                int s = kb < 6 ? kb : kb - 4;
                uint32_t dst = s < 2 ? sb + SM_A + 65536 + s * 24576 : sb + SM_X + (s - 2) * 24576;
                if (kb >= 6) mbar_wait_cluster(BAR(B_EMPTY0 + s), 0);
                uint32_t fb = BAR(B_FULL0 + kb);
                mbar_expect(fb, 24576);
                tma_5d_mc(dst + par * 8192, &tm_x, kb * 64, 0, 0, 8 * par, c, fb);
                tma_2d_mc(dst + 16384 + par * 4096, par ? &tm_bim : &tm_bre, kb * 64, 32 * c, fb);
                if (kb == 5) {
#pragma unroll 1
                    for (int k2 = par; k2 < 8; k2 += 2) {
                        asm volatile("cp.async.bulk.prefetch.tensor.2d.L2.global [%0, {%1,%2}];" ::"l"((c & 1) ? &tm_cim : &tm_cre), "r"(64 * (c >> 1)), "r"(k2 * 64) : "memory");
                        if (k2 < 4) {
                            asm volatile("cp.async.bulk.prefetch.tensor.5d.L2.global [%0, {%1,%2,%3,%4,%5}];" ::"l"(&tm_x), "r"((6 + (k2 >> 1)) * 64), "r"(0), "r"(0), "r"(8 * par), "r"(c) : "memory");
                            asm volatile("cp.async.bulk.prefetch.tensor.2d.L2.global [%0, {%1,%2}];" ::"l"(par ? &tm_bim : &tm_bre), "r"((6 + (k2 >> 1)) * 64), "r"(32 * c) : "memory");
                        }
                    }
                }
                if (kb == 7) {
                    mbar_wait_cluster(BAR(B_EMPTY0 + 0), 0);
                    mbar_wait_cluster(BAR(B_EMPTY0 + 1), 0);
                    mbar_expect(BAR(B_FULLC), 65536);
#pragma unroll 1
                    for (int k2 = par; k2 < 8; k2 += 2)
                        tma_2d_mc(sb + SM_A + 65536 + k2 * 8192, (c & 1) ? &tm_cim : &tm_cre, 64 * (c >> 1), k2 * 64, BAR(B_FULLC));
                }
            }
#pragma unroll 1
            for (int layer = 0; layer < 2; layer++) {
                wait_count(&g_bar[2 * layer], s_tgt[2 * layer]);
                TX(4 + 8 * layer);
                fence_async();
                mbar_expect(BAR(B_COL), 16384 + 8192);
                tma_5d(sb + SM_RAW, &tm_col, 32 * (b & 1), 0, b >> 1, 0, layer, BAR(B_COL));
                bulk_g2s(sb + SM_SSQ, g_ssq + layer * 2048, 8192, BAR(B_COL));
                if (layer == 0) {
                    wait_count(&g_bar[4], s_tgt[4]);
                    mbar_arrive(BAR(B_WRDY), 1);
                    fence_async();
                }
                if (layer == 0) mbar_wait(BAR(B_AFREE), 0);
                mbar_wait(BAR(B_COL), layer);
#pragma unroll 1
                for (int s = 0; s < 8; s++) {
                    if (layer == 1) mbar_wait(BAR(B_AEMPTY + s), 1);
                    mbar_expect(BAR(B_AFULL + s), 16384);
                    bulk_g2s(sb + SM_A + s * 16384, g_A1 + (uint32_t)(r * 8 + s) * 16384, 16384, BAR(B_AFULL + s));
                }
                if (layer == 1) wait_count(&g_bar[6], s_tgt[5]);
                wait_count(&g_bar[1 + 2 * layer], s_tgt[1 + 2 * layer]);
                TX(3 + 8 * layer);
                fence_async();
                const uint8_t* xsrc = g_X + (uint32_t)(layer * 16 + c) * 8 * 16384;
                const uint8_t* esrc = g_E + (uint32_t)(layer * 8 + own) * 8 * 8192;
                mbar_arrive(BAR(B_SSQ), 1);
                mbar_expect(BAR(B_HPEER), 16384);
                mbar_expect(BAR(B_HPEER1), 16384);
#pragma unroll 1
                for (int it = 0; it < 12; it++) {
                    if (it < 8) {
                        int st = it & 3, f = layer * 2 + (it >> 2);
                        if (f > 0) mbar_wait_cluster(BAR(B_XEMPTY + st), (f - 1) & 1);
                        mbar_expect(BAR(B_XFULL + st), 24576);
                        bulk_g2s_mc(sb + SM_X + st * 24576 + par * 8192, xsrc + (uint32_t)it * 16384 + par * 8192, 8192, BAR(B_XFULL + st));
                        bulk_g2s(sb + SM_X + st * 24576 + 16384, esrc + (uint32_t)it * 8192, 8192, BAR(B_XFULL + st));
                    }
                    if (it >= 4) {
                        int s = it - 4, tile = 4 * par + ((pi_ + 1 + (s >> 1)) & 3), sl = r ^ (s & 1);
                        mbar_wait(BAR(B_AEMPTY + s), 0);
                        uint32_t fb = BAR(B_AFULL + s), dst = sb + SM_A + s * 16384;
                        mbar_expect(fb, 16384);
                        if (layer == 1) {
                            tma_2d(dst, &tm_cre, 64 * sl, 64 * tile, fb);
                            tma_2d(dst + 8192, &tm_cim, 64 * sl, 64 * tile, fb);
                        } else {
                            bulk_g2s(dst, g_A2 + (uint32_t)(sl * 8 + tile) * 16384, 16384, fb);
                        }
                    }
                }
            }
        }
        return;
    }

    asm volatile("setmaxnreg.inc.sync.aligned.u32 152;");
    TS(0);
    if (wg == 0) TC(30);
    {
        const int f = 32 * r + lane;
        float cd, sd;
        __sincosf((float)f * (6.283185307179586f / 512.f), &sd, &cd);
        const uint32_t dst = sb + SM_A + (lane >> 2) * 1024 + (lane & 3) * 32;
#pragma unroll 1
        for (int ch = tid >> 5; ch < 64; ch += 12) {
            int a = (8 * ch * f) & 511;
            a = a >= 256 ? a - 512 : a;
            float cs, sn;
            __sincosf((float)a * (6.283185307179586f / 512.f), &sn, &cs);
            float cv[8], sv[8];
#pragma unroll
            for (int e = 0; e < 8; e++) {
                cv[e] = cs; sv[e] = -sn;
                float t = cs * cd - sn * sd;
                sn = sn * cd + cs * sd;
                cs = t;
            }
            uint4 o1 = make_uint4(pack_bf16(sv[0], sv[1]), pack_bf16(sv[2], sv[3]), pack_bf16(sv[4], sv[5]), pack_bf16(sv[6], sv[7]));
            if (f == 0) o1 = make_uint4(0xbf803f80u, 0xbf803f80u, 0xbf803f80u, 0xbf803f80u);
            uint32_t a0 = dst + (ch >> 3) * 8192 + (ch & 7) * 128;
            sts128(a0, make_uint4(pack_bf16(cv[0], cv[1]), pack_bf16(cv[2], cv[3]), pack_bf16(cv[4], cv[5]), pack_bf16(cv[6], cv[7])));
            sts128(a0 + 16, o1);
        }
    }
    fence_async_smem();
    bar_sync(10, 480);
    TS(1);
    {
        float acc[32];
        acc_def(acc);
        const int npos = 16 * r + 8 * (wg & 1) + 2 * w;
        float sh0 = 0.f, sh1 = 0.f, s0 = 0.f, s1 = 0.f, q0 = 0.f, q1 = 0.f;
#pragma unroll 1
        for (int kb = 0; kb < 8; kb++) {
            int s = kb < 6 ? kb : kb - 4;
            uint32_t slot = s < 2 ? sb + SM_A + 65536 + s * 24576 : sb + SM_X + (s - 2) * 24576;
            uint32_t src = slot + wg * 8192;
            mbar_wait(BAR(B_FULL0 + kb), 0);
            {
                uint32_t v0 = lds32(slot + npos * 128 + lane * 4), v1 = lds32(slot + npos * 128 + 128 + lane * 4);
                if (kb == 0) { sh0 = __shfl_sync(~0u, bf_lo(v0), 0); sh1 = __shfl_sync(~0u, bf_lo(v1), 0); }
                float a = bf_lo(v0) - sh0, bq = bf_hi(v0) - sh0, cq = bf_lo(v1) - sh1, d = bf_hi(v1) - sh1;
                s0 += a + bq; q0 += a * a + bq * bq; s1 += cq + d; q1 += cq * cq + d * d;
            }
            wg_fence();
#pragma unroll
            for (int ks = 0; ks < 4; ks++)
                wgmma_n64<0>(acc, desc_a(sb + SM_A + kb * 8192 + ks * 256), desc_k(src + ks * 32), 1);
            wg_commit();
            wg_wait<1>();
            if (kb > 0 && kb <= 4 && lane == 0) { mbar_arrive(BAR(B_EMPTY0 + kb - 1), 1); mbar_arrive_remote(mapa(BAR(B_EMPTY0 + kb - 1), par ^ 1)); }
        }
        wg_wait<0>();
        TS(2);
        if (wg < 2) {
            uint8_t* dst = g_X + (uint32_t)((c * 8 + r) * 16384 + w * 4096 + wg * 1024 + g * 16 + 4 * q);
#pragma unroll
            for (int i = 0; i < 8; i++) {
                *(uint32_t*)(dst + i * 128) = pack_bf16(acc[4 * i], acc[4 * i + 1]);
                *(uint32_t*)(dst + 2048 + i * 128) = pack_bf16(acc[4 * i + 2], acc[4 * i + 3]);
            }
#pragma unroll
            for (int o = 16; o; o >>= 1) {
                s0 += __shfl_xor_sync(~0u, s0, o); q0 += __shfl_xor_sync(~0u, q0, o);
                s1 += __shfl_xor_sync(~0u, s1, o); q1 += __shfl_xor_sync(~0u, q1, o);
            }
            if (lane == 0) *(float2*)(g_ssq + 128 * c + npos) = make_float2(fmaxf(q0 - s0 * s0 * (1.f / 512.f), 0.f), fmaxf(q1 - s1 * s1 * (1.f / 512.f), 0.f));
        } else {
            uint8_t* dst = sm + SM_B1ST + w * 256 + q * 32 + g * 2;
            const float wj0 = (r == 0 && w == 0 && g < 2) ? (g == 0 ? 0.f : 1.f / 512.f) : 2.f / 512.f;
#pragma unroll
            for (int i = 0; i < 4; i++) {
#pragma unroll
                for (int e = 0; e < 2; e++) {
                    float2 cf = *(const float2*)(sm + SM_RSTD + (8 * i + 2 * q + e) * 8);
#pragma unroll
                    for (int h = 0; h < 2; h++) {
                        float wj = h == 0 ? wj0 : 2.f / 512.f;
                        float pr = acc[4 * i + 2 * h + e] * wj, pi = acc[16 + 4 * i + 2 * h + e] * wj;
                        uint8_t* d2 = dst + i * 2048 + h * 128 + e * 16;
                        *(__nv_bfloat16*)(d2) = __float2bfloat16(cf.x * pr - cf.y * pi);
                        *(__nv_bfloat16*)(d2 + 1024) = __float2bfloat16(cf.x * pi + cf.y * pr);
                    }
                }
            }
            fence_async_smem();
        }
        bar_sync(2, 416);
        TS(3);
    }

    if (wg == 2) {
        {
            const int m = 4 * c + w, jp = 64 * r + m;
            int fp, php;
            dft_fp(jp, fp, php);
            const __nv_bfloat16* dh = (const __nv_bfloat16*)(sm + SM_RSTD);
            if (tid == 256) wait_count(&g_bar[5], s_tgt[5]);
            bar_sync(3, 128);
            float4 d4 = __ldcg((const float4*)g_Dh + (tid - 256));
            *(uint2*)(sm + SM_RSTD + (tid - 256) * 8) = make_uint2(pack_bf16(d4.x, d4.y), pack_bf16(d4.z, d4.w));
            bar_sync(3, 128);
#pragma unroll 1
            for (int it = 0; it < 2; it++) {
                const int ch = lane + 32 * it;
                float v[8];
#pragma unroll
                for (int e = 0; e < 8; e++) {
                    int j = 8 * ch + e, f, ph;
                    dft_fp(j, f, ph);
                    float wj = j == 0 ? 0.f : (j == 1 ? 1.f / 512.f : 2.f / 512.f);
                    float gsum = 0.f;
#pragma unroll
                    for (int sgn = 0; sgn < 2; sgn++) {
                        int mm = (sgn ? f - fp : f + fp) & 511, pp = (sgn ? ph - php : ph + php) & 511;
                        if (mm > 256) { mm = 512 - mm; pp = (512 - pp) & 511; }
                        int odd = (pp >> 7) & 1;
                        float t = __bfloat162float(dh[mm == 256 ? 1 : 2 * mm + odd]);
                        if (odd && (mm & 255) == 0) t = 0.f;
                        gsum += (pp & 256) ? -t : t;
                    }
                    v[e] = 0.5f * wj * gsum;
                }
                uint32_t off = (uint32_t)(r * 8 + (ch >> 3)) * 8192 + (m >> 3) * 1024 + (ch & 7) * 128 + (m & 7) * 16;
                *(uint4*)(g_E + off) = make_uint4(pack_bf16(v[0], v[1]), pack_bf16(v[2], v[3]), pack_bf16(v[4], v[5]), pack_bf16(v[6], v[7]));
            }
        }
        float acc[32];
        acc_def(acc);
        mbar_wait(BAR(B_FULLC), 0);
        wg_fence();
#pragma unroll 1
        for (int kb = 0; kb < 8; kb++) {
#pragma unroll
            for (int ks = 0; ks < 4; ks++)
                wgmma_n64<1>(acc, desc_a(sb + SM_A + kb * 8192 + ks * 256), desc_mn(sb + SM_A + 65536 + kb * 8192 + ks * 2048, 8192), 1);
            wg_commit();
        }
        wg_wait<0>();
        fence_async_smem();
        if (lane == 0) mbar_arrive(BAR(B_AFREE), 1);
        uint8_t* dst = g_A2 + (uint32_t)(((c >> 1) * 8 + r) * 16384 + (c & 1) * 8192 + w * 2048 + g * 16 + 4 * q);
#pragma unroll
        for (int i = 0; i < 8; i++) {
            *(uint32_t*)(dst + i * 128) = pack_bf16(acc[4 * i], acc[4 * i + 1]);
            *(uint32_t*)(dst + 1024 + i * 128) = pack_bf16(acc[4 * i + 2], acc[4 * i + 3]);
        }
    }

#pragma unroll 1
    for (int layer = 0; layer < 2; layer++) {
        if (wg < 2) {
            const int n1 = 32 * wg + 8 * w + g;
            const int ct = n1 >> 2;
            gen_col_consts(sb, tid);
            uint32_t tr2[4], ti2[4], tn2[4];
#pragma unroll
            for (int i = 0; i < 4; i++) {
                float cr[2], ci[2];
#pragma unroll
                for (int e = 0; e < 2; e++) {
                    int a = (n1 * (8 * i + 2 * q + e)) & 2047;
                    a = a >= 1024 ? a - 2048 : a;
                    float ang = (float)a * (-6.283185307179586f / 2048.f);
                    cr[e] = __cosf(ang); ci[e] = __sinf(ang);
                }
                tr2[i] = pack_bf16(cr[0], cr[1]); ti2[i] = pack_bf16(ci[0], ci[1]); tn2[i] = ti2[i] ^ 0x80008000u;
            }
            mbar_wait(BAR(B_COL), layer);
            TS(4 + 12 * layer);
            if (wg == 0) TC(0 + 10 * layer);
            const uint32_t rw0 = sb + SM_RAW + ct * 1024 + q * 64 + ((q >> 1) << 4) + (g & 3) * 4, rw1 = rw0 ^ 16;
            const int pos0 = 128 * ct + 8 * q + 2 * (g & 3);
            const int sw = b == 0 ? 1 : 0;
            uint32_t xr[4][4];
            const uint32_t st0 = sb + SM_H + (n1 >> 3) * 1024 + g * 16 + 4 * q;
#pragma unroll
            for (int i = 0; i < 4; i++) {
                float2 sq = *(const float2*)(sm + SM_SSQ + (pos0 + 32 * i) * 4);
                const uint32_t rs2 = pack_bf16(rsqrtf(sq.x * (1.f / 512.f) + 1e-5f), rsqrtf(sq.y * (1.f / 512.f) + 1e-5f));
#pragma unroll
                for (int jj = 0; jj < 4; jj++) {
                    const int K = jj ^ (2 * (i & 1));
                    uint32_t a = ((K & 1) ? rw1 : rw0) + i * 256 + (K & 2) * 16;
                    if (jj < 2) a ^= sw << 4;
                    uint32_t v = lds32(a);
                    xr[jj][i] = v;
                    uint32_t o = hmul2(v, rs2);
                    if (jj == 1 && sw) o = 0u;
                    sts32(st0 + (jj & 1) * 8192 + (4 * (jj >> 1) + i) * 128, o);
                }
            }
            if (wg == 0) TC(1 + 10 * layer);
            fence_async_smem();
            bar_sync(1, 256);
            float acc[32];
            const uint32_t s1a = sb + SM_X + wg * 16384, s2b = sb + SM_X + 32768;
            wg_fence();
#pragma unroll
            for (int ks = 0; ks < 8; ks++)
                wgmma_n64<1>(acc, desc_a(s1a + (ks >> 2) * 8192 + (ks & 3) * 256), desc_b<64>(sb + SM_H + ks * 2048), ks != 0);
            wg_commit();
            mbar_wait(BAR(B_WRDY), 0);
            uint32_t wf[16];
            {
                const uint4* ws = g_Wfrag + (uint32_t)(b * 1024 + n1 * 4 + q);
#pragma unroll
                for (int i = 0; i < 4; i++) {
                    uint4 v = __ldcg(ws + i * 256);
                    wf[4 * i] = v.x; wf[4 * i + 1] = v.y; wf[4 * i + 2] = v.z; wf[4 * i + 3] = v.w;
                }
            }
            wg_wait<0>();
            if (wg == 0) TC(2 + 10 * layer);
            uint32_t are[2][4], aim[2][4];
#pragma unroll
            for (int col = 0; col < 2; col++) {
#pragma unroll
                for (int i = 0; i < 4; i++) {
                    int o = 4 * (4 * col + i);
                    uint32_t zr = pack_bf16(acc[o], acc[o + 1]), zi = pack_bf16(acc[o + 2], acc[o + 3]);
                    are[col][i] = hfma2(zr, tr2[i], hmul2(zi, tn2[i]));
                    aim[col][i] = hfma2(zr, ti2[i], hmul2(zi, tr2[i]));
                }
            }
            wg_fence();
#pragma unroll
            for (int ks = 0; ks < 2; ks++)
                wgmma_n64_rs(acc, are[0][2 * ks], are[1][2 * ks], are[0][2 * ks + 1], are[1][2 * ks + 1], desc_b<64>(s2b + ks * 2048), ks != 0);
#pragma unroll
            for (int ks = 0; ks < 2; ks++)
                wgmma_n64_rs(acc, aim[0][2 * ks], aim[1][2 * ks], aim[0][2 * ks + 1], aim[1][2 * ks + 1], desc_b<64>(s2b + 4096 + ks * 2048), 1);
            wg_commit();
            wg_wait<0>();
            if (wg == 0) TC(3 + 10 * layer);
#pragma unroll
            for (int col = 0; col < 2; col++) {
#pragma unroll
                for (int i = 0; i < 4; i++) {
                    uint32_t wr = wf[col * 8 + 2 * i], wn = wf[col * 8 + 2 * i + 1];
                    uint32_t zr = pack_bf16(acc[4 * i + 2 * col], acc[4 * i + 2 * col + 1]);
                    uint32_t zi = pack_bf16(acc[16 + 4 * i + 2 * col], acc[16 + 4 * i + 2 * col + 1]);
                    are[col][i] = hfma2(zr, wr, hmul2(zi, wn));
                    aim[col][i] = hfma2(zr, wn, hmul2(zi ^ 0x80008000u, wr));
                }
            }
            wg_fence();
#pragma unroll
            for (int ks = 0; ks < 2; ks++)
                wgmma_n64_rs(acc, are[0][2 * ks], are[1][2 * ks], are[0][2 * ks + 1], are[1][2 * ks + 1], desc_b<64>(s2b + ks * 2048), ks != 0);
#pragma unroll
            for (int ks = 0; ks < 2; ks++)
                wgmma_n64_rs(acc, aim[0][2 * ks], aim[1][2 * ks], aim[0][2 * ks + 1], aim[1][2 * ks + 1], desc_b<64>(s2b + 4096 + ks * 2048), 1);
            wg_commit();
            wg_wait<0>();
            if (wg == 0) TC(4 + 10 * layer);
#pragma unroll
            for (int col = 0; col < 2; col++) {
#pragma unroll
                for (int i = 0; i < 4; i++) {
                    uint32_t zr = pack_bf16(acc[4 * i + 2 * col], acc[4 * i + 2 * col + 1]);
                    uint32_t zi = pack_bf16(acc[16 + 4 * i + 2 * col], acc[16 + 4 * i + 2 * col + 1]);
                    sts32(st0 + 16384 + (4 * col + i) * 128, hfma2(zr, tr2[i], hmul2(zi, tn2[i])));
                    sts32(st0 + 16384 + 8192 + (4 * col + i) * 128, hfma2(zr, ti2[i], hmul2(zi, tr2[i])));
                }
            }
            if (wg == 0) TC(5 + 10 * layer);
            fence_async_smem();
            bar_sync(1, 256);
            wg_fence();
#pragma unroll
            for (int ks = 0; ks < 8; ks++)
                wgmma_n64<1>(acc, desc_a(s1a + (ks >> 2) * 8192 + (ks & 3) * 256), desc_b<64>(sb + SM_H + 16384 + ks * 2048), ks != 0);
            wg_commit();
            wg_wait<0>();
            if (wg == 0) TC(6 + 10 * layer);
            const float sc = 1.f / 2048.f;
            const float sci0 = sw ? 0.f : -sc;
            const float wr0 = sw ? 0.5f : 1.f, wi0 = sw ? 0.f : 1.f;
#pragma unroll
            for (int i = 0; i < 4; i++) {
                float ss0, ss1;
#pragma unroll
                for (int col = 0; col < 2; col++) {
                    int o = 4 * (4 * col + i);
                    uint32_t vr = xr[2 * col][i], vi = xr[2 * col + 1][i];
                    float si = col == 0 ? sci0 : -sc;
                    uint32_t nr = pack_bf16(fmaf(acc[o], sc, bf_lo(vr)), fmaf(acc[o + 1], sc, bf_hi(vr)));
                    uint32_t ni = pack_bf16(fmaf(acc[o + 2], si, bf_lo(vi)), fmaf(acc[o + 3], si, bf_hi(vi)));
                    float a0 = bf_lo(nr), a1 = bf_hi(nr), b0 = bf_lo(ni), b1 = bf_hi(ni);
                    if (col == 0) {
                        ss0 = wr0 * a0 * a0 + wi0 * b0 * b0;
                        ss1 = wr0 * a1 * a1 + wi0 * b1 * b1;
                    } else {
                        ss0 += a0 * a0 + b0 * b0;
                        ss1 += a1 * a1 + b1 * b1;
                    }
                    const int K = (2 * col) ^ (2 * (i & 1));
                    uint32_t a = rw0 + i * 256 + K * 16;
                    if (col == 0) a ^= sw << 4;
                    sts32(a, nr);
                    sts32(a ^ 16, ni);
                }
                *(float2*)(sm + SM_SSQ + (pos0 + 32 * i) * 4) = make_float2(ss0 * (2.f / 512.f), ss1 * (2.f / 512.f));
            }
            fence_async_smem();
        }
        TS(5 + 12 * layer);
        if (wg == 0) TC(7 + 10 * layer);
        bar_arrive(5, 416);

        float acc[64];
        float* s_rstd = (float*)(sm + SM_RSTD);
        float* s_mean = (float*)(sm + SM_MEAN);
        const unsigned epoch = s_tgt[0] >> 7;
        const uint32_t pt3 = 1u + (2u * epoch + layer) % 3u;
        const uint32_t ptag = (pt3 & 1u) | ((pt3 & 2u) << 15);
        const uint64_t dstep = layer == 0 ? 16 : 2;
        auto c_desc = [&](int s) { return layer == 0 ? desc_a(sb + SM_A + s * 16384) : desc_k(sb + SM_A + s * 16384); };
        if (wg < 2) {
            const int prow = 32 * wg + 8 * w + g;
            const float2 l1 = *(const float2*)(sm + SM_LAM + prow * 8);
            float lr32 = l1.x, li32 = l1.y;
#pragma unroll
            for (int i = 0; i < 5; i++) { float t = lr32 * lr32 - li32 * li32; li32 = 2.f * lr32 * li32; lr32 = t; }
            float lr128 = lr32, li128 = li32;
#pragma unroll
            for (int i = 0; i < 2; i++) { float t = lr128 * lr128 - li128 * li128; li128 = 2.f * lr128 * li128; lr128 = t; }
            const float lr1 = l1.x, li1 = l1.y;
            acc_def(acc);
#pragma unroll 1
            for (int kb = 0; kb < 8; kb++) {
                mbar_wait(BAR(B_AFULL + kb), 0);
                mbar_wait(BAR(B_XFULL + (kb & 3)), (kb >> 2) & 1);
                wg_fence();
#pragma unroll
                for (int ks = 0; ks < 4; ks++)
                    wgmma_n128<1>(acc, desc_a(sb + SM_A + kb * 16384 + wg * 8192 + ks * 256),
                                  desc_b<128>(sb + SM_X + (kb & 3) * 24576 + ks * 4096), 1);
                wg_commit();
                wg_wait<1>();
                if (kb > 0 && lane == 0) {
                    mbar_arrive(BAR(B_AEMPTY + kb - 1), 1); mbar_arrive(BAR(B_XEMPTY + ((kb - 1) & 3)), 1);
                    mbar_arrive_remote(mapa(BAR(B_XEMPTY + ((kb - 1) & 3)), par ^ 1));
                }
            }
            wg_wait<0>();
            if (lane == 0) {
                mbar_arrive(BAR(B_AEMPTY + 7), 1); mbar_arrive(BAR(B_XEMPTY + 3), 1);
                mbar_arrive_remote(mapa(BAR(B_XEMPTY + 3), par ^ 1)); mbar_arrive_remote(mapa(BAR(B_RFREE), par ^ 1));
            }
            bar_arrive(14, 384);
            TS(6 + 12 * layer);
            bar_sync(4, 384);
            TS(7 + 12 * layer);
            float er = 0.f, ei = 0.f;
#pragma unroll
            for (int i = 0; i < 16; i++) {
                float2 rs = *(const float2*)(s_rstd + 128 + 8 * i + 2 * q);
                acc[4 * i] *= rs.x; acc[4 * i + 1] *= rs.y; acc[4 * i + 2] *= rs.x; acc[4 * i + 3] *= rs.y;
                float nr = lr1 * er - li1 * ei + acc[4 * i], ni = lr1 * ei + li1 * er + acc[4 * i + 2];
                er = lr1 * nr - li1 * ni + acc[4 * i + 1];
                ei = lr1 * ni + li1 * nr + acc[4 * i + 3];
            }
            float cr = 0.f, ci = 0.f, tr = 0.f, ti = 0.f;
#pragma unroll
            for (int qq = 0; qq < 4; qq++) {
                float xr_ = __shfl_sync(~0u, er, (lane & ~3) | qq), xi_ = __shfl_sync(~0u, ei, (lane & ~3) | qq);
                if (qq == q) { cr = tr; ci = ti; }
                float nr = lr32 * tr - li32 * ti + xr_, ni = lr32 * ti + li32 * tr + xi_;
                tr = nr; ti = ni;
            }
            float4* eb = g_Ebuf + (uint32_t)(layer * 16 * 512 + 64 * r + prow);
            if (q == 0 && c < 15) st_relaxed_f4(eb + c * 512, make_float4(tr, ti, __uint_as_float(epoch), 0.f));
            TS(8 + 12 * layer);
            float pr[4], pi[4];
            {
                unsigned n = 0;
                bool ok;
#pragma unroll 1
                do {
                    ok = true;
#pragma unroll
                    for (int k = 0; k < 4; k++) {
                        float4 v = make_float4(0.f, 0.f, __uint_as_float(epoch), 0.f);
                        if (4 * k + q < c) v = ld_relaxed_f4(eb + (4 * k + q) * 512);
                        pr[k] = v.x; pi[k] = v.y;
                        ok = ok && __float_as_uint(v.z) == epoch;
                    }
                } while (!ok && ++n < SPIN_LIMIT);
            }
            __syncwarp();
            TS(9 + 12 * layer);
            float hr = 0.f, hi = 0.f;
#pragma unroll
            for (int cc = 0; cc < 15; cc++) {
                float xr_ = __shfl_sync(~0u, pr[cc >> 2], (lane & ~3) | (cc & 3)), xi_ = __shfl_sync(~0u, pi[cc >> 2], (lane & ~3) | (cc & 3));
                if (cc < c) {
                    float nr = lr128 * hr - li128 * hi + xr_, ni = lr128 * hi + li128 * hr + xi_;
                    hr = nr; hi = ni;
                }
            }
#pragma unroll
            for (int qq = 0; qq < 3; qq++) {
                if (qq < q) { float nr = lr32 * hr - li32 * hi, ni = lr32 * hi + li32 * hr; hr = nr; hi = ni; }
            }
            er = cr + hr; ei = ci + hi;
            bar_sync(7, 384);
            mbar_wait_cluster(BAR(B_RFREE), layer);
            const uint32_t ha = sb + SM_HH + par * 32768 + (prow >> 3) * 1024 + g * 16 + 4 * q;
#pragma unroll
            for (int i = 0; i < 16; i++) {
                float nr = lr1 * er - li1 * ei + acc[4 * i], ni = lr1 * ei + li1 * er + acc[4 * i + 2];
                er = lr1 * nr - li1 * ni + acc[4 * i + 1];
                ei = lr1 * ni + li1 * nr + acc[4 * i + 3];
                sts32(ha + (i >> 3) * 16384 + (i & 7) * 128, pack_bf16(nr, er));
                sts32(ha + (i >> 3) * 16384 + 8192 + (i & 7) * 128, pack_bf16(ni, ei));
                if (i == 7) { fence_async_smem(); bar_arrive(13, 288); }
            }
            fence_async_smem();
            acc_def(acc);
            float acc2[32];
            acc_def(acc2);
            TS(10 + 12 * layer);
            bar_sync(6, 416);
            TS(11 + 12 * layer);
            float (&a0)[32] = *reinterpret_cast<float (*)[32]>(&acc[0]);
            float (&a1)[32] = *reinterpret_cast<float (*)[32]>(&acc[32]);
            auto tile_mma = [&](float (&d)[32], int u) {
#pragma unroll 1
                for (int k = 0; k < 2; k++) {
                    const uint32_t hb = sb + SM_HH + (par ^ k) * 32768 + wg * 16384;
                    if (k == 1) mbar_wait(BAR(wg ? B_HPEER1 : B_HPEER), layer);
                    mbar_wait(BAR(B_AFULL + 2 * u + k), 1);
                    const uint64_t da = c_desc(2 * u + k);
                    wg_fence();
#pragma unroll
                    for (int ks = 0; ks < 4; ks++) wgmma_n64s<1>(d, da + ks * dstep, desc_b<64>(hb + ks * 2048), 1);
#pragma unroll
                    for (int ks = 0; ks < 4; ks++) wgmma_n64s<-1>(d, da + 512 + ks * dstep, desc_b<64>(hb + 8192 + ks * 2048), 1);
                }
                wg_commit();
            };
            auto tile_ship = [&](float (&d)[32], int u) {
                uint4* dst = g_P + (uint32_t)(((c * 8 + 2 * ((pi_ + 1 + u) & 3) + par) * 4 + pi_) * 1024 + wg * 512 + (tid & 127));
#pragma unroll
                for (int i = 0; i < 4; i++)
                    dst[i * 128] = make_uint4((pack_bf16(d[8 * i], d[8 * i + 1]) & 0xfffefffeu) | ptag, pack_bf16(d[8 * i + 2], d[8 * i + 3]),
                                              pack_bf16(d[8 * i + 4], d[8 * i + 5]), pack_bf16(d[8 * i + 6], d[8 * i + 7]));
            };
            tile_mma(a0, 0);
            if ((tid & 127) == 0) mbar_arrive_remote(mapa(BAR(B_HDONE), par ^ 1));
            __syncwarp();
            tile_mma(a1, 1);
            wg_wait<1>();
            tile_ship(a0, 0);
            tile_mma(acc2, 2);
            bar_arrive(12, 384);
            wg_wait<1>();
            tile_ship(a1, 1);
            wg_wait<0>();
            tile_ship(acc2, 2);
            if (lane < 6) mbar_arrive(BAR(B_AEMPTY + lane), 1);
            TS(12 + 12 * layer);
        } else {
            const int t2 = tid - 256;
            const uint8_t* ximg = g_X + (uint32_t)layer * 16 * 8 * 16384;
            mbar_wait(BAR(B_SSQ), layer);
            TS(6 + 12 * layer);
            {
                float tot = 0.f;
#pragma unroll
                for (int i = 0; i < 16; i++) tot += __ldcg(g_ssqc + (layer * 16 + i) * 2048 + 128 * c + t2);
                float rs = rsqrtf(tot * (1.f / 512.f) + 1e-5f);
                s_rstd[t2] = rs;
                s_rstd[128 + t2] = 2.f * rs;
                if (layer == 0) s_mean[t2] = 0.f;
                if (layer == 1) {
                    unsigned short u = __ldcg((const unsigned short*)(ximg + (uint32_t)(c * 8 * 16384 + (t2 >> 3) * 128 + (t2 & 7) * 2)));
                    s_mean[t2] = __uint_as_float((uint32_t)u << 16) * (1.f / 512.f);
                }
            }
            TS(7 + 12 * layer);
            bar_arrive(4, 384);
            acc_def(acc);
#pragma unroll 1
            for (int kb = 0; kb < 8; kb++) {
                if (kb == 4) {
                    wg_wait<0>();
                    if (lane == 0) { mbar_arrive(BAR(B_XEMPTY + 3), 1); mbar_arrive_remote(mapa(BAR(B_XEMPTY + 3), par ^ 1)); }
                    bar_sync(14, 384);
                }
                mbar_wait(BAR(B_XFULL + (kb & 3)), (kb >> 2) & 1);
                wg_fence();
#pragma unroll
                for (int ks = 0; ks < 4; ks++)
                    wgmma_n128<1>(acc, desc_a(sb + SM_X + (kb & 3) * 24576 + 16384 + ks * 256), desc_b<128>(sb + SM_X + (kb & 3) * 24576 + ks * 4096), 1);
                wg_commit();
                wg_wait<1>();
                if ((kb & 3) != 0 && lane == 0) { mbar_arrive(BAR(B_XEMPTY + ((kb - 1) & 3)), 1); mbar_arrive_remote(mapa(BAR(B_XEMPTY + ((kb - 1) & 3)), par ^ 1)); }
            }
            wg_wait<0>();
            if (lane == 0) { mbar_arrive(BAR(B_XEMPTY + 3), 1); mbar_arrive_remote(mapa(BAR(B_XEMPTY + 3), par ^ 1)); mbar_arrive_remote(mapa(BAR(B_RFREE), par ^ 1)); }
            bar_arrive(7, 384);
            bar_sync(3, 128);
            TS(9 + 12 * layer);
            const int m0 = 16 * w + g;
            const uint32_t xoff = (uint32_t)((c * 8 + own) * 16384 + w * 4096 + g * 16 + 4 * q);
            if (layer == 0) {
                const uint8_t* xs = g_X + xoff;
#pragma unroll
                for (int i = 0; i < 16; i++) {
                    float2 rs = *(const float2*)(s_rstd + 8 * i + 2 * q);
                    uint32_t x0v = __ldcg((const uint32_t*)(xs + i * 128)), x1v = __ldcg((const uint32_t*)(xs + 2048 + i * 128));
                    acc[4 * i] = acc[4 * i] * rs.x + bf_lo(x0v);
                    acc[4 * i + 1] = acc[4 * i + 1] * rs.y + bf_hi(x0v);
                    acc[4 * i + 2] = acc[4 * i + 2] * rs.x + bf_lo(x1v);
                    acc[4 * i + 3] = acc[4 * i + 3] * rs.y + bf_hi(x1v);
                }
            } else {
                float d0 = ldbf(p.dskip + 64 * own + m0), d1 = ldbf(p.dskip + 64 * own + m0 + 8);
#pragma unroll
                for (int i = 0; i < 16; i++) {
                    float2 rs = *(const float2*)(s_rstd + 8 * i + 2 * q);
                    float2 mn = *(const float2*)(s_mean + 8 * i + 2 * q);
                    acc[4 * i] = acc[4 * i] * (1.f + rs.x * d0) + mn.x;
                    acc[4 * i + 1] = acc[4 * i + 1] * (1.f + rs.y * d0) + mn.y;
                    acc[4 * i + 2] = acc[4 * i + 2] * (1.f + rs.x * d1) + mn.x;
                    acc[4 * i + 3] = acc[4 * i + 3] * (1.f + rs.y * d1) + mn.y;
                }
            }
            TS(10 + 12 * layer);
            bar_sync(6, 416);
            TS(11 + 12 * layer);
            {
                float (&a0)[32] = *reinterpret_cast<float (*)[32]>(&acc[0]);
                float (&a1)[32] = *reinterpret_cast<float (*)[32]>(&acc[32]);
#pragma unroll 1
                for (int k = 0; k < 2; k++) {
                    const uint32_t hb = sb + SM_HH + (par ^ k) * 32768;
                    if (k == 1) {
                        mbar_wait(BAR(B_HPEER), layer);
                        mbar_wait(BAR(B_HPEER1), layer);
                        bar_sync(12, 384);
                    }
                    mbar_wait(BAR(B_AFULL + 6 + k), 1);
                    const uint64_t da = c_desc(6 + k);
                    wg_fence();
#pragma unroll
                    for (int ks = 0; ks < 4; ks++) {
                        wgmma_n64s<1>(a0, da + ks * dstep, desc_b<64>(hb + ks * 2048), 1);
                        wgmma_n64s<1>(a1, da + ks * dstep, desc_b<64>(hb + 16384 + ks * 2048), 1);
                    }
#pragma unroll
                    for (int ks = 0; ks < 4; ks++) {
                        wgmma_n64s<-1>(a0, da + 512 + ks * dstep, desc_b<64>(hb + 8192 + ks * 2048), 1);
                        wgmma_n64s<-1>(a1, da + 512 + ks * dstep, desc_b<64>(hb + 16384 + 8192 + ks * 2048), 1);
                    }
                    wg_commit();
                }
                wg_wait<0>();
            }
#pragma unroll
            for (int i = 0; i < 16; i++)
                *(float4*)(sm + SM_A + 6 * 16384 + i * 2048 + t2 * 16) = make_float4(acc[4 * i], acc[4 * i + 1], acc[4 * i + 2], acc[4 * i + 3]);
            TS(12 + 12 * layer);
        }
        {
            const int t = tid & 127;
            const int nch = wg == 2 ? 2 : 3;
            const uint4* pb = g_P + (uint32_t)((c * 8 + r) * 4 * 1024 + wg * 128 + t);
            uint4 v[3][3];
            unsigned n = 0;
#pragma unroll 1
            while (true) {
                if (lane == 31) {
#pragma unroll 1
                    while (true) {
                        uint32_t bad = 0;
#pragma unroll
                        for (int sx = 0; sx < 3; sx++) {
                            uint32_t t0;
                            asm volatile("ld.relaxed.gpu.global.u32 %0, [%1];" : "=r"(t0) : "l"(pb + ((pi_ + 1 + sx) & 3) * 1024 + (nch - 1) * 384) : "memory");
                            bad |= t0 ^ ptag;
                        }
                        if (!(bad & 0x00010001u) || ++n >= SPIN_LIMIT) break;
                    }
                }
                __syncwarp();
                uint32_t bad = 0;
#pragma unroll
                for (int k = 0; k < 3; k++)
#pragma unroll
                    for (int sx = 0; sx < 3; sx++) {
                        v[k][sx] = make_uint4(ptag, 0, 0, 0);
                        if (k < nch) v[k][sx] = ld_relaxed_u4(pb + ((pi_ + 1 + sx) & 3) * 1024 + k * 384);
                        bad |= v[k][sx].x ^ ptag;
                    }
                if (!__any_sync(~0u, bad & 0x00010001u) || ++n >= SPIN_LIMIT) break;
            }
            bar_sync(8, 384);
            TS(13 + 12 * layer);
            const int m0 = 16 * w + g;
            const float w0 = (own == 0 && m0 < 2) ? (m0 == 0 ? 0.f : 0.5f) : 1.f;
#pragma unroll
            for (int k = 0; k < 3; k++) {
                if (k < nch) {
                    const int i = wg + 3 * k;
                    float4 a = *(const float4*)(sm + SM_A + 6 * 16384 + (2 * i) * 2048 + t * 16);
                    float4 bq = *(const float4*)(sm + SM_A + 6 * 16384 + (2 * i + 1) * 2048 + t * 16);
#pragma unroll
                    for (int sx = 0; sx < 3; sx++) {
                        a.x += bf_lo(v[k][sx].x); a.y += bf_hi(v[k][sx].x); a.z += bf_lo(v[k][sx].y); a.w += bf_hi(v[k][sx].y);
                        bq.x += bf_lo(v[k][sx].z); bq.y += bf_hi(v[k][sx].z); bq.z += bf_lo(v[k][sx].w); bq.w += bf_hi(v[k][sx].w);
                    }
                    if (layer == 0) {
                        uint8_t* xd = g_X + (uint32_t)((16 * 8 + c * 8 + own) * 16384 + w * 4096 + g * 16 + 4 * q + i * 256);
                        uint32_t v0 = pack_bf16(a.x, a.y), v1 = pack_bf16(a.z, a.w), v2 = pack_bf16(bq.x, bq.y), v3 = pack_bf16(bq.z, bq.w);
                        *(uint32_t*)(xd) = v0; *(uint32_t*)(xd + 2048) = v1; *(uint32_t*)(xd + 128) = v2; *(uint32_t*)(xd + 2048 + 128) = v3;
                        float sq[4];
                        sq[0] = w0 * bf_lo(v0) * bf_lo(v0) + bf_lo(v1) * bf_lo(v1);
                        sq[1] = w0 * bf_hi(v0) * bf_hi(v0) + bf_hi(v1) * bf_hi(v1);
                        sq[2] = w0 * bf_lo(v2) * bf_lo(v2) + bf_lo(v3) * bf_lo(v3);
                        sq[3] = w0 * bf_hi(v2) * bf_hi(v2) + bf_hi(v3) * bf_hi(v3);
                        float u0 = (g & 1) ? sq[2] : sq[0], u1 = (g & 1) ? sq[3] : sq[1];
                        u0 += __shfl_xor_sync(~0u, (g & 1) ? sq[0] : sq[2], 4);
                        u1 += __shfl_xor_sync(~0u, (g & 1) ? sq[1] : sq[3], 4);
                        float z = (g & 2) ? u1 : u0;
                        z += __shfl_xor_sync(~0u, (g & 2) ? u0 : u1, 8);
                        z += __shfl_xor_sync(~0u, z, 16);
                        if (g < 4) atomicAdd(s_mean + 16 * i + 8 * (g & 1) + 2 * q + (g >> 1), z);
                    } else {
                        float* o = p.out + (uint32_t)((128 * c + 32 * q + 4 * i) * 512 + 64 * own + m0);
                        o[0] = a.x; o[512] = a.y; o[8] = a.z; o[512 + 8] = a.w;
                        o[1024] = bq.x; o[1536] = bq.y; o[1024 + 8] = bq.z; o[1536 + 8] = bq.w;
                    }
                }
            }
            if (wg < 2) mbar_wait_cluster(BAR(B_HDONE), layer);
            if (layer == 0) {
                fence_async_smem();
                bar_sync(9, 384);
                TS(14 + 12 * layer);
                if (wg == 2) {
                    atomicAdd(g_ssq + 2048 + 128 * c + t, s_mean[t] * (2.f / 512.f));
                    bar_sync(3, 128);
                    if (lane == 0) { mbar_arrive(BAR(B_AEMPTY + 6), 2); mbar_arrive(BAR(B_AEMPTY + 7), 2); }
                    if (t == 0) { fence_async(); red_release(&g_bar[2], 1); }
                }
            }
        }
        TS(15 + 12 * layer);
        if (wg == 0) TC(31);
    }
}

typedef CUresult (*EncFn)(CUtensorMap*, CUtensorMapDataType, cuuint32_t, void*, const cuuint64_t*, const cuuint64_t*,
                          const cuuint32_t*, const cuuint32_t*, CUtensorMapInterleave, CUtensorMapSwizzle,
                          CUtensorMapL2promotion, CUtensorMapFloatOOBfill);

void launch_impl(void* const* d_in, void* d_out, int stop) {
    static EncFn enc = nullptr;
    if (!enc) {
        void* fn = nullptr;
        cudaDriverEntryPointQueryResult qr;
        cudaGetDriverEntryPoint("cuTensorMapEncodeTiled", &fn, cudaEnableDefault, &qr);
        enc = (EncFn)fn;
        cudaFuncSetAttribute(fused_kernel, cudaFuncAttributeMaxDynamicSharedMemorySize, SM_TOTAL);
    }
    CUtensorMap tx, tbr, tbi, tcr, tci, tcol;
    {
        void* gx = nullptr;
        cudaGetSymbolAddress(&gx, g_X);
        cuuint64_t gd[5] = {64, 16, 64, 16, 2};
        cuuint64_t gs[4] = {128, 2048, 128 * 1024, 2048 * 1024};
        cuuint32_t bx[5] = {32, 16, 1, 16, 1};
        cuuint32_t es[5] = {1, 1, 1, 1, 1};
        enc(&tcol, CU_TENSOR_MAP_DATA_TYPE_BFLOAT16, 5, gx, gd, gs, bx, es, CU_TENSOR_MAP_INTERLEAVE_NONE,
            CU_TENSOR_MAP_SWIZZLE_64B, CU_TENSOR_MAP_L2_PROMOTION_NONE, CU_TENSOR_MAP_FLOAT_OOB_FILL_NONE);
    }
    {
        cuuint64_t gd[5] = {512, 2, 4, 16, 16};
        cuuint64_t gs[4] = {1024, 32 * 1024, 2 * 1024, 128 * 1024};
        cuuint32_t bx[5] = {64, 2, 4, 8, 1};
        cuuint32_t es[5] = {1, 1, 1, 1, 1};
        enc(&tx, CU_TENSOR_MAP_DATA_TYPE_BFLOAT16, 5, d_in[0], gd, gs, bx, es, CU_TENSOR_MAP_INTERLEAVE_NONE,
            CU_TENSOR_MAP_SWIZZLE_128B, CU_TENSOR_MAP_L2_PROMOTION_L2_128B, CU_TENSOR_MAP_FLOAT_OOB_FILL_NONE);
    }
    auto mk2 = [&](CUtensorMap* m, void* ptr, cuuint32_t rows) {
        cuuint64_t gd[2] = {512, 512};
        cuuint64_t gs[1] = {1024};
        cuuint32_t bx[2] = {64, rows};
        cuuint32_t es[2] = {1, 1};
        enc(m, CU_TENSOR_MAP_DATA_TYPE_BFLOAT16, 2, ptr, gd, gs, bx, es, CU_TENSOR_MAP_INTERLEAVE_NONE,
            CU_TENSOR_MAP_SWIZZLE_128B, CU_TENSOR_MAP_L2_PROMOTION_L2_128B, CU_TENSOR_MAP_FLOAT_OOB_FILL_NONE);
    };
    mk2(&tbr, d_in[6], 32);
    mk2(&tbi, d_in[7], 32);
    mk2(&tcr, d_in[8], 64);
    mk2(&tci, d_in[9], 64);
    Params p;
    p.x0 = (const __nv_bfloat16*)d_in[0];
    p.w_r = (const __nv_bfloat16*)d_in[1];
    p.w_i = (const __nv_bfloat16*)d_in[2];
    p.lam_re = (const __nv_bfloat16*)d_in[4];
    p.lam_im = (const __nv_bfloat16*)d_in[5];
    p.log_dt = (const __nv_bfloat16*)d_in[10];
    p.dskip = (const __nv_bfloat16*)d_in[11];
    p.out = (float*)d_out;
    p.stop = stop;
    cudaLaunchConfig_t cfg = {};
    cfg.gridDim = dim3(NCTA); cfg.blockDim = dim3(NTHREADS); cfg.dynamicSmemBytes = SM_TOTAL; cfg.stream = cudaStreamPerThread;
    cudaLaunchAttribute at[1];
    at[0].id = cudaLaunchAttributeClusterDimension;
    at[0].val.clusterDim.x = 2; at[0].val.clusterDim.y = 1; at[0].val.clusterDim.z = 1;
    cfg.attrs = at; cfg.numAttrs = 1;
    cudaLaunchKernelEx(&cfg, fused_kernel, tx, tbr, tbi, tcr, tci, tcol, p);
}

}

extern "C" void kernel_launch(void* const* d_in, const int* in_sizes, int n_in, void* d_out, int out_size) {
    (void)in_sizes; (void)n_in; (void)out_size;
    launch_impl(d_in, d_out, 100);
}
```

```cpp
#include <cuda_runtime.h>
#include <cuda_bf16.h>
#include <cuda.h>
#include <stdint.h>

namespace {

constexpr int NCTA = 128;
constexpr int NTHREADS = 512;
constexpr int SM_A = 0;
constexpr int SM_X = 131072;
constexpr int SM_H = 196608;
constexpr int SM_HH = SM_X + 32768;
constexpr int SM_M = 229376;
constexpr int SM_TOTAL = 232448;
constexpr int SM_BAR = SM_M;
constexpr int SM_TGT = SM_M + 360;
constexpr int SM_LAM = SM_M + 384;
constexpr int SM_TAB = SM_M + 896;
constexpr int SM_RSTD = SM_M + 1920;
constexpr int SM_MEAN = SM_TAB;
constexpr int SM_T64 = SM_M + 2944;
constexpr int SM_B1ST = SM_H + 24576;
constexpr int SM_RAW = SM_X + 40960;
constexpr int SM_SSQ = SM_X + 57344;
constexpr int B_FULL0 = 0;
constexpr int B_EMPTY0 = 8;
constexpr int B_FULLC = 12;
constexpr int B_AFULL = 13;
constexpr int B_AEMPTY = 21;
constexpr int B_XFULL = 29;
constexpr int B_XEMPTY = 33;
constexpr int B_AFREE = 37;
constexpr int B_COL = 38;
constexpr int B_SSQ = 39;
constexpr int B_HPEER = 40;
constexpr int B_RFREE = 41;
constexpr int B_HDONE = 42;
constexpr int B_WRDY = 43;
constexpr int B_HPEER1 = 44;
constexpr int NBARS = 45;

__device__ __align__(1024) uint8_t g_X[2 * 16 * 8 * 16384];
__device__ __align__(1024) uint8_t g_A1[8 * 8 * 16384];
__device__ __align__(1024) uint8_t g_A2[8 * 8 * 16384];
__device__ __align__(1024) uint8_t g_E[2 * 8 * 8 * 8192];
__device__ __align__(16) float g_ssq[2 * 2048];
__device__ __align__(16) float g_ssqc[2 * 16 * 2048];
__device__ __align__(16) float g_Dh[512];
__device__ __align__(16) uint4 g_Wfrag[128 * 4 * 256];
__device__ __align__(16) float4 g_Ebuf[2 * 16 * 512];
__device__ __align__(16) uint4 g_P[16 * 8 * 4 * 1024];
__device__ unsigned g_bar[8];
__device__ unsigned g_err;
#define TX(i)
#define TQ(i)
#define TS(i)
#define TC(i)

constexpr unsigned SPIN_LIMIT = 1u << 22;

__device__ __forceinline__ uint32_t s2u(const void* p) { return (uint32_t)__cvta_generic_to_shared(p); }
__device__ __forceinline__ void mbar_init(uint32_t a, uint32_t c) {
    asm volatile("mbarrier.init.shared::cta.b64 [%0], %1;" ::"r"(a), "r"(c) : "memory");
}
__device__ __forceinline__ void mbar_expect(uint32_t a, uint32_t bytes) {
    asm volatile("mbarrier.arrive.expect_tx.shared::cta.b64 _, [%0], %1;" ::"r"(a), "r"(bytes) : "memory");
}
__device__ __forceinline__ void mbar_arrive(uint32_t a, uint32_t cnt) {
    asm volatile("mbarrier.arrive.shared::cta.b64 _, [%0], %1;" ::"r"(a), "r"(cnt) : "memory");
}
__device__ __forceinline__ bool mbar_try(uint32_t a, uint32_t parity) {
    uint32_t ok;
    asm volatile("{\n.reg .pred p;\nmbarrier.try_wait.parity.shared::cta.b64 p, [%1], %2;\nselp.u32 %0, 1, 0, p;\n}"
                 : "=r"(ok) : "r"(a), "r"(parity) : "memory");
    return ok != 0;
}
__device__ __forceinline__ void mbar_wait(uint32_t a, uint32_t parity) {
    asm volatile("{\n.reg .pred p, q;\n.reg .u32 n;\nmov.u32 n, 0;\n"
                 "W_%=:\nmbarrier.try_wait.parity.shared::cta.b64 p, [%0], %1;\n@p bra D_%=;\n"
                 "add.u32 n, n, 1;\nsetp.lt.u32 q, n, 4194304;\n@q bra W_%=;\nD_%=:\n}" ::"r"(a), "r"(parity) : "memory");
}
__device__ __forceinline__ void bulk_g2s(uint32_t dst, const void* src, uint32_t bytes, uint32_t bar) {
    asm volatile("cp.async.bulk.shared::cluster.global.mbarrier::complete_tx::bytes [%0], [%1], %2, [%3];" ::"r"(dst),
                 "l"(src), "r"(bytes), "r"(bar) : "memory");
}
__device__ __forceinline__ void tma_2d(uint32_t dst, const CUtensorMap* m, int c0, int c1, uint32_t bar) {
    asm volatile("cp.async.bulk.tensor.2d.shared::cluster.global.mbarrier::complete_tx::bytes [%0], [%1, {%3,%4}], [%2];" ::"r"(dst),
                 "l"(m), "r"(bar), "r"(c0), "r"(c1) : "memory");
}
__device__ __forceinline__ void tma_5d(uint32_t dst, const CUtensorMap* m, int c0, int c1, int c2, int c3, int c4, uint32_t bar) {
    asm volatile("cp.async.bulk.tensor.5d.shared::cluster.global.mbarrier::complete_tx::bytes [%0], [%1, {%3,%4,%5,%6,%7}], [%2];" ::"r"(dst),
                 "l"(m), "r"(bar), "r"(c0), "r"(c1), "r"(c2), "r"(c3), "r"(c4) : "memory");
}
__device__ __forceinline__ void tma_2d_mc(uint32_t dst, const CUtensorMap* m, int c0, int c1, uint32_t bar) {
    asm volatile("cp.async.bulk.tensor.2d.shared::cluster.global.mbarrier::complete_tx::bytes.multicast::cluster [%0], [%1, {%3,%4}], [%2], %5;" ::"r"(dst),
                 "l"(m), "r"(bar), "r"(c0), "r"(c1), "h"((unsigned short)3) : "memory");
}
__device__ __forceinline__ void tma_5d_mc(uint32_t dst, const CUtensorMap* m, int c0, int c1, int c2, int c3, int c4, uint32_t bar) {
    asm volatile("cp.async.bulk.tensor.5d.shared::cluster.global.mbarrier::complete_tx::bytes.multicast::cluster [%0], [%1, {%3,%4,%5,%6,%7}], [%2], %8;" ::"r"(dst),
                 "l"(m), "r"(bar), "r"(c0), "r"(c1), "r"(c2), "r"(c3), "r"(c4), "h"((unsigned short)3) : "memory");
}
__device__ __forceinline__ void bulk_g2s_mc(uint32_t dst, const void* src, uint32_t bytes, uint32_t bar) {
    asm volatile("cp.async.bulk.shared::cluster.global.mbarrier::complete_tx::bytes.multicast::cluster [%0], [%1], %2, [%3], %4;" ::"r"(dst),
                 "l"(src), "r"(bytes), "r"(bar), "h"((unsigned short)3) : "memory");
}
__device__ __forceinline__ void tma_store_5d(const CUtensorMap* m, int c0, int c1, int c2, int c3, int c4, uint32_t src) {
    asm volatile("cp.async.bulk.tensor.5d.global.shared::cta.bulk_group [%0, {%2,%3,%4,%5,%6}], [%1];" ::"l"(m), "r"(src),
                 "r"(c0), "r"(c1), "r"(c2), "r"(c3), "r"(c4) : "memory");
}
__device__ __forceinline__ uint32_t lds32(uint32_t a) { uint32_t v; asm volatile("ld.shared.u32 %0, [%1];" : "=r"(v) : "r"(a) : "memory"); return v; }
__device__ __forceinline__ uint4 ld_relaxed_u4(const uint4* p) {
    uint4 v;
    asm volatile("ld.relaxed.gpu.global.v4.u32 {%0,%1,%2,%3}, [%4];" : "=r"(v.x), "=r"(v.y), "=r"(v.z), "=r"(v.w) : "l"(p) : "memory");
    return v;
}
__device__ __forceinline__ void fence_async() { asm volatile("fence.proxy.async.global;" ::: "memory"); }
__device__ __forceinline__ void red_relaxed(unsigned* p, unsigned v) {
    asm volatile("red.relaxed.gpu.global.add.u32 [%0], %1;" ::"l"(p), "r"(v) : "memory");
}
__device__ __forceinline__ uint32_t mapa(uint32_t a, uint32_t rank) {
    uint32_t d;
    asm("mapa.shared::cluster.u32 %0, %1, %2;" : "=r"(d) : "r"(a), "r"(rank));
    return d;
}
__device__ __forceinline__ void mbar_arrive_remote(uint32_t ra) {
    asm volatile("mbarrier.arrive.relaxed.cluster.shared::cluster.b64 _, [%0];" ::"r"(ra) : "memory");
}
__device__ __forceinline__ void mbar_wait_cluster(uint32_t a, uint32_t parity) {
    asm volatile("{\n.reg .pred p, q;\n.reg .u32 n;\nmov.u32 n, 0;\n"
                 "W_%=:\nmbarrier.try_wait.parity.acquire.cluster.shared::cta.b64 p, [%0], %1;\n@p bra D_%=;\n"
                 "add.u32 n, n, 1;\nsetp.lt.u32 q, n, 4194304;\n@q bra W_%=;\nD_%=:\n}" ::"r"(a), "r"(parity) : "memory");
}
__device__ __forceinline__ void bulk_s2peer(uint32_t rdst, uint32_t src, uint32_t bytes, uint32_t rbar) {
    asm volatile("cp.async.bulk.shared::cluster.shared::cta.mbarrier::complete_tx::bytes [%0], [%1], %2, [%3];" ::"r"(rdst),
                 "r"(src), "r"(bytes), "r"(rbar) : "memory");
}
__device__ __forceinline__ void fence_async_smem() { asm volatile("fence.proxy.async.shared::cta;" ::: "memory"); }
__device__ __forceinline__ void wg_fence() { asm volatile("wgmma.fence.sync.aligned;" ::: "memory"); }
__device__ __forceinline__ void wg_commit() { asm volatile("wgmma.commit_group.sync.aligned;" ::: "memory"); }
template <int N> __device__ __forceinline__ void wg_wait() { asm volatile("wgmma.wait_group.sync.aligned %0;" ::"n"(N) : "memory"); }
__device__ __forceinline__ void bar_sync(int id, int n) { asm volatile("bar.sync %0, %1;" ::"r"(id), "r"(n) : "memory"); }
__device__ __forceinline__ void bar_arrive(int id, int n) { asm volatile("bar.arrive %0, %1;" ::"r"(id), "r"(n) : "memory"); }
__device__ __forceinline__ unsigned ld_acquire(const unsigned* p) {
    unsigned v;
    asm volatile("ld.acquire.gpu.global.u32 %0, [%1];" : "=r"(v) : "l"(p) : "memory");
    return v;
}
__device__ __forceinline__ void red_release(unsigned* p, unsigned v) {
    asm volatile("red.release.gpu.global.add.u32 [%0], %1;" ::"l"(p), "r"(v) : "memory");
}
__device__ __forceinline__ void wait_count(const unsigned* p, unsigned target) {
    unsigned n = 0;
#pragma unroll 1
    while ((int)(ld_acquire(p) - target) < 0 && ++n < SPIN_LIMIT) {}
}
__device__ __forceinline__ float4 ld_relaxed_f4(const float4* p) {
    float4 v;
    asm volatile("ld.relaxed.gpu.global.v4.f32 {%0,%1,%2,%3}, [%4];" : "=f"(v.x), "=f"(v.y), "=f"(v.z), "=f"(v.w) : "l"(p) : "memory");
    return v;
}
__device__ __forceinline__ void st_relaxed_f4(float4* p, float4 v) {
    asm volatile("st.relaxed.gpu.global.v4.f32 [%0], {%1,%2,%3,%4};" ::"l"(p), "f"(v.x), "f"(v.y), "f"(v.z), "f"(v.w) : "memory");
}
__device__ __forceinline__ uint32_t pack_bf16(float lo, float hi) {
    uint32_t r;
    asm("cvt.rn.bf16x2.f32 %0, %1, %2;" : "=r"(r) : "f"(hi), "f"(lo));
    return r;
}
__device__ __forceinline__ uint32_t hmul2(uint32_t a, uint32_t b) {
    uint32_t r;
    asm("mul.rn.bf16x2 %0, %1, %2;" : "=r"(r) : "r"(a), "r"(b));
    return r;
}
__device__ __forceinline__ uint32_t hfma2(uint32_t a, uint32_t b, uint32_t c) {
    uint32_t r;
    asm("fma.rn.bf16x2 %0, %1, %2, %3;" : "=r"(r) : "r"(a), "r"(b), "r"(c));
    return r;
}
__device__ __forceinline__ float bf_lo(uint32_t v) { return __uint_as_float(v << 16); }
__device__ __forceinline__ float bf_hi(uint32_t v) { return __uint_as_float(v & 0xffff0000u); }
__device__ __forceinline__ void sts32(uint32_t a, uint32_t v) { asm volatile("st.shared.u32 [%0], %1;" ::"r"(a), "r"(v) : "memory"); }
__device__ __forceinline__ void sts128(uint32_t a, uint4 v) {
    asm volatile("st.shared.v4.u32 [%0], {%1,%2,%3,%4};" ::"r"(a), "r"(v.x), "r"(v.y), "r"(v.z), "r"(v.w) : "memory");
}

__device__ __forceinline__ uint64_t desc_ni(uint32_t addr, uint32_t lbo, uint32_t sbo) {
    return (uint64_t)((addr & 0x3FFFF) >> 4) | ((uint64_t)(lbo >> 4) << 16) | ((uint64_t)(sbo >> 4) << 32);
}
__device__ __forceinline__ uint64_t desc_a(uint32_t addr) { return desc_ni(addr, 128, 1024); }
template <int N> __device__ __forceinline__ uint64_t desc_b(uint32_t addr) { return desc_ni(addr, 16 * N, 128); }
__device__ __forceinline__ uint64_t desc_k(uint32_t addr) {
    return (uint64_t)((addr & 0x3FFFF) >> 4) | (1ull << 16) | (64ull << 32) | (1ull << 62);
}
__device__ __forceinline__ uint64_t desc_mn(uint32_t addr, uint32_t lbo) {
    return (uint64_t)((addr & 0x3FFFF) >> 4) | ((uint64_t)(lbo >> 4) << 16) | (64ull << 32) | (1ull << 62);
}

#define ACC8(d, o) "+f"(d[o + 0]), "+f"(d[o + 1]), "+f"(d[o + 2]), "+f"(d[o + 3]), "+f"(d[o + 4]), "+f"(d[o + 5]), "+f"(d[o + 6]), "+f"(d[o + 7])
template <int TB, int SA = 1>
__device__ __forceinline__ void wgmma_n128(float (&d)[64], uint64_t da, uint64_t db, int sd) {
    asm volatile(
        "{\n.reg .pred p;\nsetp.ne.b32 p, %66, 0;\n"
        "wgmma.mma_async.sync.aligned.m64n128k16.f32.bf16.bf16 "
        "{%0,%1,%2,%3,%4,%5,%6,%7,%8,%9,%10,%11,%12,%13,%14,%15,%16,%17,%18,%19,%20,%21,%22,%23,%24,%25,%26,%27,%28,%29,%30,%31,"
        "%32,%33,%34,%35,%36,%37,%38,%39,%40,%41,%42,%43,%44,%45,%46,%47,%48,%49,%50,%51,%52,%53,%54,%55,%56,%57,%58,%59,%60,%61,%62,%63},"
        " %64, %65, p, %68, 1, 0, %67;\n}"
        : ACC8(d, 0), ACC8(d, 8), ACC8(d, 16), ACC8(d, 24), ACC8(d, 32), ACC8(d, 40), ACC8(d, 48), ACC8(d, 56)
        : "l"(da), "l"(db), "r"(sd), "n"(TB), "n"(SA));
}
template <int N> __device__ __forceinline__ void acc_def(float (&d)[N]) {
#pragma unroll
    for (int i = 0; i < N; i++) d[i] = 0.f;
}
template <int TB>
__device__ __forceinline__ void wgmma_n64(float (&d)[32], uint64_t da, uint64_t db, int sd) {
    asm volatile(
        "{\n.reg .pred p;\nsetp.ne.b32 p, %34, 0;\n"
        "wgmma.mma_async.sync.aligned.m64n64k16.f32.bf16.bf16 "
        "{%0,%1,%2,%3,%4,%5,%6,%7,%8,%9,%10,%11,%12,%13,%14,%15,%16,%17,%18,%19,%20,%21,%22,%23,%24,%25,%26,%27,%28,%29,%30,%31},"
        " %32, %33, p, 1, 1, 0, %35;\n}"
        : ACC8(d, 0), ACC8(d, 8), ACC8(d, 16), ACC8(d, 24)
        : "l"(da), "l"(db), "r"(sd), "n"(TB));
}
template <int SA>
__device__ __forceinline__ void wgmma_n64s(float (&d)[32], uint64_t da, uint64_t db, int sd) {
    asm volatile(
        "{\n.reg .pred p;\nsetp.ne.b32 p, %34, 0;\n"
        "wgmma.mma_async.sync.aligned.m64n64k16.f32.bf16.bf16 "
        "{%0,%1,%2,%3,%4,%5,%6,%7,%8,%9,%10,%11,%12,%13,%14,%15,%16,%17,%18,%19,%20,%21,%22,%23,%24,%25,%26,%27,%28,%29,%30,%31},"
        " %32, %33, p, %35, 1, 0, 1;\n}"
        : ACC8(d, 0), ACC8(d, 8), ACC8(d, 16), ACC8(d, 24)
        : "l"(da), "l"(db), "r"(sd), "n"(SA));
}
__device__ __forceinline__ void wgmma_n64_rs(float (&d)[32], uint32_t a0, uint32_t a1, uint32_t a2, uint32_t a3, uint64_t db, int sd) {
    asm volatile(
        "{\n.reg .pred p;\nsetp.ne.b32 p, %37, 0;\n"
        "wgmma.mma_async.sync.aligned.m64n64k16.f32.bf16.bf16 "
        "{%0,%1,%2,%3,%4,%5,%6,%7,%8,%9,%10,%11,%12,%13,%14,%15,%16,%17,%18,%19,%20,%21,%22,%23,%24,%25,%26,%27,%28,%29,%30,%31},"
        " {%32,%33,%34,%35}, %36, p, 1, 1, 1;\n}"
        : ACC8(d, 0), ACC8(d, 8), ACC8(d, 16), ACC8(d, 24)
        : "r"(a0), "r"(a1), "r"(a2), "r"(a3), "l"(db), "r"(sd));
}

struct Params {
    const __nv_bfloat16* x0;
    const __nv_bfloat16* w_r;
    const __nv_bfloat16* w_i;
    const __nv_bfloat16* lam_re;
    const __nv_bfloat16* lam_im;
    const __nv_bfloat16* log_dt;
    const __nv_bfloat16* dskip;
    float* out;
    int stop;
};

__device__ __forceinline__ float ldbf(const __nv_bfloat16* p) { return __bfloat162float(*p); }

__device__ __forceinline__ void dft_fp(int j, int& f, int& ph) {
    int cs = j >> 1;
    if (j == 1) { f = 256; ph = 0; }
    else { f = cs; ph = (j & 1) ? 128 : 0; }
}

__device__ __forceinline__ void gen_col_consts(uint32_t sb, int tid) {
#pragma unroll 1
    for (int task = tid; task < 640; task += 256) {
        int f, c8;
        uint32_t a_cc, d_pi, d_po;
        if (task < 512) {
            f = task & 63; c8 = task >> 6;
            a_cc = sb + SM_X + (f >> 5) * 16384 + ((f >> 3) & 3) * 2048 + c8 * 128 + (f & 7) * 16;
            d_pi = 8192; d_po = 1024;
        } else {
            int n2 = task & 31;
            f = 2 * n2; c8 = (task >> 5) & 3;
            a_cc = sb + SM_X + 32768 + (n2 >> 3) * 1024 + c8 * 128 + (n2 & 7) * 16;
            d_pi = 4096; d_po = 512;
        }
        float cd, sd, cs, sn;
        __sincosf((float)(f >= 32 ? f - 64 : f) * (6.283185307179586f / 64.f), &sd, &cd);
        int a = (8 * c8 * f) & 63;
        __sincosf((float)(a >= 32 ? a - 64 : a) * (6.283185307179586f / 64.f), &sn, &cs);
        float cv[8], sv[8];
#pragma unroll
        for (int e = 0; e < 8; e++) {
            cv[e] = cs; sv[e] = sn;
            float t = cs * cd - sn * sd;
            sn = sn * cd + cs * sd;
            cs = t;
        }
        uint4 oc = make_uint4(pack_bf16(cv[0], cv[1]), pack_bf16(cv[2], cv[3]), pack_bf16(cv[4], cv[5]), pack_bf16(cv[6], cv[7]));
        uint4 os = make_uint4(pack_bf16(sv[0], sv[1]), pack_bf16(sv[2], sv[3]), pack_bf16(sv[4], sv[5]), pack_bf16(sv[6], sv[7]));
        sts128(a_cc, oc);
        sts128(a_cc + d_pi, os);
        sts128(a_cc + d_po, make_uint4(os.x ^ 0x80008000u, os.y ^ 0x80008000u, os.z ^ 0x80008000u, os.w ^ 0x80008000u));
        sts128(a_cc + d_pi + d_po, oc);
    }
}

__global__ void __launch_bounds__(NTHREADS, 1)
fused_kernel(const __grid_constant__ CUtensorMap tm_x, const __grid_constant__ CUtensorMap tm_bre,
             const __grid_constant__ CUtensorMap tm_bim, const __grid_constant__ CUtensorMap tm_cre,
             const __grid_constant__ CUtensorMap tm_cim, const __grid_constant__ CUtensorMap tm_col, const Params p) {
    extern __shared__ __align__(1024) uint8_t sm[];
    const uint32_t sb = s2u(sm);
    const int tid = threadIdx.x, b = blockIdx.x;
    const int c = b >> 3, r = b & 7;
    const int par = r & 1, pi_ = r >> 1, own = 4 * par + pi_;
    const int wg = __shfl_sync(~0u, tid >> 7, 0), w = __shfl_sync(~0u, (tid >> 5) & 3, 0), lane = tid & 31, g = lane >> 2, q = lane & 3;
    auto BAR = [&](int i) { return sb + SM_BAR + 8 * i; };
    unsigned* s_tgt = (unsigned*)(sm + SM_TGT);

    if (tid < NBARS) {
        int cnt = 1;
        if ((tid >= B_EMPTY0 && tid < B_EMPTY0 + 4) || (tid >= B_XEMPTY && tid < B_XEMPTY + 4)) cnt = 24;
        if (tid == B_RFREE) cnt = 12;
        if (tid == B_HDONE) cnt = 2;
        if (tid >= B_AEMPTY && tid < B_AEMPTY + 8) cnt = 8;
        if (tid == B_AFREE) cnt = 4;
        mbar_init(BAR(tid), cnt);
        asm volatile("fence.mbarrier_init.release.cluster;" ::: "memory");
    }
    asm volatile("barrier.cluster.arrive.release.aligned;" ::: "memory");
    if (tid >= 64 && tid < 70) {
        s_tgt[tid - 64] = ((ld_acquire(&g_bar[tid - 64]) >> 7) + 1u) << 7;
    } else if (tid >= 96 && tid < 112) {
        g_ssq[2048 + 16 * b + tid - 96] = 0.f;
    } else if (tid >= 128 && tid < 384) {
        int i = tid - 128;
        if (i < 128) ((float4*)g_ssqc)[b * 128 + i] = make_float4(0.f, 0.f, 0.f, 0.f);
    } else if (tid >= 416) {
        int i = tid - 416;
        int ps = i < 64 ? 64 * r + i : 32 * c + i - 64;
        float lr = ldbf(p.lam_re + ps), li = ldbf(p.lam_im + ps);
        float dt = __bfloat162float(__float2bfloat16(expf(ldbf(p.log_dt + ps))));
        float mag = expf(lr * dt), t = li * dt * 0.15915494309189535f, sn, cs;
        t -= rintf(t);
        sincospif(2.f * t, &sn, &cs);
        float er = mag * cs, ei = mag * sn;
        if (i < 64) {
            *(float2*)(sm + SM_LAM + i * 8) = make_float2(er, ei);
        } else {
            er -= 1.f;
            float inv = 1.f / (lr * lr + li * li);
            *(float2*)(sm + SM_RSTD + (i - 64) * 8) = make_float2((er * lr + ei * li) * inv, (ei * lr - er * li) * inv);
        }
    } else if (tid >= 384 && tid < 390) {
        const CUtensorMap* tm = tid == 384 ? &tm_x : tid == 385 ? &tm_bre : tid == 386 ? &tm_bim : tid == 387 ? &tm_cre : tid == 388 ? &tm_cim : &tm_col;
        asm volatile("prefetch.tensormap [%0];" ::"l"(tm) : "memory");
    }
    __syncwarp();
    asm volatile("barrier.cluster.wait.acquire.aligned;" ::: "memory");

    if (wg == 3) {
        asm volatile("setmaxnreg.dec.sync.aligned.u32 56;");
        if (w > 0) {
            bar_arrive(10, 480);
            if (w == 2) {
                const int kq = 2 * b + (lane >> 4), row = (kq >> 2) + 128 * (kq & 3) + 512 * ((lane >> 1) & 3) + 64 * (lane & 1);
                const char* src = (const char*)(((lane >> 3) & 1) ? p.w_i : p.w_r) + (size_t)row * 514;
                size_t a0 = (size_t)src & ~(size_t)15;
                int bytes = row == 2047 ? 512 : 544;
                asm volatile("cp.async.bulk.prefetch.L2.global [%0], %1;" ::"l"(a0), "r"(bytes) : "memory");
            }
#pragma unroll 1
            for (int i = tid - 448; i < 1536 + 128 && w > 1; i += 64) {
                if (i < 1536) g_P[(uint32_t)(b * 4 + i / 384) * 1024 + 640 + i % 384] = make_uint4(0, 0, 0, 0);
                else g_Ebuf[b * 128 + i - 1536] = make_float4(0.f, 0.f, 0.f, 0.f);
            }
#pragma unroll 1
            for (int task = tid - 448; task < 256 && w > 1; task += 64) {
                const int cb = task & 127, kq = 2 * b + (task >> 7), k1 = kq >> 2, qq = kq & 3;
                const unsigned short* wr_ = (const unsigned short*)p.w_r + (k1 + 128 * qq) * 257;
                const unsigned short* wi_ = (const unsigned short*)p.w_i + (k1 + 128 * qq) * 257;
                const int c0 = cb == 0 ? 256 : 2 * cb, c1 = 2 * cb + 1;
                uint32_t wf[16];
#pragma unroll
                for (int i = 0; i < 4; i++) {
                    int o = 512 * i * 257;
                    wf[2 * i] = (uint32_t)__ldg(wr_ + o + c0) | ((uint32_t)__ldg(wr_ + o + 64 * 257 + c0) << 16);
                    wf[2 * i + 1] = ((uint32_t)__ldg(wi_ + o + c0) | ((uint32_t)__ldg(wi_ + o + 64 * 257 + c0) << 16)) ^ 0x80008000u;
                    wf[8 + 2 * i] = (uint32_t)__ldg(wr_ + o + c1) | ((uint32_t)__ldg(wr_ + o + 64 * 257 + c1) << 16);
                    wf[8 + 2 * i + 1] = ((uint32_t)__ldg(wi_ + o + c1) | ((uint32_t)__ldg(wi_ + o + 64 * 257 + c1) << 16)) ^ 0x80008000u;
                }
                uint4* wd = g_Wfrag + (uint32_t)(cb * 1024 + kq);
#pragma unroll
                for (int i = 0; i < 4; i++) wd[i * 256] = make_uint4(wf[4 * i], wf[4 * i + 1], wf[4 * i + 2], wf[4 * i + 3]);
            }
            __syncwarp();
            if (w > 1) bar_arrive(11, 96);
            if (w == 3) {
#pragma unroll 1
                for (int it = 0; it < 8; it++) {
                    const int m = 4 * c + (it >> 1), d = 64 * r + m, ch = lane + 32 * (it & 1);
                    float v[8];
#pragma unroll
                    for (int e = 0; e < 8; e++) {
                        int j = 8 * ch + e, f, ph;
                        dft_fp(j, f, ph);
                        int a = (d * f + ph) & 511;
                        a = a >= 256 ? a - 512 : a;
                        float wj = j == 0 ? 0.f : (j == 1 ? 1.f / 512.f : 2.f / 512.f);
                        v[e] = wj * __cosf((float)a * (6.283185307179586f / 512.f));
                    }
                    uint32_t off = (uint32_t)(64 + r * 8 + (ch >> 3)) * 8192 + (m >> 3) * 1024 + (ch & 7) * 128 + (m & 7) * 16;
                    *(uint4*)(g_E + off) = make_uint4(pack_bf16(v[0], v[1]), pack_bf16(v[2], v[3]), pack_bf16(v[4], v[5]), pack_bf16(v[6], v[7]));
                }
                __syncwarp();
                if (lane == 0) { fence_async(); red_release(&g_bar[6], 1); }
                return;
            }
            if (w == 2) {
#pragma unroll 1
                for (int it = 0; it < 4; it++) {
                    const int hf = it & 1;
                    __syncwarp();
                    if (hf == 0) bar_sync(13, 288); else bar_sync(6, 416);
                    if (lane == 0) {
                        const uint32_t src = sb + SM_HH + par * 32768 + hf * 16384;
                        bulk_s2peer(mapa(src, par ^ 1), src, 16384, mapa(BAR(hf ? B_HPEER1 : B_HPEER), par ^ 1));
                    }
                }
                return;
            }
            {
                uint4 p0 = __ldg((const uint4*)p.dskip + 2 * lane), p1 = __ldg((const uint4*)p.dskip + 2 * lane + 1);
                uint32_t u[8] = {p0.x, p0.y, p0.z, p0.w, p1.x, p1.y, p1.z, p1.w};
#pragma unroll 1
                for (int jj = 0; jj < 4; jj++) {
                    int j = 64 * r + 4 * c + jj, f, ph;
                    dft_fp(j, f, ph);
                    float s = 0.f;
                    int idx = 16 * lane * f + ph;
#pragma unroll
                    for (int i = 0; i < 16; i++) {
                        int a = idx & 511;
                        idx += f;
                        a = a >= 256 ? a - 512 : a;
                        s += ((i & 1) ? bf_hi(u[i >> 1]) : bf_lo(u[i >> 1])) * __cosf((float)a * (6.283185307179586f / 512.f));
                    }
#pragma unroll
                    for (int o = 16; o; o >>= 1) s += __shfl_xor_sync(~0u, s, o);
                    if (lane == 0) g_Dh[j] = s;
                }
                if (lane == 0) red_release(&g_bar[5], 1);
                __syncwarp();
            }
            bar_sync(2, 416);
            if (lane == 0) {
                TX(5);
                asm volatile("cp.async.bulk.global.shared::cta.bulk_group [%0], [%1], 8192;" ::"l"(g_A1 + (uint32_t)(((c >> 1) * 8 + r) * 16384 + (c & 1) * 8192)),
                             "r"(sb + SM_B1ST) : "memory");
                asm volatile("cp.async.bulk.commit_group;" ::: "memory");
                fence_async();
                red_release(&g_bar[0], 1);
                TX(6);
                asm volatile("cp.async.bulk.wait_group 0;" ::: "memory");
                fence_async();
            }
            __syncwarp();
            bar_sync(11, 96);
            if (lane == 0) red_release(&g_bar[4], 1);
#pragma unroll 1
            for (int layer = 0; layer < 2; layer++) {
                __syncwarp();
                bar_sync(5, 416);
                if (lane == 0) {
                    TX(0 + 8 * layer);
                    tma_store_5d(&tm_col, 32 * (b & 1), 0, b >> 1, 0, layer, sb + SM_RAW);
                    asm volatile("cp.reduce.async.bulk.global.shared::cta.bulk_group.add.f32 [%0], [%1], 8192;" ::"l"(g_ssqc + (layer * 16 + (b & 15)) * 2048),
                                 "r"(sb + SM_SSQ) : "memory");
                    asm volatile("cp.async.bulk.commit_group;" ::: "memory");
                    asm volatile("cp.async.bulk.wait_group 0;" ::: "memory");
                    TX(1 + 8 * layer);
                    fence_async();
                    red_release(&g_bar[1 + 2 * layer], 1);
                    TX(2 + 8 * layer);
                }
            }
        } else if (tid == 384) {
#pragma unroll 1
            for (int kb = 0; kb < 8; kb++) {
                int s = kb < 6 ? kb : kb - 4;
                uint32_t dst = s < 2 ? sb + SM_A + 65536 + s * 24576 : sb + SM_X + (s - 2) * 24576;
                if (kb >= 6) mbar_wait_cluster(BAR(B_EMPTY0 + s), 0);
                uint32_t fb = BAR(B_FULL0 + kb);
                mbar_expect(fb, 24576);
                tma_5d_mc(dst + par * 8192, &tm_x, kb * 64, 0, 0, 8 * par, c, fb);
                tma_2d_mc(dst + 16384 + par * 4096, par ? &tm_bim : &tm_bre, kb * 64, 32 * c, fb);
                if (kb == 5) {
#pragma unroll 1
                    for (int k2 = par; k2 < 8; k2 += 2) {
                        asm volatile("cp.async.bulk.prefetch.tensor.2d.L2.global [%0, {%1,%2}];" ::"l"((c & 1) ? &tm_cim : &tm_cre), "r"(64 * (c >> 1)), "r"(k2 * 64) : "memory");
                        if (k2 < 4) {
                            asm volatile("cp.async.bulk.prefetch.tensor.5d.L2.global [%0, {%1,%2,%3,%4,%5}];" ::"l"(&tm_x), "r"((6 + (k2 >> 1)) * 64), "r"(0), "r"(0), "r"(8 * par), "r"(c) : "memory");
                            asm volatile("cp.async.bulk.prefetch.tensor.2d.L2.global [%0, {%1,%2}];" ::"l"(par ? &tm_bim : &tm_bre), "r"((6 + (k2 >> 1)) * 64), "r"(32 * c) : "memory");
                        }
                    }
                }
                if (kb == 7) {
                    mbar_wait_cluster(BAR(B_EMPTY0 + 0), 0);
                    mbar_wait_cluster(BAR(B_EMPTY0 + 1), 0);
                    mbar_expect(BAR(B_FULLC), 65536);
#pragma unroll 1
                    for (int k2 = par; k2 < 8; k2 += 2)
                        tma_2d_mc(sb + SM_A + 65536 + k2 * 8192, (c & 1) ? &tm_cim : &tm_cre, 64 * (c >> 1), k2 * 64, BAR(B_FULLC));
                }
            }
#pragma unroll 1
            for (int layer = 0; layer < 2; layer++) {
                wait_count(&g_bar[2 * layer], s_tgt[2 * layer]);
                TX(4 + 8 * layer);
                fence_async();
                mbar_expect(BAR(B_COL), 16384 + 8192);
                tma_5d(sb + SM_RAW, &tm_col, 32 * (b & 1), 0, b >> 1, 0, layer, BAR(B_COL));
                bulk_g2s(sb + SM_SSQ, g_ssq + layer * 2048, 8192, BAR(B_COL));
                if (layer == 0) {
                    wait_count(&g_bar[4], s_tgt[4]);
                    mbar_arrive(BAR(B_WRDY), 1);
                    fence_async();
                }
                if (layer == 0) mbar_wait(BAR(B_AFREE), 0);
                mbar_wait(BAR(B_COL), layer);
#pragma unroll 1
                for (int s = 0; s < 8; s++) {
                    if (layer == 1) mbar_wait(BAR(B_AEMPTY + s), 1);
                    if (s >= 2) mbar_wait(BAR(B_AFULL + s - 2), 0);
                    mbar_expect(BAR(B_AFULL + s), 16384);
                    bulk_g2s(sb + SM_A + s * 16384, g_A1 + (uint32_t)(r * 8 + s) * 16384, 16384, BAR(B_AFULL + s));
                }
                if (layer == 1) wait_count(&g_bar[6], s_tgt[5]);
                wait_count(&g_bar[1 + 2 * layer], s_tgt[1 + 2 * layer]);
                TX(3 + 8 * layer);
                fence_async();
                const uint8_t* xsrc = g_X + (uint32_t)(layer * 16 + c) * 8 * 16384;
                const uint8_t* esrc = g_E + (uint32_t)(layer * 8 + own) * 8 * 8192;
                mbar_arrive(BAR(B_SSQ), 1);
                mbar_expect(BAR(B_HPEER), 16384);
                mbar_expect(BAR(B_HPEER1), 16384);
#pragma unroll 1
                for (int it = 0; it < 12; it++) {
                    if (it < 8) {
                        int st = it & 3, f = layer * 2 + (it >> 2);
                        if (f > 0) mbar_wait_cluster(BAR(B_XEMPTY + st), (f - 1) & 1);
                        mbar_expect(BAR(B_XFULL + st), 24576);
                        bulk_g2s_mc(sb + SM_X + st * 24576 + par * 8192, xsrc + (uint32_t)it * 16384 + par * 8192, 8192, BAR(B_XFULL + st));
                        bulk_g2s(sb + SM_X + st * 24576 + 16384, esrc + (uint32_t)it * 8192, 8192, BAR(B_XFULL + st));
                    }
                    if (it >= 4) {
                        int s = it - 4, tile = 4 * par + ((pi_ + 1 + (s >> 1)) & 3), sl = r ^ (s & 1);
                        mbar_wait(BAR(B_AEMPTY + s), 0);
                        uint32_t fb = BAR(B_AFULL + s), dst = sb + SM_A + s * 16384;
                        mbar_expect(fb, 16384);
                        if (layer == 1) {
                            tma_2d(dst, &tm_cre, 64 * sl, 64 * tile, fb);
                            tma_2d(dst + 8192, &tm_cim, 64 * sl, 64 * tile, fb);
                        } else {
                            bulk_g2s(dst, g_A2 + (uint32_t)(sl * 8 + tile) * 16384, 16384, fb);
                        }
                    }
                }
            }
        }
        return;
    }

    asm volatile("setmaxnreg.inc.sync.aligned.u32 152;");
    TS(0);
    if (wg == 0) TC(30);
    {
        const int f = 32 * r + lane;
        float cd, sd;
        __sincosf((float)f * (6.283185307179586f / 512.f), &sd, &cd);
        const uint32_t dst = sb + SM_A + (lane >> 2) * 1024 + (lane & 3) * 32;
#pragma unroll 1
        for (int ch = tid >> 5; ch < 64; ch += 12) {
            int a = (8 * ch * f) & 511;
            a = a >= 256 ? a - 512 : a;
            float cs, sn;
            __sincosf((float)a * (6.283185307179586f / 512.f), &sn, &cs);
            float cv[8], sv[8];
#pragma unroll
            for (int e = 0; e < 8; e++) {
                cv[e] = cs; sv[e] = -sn;
                float t = cs * cd - sn * sd;
                sn = sn * cd + cs * sd;
                cs = t;
            }
            uint4 o1 = make_uint4(pack_bf16(sv[0], sv[1]), pack_bf16(sv[2], sv[3]), pack_bf16(sv[4], sv[5]), pack_bf16(sv[6], sv[7]));
            if (f == 0) o1 = make_uint4(0xbf803f80u, 0xbf803f80u, 0xbf803f80u, 0xbf803f80u);
            uint32_t a0 = dst + (ch >> 3) * 8192 + (ch & 7) * 128;
            sts128(a0, make_uint4(pack_bf16(cv[0], cv[1]), pack_bf16(cv[2], cv[3]), pack_bf16(cv[4], cv[5]), pack_bf16(cv[6], cv[7])));
            sts128(a0 + 16, o1);
        }
    }
    fence_async_smem();
    bar_sync(10, 480);
    TS(1);
    {
        float acc[32];
        acc_def(acc);
        const int npos = 16 * r + 8 * (wg & 1) + 2 * w;
        float sh0 = 0.f, sh1 = 0.f, s0 = 0.f, s1 = 0.f, q0 = 0.f, q1 = 0.f;
#pragma unroll 1
        for (int kb = 0; kb < 8; kb++) {
            int s = kb < 6 ? kb : kb - 4;
            uint32_t slot = s < 2 ? sb + SM_A + 65536 + s * 24576 : sb + SM_X + (s - 2) * 24576;
            uint32_t src = slot + wg * 8192;
            mbar_wait(BAR(B_FULL0 + kb), 0);
            {
                uint32_t v0 = lds32(slot + npos * 128 + lane * 4), v1 = lds32(slot + npos * 128 + 128 + lane * 4);
                if (kb == 0) { sh0 = __shfl_sync(~0u, bf_lo(v0), 0); sh1 = __shfl_sync(~0u, bf_lo(v1), 0); }
                float a = bf_lo(v0) - sh0, bq = bf_hi(v0) - sh0, cq = bf_lo(v1) - sh1, d = bf_hi(v1) - sh1;
                s0 += a + bq; q0 += a * a + bq * bq; s1 += cq + d; q1 += cq * cq + d * d;
            }
            wg_fence();
#pragma unroll
            for (int ks = 0; ks < 4; ks++)
                wgmma_n64<0>(acc, desc_a(sb + SM_A + kb * 8192 + ks * 256), desc_k(src + ks * 32), 1);
            wg_commit();
            wg_wait<1>();
            if (kb > 0 && kb <= 4 && lane == 0) { mbar_arrive(BAR(B_EMPTY0 + kb - 1), 1); mbar_arrive_remote(mapa(BAR(B_EMPTY0 + kb - 1), par ^ 1)); }
        }
        wg_wait<0>();
        TS(2);
        if (wg < 2) {
            uint8_t* dst = g_X + (uint32_t)((c * 8 + r) * 16384 + w * 4096 + wg * 1024 + g * 16 + 4 * q);
#pragma unroll
            for (int i = 0; i < 8; i++) {
                *(uint32_t*)(dst + i * 128) = pack_bf16(acc[4 * i], acc[4 * i + 1]);
                *(uint32_t*)(dst + 2048 + i * 128) = pack_bf16(acc[4 * i + 2], acc[4 * i + 3]);
            }
#pragma unroll
            for (int o = 16; o; o >>= 1) {
                s0 += __shfl_xor_sync(~0u, s0, o); q0 += __shfl_xor_sync(~0u, q0, o);
                s1 += __shfl_xor_sync(~0u, s1, o); q1 += __shfl_xor_sync(~0u, q1, o);
            }
            if (lane == 0) *(float2*)(g_ssq + 128 * c + npos) = make_float2(fmaxf(q0 - s0 * s0 * (1.f / 512.f), 0.f), fmaxf(q1 - s1 * s1 * (1.f / 512.f), 0.f));
        } else {
            uint8_t* dst = sm + SM_B1ST + w * 256 + q * 32 + g * 2;
            const float wj0 = (r == 0 && w == 0 && g < 2) ? (g == 0 ? 0.f : 1.f / 512.f) : 2.f / 512.f;
#pragma unroll
            for (int i = 0; i < 4; i++) {
#pragma unroll
                for (int e = 0; e < 2; e++) {
                    float2 cf = *(const float2*)(sm + SM_RSTD + (8 * i + 2 * q + e) * 8);
#pragma unroll
                    for (int h = 0; h < 2; h++) {
                        float wj = h == 0 ? wj0 : 2.f / 512.f;
                        float pr = acc[4 * i + 2 * h + e] * wj, pi = acc[16 + 4 * i + 2 * h + e] * wj;
                        uint8_t* d2 = dst + i * 2048 + h * 128 + e * 16;
                        *(__nv_bfloat16*)(d2) = __float2bfloat16(cf.x * pr - cf.y * pi);
                        *(__nv_bfloat16*)(d2 + 1024) = __float2bfloat16(cf.x * pi + cf.y * pr);
                    }
                }
            }
            fence_async_smem();
        }
        bar_sync(2, 416);
        TS(3);
    }

    if (wg == 2) {
        {
            const int m = 4 * c + w, jp = 64 * r + m;
            int fp, php;
            dft_fp(jp, fp, php);
            const __nv_bfloat16* dh = (const __nv_bfloat16*)(sm + SM_RSTD);
            if (tid == 256) wait_count(&g_bar[5], s_tgt[5]);
            bar_sync(3, 128);
            float4 d4 = __ldcg((const float4*)g_Dh + (tid - 256));
            *(uint2*)(sm + SM_RSTD + (tid - 256) * 8) = make_uint2(pack_bf16(d4.x, d4.y), pack_bf16(d4.z, d4.w));
            bar_sync(3, 128);
#pragma unroll 1
            for (int it = 0; it < 2; it++) {
                const int ch = lane + 32 * it;
                float v[8];
#pragma unroll
                for (int e = 0; e < 8; e++) {
                    int j = 8 * ch + e, f, ph;
                    dft_fp(j, f, ph);
                    float wj = j == 0 ? 0.f : (j == 1 ? 1.f / 512.f : 2.f / 512.f);
                    float gsum = 0.f;
#pragma unroll
                    for (int sgn = 0; sgn < 2; sgn++) {
                        int mm = (sgn ? f - fp : f + fp) & 511, pp = (sgn ? ph - php : ph + php) & 511;
                        if (mm > 256) { mm = 512 - mm; pp = (512 - pp) & 511; }
                        int odd = (pp >> 7) & 1;
                        float t = __bfloat162float(dh[mm == 256 ? 1 : 2 * mm + odd]);
                        if (odd && (mm & 255) == 0) t = 0.f;
                        gsum += (pp & 256) ? -t : t;
                    }
                    v[e] = 0.5f * wj * gsum;
                }
                uint32_t off = (uint32_t)(r * 8 + (ch >> 3)) * 8192 + (m >> 3) * 1024 + (ch & 7) * 128 + (m & 7) * 16;
                *(uint4*)(g_E + off) = make_uint4(pack_bf16(v[0], v[1]), pack_bf16(v[2], v[3]), pack_bf16(v[4], v[5]), pack_bf16(v[6], v[7]));
            }
        }
        float acc[32];
        acc_def(acc);
        mbar_wait(BAR(B_FULLC), 0);
        wg_fence();
#pragma unroll 1
        for (int kb = 0; kb < 8; kb++) {
#pragma unroll
            for (int ks = 0; ks < 4; ks++)
                wgmma_n64<1>(acc, desc_a(sb + SM_A + kb * 8192 + ks * 256), desc_mn(sb + SM_A + 65536 + kb * 8192 + ks * 2048, 8192), 1);
            wg_commit();
        }
        wg_wait<0>();
        fence_async_smem();
        if (lane == 0) mbar_arrive(BAR(B_AFREE), 1);
        uint8_t* dst = g_A2 + (uint32_t)(((c >> 1) * 8 + r) * 16384 + (c & 1) * 8192 + w * 2048 + g * 16 + 4 * q);
#pragma unroll
        for (int i = 0; i < 8; i++) {
            *(uint32_t*)(dst + i * 128) = pack_bf16(acc[4 * i], acc[4 * i + 1]);
            *(uint32_t*)(dst + 1024 + i * 128) = pack_bf16(acc[4 * i + 2], acc[4 * i + 3]);
        }
    }

#pragma unroll 1
    for (int layer = 0; layer < 2; layer++) {
        if (wg < 2) {
            const int n1 = 32 * wg + 8 * w + g;
            const int ct = n1 >> 2;
            gen_col_consts(sb, tid);
            uint32_t tr2[4], ti2[4], tn2[4];
#pragma unroll
            for (int i = 0; i < 4; i++) {
                float cr[2], ci[2];
#pragma unroll
                for (int e = 0; e < 2; e++) {
                    int a = (n1 * (8 * i + 2 * q + e)) & 2047;
                    a = a >= 1024 ? a - 2048 : a;
                    float ang = (float)a * (-6.283185307179586f / 2048.f);
                    cr[e] = __cosf(ang); ci[e] = __sinf(ang);
                }
                tr2[i] = pack_bf16(cr[0], cr[1]); ti2[i] = pack_bf16(ci[0], ci[1]); tn2[i] = ti2[i] ^ 0x80008000u;
            }
            uint32_t wf[16];
            const uint4* ws = g_Wfrag + (uint32_t)(b * 1024 + n1 * 4 + q);
#pragma unroll
            for (int i = 0; i < 4; i++) {
                uint4 v = make_uint4(0, 0, 0, 0);
                if (layer == 1) v = __ldcg(ws + i * 256);
                wf[4 * i] = v.x; wf[4 * i + 1] = v.y; wf[4 * i + 2] = v.z; wf[4 * i + 3] = v.w;
            }
            mbar_wait(BAR(B_COL), layer);
            TS(4 + 12 * layer);
            if (wg == 0) TC(0 + 10 * layer);
            const uint32_t rw0 = sb + SM_RAW + ct * 1024 + q * 64 + ((q >> 1) << 4) + (g & 3) * 4, rw1 = rw0 ^ 16;
            const int pos0 = 128 * ct + 8 * q + 2 * (g & 3);
            const int sw = b == 0 ? 1 : 0;
            uint32_t xr[4][4];
            const uint32_t st0 = sb + SM_H + (n1 >> 3) * 1024 + g * 16 + 4 * q;
#pragma unroll
            for (int i = 0; i < 4; i++) {
                float2 sq = *(const float2*)(sm + SM_SSQ + (pos0 + 32 * i) * 4);
                const uint32_t rs2 = pack_bf16(rsqrtf(sq.x * (1.f / 512.f) + 1e-5f), rsqrtf(sq.y * (1.f / 512.f) + 1e-5f));
#pragma unroll
                for (int jj = 0; jj < 4; jj++) {
                    const int K = jj ^ (2 * (i & 1));
                    uint32_t a = ((K & 1) ? rw1 : rw0) + i * 256 + (K & 2) * 16;
                    if (jj < 2) a ^= sw << 4;
                    uint32_t v = lds32(a);
                    xr[jj][i] = v;
                    uint32_t o = hmul2(v, rs2);
                    if (jj == 1 && sw) o = 0u;
                    sts32(st0 + (jj & 1) * 8192 + (4 * (jj >> 1) + i) * 128, o);
                }
            }
            if (wg == 0) TC(1 + 10 * layer);
            fence_async_smem();
            bar_sync(1, 256);
            float acc[32];
            const uint32_t s1a = sb + SM_X + wg * 16384, s2b = sb + SM_X + 32768;
            wg_fence();
#pragma unroll
            for (int ks = 0; ks < 8; ks++)
                wgmma_n64<1>(acc, desc_a(s1a + (ks >> 2) * 8192 + (ks & 3) * 256), desc_b<64>(sb + SM_H + ks * 2048), ks != 0);
            wg_commit();
            if (layer == 0) {
                mbar_wait(BAR(B_WRDY), 0);
#pragma unroll
                for (int i = 0; i < 4; i++) {
                    uint4 v = __ldcg(ws + i * 256);
                    wf[4 * i] = v.x; wf[4 * i + 1] = v.y; wf[4 * i + 2] = v.z; wf[4 * i + 3] = v.w;
                }
            }
            wg_wait<0>();
            if (wg == 0) TC(2 + 10 * layer);
            uint32_t are[2][4], aim[2][4];
#pragma unroll
            for (int col = 0; col < 2; col++) {
#pragma unroll
                for (int i = 0; i < 4; i++) {
                    int o = 4 * (4 * col + i);
                    uint32_t zr = pack_bf16(acc[o], acc[o + 1]), zi = pack_bf16(acc[o + 2], acc[o + 3]);
                    are[col][i] = hfma2(zr, tr2[i], hmul2(zi, tn2[i]));
                    aim[col][i] = hfma2(zr, ti2[i], hmul2(zi, tr2[i]));
                }
            }
            wg_fence();
#pragma unroll
            for (int ks = 0; ks < 2; ks++)
                wgmma_n64_rs(acc, are[0][2 * ks], are[1][2 * ks], are[0][2 * ks + 1], are[1][2 * ks + 1], desc_b<64>(s2b + ks * 2048), ks != 0);
#pragma unroll
            for (int ks = 0; ks < 2; ks++)
                wgmma_n64_rs(acc, aim[0][2 * ks], aim[1][2 * ks], aim[0][2 * ks + 1], aim[1][2 * ks + 1], desc_b<64>(s2b + 4096 + ks * 2048), 1);
            wg_commit();
            wg_wait<0>();
            if (wg == 0) TC(3 + 10 * layer);
#pragma unroll
            for (int col = 0; col < 2; col++) {
#pragma unroll
                for (int i = 0; i < 4; i++) {
                    uint32_t wr = wf[col * 8 + 2 * i], wn = wf[col * 8 + 2 * i + 1];
                    uint32_t zr = pack_bf16(acc[4 * i + 2 * col], acc[4 * i + 2 * col + 1]);
                    uint32_t zi = pack_bf16(acc[16 + 4 * i + 2 * col], acc[16 + 4 * i + 2 * col + 1]);
                    are[col][i] = hfma2(zr, wr, hmul2(zi, wn));
                    aim[col][i] = hfma2(zr, wn, hmul2(zi ^ 0x80008000u, wr));
                }
            }
            wg_fence();
#pragma unroll
            for (int ks = 0; ks < 2; ks++)
                wgmma_n64_rs(acc, are[0][2 * ks], are[1][2 * ks], are[0][2 * ks + 1], are[1][2 * ks + 1], desc_b<64>(s2b + ks * 2048), ks != 0);
#pragma unroll
            for (int ks = 0; ks < 2; ks++)
                wgmma_n64_rs(acc, aim[0][2 * ks], aim[1][2 * ks], aim[0][2 * ks + 1], aim[1][2 * ks + 1], desc_b<64>(s2b + 4096 + ks * 2048), 1);
            wg_commit();
            wg_wait<0>();
            if (wg == 0) TC(4 + 10 * layer);
#pragma unroll
            for (int col = 0; col < 2; col++) {
#pragma unroll
                for (int i = 0; i < 4; i++) {
                    uint32_t zr = pack_bf16(acc[4 * i + 2 * col], acc[4 * i + 2 * col + 1]);
                    uint32_t zi = pack_bf16(acc[16 + 4 * i + 2 * col], acc[16 + 4 * i + 2 * col + 1]);
                    sts32(st0 + 16384 + (4 * col + i) * 128, hfma2(zr, tr2[i], hmul2(zi, tn2[i])));
                    sts32(st0 + 16384 + 8192 + (4 * col + i) * 128, hfma2(zr, ti2[i], hmul2(zi, tr2[i])));
                }
            }
            if (wg == 0) TC(5 + 10 * layer);
            fence_async_smem();
            bar_sync(1, 256);
            wg_fence();
#pragma unroll
            for (int ks = 0; ks < 8; ks++)
                wgmma_n64<1>(acc, desc_a(s1a + (ks >> 2) * 8192 + (ks & 3) * 256), desc_b<64>(sb + SM_H + 16384 + ks * 2048), ks != 0);
            wg_commit();
            wg_wait<0>();
            if (wg == 0) TC(6 + 10 * layer);
            const float sc = 1.f / 2048.f;
            const float sci0 = sw ? 0.f : -sc;
            const float wr0 = sw ? 0.5f : 1.f, wi0 = sw ? 0.f : 1.f;
#pragma unroll
            for (int i = 0; i < 4; i++) {
                float ss0, ss1;
#pragma unroll
                for (int col = 0; col < 2; col++) {
                    int o = 4 * (4 * col + i);
                    uint32_t vr = xr[2 * col][i], vi = xr[2 * col + 1][i];
                    float si = col == 0 ? sci0 : -sc;
                    uint32_t nr = pack_bf16(fmaf(acc[o], sc, bf_lo(vr)), fmaf(acc[o + 1], sc, bf_hi(vr)));
                    uint32_t ni = pack_bf16(fmaf(acc[o + 2], si, bf_lo(vi)), fmaf(acc[o + 3], si, bf_hi(vi)));
                    float a0 = bf_lo(nr), a1 = bf_hi(nr), b0 = bf_lo(ni), b1 = bf_hi(ni);
                    if (col == 0) {
                        ss0 = wr0 * a0 * a0 + wi0 * b0 * b0;
                        ss1 = wr0 * a1 * a1 + wi0 * b1 * b1;
                    } else {
                        ss0 += a0 * a0 + b0 * b0;
                        ss1 += a1 * a1 + b1 * b1;
                    }
                    const int K = (2 * col) ^ (2 * (i & 1));
                    uint32_t a = rw0 + i * 256 + K * 16;
                    if (col == 0) a ^= sw << 4;
                    sts32(a, nr);
                    sts32(a ^ 16, ni);
                }
                *(float2*)(sm + SM_SSQ + (pos0 + 32 * i) * 4) = make_float2(ss0 * (2.f / 512.f), ss1 * (2.f / 512.f));
            }
            fence_async_smem();
        }
        TS(5 + 12 * layer);
        if (wg == 0) TC(7 + 10 * layer);
        bar_arrive(5, 416);

        float acc[64];
        float* s_rstd = (float*)(sm + SM_RSTD);
        float* s_mean = (float*)(sm + SM_MEAN);
        const unsigned epoch = s_tgt[0] >> 7;
        const uint32_t pt3 = 1u + (2u * epoch + layer) % 3u;
        const uint32_t ptag = (pt3 & 1u) | ((pt3 & 2u) << 15);
        const uint64_t dstep = layer == 0 ? 16 : 2;
        auto c_desc = [&](int s) { return layer == 0 ? desc_a(sb + SM_A + s * 16384) : desc_k(sb + SM_A + s * 16384); };
        if (wg < 2) {
            const int prow = 32 * wg + 8 * w + g;
            const float2 l1 = *(const float2*)(sm + SM_LAM + prow * 8);
            float lr32 = l1.x, li32 = l1.y;
#pragma unroll
            for (int i = 0; i < 5; i++) { float t = lr32 * lr32 - li32 * li32; li32 = 2.f * lr32 * li32; lr32 = t; }
            float lr128 = lr32, li128 = li32;
#pragma unroll
            for (int i = 0; i < 2; i++) { float t = lr128 * lr128 - li128 * li128; li128 = 2.f * lr128 * li128; lr128 = t; }
            const float lr1 = l1.x, li1 = l1.y;
            acc_def(acc);
#pragma unroll 1
            for (int kb = 0; kb < 8; kb++) {
                mbar_wait(BAR(B_AFULL + kb), 0);
                mbar_wait(BAR(B_XFULL + (kb & 3)), (kb >> 2) & 1);
                wg_fence();
#pragma unroll
                for (int ks = 0; ks < 4; ks++)
                    wgmma_n128<1>(acc, desc_a(sb + SM_A + kb * 16384 + wg * 8192 + ks * 256),
                                  desc_b<128>(sb + SM_X + (kb & 3) * 24576 + ks * 4096), 1);
                wg_commit();
                wg_wait<1>();
                if (kb > 0 && lane == 0) {
                    mbar_arrive(BAR(B_AEMPTY + kb - 1), 1); mbar_arrive(BAR(B_XEMPTY + ((kb - 1) & 3)), 1);
                    mbar_arrive_remote(mapa(BAR(B_XEMPTY + ((kb - 1) & 3)), par ^ 1));
                }
            }
            wg_wait<0>();
            if (lane == 0) {
                mbar_arrive(BAR(B_AEMPTY + 7), 1); mbar_arrive(BAR(B_XEMPTY + 3), 1);
                mbar_arrive_remote(mapa(BAR(B_XEMPTY + 3), par ^ 1)); mbar_arrive_remote(mapa(BAR(B_RFREE), par ^ 1));
            }
            bar_arrive(14, 384);
            TS(6 + 12 * layer);
            bar_sync(4, 384);
            TS(7 + 12 * layer);
            float er = 0.f, ei = 0.f;
#pragma unroll
            for (int i = 0; i < 16; i++) {
                float2 rs = *(const float2*)(s_rstd + 128 + 8 * i + 2 * q);
                acc[4 * i] *= rs.x; acc[4 * i + 1] *= rs.y; acc[4 * i + 2] *= rs.x; acc[4 * i + 3] *= rs.y;
                float nr = lr1 * er - li1 * ei + acc[4 * i], ni = lr1 * ei + li1 * er + acc[4 * i + 2];
                er = lr1 * nr - li1 * ni + acc[4 * i + 1];
                ei = lr1 * ni + li1 * nr + acc[4 * i + 3];
            }
            float cr = 0.f, ci = 0.f, tr = 0.f, ti = 0.f;
#pragma unroll
            for (int qq = 0; qq < 4; qq++) {
                float xr_ = __shfl_sync(~0u, er, (lane & ~3) | qq), xi_ = __shfl_sync(~0u, ei, (lane & ~3) | qq);
                if (qq == q) { cr = tr; ci = ti; }
                float nr = lr32 * tr - li32 * ti + xr_, ni = lr32 * ti + li32 * tr + xi_;
                tr = nr; ti = ni;
            }
            float4* eb = g_Ebuf + (uint32_t)(layer * 16 * 512 + 64 * r + prow);
            if (q == 0 && c < 15) st_relaxed_f4(eb + c * 512, make_float4(tr, ti, __uint_as_float(epoch), 0.f));
            TS(8 + 12 * layer);
            float pr[4], pi[4];
            {
                unsigned n = 0;
                bool ok;
#pragma unroll 1
                do {
                    ok = true;
#pragma unroll
                    for (int k = 0; k < 4; k++) {
                        float4 v = make_float4(0.f, 0.f, __uint_as_float(epoch), 0.f);
                        if (4 * k + q < c) v = ld_relaxed_f4(eb + (4 * k + q) * 512);
                        pr[k] = v.x; pi[k] = v.y;
                        ok = ok && __float_as_uint(v.z) == epoch;
                    }
                } while (!ok && ++n < SPIN_LIMIT);
            }
            __syncwarp();
            TS(9 + 12 * layer);
            float hr = 0.f, hi = 0.f;
#pragma unroll
            for (int cc = 0; cc < 15; cc++) {
                float xr_ = __shfl_sync(~0u, pr[cc >> 2], (lane & ~3) | (cc & 3)), xi_ = __shfl_sync(~0u, pi[cc >> 2], (lane & ~3) | (cc & 3));
                if (cc < c) {
                    float nr = lr128 * hr - li128 * hi + xr_, ni = lr128 * hi + li128 * hr + xi_;
                    hr = nr; hi = ni;
                }
            }
#pragma unroll
            for (int qq = 0; qq < 3; qq++) {
                if (qq < q) { float nr = lr32 * hr - li32 * hi, ni = lr32 * hi + li32 * hr; hr = nr; hi = ni; }
            }
            er = cr + hr; ei = ci + hi;
            bar_sync(7, 384);
            mbar_wait_cluster(BAR(B_RFREE), layer);
            const uint32_t ha = sb + SM_HH + par * 32768 + (prow >> 3) * 1024 + g * 16 + 4 * q;
#pragma unroll
            for (int i = 0; i < 16; i++) {
                float nr = lr1 * er - li1 * ei + acc[4 * i], ni = lr1 * ei + li1 * er + acc[4 * i + 2];
                er = lr1 * nr - li1 * ni + acc[4 * i + 1];
                ei = lr1 * ni + li1 * nr + acc[4 * i + 3];
                sts32(ha + (i >> 3) * 16384 + (i & 7) * 128, pack_bf16(nr, er));
                sts32(ha + (i >> 3) * 16384 + 8192 + (i & 7) * 128, pack_bf16(ni, ei));
                if (i == 7) { fence_async_smem(); bar_arrive(13, 288); }
            }
            fence_async_smem();
            acc_def(acc);
            float acc2[32];
            acc_def(acc2);
            TS(10 + 12 * layer);
            bar_sync(6, 416);
            TS(11 + 12 * layer);
            float (&a0)[32] = *reinterpret_cast<float (*)[32]>(&acc[0]);
            float (&a1)[32] = *reinterpret_cast<float (*)[32]>(&acc[32]);
            auto tile_mma = [&](float (&d)[32], int u) {
#pragma unroll 1
                for (int k = 0; k < 2; k++) {
                    const uint32_t hb = sb + SM_HH + (par ^ k) * 32768 + wg * 16384;
                    if (k == 1) mbar_wait(BAR(wg ? B_HPEER1 : B_HPEER), layer);
                    mbar_wait(BAR(B_AFULL + 2 * u + k), 1);
                    const uint64_t da = c_desc(2 * u + k);
                    wg_fence();
#pragma unroll
                    for (int ks = 0; ks < 4; ks++) wgmma_n64s<1>(d, da + ks * dstep, desc_b<64>(hb + ks * 2048), 1);
#pragma unroll
                    for (int ks = 0; ks < 4; ks++) wgmma_n64s<-1>(d, da + 512 + ks * dstep, desc_b<64>(hb + 8192 + ks * 2048), 1);
                }
                wg_commit();
            };
            auto tile_ship = [&](float (&d)[32], int u) {
                uint4* dst = g_P + (uint32_t)(((c * 8 + 2 * ((pi_ + 1 + u) & 3) + par) * 4 + pi_) * 1024 + wg * 512 + (tid & 127));
#pragma unroll
                for (int i = 0; i < 4; i++)
                    dst[i * 128] = make_uint4((pack_bf16(d[8 * i], d[8 * i + 1]) & 0xfffefffeu) | ptag, pack_bf16(d[8 * i + 2], d[8 * i + 3]),
                                              pack_bf16(d[8 * i + 4], d[8 * i + 5]), pack_bf16(d[8 * i + 6], d[8 * i + 7]));
            };
            tile_mma(a0, 0);
            if ((tid & 127) == 0) mbar_arrive_remote(mapa(BAR(B_HDONE), par ^ 1));
            __syncwarp();
            tile_mma(a1, 1);
            wg_wait<1>();
            tile_ship(a0, 0);
            tile_mma(acc2, 2);
            bar_arrive(12, 384);
            wg_wait<1>();
            tile_ship(a1, 1);
            wg_wait<0>();
            tile_ship(acc2, 2);
            if (lane < 6) mbar_arrive(BAR(B_AEMPTY + lane), 1);
            TS(12 + 12 * layer);
        } else {
            const int t2 = tid - 256;
            const uint8_t* ximg = g_X + (uint32_t)layer * 16 * 8 * 16384;
            mbar_wait(BAR(B_SSQ), layer);
            TS(6 + 12 * layer);
            {
                float tot = 0.f;
#pragma unroll
                for (int i = 0; i < 16; i++) tot += __ldcg(g_ssqc + (layer * 16 + i) * 2048 + 128 * c + t2);
                float rs = rsqrtf(tot * (1.f / 512.f) + 1e-5f);
                s_rstd[t2] = rs;
                s_rstd[128 + t2] = 2.f * rs;
                if (layer == 0) s_mean[t2] = 0.f;
                if (layer == 1) {
                    unsigned short u = __ldcg((const unsigned short*)(ximg + (uint32_t)(c * 8 * 16384 + (t2 >> 3) * 128 + (t2 & 7) * 2)));
                    s_mean[t2] = __uint_as_float((uint32_t)u << 16) * (1.f / 512.f);
                }
            }
            TS(7 + 12 * layer);
            bar_arrive(4, 384);
            acc_def(acc);
#pragma unroll 1
            for (int kb = 0; kb < 8; kb++) {
                if (kb == 4) {
                    wg_wait<0>();
                    if (lane == 0) { mbar_arrive(BAR(B_XEMPTY + 3), 1); mbar_arrive_remote(mapa(BAR(B_XEMPTY + 3), par ^ 1)); }
                    bar_sync(14, 384);
                }
                mbar_wait(BAR(B_XFULL + (kb & 3)), (kb >> 2) & 1);
                wg_fence();
#pragma unroll
                for (int ks = 0; ks < 4; ks++)
                    wgmma_n128<1>(acc, desc_a(sb + SM_X + (kb & 3) * 24576 + 16384 + ks * 256), desc_b<128>(sb + SM_X + (kb & 3) * 24576 + ks * 4096), 1);
                wg_commit();
                wg_wait<1>();
                if ((kb & 3) != 0 && lane == 0) { mbar_arrive(BAR(B_XEMPTY + ((kb - 1) & 3)), 1); mbar_arrive_remote(mapa(BAR(B_XEMPTY + ((kb - 1) & 3)), par ^ 1)); }
            }
            wg_wait<0>();
            if (lane == 0) { mbar_arrive(BAR(B_XEMPTY + 3), 1); mbar_arrive_remote(mapa(BAR(B_XEMPTY + 3), par ^ 1)); mbar_arrive_remote(mapa(BAR(B_RFREE), par ^ 1)); }
            bar_arrive(7, 384);
            bar_sync(3, 128);
            TS(9 + 12 * layer);
            const int m0 = 16 * w + g;
            const uint32_t xoff = (uint32_t)((c * 8 + own) * 16384 + w * 4096 + g * 16 + 4 * q);
            if (layer == 0) {
                const uint8_t* xs = g_X + xoff;
#pragma unroll
                for (int i = 0; i < 16; i++) {
                    float2 rs = *(const float2*)(s_rstd + 8 * i + 2 * q);
                    uint32_t x0v = __ldcg((const uint32_t*)(xs + i * 128)), x1v = __ldcg((const uint32_t*)(xs + 2048 + i * 128));
                    acc[4 * i] = acc[4 * i] * rs.x + bf_lo(x0v);
                    acc[4 * i + 1] = acc[4 * i + 1] * rs.y + bf_hi(x0v);
                    acc[4 * i + 2] = acc[4 * i + 2] * rs.x + bf_lo(x1v);
                    acc[4 * i + 3] = acc[4 * i + 3] * rs.y + bf_hi(x1v);
                }
            } else {
                float d0 = ldbf(p.dskip + 64 * own + m0), d1 = ldbf(p.dskip + 64 * own + m0 + 8);
#pragma unroll
                for (int i = 0; i < 16; i++) {
                    float2 rs = *(const float2*)(s_rstd + 8 * i + 2 * q);
                    float2 mn = *(const float2*)(s_mean + 8 * i + 2 * q);
                    acc[4 * i] = acc[4 * i] * (1.f + rs.x * d0) + mn.x;
                    acc[4 * i + 1] = acc[4 * i + 1] * (1.f + rs.y * d0) + mn.y;
                    acc[4 * i + 2] = acc[4 * i + 2] * (1.f + rs.x * d1) + mn.x;
                    acc[4 * i + 3] = acc[4 * i + 3] * (1.f + rs.y * d1) + mn.y;
                }
            }
            TS(10 + 12 * layer);
            bar_sync(6, 416);
            TS(11 + 12 * layer);
            {
                float (&a0)[32] = *reinterpret_cast<float (*)[32]>(&acc[0]);
                float (&a1)[32] = *reinterpret_cast<float (*)[32]>(&acc[32]);
#pragma unroll 1
                for (int k = 0; k < 2; k++) {
                    const uint32_t hb = sb + SM_HH + (par ^ k) * 32768;
                    if (k == 1) {
                        mbar_wait(BAR(B_HPEER), layer);
                        mbar_wait(BAR(B_HPEER1), layer);
                        bar_sync(12, 384);
                    }
                    mbar_wait(BAR(B_AFULL + 6 + k), 1);
                    const uint64_t da = c_desc(6 + k);
                    wg_fence();
#pragma unroll
                    for (int ks = 0; ks < 4; ks++) {
                        wgmma_n64s<1>(a0, da + ks * dstep, desc_b<64>(hb + ks * 2048), 1);
                        wgmma_n64s<1>(a1, da + ks * dstep, desc_b<64>(hb + 16384 + ks * 2048), 1);
                    }
#pragma unroll
                    for (int ks = 0; ks < 4; ks++) {
                        wgmma_n64s<-1>(a0, da + 512 + ks * dstep, desc_b<64>(hb + 8192 + ks * 2048), 1);
                        wgmma_n64s<-1>(a1, da + 512 + ks * dstep, desc_b<64>(hb + 16384 + 8192 + ks * 2048), 1);
                    }
                    wg_commit();
                }
                wg_wait<0>();
            }
#pragma unroll
            for (int i = 0; i < 16; i++)
                *(float4*)(sm + SM_A + 6 * 16384 + i * 2048 + t2 * 16) = make_float4(acc[4 * i], acc[4 * i + 1], acc[4 * i + 2], acc[4 * i + 3]);
            TS(12 + 12 * layer);
        }
        {
            const int t = tid & 127;
            const int nch = wg == 2 ? 2 : 3;
            const uint4* pb = g_P + (uint32_t)((c * 8 + r) * 4 * 1024 + wg * 128 + t);
            uint4 v[3][3];
            unsigned n = 0;
#pragma unroll 1
            while (true) {
                if (lane == 31) {
#pragma unroll 1
                    while (true) {
                        uint32_t bad = 0;
#pragma unroll
                        for (int sx = 0; sx < 3; sx++) {
                            uint32_t t0;
                            asm volatile("ld.relaxed.gpu.global.u32 %0, [%1];" : "=r"(t0) : "l"(pb + ((pi_ + 1 + sx) & 3) * 1024 + (nch - 1) * 384) : "memory");
                            bad |= t0 ^ ptag;
                        }
                        if (!(bad & 0x00010001u) || ++n >= SPIN_LIMIT) break;
                    }
                }
                __syncwarp();
                uint32_t bad = 0;
#pragma unroll
                for (int k = 0; k < 3; k++)
#pragma unroll
                    for (int sx = 0; sx < 3; sx++) {
                        v[k][sx] = make_uint4(ptag, 0, 0, 0);
                        if (k < nch) v[k][sx] = ld_relaxed_u4(pb + ((pi_ + 1 + sx) & 3) * 1024 + k * 384);
                        bad |= v[k][sx].x ^ ptag;
                    }
                if (!__any_sync(~0u, bad & 0x00010001u) || ++n >= SPIN_LIMIT) break;
            }
            bar_sync(8, 384);
            TS(13 + 12 * layer);
            const int m0 = 16 * w + g;
            const float w0 = (own == 0 && m0 < 2) ? (m0 == 0 ? 0.f : 0.5f) : 1.f;
#pragma unroll
            for (int k = 0; k < 3; k++) {
                if (k < nch) {
                    const int i = wg + 3 * k;
                    float4 a = *(const float4*)(sm + SM_A + 6 * 16384 + (2 * i) * 2048 + t * 16);
                    float4 bq = *(const float4*)(sm + SM_A + 6 * 16384 + (2 * i + 1) * 2048 + t * 16);
#pragma unroll
                    for (int sx = 0; sx < 3; sx++) {
                        a.x += bf_lo(v[k][sx].x); a.y += bf_hi(v[k][sx].x); a.z += bf_lo(v[k][sx].y); a.w += bf_hi(v[k][sx].y);
                        bq.x += bf_lo(v[k][sx].z); bq.y += bf_hi(v[k][sx].z); bq.z += bf_lo(v[k][sx].w); bq.w += bf_hi(v[k][sx].w);
                    }
                    if (layer == 0) {
                        uint8_t* xd = g_X + (uint32_t)((16 * 8 + c * 8 + own) * 16384 + w * 4096 + g * 16 + 4 * q + i * 256);
                        uint32_t v0 = pack_bf16(a.x, a.y), v1 = pack_bf16(a.z, a.w), v2 = pack_bf16(bq.x, bq.y), v3 = pack_bf16(bq.z, bq.w);
                        *(uint32_t*)(xd) = v0; *(uint32_t*)(xd + 2048) = v1; *(uint32_t*)(xd + 128) = v2; *(uint32_t*)(xd + 2048 + 128) = v3;
                        float sq[4];
                        sq[0] = w0 * bf_lo(v0) * bf_lo(v0) + bf_lo(v1) * bf_lo(v1);
                        sq[1] = w0 * bf_hi(v0) * bf_hi(v0) + bf_hi(v1) * bf_hi(v1);
                        sq[2] = w0 * bf_lo(v2) * bf_lo(v2) + bf_lo(v3) * bf_lo(v3);
                        sq[3] = w0 * bf_hi(v2) * bf_hi(v2) + bf_hi(v3) * bf_hi(v3);
                        float u0 = (g & 1) ? sq[2] : sq[0], u1 = (g & 1) ? sq[3] : sq[1];
                        u0 += __shfl_xor_sync(~0u, (g & 1) ? sq[0] : sq[2], 4);
                        u1 += __shfl_xor_sync(~0u, (g & 1) ? sq[1] : sq[3], 4);
                        float z = (g & 2) ? u1 : u0;
                        z += __shfl_xor_sync(~0u, (g & 2) ? u0 : u1, 8);
                        z += __shfl_xor_sync(~0u, z, 16);
                        if (g < 4) atomicAdd(s_mean + 16 * i + 8 * (g & 1) + 2 * q + (g >> 1), z);
                    } else {
                        float* o = p.out + (uint32_t)((128 * c + 32 * q + 4 * i) * 512 + 64 * own + m0);
                        o[0] = a.x; o[512] = a.y; o[8] = a.z; o[512 + 8] = a.w;
                        o[1024] = bq.x; o[1536] = bq.y; o[1024 + 8] = bq.z; o[1536 + 8] = bq.w;
                    }
                }
            }
            if (wg < 2) mbar_wait_cluster(BAR(B_HDONE), layer);
            if (layer == 0) {
                fence_async_smem();
                bar_sync(9, 384);
                TS(14 + 12 * layer);
                if (wg == 2) {
                    atomicAdd(g_ssq + 2048 + 128 * c + t, s_mean[t] * (2.f / 512.f));
                    bar_sync(3, 128);
                    if (lane == 0) { mbar_arrive(BAR(B_AEMPTY + 6), 2); mbar_arrive(BAR(B_AEMPTY + 7), 2); }
                    if (t == 0) { fence_async(); red_release(&g_bar[2], 1); }
                }
            }
        }
        TS(15 + 12 * layer);
        if (wg == 0) TC(31);
    }
}

typedef CUresult (*EncFn)(CUtensorMap*, CUtensorMapDataType, cuuint32_t, void*, const cuuint64_t*, const cuuint64_t*,
                          const cuuint32_t*, const cuuint32_t*, CUtensorMapInterleave, CUtensorMapSwizzle,
                          CUtensorMapL2promotion, CUtensorMapFloatOOBfill);

void launch_impl(void* const* d_in, void* d_out, int stop) {
    static EncFn enc = nullptr;
    if (!enc) {
        void* fn = nullptr;
        cudaDriverEntryPointQueryResult qr;
        cudaGetDriverEntryPoint("cuTensorMapEncodeTiled", &fn, cudaEnableDefault, &qr);
        enc = (EncFn)fn;
        cudaFuncSetAttribute(fused_kernel, cudaFuncAttributeMaxDynamicSharedMemorySize, SM_TOTAL);
    }
    CUtensorMap tx, tbr, tbi, tcr, tci, tcol;
    {
        void* gx = nullptr;
        cudaGetSymbolAddress(&gx, g_X);
        cuuint64_t gd[5] = {64, 16, 64, 16, 2};
        cuuint64_t gs[4] = {128, 2048, 128 * 1024, 2048 * 1024};
        cuuint32_t bx[5] = {32, 16, 1, 16, 1};
        cuuint32_t es[5] = {1, 1, 1, 1, 1};
        enc(&tcol, CU_TENSOR_MAP_DATA_TYPE_BFLOAT16, 5, gx, gd, gs, bx, es, CU_TENSOR_MAP_INTERLEAVE_NONE,
            CU_TENSOR_MAP_SWIZZLE_64B, CU_TENSOR_MAP_L2_PROMOTION_NONE, CU_TENSOR_MAP_FLOAT_OOB_FILL_NONE);
    }
    {
        cuuint64_t gd[5] = {512, 2, 4, 16, 16};
        cuuint64_t gs[4] = {1024, 32 * 1024, 2 * 1024, 128 * 1024};
        cuuint32_t bx[5] = {64, 2, 4, 8, 1};
        cuuint32_t es[5] = {1, 1, 1, 1, 1};
        enc(&tx, CU_TENSOR_MAP_DATA_TYPE_BFLOAT16, 5, d_in[0], gd, gs, bx, es, CU_TENSOR_MAP_INTERLEAVE_NONE,
            CU_TENSOR_MAP_SWIZZLE_128B, CU_TENSOR_MAP_L2_PROMOTION_L2_128B, CU_TENSOR_MAP_FLOAT_OOB_FILL_NONE);
    }
    auto mk2 = [&](CUtensorMap* m, void* ptr, cuuint32_t rows) {
        cuuint64_t gd[2] = {512, 512};
        cuuint64_t gs[1] = {1024};
        cuuint32_t bx[2] = {64, rows};
        cuuint32_t es[2] = {1, 1};
        enc(m, CU_TENSOR_MAP_DATA_TYPE_BFLOAT16, 2, ptr, gd, gs, bx, es, CU_TENSOR_MAP_INTERLEAVE_NONE,
            CU_TENSOR_MAP_SWIZZLE_128B, CU_TENSOR_MAP_L2_PROMOTION_L2_128B, CU_TENSOR_MAP_FLOAT_OOB_FILL_NONE);
    };
    mk2(&tbr, d_in[6], 32);
    mk2(&tbi, d_in[7], 32);
    mk2(&tcr, d_in[8], 64);
    mk2(&tci, d_in[9], 64);
    Params p;
    p.x0 = (const __nv_bfloat16*)d_in[0];
    p.w_r = (const __nv_bfloat16*)d_in[1];
    p.w_i = (const __nv_bfloat16*)d_in[2];
    p.lam_re = (const __nv_bfloat16*)d_in[4];
    p.lam_im = (const __nv_bfloat16*)d_in[5];
    p.log_dt = (const __nv_bfloat16*)d_in[10];
    p.dskip = (const __nv_bfloat16*)d_in[11];
    p.out = (float*)d_out;
    p.stop = stop;
    cudaLaunchConfig_t cfg = {};
    cfg.gridDim = dim3(NCTA); cfg.blockDim = dim3(NTHREADS); cfg.dynamicSmemBytes = SM_TOTAL; cfg.stream = cudaStreamPerThread;
    cudaLaunchAttribute at[1];
    at[0].id = cudaLaunchAttributeClusterDimension;
    at[0].val.clusterDim.x = 2; at[0].val.clusterDim.y = 1; at[0].val.clusterDim.z = 1;
    cfg.attrs = at; cfg.numAttrs = 1;
    cudaLaunchKernelEx(&cfg, fused_kernel, tx, tbr, tbi, tcr, tci, tcol, p);
}

}

extern "C" void kernel_launch(void* const* d_in, const int* in_sizes, int n_in, void* d_out, int out_size) {
    (void)in_sizes; (void)n_in; (void)out_size;
    launch_impl(d_in, d_out, 100);
}
```

```cpp
#include <cuda_runtime.h>
#include <cuda_bf16.h>
#include <cuda.h>
#include <stdint.h>

namespace {

constexpr int NCTA = 128;
constexpr int NTHREADS = 512;
constexpr int SM_A = 0;
constexpr int SM_X = 131072;
constexpr int SM_H = 196608;
constexpr int SM_HH = SM_X + 32768;
constexpr int SM_M = 229376;
constexpr int SM_TOTAL = 232448;
constexpr int SM_BAR = SM_M;
constexpr int SM_TGT = SM_M + 360;
constexpr int SM_LAM = SM_M + 384;
constexpr int SM_TAB = SM_M + 896;
constexpr int SM_RSTD = SM_M + 1920;
constexpr int SM_MEAN = SM_TAB;
constexpr int SM_T64 = SM_M + 2944;
constexpr int SM_B1ST = SM_H + 24576;
constexpr int SM_RAW = SM_X + 40960;
constexpr int SM_SSQ = SM_X + 57344;
constexpr int B_FULL0 = 0;
constexpr int B_EMPTY0 = 8;
constexpr int B_FULLC = 12;
constexpr int B_AFULL = 13;
constexpr int B_AEMPTY = 21;
constexpr int B_XFULL = 29;
constexpr int B_XEMPTY = 33;
constexpr int B_AFREE = 37;
constexpr int B_COL = 38;
constexpr int B_SSQ = 39;
constexpr int B_HPEER = 40;
constexpr int B_RFREE = 41;
constexpr int B_HDONE = 42;
constexpr int B_WRDY = 43;
constexpr int B_HPEER1 = 44;
constexpr int NBARS = 45;

__device__ __align__(1024) uint8_t g_X[2 * 16 * 8 * 16384];
__device__ __align__(1024) uint8_t g_A1[8 * 8 * 16384];
__device__ __align__(1024) uint8_t g_A2[8 * 8 * 16384];
__device__ __align__(1024) uint8_t g_E[2 * 8 * 8 * 8192];
__device__ __align__(16) float g_ssq[2 * 2048];
__device__ __align__(16) float g_ssqc[2 * 16 * 2048];
__device__ __align__(16) float g_Dh[512];
__device__ __align__(16) uint4 g_Wfrag[128 * 4 * 256];
__device__ __align__(16) float4 g_Ebuf[2 * 16 * 512];
__device__ __align__(16) uint4 g_P[16 * 8 * 4 * 1024];
__device__ unsigned g_bar[8];
__device__ unsigned g_err;
#define TX(i)
#define TQ(i)
#define TS(i)
#define TC(i)

constexpr unsigned SPIN_LIMIT = 1u << 22;

__device__ __forceinline__ uint32_t s2u(const void* p) { return (uint32_t)__cvta_generic_to_shared(p); }
__device__ __forceinline__ void mbar_init(uint32_t a, uint32_t c) {
    asm volatile("mbarrier.init.shared::cta.b64 [%0], %1;" ::"r"(a), "r"(c) : "memory");
}
__device__ __forceinline__ void mbar_expect(uint32_t a, uint32_t bytes) {
    asm volatile("mbarrier.arrive.expect_tx.shared::cta.b64 _, [%0], %1;" ::"r"(a), "r"(bytes) : "memory");
}
__device__ __forceinline__ void mbar_arrive(uint32_t a, uint32_t cnt) {
    asm volatile("mbarrier.arrive.shared::cta.b64 _, [%0], %1;" ::"r"(a), "r"(cnt) : "memory");
}
__device__ __forceinline__ bool mbar_try(uint32_t a, uint32_t parity) {
    uint32_t ok;
    asm volatile("{\n.reg .pred p;\nmbarrier.try_wait.parity.shared::cta.b64 p, [%1], %2;\nselp.u32 %0, 1, 0, p;\n}"
                 : "=r"(ok) : "r"(a), "r"(parity) : "memory");
    return ok != 0;
}
__device__ __forceinline__ void mbar_wait(uint32_t a, uint32_t parity) {
    asm volatile("{\n.reg .pred p, q;\n.reg .u32 n;\nmov.u32 n, 0;\n"
                 "W_%=:\nmbarrier.try_wait.parity.shared::cta.b64 p, [%0], %1;\n@p bra D_%=;\n"
                 "add.u32 n, n, 1;\nsetp.lt.u32 q, n, 4194304;\n@q bra W_%=;\nD_%=:\n}" ::"r"(a), "r"(parity) : "memory");
}
__device__ __forceinline__ void bulk_g2s(uint32_t dst, const void* src, uint32_t bytes, uint32_t bar) {
    asm volatile("cp.async.bulk.shared::cluster.global.mbarrier::complete_tx::bytes [%0], [%1], %2, [%3];" ::"r"(dst),
                 "l"(src), "r"(bytes), "r"(bar) : "memory");
}
__device__ __forceinline__ void tma_2d(uint32_t dst, const CUtensorMap* m, int c0, int c1, uint32_t bar) {
    asm volatile("cp.async.bulk.tensor.2d.shared::cluster.global.mbarrier::complete_tx::bytes [%0], [%1, {%3,%4}], [%2];" ::"r"(dst),
                 "l"(m), "r"(bar), "r"(c0), "r"(c1) : "memory");
}
__device__ __forceinline__ void tma_5d(uint32_t dst, const CUtensorMap* m, int c0, int c1, int c2, int c3, int c4, uint32_t bar) {
    asm volatile("cp.async.bulk.tensor.5d.shared::cluster.global.mbarrier::complete_tx::bytes [%0], [%1, {%3,%4,%5,%6,%7}], [%2];" ::"r"(dst),
                 "l"(m), "r"(bar), "r"(c0), "r"(c1), "r"(c2), "r"(c3), "r"(c4) : "memory");
}
__device__ __forceinline__ void tma_2d_mc(uint32_t dst, const CUtensorMap* m, int c0, int c1, uint32_t bar) {
    asm volatile("cp.async.bulk.tensor.2d.shared::cluster.global.mbarrier::complete_tx::bytes.multicast::cluster [%0], [%1, {%3,%4}], [%2], %5;" ::"r"(dst),
                 "l"(m), "r"(bar), "r"(c0), "r"(c1), "h"((unsigned short)3) : "memory");
}
__device__ __forceinline__ void tma_5d_mc(uint32_t dst, const CUtensorMap* m, int c0, int c1, int c2, int c3, int c4, uint32_t bar) {
    asm volatile("cp.async.bulk.tensor.5d.shared::cluster.global.mbarrier::complete_tx::bytes.multicast::cluster [%0], [%1, {%3,%4,%5,%6,%7}], [%2], %8;" ::"r"(dst),
                 "l"(m), "r"(bar), "r"(c0), "r"(c1), "r"(c2), "r"(c3), "r"(c4), "h"((unsigned short)3) : "memory");
}
__device__ __forceinline__ void bulk_g2s_mc(uint32_t dst, const void* src, uint32_t bytes, uint32_t bar) {
    asm volatile("cp.async.bulk.shared::cluster.global.mbarrier::complete_tx::bytes.multicast::cluster [%0], [%1], %2, [%3], %4;" ::"r"(dst),
                 "l"(src), "r"(bytes), "r"(bar), "h"((unsigned short)3) : "memory");
}
__device__ __forceinline__ void tma_store_5d(const CUtensorMap* m, int c0, int c1, int c2, int c3, int c4, uint32_t src) {
    asm volatile("cp.async.bulk.tensor.5d.global.shared::cta.bulk_group [%0, {%2,%3,%4,%5,%6}], [%1];" ::"l"(m), "r"(src),
                 "r"(c0), "r"(c1), "r"(c2), "r"(c3), "r"(c4) : "memory");
}
__device__ __forceinline__ uint32_t lds32(uint32_t a) { uint32_t v; asm volatile("ld.shared.u32 %0, [%1];" : "=r"(v) : "r"(a) : "memory"); return v; }
__device__ __forceinline__ uint4 ld_relaxed_u4(const uint4* p) {
    uint4 v;
    asm volatile("ld.relaxed.gpu.global.v4.u32 {%0,%1,%2,%3}, [%4];" : "=r"(v.x), "=r"(v.y), "=r"(v.z), "=r"(v.w) : "l"(p) : "memory");
    return v;
}
__device__ __forceinline__ void fence_async() { asm volatile("fence.proxy.async.global;" ::: "memory"); }
__device__ __forceinline__ void red_relaxed(unsigned* p, unsigned v) {
    asm volatile("red.relaxed.gpu.global.add.u32 [%0], %1;" ::"l"(p), "r"(v) : "memory");
}
__device__ __forceinline__ uint32_t mapa(uint32_t a, uint32_t rank) {
    uint32_t d;
    asm("mapa.shared::cluster.u32 %0, %1, %2;" : "=r"(d) : "r"(a), "r"(rank));
    return d;
}
__device__ __forceinline__ void mbar_arrive_remote(uint32_t ra) {
    asm volatile("mbarrier.arrive.relaxed.cluster.shared::cluster.b64 _, [%0];" ::"r"(ra) : "memory");
}
__device__ __forceinline__ void mbar_wait_cluster(uint32_t a, uint32_t parity) {
    asm volatile("{\n.reg .pred p, q;\n.reg .u32 n;\nmov.u32 n, 0;\n"
                 "W_%=:\nmbarrier.try_wait.parity.acquire.cluster.shared::cta.b64 p, [%0], %1;\n@p bra D_%=;\n"
                 "add.u32 n, n, 1;\nsetp.lt.u32 q, n, 4194304;\n@q bra W_%=;\nD_%=:\n}" ::"r"(a), "r"(parity) : "memory");
}
__device__ __forceinline__ void bulk_s2peer(uint32_t rdst, uint32_t src, uint32_t bytes, uint32_t rbar) {
    asm volatile("cp.async.bulk.shared::cluster.shared::cta.mbarrier::complete_tx::bytes [%0], [%1], %2, [%3];" ::"r"(rdst),
                 "r"(src), "r"(bytes), "r"(rbar) : "memory");
}
__device__ __forceinline__ void fence_async_smem() { asm volatile("fence.proxy.async.shared::cta;" ::: "memory"); }
__device__ __forceinline__ void wg_fence() { asm volatile("wgmma.fence.sync.aligned;" ::: "memory"); }
__device__ __forceinline__ void wg_commit() { asm volatile("wgmma.commit_group.sync.aligned;" ::: "memory"); }
template <int N> __device__ __forceinline__ void wg_wait() { asm volatile("wgmma.wait_group.sync.aligned %0;" ::"n"(N) : "memory"); }
__device__ __forceinline__ void bar_sync(int id, int n) { asm volatile("bar.sync %0, %1;" ::"r"(id), "r"(n) : "memory"); }
__device__ __forceinline__ void bar_arrive(int id, int n) { asm volatile("bar.arrive %0, %1;" ::"r"(id), "r"(n) : "memory"); }
__device__ __forceinline__ unsigned ld_acquire(const unsigned* p) {
    unsigned v;
    asm volatile("ld.acquire.gpu.global.u32 %0, [%1];" : "=r"(v) : "l"(p) : "memory");
    return v;
}
__device__ __forceinline__ void red_release(unsigned* p, unsigned v) {
    asm volatile("red.release.gpu.global.add.u32 [%0], %1;" ::"l"(p), "r"(v) : "memory");
}
__device__ __forceinline__ void wait_count(const unsigned* p, unsigned target) {
    unsigned n = 0;
#pragma unroll 1
    while ((int)(ld_acquire(p) - target) < 0 && ++n < SPIN_LIMIT) {}
}
__device__ __forceinline__ float4 ld_relaxed_f4(const float4* p) {
    float4 v;
    asm volatile("ld.relaxed.gpu.global.v4.f32 {%0,%1,%2,%3}, [%4];" : "=f"(v.x), "=f"(v.y), "=f"(v.z), "=f"(v.w) : "l"(p) : "memory");
    return v;
}
__device__ __forceinline__ void st_relaxed_f4(float4* p, float4 v) {
    asm volatile("st.relaxed.gpu.global.v4.f32 [%0], {%1,%2,%3,%4};" ::"l"(p), "f"(v.x), "f"(v.y), "f"(v.z), "f"(v.w) : "memory");
}
__device__ __forceinline__ uint32_t pack_bf16(float lo, float hi) {
    uint32_t r;
    asm("cvt.rn.bf16x2.f32 %0, %1, %2;" : "=r"(r) : "f"(hi), "f"(lo));
    return r;
}
__device__ __forceinline__ uint32_t hmul2(uint32_t a, uint32_t b) {
    uint32_t r;
    asm("mul.rn.bf16x2 %0, %1, %2;" : "=r"(r) : "r"(a), "r"(b));
    return r;
}
__device__ __forceinline__ uint32_t hfma2(uint32_t a, uint32_t b, uint32_t c) {
    uint32_t r;
    asm("fma.rn.bf16x2 %0, %1, %2, %3;" : "=r"(r) : "r"(a), "r"(b), "r"(c));
    return r;
}
__device__ __forceinline__ float bf_lo(uint32_t v) { return __uint_as_float(v << 16); }
__device__ __forceinline__ float bf_hi(uint32_t v) { return __uint_as_float(v & 0xffff0000u); }
__device__ __forceinline__ void sts32(uint32_t a, uint32_t v) { asm volatile("st.shared.u32 [%0], %1;" ::"r"(a), "r"(v) : "memory"); }
__device__ __forceinline__ void sts128(uint32_t a, uint4 v) {
    asm volatile("st.shared.v4.u32 [%0], {%1,%2,%3,%4};" ::"r"(a), "r"(v.x), "r"(v.y), "r"(v.z), "r"(v.w) : "memory");
}

__device__ __forceinline__ uint64_t desc_ni(uint32_t addr, uint32_t lbo, uint32_t sbo) {
    return (uint64_t)((addr & 0x3FFFF) >> 4) | ((uint64_t)(lbo >> 4) << 16) | ((uint64_t)(sbo >> 4) << 32);
}
__device__ __forceinline__ uint64_t desc_a(uint32_t addr) { return desc_ni(addr, 128, 1024); }
template <int N> __device__ __forceinline__ uint64_t desc_b(uint32_t addr) { return desc_ni(addr, 16 * N, 128); }
__device__ __forceinline__ uint64_t desc_k(uint32_t addr) {
    return (uint64_t)((addr & 0x3FFFF) >> 4) | (1ull << 16) | (64ull << 32) | (1ull << 62);
}
__device__ __forceinline__ uint64_t desc_mn(uint32_t addr, uint32_t lbo) {
    return (uint64_t)((addr & 0x3FFFF) >> 4) | ((uint64_t)(lbo >> 4) << 16) | (64ull << 32) | (1ull << 62);
}

#define ACC8(d, o) "+f"(d[o + 0]), "+f"(d[o + 1]), "+f"(d[o + 2]), "+f"(d[o + 3]), "+f"(d[o + 4]), "+f"(d[o + 5]), "+f"(d[o + 6]), "+f"(d[o + 7])
template <int TB, int SA = 1>
__device__ __forceinline__ void wgmma_n128(float (&d)[64], uint64_t da, uint64_t db, int sd) {
    asm volatile(
        "{\n.reg .pred p;\nsetp.ne.b32 p, %66, 0;\n"
        "wgmma.mma_async.sync.aligned.m64n128k16.f32.bf16.bf16 "
        "{%0,%1,%2,%3,%4,%5,%6,%7,%8,%9,%10,%11,%12,%13,%14,%15,%16,%17,%18,%19,%20,%21,%22,%23,%24,%25,%26,%27,%28,%29,%30,%31,"
        "%32,%33,%34,%35,%36,%37,%38,%39,%40,%41,%42,%43,%44,%45,%46,%47,%48,%49,%50,%51,%52,%53,%54,%55,%56,%57,%58,%59,%60,%61,%62,%63},"
        " %64, %65, p, %68, 1, 0, %67;\n}"
        : ACC8(d, 0), ACC8(d, 8), ACC8(d, 16), ACC8(d, 24), ACC8(d, 32), ACC8(d, 40), ACC8(d, 48), ACC8(d, 56)
        : "l"(da), "l"(db), "r"(sd), "n"(TB), "n"(SA));
}
template <int N> __device__ __forceinline__ void acc_def(float (&d)[N]) {
#pragma unroll
    for (int i = 0; i < N; i++) d[i] = 0.f;
}
template <int TB>
__device__ __forceinline__ void wgmma_n64(float (&d)[32], uint64_t da, uint64_t db, int sd) {
    asm volatile(
        "{\n.reg .pred p;\nsetp.ne.b32 p, %34, 0;\n"
        "wgmma.mma_async.sync.aligned.m64n64k16.f32.bf16.bf16 "
        "{%0,%1,%2,%3,%4,%5,%6,%7,%8,%9,%10,%11,%12,%13,%14,%15,%16,%17,%18,%19,%20,%21,%22,%23,%24,%25,%26,%27,%28,%29,%30,%31},"
        " %32, %33, p, 1, 1, 0, %35;\n}"
        : ACC8(d, 0), ACC8(d, 8), ACC8(d, 16), ACC8(d, 24)
        : "l"(da), "l"(db), "r"(sd), "n"(TB));
}
template <int SA>
__device__ __forceinline__ void wgmma_n64s(float (&d)[32], uint64_t da, uint64_t db, int sd) {
    asm volatile(
        "{\n.reg .pred p;\nsetp.ne.b32 p, %34, 0;\n"
        "wgmma.mma_async.sync.aligned.m64n64k16.f32.bf16.bf16 "
        "{%0,%1,%2,%3,%4,%5,%6,%7,%8,%9,%10,%11,%12,%13,%14,%15,%16,%17,%18,%19,%20,%21,%22,%23,%24,%25,%26,%27,%28,%29,%30,%31},"
        " %32, %33, p, %35, 1, 0, 1;\n}"
        : ACC8(d, 0), ACC8(d, 8), ACC8(d, 16), ACC8(d, 24)
        : "l"(da), "l"(db), "r"(sd), "n"(SA));
}
__device__ __forceinline__ void wgmma_n64_rs(float (&d)[32], uint32_t a0, uint32_t a1, uint32_t a2, uint32_t a3, uint64_t db, int sd) {
    asm volatile(
        "{\n.reg .pred p;\nsetp.ne.b32 p, %37, 0;\n"
        "wgmma.mma_async.sync.aligned.m64n64k16.f32.bf16.bf16 "
        "{%0,%1,%2,%3,%4,%5,%6,%7,%8,%9,%10,%11,%12,%13,%14,%15,%16,%17,%18,%19,%20,%21,%22,%23,%24,%25,%26,%27,%28,%29,%30,%31},"
        " {%32,%33,%34,%35}, %36, p, 1, 1, 1;\n}"
        : ACC8(d, 0), ACC8(d, 8), ACC8(d, 16), ACC8(d, 24)
        : "r"(a0), "r"(a1), "r"(a2), "r"(a3), "l"(db), "r"(sd));
}

struct Params {
    const __nv_bfloat16* x0;
    const __nv_bfloat16* w_r;
    const __nv_bfloat16* w_i;
    const __nv_bfloat16* lam_re;
    const __nv_bfloat16* lam_im;
    const __nv_bfloat16* log_dt;
    const __nv_bfloat16* dskip;
    float* out;
    int stop;
};

__device__ __forceinline__ float ldbf(const __nv_bfloat16* p) { return __bfloat162float(*p); }

__device__ __forceinline__ void dft_fp(int j, int& f, int& ph) {
    int cs = j >> 1;
    if (j == 1) { f = 256; ph = 0; }
    else { f = cs; ph = (j & 1) ? 128 : 0; }
}

__device__ __forceinline__ void gen_col_consts(uint32_t sb, int tid) {
#pragma unroll 1
    for (int task = tid; task < 640; task += 256) {
        int f, c8;
        uint32_t a_cc, d_pi, d_po;
        if (task < 512) {
            f = task & 63; c8 = task >> 6;
            a_cc = sb + SM_X + (f >> 5) * 16384 + ((f >> 3) & 3) * 2048 + c8 * 128 + (f & 7) * 16;
            d_pi = 8192; d_po = 1024;
        } else {
            int n2 = task & 31;
            f = 2 * n2; c8 = (task >> 5) & 3;
            a_cc = sb + SM_X + 32768 + (n2 >> 3) * 1024 + c8 * 128 + (n2 & 7) * 16;
            d_pi = 4096; d_po = 512;
        }
        float cd, sd, cs, sn;
        __sincosf((float)(f >= 32 ? f - 64 : f) * (6.283185307179586f / 64.f), &sd, &cd);
        int a = (8 * c8 * f) & 63;
        __sincosf((float)(a >= 32 ? a - 64 : a) * (6.283185307179586f / 64.f), &sn, &cs);
        float cv[8], sv[8];
#pragma unroll
        for (int e = 0; e < 8; e++) {
            cv[e] = cs; sv[e] = sn;
            float t = cs * cd - sn * sd;
            sn = sn * cd + cs * sd;
            cs = t;
        }
        uint4 oc = make_uint4(pack_bf16(cv[0], cv[1]), pack_bf16(cv[2], cv[3]), pack_bf16(cv[4], cv[5]), pack_bf16(cv[6], cv[7]));
        uint4 os = make_uint4(pack_bf16(sv[0], sv[1]), pack_bf16(sv[2], sv[3]), pack_bf16(sv[4], sv[5]), pack_bf16(sv[6], sv[7]));
        sts128(a_cc, oc);
        sts128(a_cc + d_pi, os);
        sts128(a_cc + d_po, make_uint4(os.x ^ 0x80008000u, os.y ^ 0x80008000u, os.z ^ 0x80008000u, os.w ^ 0x80008000u));
        sts128(a_cc + d_pi + d_po, oc);
    }
}

__global__ void __launch_bounds__(NTHREADS, 1)
fused_kernel(const __grid_constant__ CUtensorMap tm_x, const __grid_constant__ CUtensorMap tm_bre,
             const __grid_constant__ CUtensorMap tm_bim, const __grid_constant__ CUtensorMap tm_cre,
             const __grid_constant__ CUtensorMap tm_cim, const __grid_constant__ CUtensorMap tm_col, const Params p) {
    extern __shared__ __align__(1024) uint8_t sm[];
    const uint32_t sb = s2u(sm);
    const int tid = threadIdx.x, b = blockIdx.x;
    const int c = b >> 3, r = b & 7;
    const int par = r & 1, pi_ = r >> 1, own = 4 * par + pi_;
    const int wg = __shfl_sync(~0u, tid >> 7, 0), w = __shfl_sync(~0u, (tid >> 5) & 3, 0), lane = tid & 31, g = lane >> 2, q = lane & 3;
    auto BAR = [&](int i) { return sb + SM_BAR + 8 * i; };
    unsigned* s_tgt = (unsigned*)(sm + SM_TGT);

    if (tid < NBARS) {
        int cnt = 1;
        if ((tid >= B_EMPTY0 && tid < B_EMPTY0 + 4) || (tid >= B_XEMPTY && tid < B_XEMPTY + 4)) cnt = 24;
        if (tid == B_RFREE) cnt = 12;
        if (tid == B_HDONE) cnt = 2;
        if (tid >= B_AEMPTY && tid < B_AEMPTY + 8) cnt = 8;
        if (tid == B_AFREE) cnt = 4;
        mbar_init(BAR(tid), cnt);
        asm volatile("fence.mbarrier_init.release.cluster;" ::: "memory");
    }
    asm volatile("barrier.cluster.arrive.release.aligned;" ::: "memory");
    if (tid >= 64 && tid < 70) {
        s_tgt[tid - 64] = ((ld_acquire(&g_bar[tid - 64]) >> 7) + 1u) << 7;
    } else if (tid >= 96 && tid < 112) {
        g_ssq[2048 + 16 * b + tid - 96] = 0.f;
    } else if (tid >= 128 && tid < 384) {
        int i = tid - 128;
        if (i < 128) ((float4*)g_ssqc)[b * 128 + i] = make_float4(0.f, 0.f, 0.f, 0.f);
    } else if (tid >= 416) {
        int i = tid - 416;
        int ps = i < 64 ? 64 * r + i : 32 * c + i - 64;
        float lr = ldbf(p.lam_re + ps), li = ldbf(p.lam_im + ps);
        float dt = __bfloat162float(__float2bfloat16(expf(ldbf(p.log_dt + ps))));
        float mag = expf(lr * dt), t = li * dt * 0.15915494309189535f, sn, cs;
        t -= rintf(t);
        sincospif(2.f * t, &sn, &cs);
        float er = mag * cs, ei = mag * sn;
        if (i < 64) {
            *(float2*)(sm + SM_LAM + i * 8) = make_float2(er, ei);
        } else {
            er -= 1.f;
            float inv = 1.f / (lr * lr + li * li);
            *(float2*)(sm + SM_RSTD + (i - 64) * 8) = make_float2((er * lr + ei * li) * inv, (ei * lr - er * li) * inv);
        }
    } else if (tid >= 384 && tid < 390) {
        const CUtensorMap* tm = tid == 384 ? &tm_x : tid == 385 ? &tm_bre : tid == 386 ? &tm_bim : tid == 387 ? &tm_cre : tid == 388 ? &tm_cim : &tm_col;
        asm volatile("prefetch.tensormap [%0];" ::"l"(tm) : "memory");
    }
    __syncwarp();
    asm volatile("barrier.cluster.wait.acquire.aligned;" ::: "memory");

    if (wg == 3) {
        asm volatile("setmaxnreg.dec.sync.aligned.u32 56;");
        if (w > 0) {
            bar_arrive(10, 480);
            if (w == 2) {
                const int kq = 2 * b + (lane >> 4), row = (kq >> 2) + 128 * (kq & 3) + 512 * ((lane >> 1) & 3) + 64 * (lane & 1);
                const char* src = (const char*)(((lane >> 3) & 1) ? p.w_i : p.w_r) + (size_t)row * 514;
                size_t a0 = (size_t)src & ~(size_t)15;
                int bytes = row == 2047 ? 512 : 544;
                asm volatile("cp.async.bulk.prefetch.L2.global [%0], %1;" ::"l"(a0), "r"(bytes) : "memory");
            }
#pragma unroll 1
            for (int i = tid - 448; i < 1536 + 128 && w > 1; i += 64) {
                if (i < 1536) g_P[(uint32_t)(b * 4 + i / 384) * 1024 + 640 + i % 384] = make_uint4(0, 0, 0, 0);
                else g_Ebuf[b * 128 + i - 1536] = make_float4(0.f, 0.f, 0.f, 0.f);
            }
#pragma unroll 1
            for (int task = tid - 448; task < 256 && w > 1; task += 64) {
                const int cb = task & 127, kq = 2 * b + (task >> 7), k1 = kq >> 2, qq = kq & 3;
                const unsigned short* wr_ = (const unsigned short*)p.w_r + (k1 + 128 * qq) * 257;
                const unsigned short* wi_ = (const unsigned short*)p.w_i + (k1 + 128 * qq) * 257;
                const int c0 = cb == 0 ? 256 : 2 * cb, c1 = 2 * cb + 1;
                uint32_t wf[16];
#pragma unroll
                for (int i = 0; i < 4; i++) {
                    int o = 512 * i * 257;
                    wf[2 * i] = (uint32_t)__ldg(wr_ + o + c0) | ((uint32_t)__ldg(wr_ + o + 64 * 257 + c0) << 16);
                    wf[2 * i + 1] = ((uint32_t)__ldg(wi_ + o + c0) | ((uint32_t)__ldg(wi_ + o + 64 * 257 + c0) << 16)) ^ 0x80008000u;
                    wf[8 + 2 * i] = (uint32_t)__ldg(wr_ + o + c1) | ((uint32_t)__ldg(wr_ + o + 64 * 257 + c1) << 16);
                    wf[8 + 2 * i + 1] = ((uint32_t)__ldg(wi_ + o + c1) | ((uint32_t)__ldg(wi_ + o + 64 * 257 + c1) << 16)) ^ 0x80008000u;
                }
                uint4* wd = g_Wfrag + (uint32_t)(cb * 1024 + kq);
#pragma unroll
                for (int i = 0; i < 4; i++) wd[i * 256] = make_uint4(wf[4 * i], wf[4 * i + 1], wf[4 * i + 2], wf[4 * i + 3]);
            }
            __syncwarp();
            if (w > 1) bar_arrive(11, 96);
            if (w == 3) {
#pragma unroll 1
                for (int it = 0; it < 8; it++) {
                    const int m = 4 * c + (it >> 1), d = 64 * r + m, ch = lane + 32 * (it & 1);
                    float v[8];
#pragma unroll
                    for (int e = 0; e < 8; e++) {
                        int j = 8 * ch + e, f, ph;
                        dft_fp(j, f, ph);
                        int a = (d * f + ph) & 511;
                        a = a >= 256 ? a - 512 : a;
                        float wj = j == 0 ? 0.f : (j == 1 ? 1.f / 512.f : 2.f / 512.f);
                        v[e] = wj * __cosf((float)a * (6.283185307179586f / 512.f));
                    }
                    uint32_t off = (uint32_t)(64 + r * 8 + (ch >> 3)) * 8192 + (m >> 3) * 1024 + (ch & 7) * 128 + (m & 7) * 16;
                    *(uint4*)(g_E + off) = make_uint4(pack_bf16(v[0], v[1]), pack_bf16(v[2], v[3]), pack_bf16(v[4], v[5]), pack_bf16(v[6], v[7]));
                }
                __syncwarp();
                if (lane == 0) { fence_async(); red_release(&g_bar[6], 1); }
                return;
            }
            if (w == 2) {
#pragma unroll 1
                for (int it = 0; it < 4; it++) {
                    const int hf = it & 1;
                    __syncwarp();
                    if (hf == 0) bar_sync(13, 288); else bar_sync(6, 416);
                    if (lane == 0) {
                        const uint32_t src = sb + SM_HH + par * 32768 + hf * 16384;
                        bulk_s2peer(mapa(src, par ^ 1), src, 16384, mapa(BAR(hf ? B_HPEER1 : B_HPEER), par ^ 1));
                    }
                }
                return;
            }
            {
                uint4 p0 = __ldg((const uint4*)p.dskip + 2 * lane), p1 = __ldg((const uint4*)p.dskip + 2 * lane + 1);
                uint32_t u[8] = {p0.x, p0.y, p0.z, p0.w, p1.x, p1.y, p1.z, p1.w};
#pragma unroll 1
                for (int jj = 0; jj < 4; jj++) {
                    int j = 64 * r + 4 * c + jj, f, ph;
                    dft_fp(j, f, ph);
                    float s = 0.f;
                    int idx = 16 * lane * f + ph;
#pragma unroll
                    for (int i = 0; i < 16; i++) {
                        int a = idx & 511;
                        idx += f;
                        a = a >= 256 ? a - 512 : a;
                        s += ((i & 1) ? bf_hi(u[i >> 1]) : bf_lo(u[i >> 1])) * __cosf((float)a * (6.283185307179586f / 512.f));
                    }
#pragma unroll
                    for (int o = 16; o; o >>= 1) s += __shfl_xor_sync(~0u, s, o);
                    if (lane == 0) g_Dh[j] = s;
                }
                if (lane == 0) red_release(&g_bar[5], 1);
                __syncwarp();
            }
            bar_sync(2, 416);
            if (lane == 0) {
                TX(5);
                asm volatile("cp.async.bulk.global.shared::cta.bulk_group [%0], [%1], 8192;" ::"l"(g_A1 + (uint32_t)(((c >> 1) * 8 + r) * 16384 + (c & 1) * 8192)),
                             "r"(sb + SM_B1ST) : "memory");
                asm volatile("cp.async.bulk.commit_group;" ::: "memory");
                fence_async();
                red_release(&g_bar[0], 1);
                TX(6);
                asm volatile("cp.async.bulk.wait_group 0;" ::: "memory");
                fence_async();
            }
            __syncwarp();
            bar_sync(11, 96);
            if (lane == 0) red_release(&g_bar[4], 1);
#pragma unroll 1
            for (int layer = 0; layer < 2; layer++) {
                __syncwarp();
                bar_sync(5, 416);
                if (lane == 0) {
                    TX(0 + 8 * layer);
                    tma_store_5d(&tm_col, 32 * (b & 1), 0, b >> 1, 0, layer, sb + SM_RAW);
                    asm volatile("cp.reduce.async.bulk.global.shared::cta.bulk_group.add.f32 [%0], [%1], 8192;" ::"l"(g_ssqc + (layer * 16 + (b & 15)) * 2048),
                                 "r"(sb + SM_SSQ) : "memory");
                    asm volatile("cp.async.bulk.commit_group;" ::: "memory");
                    asm volatile("cp.async.bulk.wait_group 0;" ::: "memory");
                    TX(1 + 8 * layer);
                    fence_async();
                    red_release(&g_bar[1 + 2 * layer], 1);
                    TX(2 + 8 * layer);
                }
            }
        } else if (tid == 384) {
#pragma unroll 1
            for (int kb = 0; kb < 8; kb++) {
                int s = kb < 6 ? kb : kb - 4;
                uint32_t dst = s < 2 ? sb + SM_A + 65536 + s * 24576 : sb + SM_X + (s - 2) * 24576;
                if (kb >= 6) mbar_wait_cluster(BAR(B_EMPTY0 + s), 0);
                uint32_t fb = BAR(B_FULL0 + kb);
                mbar_expect(fb, 24576);
                tma_5d_mc(dst + par * 8192, &tm_x, kb * 64, 0, 0, 8 * par, c, fb);
                tma_2d_mc(dst + 16384 + par * 4096, par ? &tm_bim : &tm_bre, kb * 64, 32 * c, fb);
                if (kb == 5) {
#pragma unroll 1
                    for (int k2 = par; k2 < 8; k2 += 2) {
                        asm volatile("cp.async.bulk.prefetch.tensor.2d.L2.global [%0, {%1,%2}];" ::"l"((c & 1) ? &tm_cim : &tm_cre), "r"(64 * (c >> 1)), "r"(k2 * 64) : "memory");
                        if (k2 < 4) {
                            asm volatile("cp.async.bulk.prefetch.tensor.5d.L2.global [%0, {%1,%2,%3,%4,%5}];" ::"l"(&tm_x), "r"((6 + (k2 >> 1)) * 64), "r"(0), "r"(0), "r"(8 * par), "r"(c) : "memory");
                            asm volatile("cp.async.bulk.prefetch.tensor.2d.L2.global [%0, {%1,%2}];" ::"l"(par ? &tm_bim : &tm_bre), "r"((6 + (k2 >> 1)) * 64), "r"(32 * c) : "memory");
                        }
                    }
                }
                if (kb == 7) {
                    mbar_wait_cluster(BAR(B_EMPTY0 + 0), 0);
                    mbar_wait_cluster(BAR(B_EMPTY0 + 1), 0);
                    mbar_expect(BAR(B_FULLC), 65536);
#pragma unroll 1
                    for (int k2 = par; k2 < 8; k2 += 2)
                        tma_2d_mc(sb + SM_A + 65536 + k2 * 8192, (c & 1) ? &tm_cim : &tm_cre, 64 * (c >> 1), k2 * 64, BAR(B_FULLC));
                }
            }
#pragma unroll 1
            for (int layer = 0; layer < 2; layer++) {
                wait_count(&g_bar[2 * layer], s_tgt[2 * layer]);
                TX(4 + 8 * layer);
                fence_async();
                mbar_expect(BAR(B_COL), 16384 + 8192);
                tma_5d(sb + SM_RAW, &tm_col, 32 * (b & 1), 0, b >> 1, 0, layer, BAR(B_COL));
                bulk_g2s(sb + SM_SSQ, g_ssq + layer * 2048, 8192, BAR(B_COL));
                if (layer == 0) {
                    wait_count(&g_bar[4], s_tgt[4]);
                    mbar_arrive(BAR(B_WRDY), 1);
                    fence_async();
                }
                if (layer == 0) mbar_wait(BAR(B_AFREE), 0);
                mbar_wait(BAR(B_COL), layer);
#pragma unroll 1
                for (int s = 0; s < 8; s++) {
                    if (layer == 1) mbar_wait(BAR(B_AEMPTY + s), 1);
                    if (s >= 2) mbar_wait(BAR(B_AFULL + s - 2), 0);
                    mbar_expect(BAR(B_AFULL + s), 16384);
                    bulk_g2s(sb + SM_A + s * 16384, g_A1 + (uint32_t)(r * 8 + s) * 16384, 16384, BAR(B_AFULL + s));
                }
                if (layer == 1) wait_count(&g_bar[6], s_tgt[5]);
                wait_count(&g_bar[1 + 2 * layer], s_tgt[1 + 2 * layer]);
                TX(3 + 8 * layer);
                fence_async();
                const uint8_t* xsrc = g_X + (uint32_t)(layer * 16 + c) * 8 * 16384;
                const uint8_t* esrc = g_E + (uint32_t)(layer * 8 + own) * 8 * 8192;
                mbar_arrive(BAR(B_SSQ), 1);
                mbar_expect(BAR(B_HPEER), 16384);
                mbar_expect(BAR(B_HPEER1), 16384);
#pragma unroll 1
                for (int it = 0; it < 16; it++) {
                    if (it < 8) {
                        int st = it & 3, f = layer * 2 + (it >> 2);
                        if (f > 0) mbar_wait_cluster(BAR(B_XEMPTY + st), (f - 1) & 1);
                        mbar_expect(BAR(B_XFULL + st), 24576);
                        bulk_g2s_mc(sb + SM_X + st * 24576 + par * 8192, xsrc + (uint32_t)it * 16384 + par * 8192, 8192, BAR(B_XFULL + st));
                        bulk_g2s(sb + SM_X + st * 24576 + 16384, esrc + (uint32_t)it * 8192, 8192, BAR(B_XFULL + st));
                    }
                    if (it >= 8) {
                        if (it == 8) mbar_wait(BAR(B_AEMPTY + 5), 0);
                        int s = it - 8, tile = 4 * par + ((pi_ + 1 + (s >> 1)) & 3), sl = r ^ (s & 1);
                        mbar_wait(BAR(B_AEMPTY + s), 0);
                        uint32_t fb = BAR(B_AFULL + s), dst = sb + SM_A + s * 16384;
                        mbar_expect(fb, 16384);
                        if (layer == 1) {
                            tma_2d(dst, &tm_cre, 64 * sl, 64 * tile, fb);
                            tma_2d(dst + 8192, &tm_cim, 64 * sl, 64 * tile, fb);
                        } else {
                            bulk_g2s(dst, g_A2 + (uint32_t)(sl * 8 + tile) * 16384, 16384, fb);
                        }
                    }
                }
            }
        }
        return;
    }

    asm volatile("setmaxnreg.inc.sync.aligned.u32 152;");
    TS(0);
    if (wg == 0) TC(30);
    {
        const int f = 32 * r + lane;
        float cd, sd;
        __sincosf((float)f * (6.283185307179586f / 512.f), &sd, &cd);
        const uint32_t dst = sb + SM_A + (lane >> 2) * 1024 + (lane & 3) * 32;
#pragma unroll 1
        for (int ch = tid >> 5; ch < 64; ch += 12) {
            int a = (8 * ch * f) & 511;
            a = a >= 256 ? a - 512 : a;
            float cs, sn;
            __sincosf((float)a * (6.283185307179586f / 512.f), &sn, &cs);
            float cv[8], sv[8];
#pragma unroll
            for (int e = 0; e < 8; e++) {
                cv[e] = cs; sv[e] = -sn;
                float t = cs * cd - sn * sd;
                sn = sn * cd + cs * sd;
                cs = t;
            }
            uint4 o1 = make_uint4(pack_bf16(sv[0], sv[1]), pack_bf16(sv[2], sv[3]), pack_bf16(sv[4], sv[5]), pack_bf16(sv[6], sv[7]));
            if (f == 0) o1 = make_uint4(0xbf803f80u, 0xbf803f80u, 0xbf803f80u, 0xbf803f80u);
            uint32_t a0 = dst + (ch >> 3) * 8192 + (ch & 7) * 128;
            sts128(a0, make_uint4(pack_bf16(cv[0], cv[1]), pack_bf16(cv[2], cv[3]), pack_bf16(cv[4], cv[5]), pack_bf16(cv[6], cv[7])));
            sts128(a0 + 16, o1);
        }
    }
    fence_async_smem();
    bar_sync(10, 480);
    TS(1);
    {
        float acc[32];
        acc_def(acc);
        const int npos = 16 * r + 8 * (wg & 1) + 2 * w;
        float sh0 = 0.f, sh1 = 0.f, s0 = 0.f, s1 = 0.f, q0 = 0.f, q1 = 0.f;
#pragma unroll 1
        for (int kb = 0; kb < 8; kb++) {
            int s = kb < 6 ? kb : kb - 4;
            uint32_t slot = s < 2 ? sb + SM_A + 65536 + s * 24576 : sb + SM_X + (s - 2) * 24576;
            uint32_t src = slot + wg * 8192;
            mbar_wait(BAR(B_FULL0 + kb), 0);
            {
                uint32_t v0 = lds32(slot + npos * 128 + lane * 4), v1 = lds32(slot + npos * 128 + 128 + lane * 4);
                if (kb == 0) { sh0 = __shfl_sync(~0u, bf_lo(v0), 0); sh1 = __shfl_sync(~0u, bf_lo(v1), 0); }
                float a = bf_lo(v0) - sh0, bq = bf_hi(v0) - sh0, cq = bf_lo(v1) - sh1, d = bf_hi(v1) - sh1;
                s0 += a + bq; q0 += a * a + bq * bq; s1 += cq + d; q1 += cq * cq + d * d;
            }
            wg_fence();
#pragma unroll
            for (int ks = 0; ks < 4; ks++)
                wgmma_n64<0>(acc, desc_a(sb + SM_A + kb * 8192 + ks * 256), desc_k(src + ks * 32), 1);
            wg_commit();
            wg_wait<1>();
            if (kb > 0 && kb <= 4 && lane == 0) { mbar_arrive(BAR(B_EMPTY0 + kb - 1), 1); mbar_arrive_remote(mapa(BAR(B_EMPTY0 + kb - 1), par ^ 1)); }
        }
        wg_wait<0>();
        TS(2);
        if (wg < 2) {
            uint8_t* dst = g_X + (uint32_t)((c * 8 + r) * 16384 + w * 4096 + wg * 1024 + g * 16 + 4 * q);
#pragma unroll
            for (int i = 0; i < 8; i++) {
                *(uint32_t*)(dst + i * 128) = pack_bf16(acc[4 * i], acc[4 * i + 1]);
                *(uint32_t*)(dst + 2048 + i * 128) = pack_bf16(acc[4 * i + 2], acc[4 * i + 3]);
            }
#pragma unroll
            for (int o = 16; o; o >>= 1) {
                s0 += __shfl_xor_sync(~0u, s0, o); q0 += __shfl_xor_sync(~0u, q0, o);
                s1 += __shfl_xor_sync(~0u, s1, o); q1 += __shfl_xor_sync(~0u, q1, o);
            }
            if (lane == 0) *(float2*)(g_ssq + 128 * c + npos) = make_float2(fmaxf(q0 - s0 * s0 * (1.f / 512.f), 0.f), fmaxf(q1 - s1 * s1 * (1.f / 512.f), 0.f));
        } else {
            uint8_t* dst = sm + SM_B1ST + w * 256 + q * 32 + g * 2;
            const float wj0 = (r == 0 && w == 0 && g < 2) ? (g == 0 ? 0.f : 1.f / 512.f) : 2.f / 512.f;
#pragma unroll
            for (int i = 0; i < 4; i++) {
#pragma unroll
                for (int e = 0; e < 2; e++) {
                    float2 cf = *(const float2*)(sm + SM_RSTD + (8 * i + 2 * q + e) * 8);
#pragma unroll
                    for (int h = 0; h < 2; h++) {
                        float wj = h == 0 ? wj0 : 2.f / 512.f;
                        float pr = acc[4 * i + 2 * h + e] * wj, pi = acc[16 + 4 * i + 2 * h + e] * wj;
                        uint8_t* d2 = dst + i * 2048 + h * 128 + e * 16;
                        *(__nv_bfloat16*)(d2) = __float2bfloat16(cf.x * pr - cf.y * pi);
                        *(__nv_bfloat16*)(d2 + 1024) = __float2bfloat16(cf.x * pi + cf.y * pr);
                    }
                }
            }
            fence_async_smem();
        }
        bar_sync(2, 416);
        TS(3);
    }

    if (wg == 2) {
        {
            const int m = 4 * c + w, jp = 64 * r + m;
            int fp, php;
            dft_fp(jp, fp, php);
            const __nv_bfloat16* dh = (const __nv_bfloat16*)(sm + SM_RSTD);
            if (tid == 256) wait_count(&g_bar[5], s_tgt[5]);
            bar_sync(3, 128);
            float4 d4 = __ldcg((const float4*)g_Dh + (tid - 256));
            *(uint2*)(sm + SM_RSTD + (tid - 256) * 8) = make_uint2(pack_bf16(d4.x, d4.y), pack_bf16(d4.z, d4.w));
            bar_sync(3, 128);
#pragma unroll 1
            for (int it = 0; it < 2; it++) {
                const int ch = lane + 32 * it;
                float v[8];
#pragma unroll
                for (int e = 0; e < 8; e++) {
                    int j = 8 * ch + e, f, ph;
                    dft_fp(j, f, ph);
                    float wj = j == 0 ? 0.f : (j == 1 ? 1.f / 512.f : 2.f / 512.f);
                    float gsum = 0.f;
#pragma unroll
                    for (int sgn = 0; sgn < 2; sgn++) {
                        int mm = (sgn ? f - fp : f + fp) & 511, pp = (sgn ? ph - php : ph + php) & 511;
                        if (mm > 256) { mm = 512 - mm; pp = (512 - pp) & 511; }
                        int odd = (pp >> 7) & 1;
                        float t = __bfloat162float(dh[mm == 256 ? 1 : 2 * mm + odd]);
                        if (odd && (mm & 255) == 0) t = 0.f;
                        gsum += (pp & 256) ? -t : t;
                    }
                    v[e] = 0.5f * wj * gsum;
                }
                uint32_t off = (uint32_t)(r * 8 + (ch >> 3)) * 8192 + (m >> 3) * 1024 + (ch & 7) * 128 + (m & 7) * 16;
                *(uint4*)(g_E + off) = make_uint4(pack_bf16(v[0], v[1]), pack_bf16(v[2], v[3]), pack_bf16(v[4], v[5]), pack_bf16(v[6], v[7]));
            }
        }
        float acc[32];
        acc_def(acc);
        mbar_wait(BAR(B_FULLC), 0);
        wg_fence();
#pragma unroll 1
        for (int kb = 0; kb < 8; kb++) {
#pragma unroll
            for (int ks = 0; ks < 4; ks++)
                wgmma_n64<1>(acc, desc_a(sb + SM_A + kb * 8192 + ks * 256), desc_mn(sb + SM_A + 65536 + kb * 8192 + ks * 2048, 8192), 1);
            wg_commit();
        }
        wg_wait<0>();
        fence_async_smem();
        if (lane == 0) mbar_arrive(BAR(B_AFREE), 1);
        uint8_t* dst = g_A2 + (uint32_t)(((c >> 1) * 8 + r) * 16384 + (c & 1) * 8192 + w * 2048 + g * 16 + 4 * q);
#pragma unroll
        for (int i = 0; i < 8; i++) {
            *(uint32_t*)(dst + i * 128) = pack_bf16(acc[4 * i], acc[4 * i + 1]);
            *(uint32_t*)(dst + 1024 + i * 128) = pack_bf16(acc[4 * i + 2], acc[4 * i + 3]);
        }
    }

#pragma unroll 1
    for (int layer = 0; layer < 2; layer++) {
        if (wg < 2) {
            const int n1 = 32 * wg + 8 * w + g;
            const int ct = n1 >> 2;
            gen_col_consts(sb, tid);
            uint32_t tr2[4], ti2[4], tn2[4];
#pragma unroll
            for (int i = 0; i < 4; i++) {
                float cr[2], ci[2];
#pragma unroll
                for (int e = 0; e < 2; e++) {
                    int a = (n1 * (8 * i + 2 * q + e)) & 2047;
                    a = a >= 1024 ? a - 2048 : a;
                    float ang = (float)a * (-6.283185307179586f / 2048.f);
                    cr[e] = __cosf(ang); ci[e] = __sinf(ang);
                }
                tr2[i] = pack_bf16(cr[0], cr[1]); ti2[i] = pack_bf16(ci[0], ci[1]); tn2[i] = ti2[i] ^ 0x80008000u;
            }
            uint32_t wf[16];
            const uint4* ws = g_Wfrag + (uint32_t)(b * 1024 + n1 * 4 + q);
#pragma unroll
            for (int i = 0; i < 4; i++) {
                uint4 v = make_uint4(0, 0, 0, 0);
                if (layer == 1) v = __ldcg(ws + i * 256);
                wf[4 * i] = v.x; wf[4 * i + 1] = v.y; wf[4 * i + 2] = v.z; wf[4 * i + 3] = v.w;
            }
            mbar_wait(BAR(B_COL), layer);
            TS(4 + 12 * layer);
            if (wg == 0) TC(0 + 10 * layer);
            const uint32_t rw0 = sb + SM_RAW + ct * 1024 + q * 64 + ((q >> 1) << 4) + (g & 3) * 4, rw1 = rw0 ^ 16;
            const int pos0 = 128 * ct + 8 * q + 2 * (g & 3);
            const int sw = b == 0 ? 1 : 0;
            uint32_t xr[4][4];
            const uint32_t st0 = sb + SM_H + (n1 >> 3) * 1024 + g * 16 + 4 * q;
#pragma unroll
            for (int i = 0; i < 4; i++) {
                float2 sq = *(const float2*)(sm + SM_SSQ + (pos0 + 32 * i) * 4);
                const uint32_t rs2 = pack_bf16(rsqrtf(sq.x * (1.f / 512.f) + 1e-5f), rsqrtf(sq.y * (1.f / 512.f) + 1e-5f));
#pragma unroll
                for (int jj = 0; jj < 4; jj++) {
                    const int K = jj ^ (2 * (i & 1));
                    uint32_t a = ((K & 1) ? rw1 : rw0) + i * 256 + (K & 2) * 16;
                    if (jj < 2) a ^= sw << 4;
                    uint32_t v = lds32(a);
                    xr[jj][i] = v;
                    uint32_t o = hmul2(v, rs2);
                    if (jj == 1 && sw) o = 0u;
                    sts32(st0 + (jj & 1) * 8192 + (4 * (jj >> 1) + i) * 128, o);
                }
            }
            if (wg == 0) TC(1 + 10 * layer);
            fence_async_smem();
            bar_sync(1, 256);
            float acc[32];
            const uint32_t s1a = sb + SM_X + wg * 16384, s2b = sb + SM_X + 32768;
            wg_fence();
#pragma unroll
            for (int ks = 0; ks < 8; ks++)
                wgmma_n64<1>(acc, desc_a(s1a + (ks >> 2) * 8192 + (ks & 3) * 256), desc_b<64>(sb + SM_H + ks * 2048), ks != 0);
            wg_commit();
            if (layer == 0) {
                mbar_wait(BAR(B_WRDY), 0);
#pragma unroll
                for (int i = 0; i < 4; i++) {
                    uint4 v = __ldcg(ws + i * 256);
                    wf[4 * i] = v.x; wf[4 * i + 1] = v.y; wf[4 * i + 2] = v.z; wf[4 * i + 3] = v.w;
                }
            }
            wg_wait<0>();
            if (wg == 0) TC(2 + 10 * layer);
            uint32_t are[2][4], aim[2][4];
#pragma unroll
            for (int col = 0; col < 2; col++) {
#pragma unroll
                for (int i = 0; i < 4; i++) {
                    int o = 4 * (4 * col + i);
                    uint32_t zr = pack_bf16(acc[o], acc[o + 1]), zi = pack_bf16(acc[o + 2], acc[o + 3]);
                    are[col][i] = hfma2(zr, tr2[i], hmul2(zi, tn2[i]));
                    aim[col][i] = hfma2(zr, ti2[i], hmul2(zi, tr2[i]));
                }
            }
            wg_fence();
#pragma unroll
            for (int ks = 0; ks < 2; ks++)
                wgmma_n64_rs(acc, are[0][2 * ks], are[1][2 * ks], are[0][2 * ks + 1], are[1][2 * ks + 1], desc_b<64>(s2b + ks * 2048), ks != 0);
#pragma unroll
            for (int ks = 0; ks < 2; ks++)
                wgmma_n64_rs(acc, aim[0][2 * ks], aim[1][2 * ks], aim[0][2 * ks + 1], aim[1][2 * ks + 1], desc_b<64>(s2b + 4096 + ks * 2048), 1);
            wg_commit();
            wg_wait<0>();
            if (wg == 0) TC(3 + 10 * layer);
#pragma unroll
            for (int col = 0; col < 2; col++) {
#pragma unroll
                for (int i = 0; i < 4; i++) {
                    uint32_t wr = wf[col * 8 + 2 * i], wn = wf[col * 8 + 2 * i + 1];
                    uint32_t zr = pack_bf16(acc[4 * i + 2 * col], acc[4 * i + 2 * col + 1]);
                    uint32_t zi = pack_bf16(acc[16 + 4 * i + 2 * col], acc[16 + 4 * i + 2 * col + 1]);
                    are[col][i] = hfma2(zr, wr, hmul2(zi, wn));
                    aim[col][i] = hfma2(zr, wn, hmul2(zi ^ 0x80008000u, wr));
                }
            }
            wg_fence();
#pragma unroll
            for (int ks = 0; ks < 2; ks++)
                wgmma_n64_rs(acc, are[0][2 * ks], are[1][2 * ks], are[0][2 * ks + 1], are[1][2 * ks + 1], desc_b<64>(s2b + ks * 2048), ks != 0);
#pragma unroll
            for (int ks = 0; ks < 2; ks++)
                wgmma_n64_rs(acc, aim[0][2 * ks], aim[1][2 * ks], aim[0][2 * ks + 1], aim[1][2 * ks + 1], desc_b<64>(s2b + 4096 + ks * 2048), 1);
            wg_commit();
            wg_wait<0>();
            if (wg == 0) TC(4 + 10 * layer);
#pragma unroll
            for (int col = 0; col < 2; col++) {
#pragma unroll
                for (int i = 0; i < 4; i++) {
                    uint32_t zr = pack_bf16(acc[4 * i + 2 * col], acc[4 * i + 2 * col + 1]);
                    uint32_t zi = pack_bf16(acc[16 + 4 * i + 2 * col], acc[16 + 4 * i + 2 * col + 1]);
                    sts32(st0 + 16384 + (4 * col + i) * 128, hfma2(zr, tr2[i], hmul2(zi, tn2[i])));
                    sts32(st0 + 16384 + 8192 + (4 * col + i) * 128, hfma2(zr, ti2[i], hmul2(zi, tr2[i])));
                }
            }
            if (wg == 0) TC(5 + 10 * layer);
            fence_async_smem();
            bar_sync(1, 256);
            wg_fence();
#pragma unroll
            for (int ks = 0; ks < 8; ks++)
                wgmma_n64<1>(acc, desc_a(s1a + (ks >> 2) * 8192 + (ks & 3) * 256), desc_b<64>(sb + SM_H + 16384 + ks * 2048), ks != 0);
            wg_commit();
            wg_wait<0>();
            if (wg == 0) TC(6 + 10 * layer);
            const float sc = 1.f / 2048.f;
            const float sci0 = sw ? 0.f : -sc;
            const float wr0 = sw ? 0.5f : 1.f, wi0 = sw ? 0.f : 1.f;
#pragma unroll
            for (int i = 0; i < 4; i++) {
                float ss0, ss1;
#pragma unroll
                for (int col = 0; col < 2; col++) {
                    int o = 4 * (4 * col + i);
                    uint32_t vr = xr[2 * col][i], vi = xr[2 * col + 1][i];
                    float si = col == 0 ? sci0 : -sc;
                    uint32_t nr = pack_bf16(fmaf(acc[o], sc, bf_lo(vr)), fmaf(acc[o + 1], sc, bf_hi(vr)));
                    uint32_t ni = pack_bf16(fmaf(acc[o + 2], si, bf_lo(vi)), fmaf(acc[o + 3], si, bf_hi(vi)));
                    float a0 = bf_lo(nr), a1 = bf_hi(nr), b0 = bf_lo(ni), b1 = bf_hi(ni);
                    if (col == 0) {
                        ss0 = wr0 * a0 * a0 + wi0 * b0 * b0;
                        ss1 = wr0 * a1 * a1 + wi0 * b1 * b1;
                    } else {
                        ss0 += a0 * a0 + b0 * b0;
                        ss1 += a1 * a1 + b1 * b1;
                    }
                    const int K = (2 * col) ^ (2 * (i & 1));
                    uint32_t a = rw0 + i * 256 + K * 16;
                    if (col == 0) a ^= sw << 4;
                    sts32(a, nr);
                    sts32(a ^ 16, ni);
                }
                *(float2*)(sm + SM_SSQ + (pos0 + 32 * i) * 4) = make_float2(ss0 * (2.f / 512.f), ss1 * (2.f / 512.f));
            }
            fence_async_smem();
        }
        TS(5 + 12 * layer);
        if (wg == 0) TC(7 + 10 * layer);
        bar_arrive(5, 416);

        float acc[64];
        float* s_rstd = (float*)(sm + SM_RSTD);
        float* s_mean = (float*)(sm + SM_MEAN);
        const unsigned epoch = s_tgt[0] >> 7;
        const uint32_t pt3 = 1u + (2u * epoch + layer) % 3u;
        const uint32_t ptag = (pt3 & 1u) | ((pt3 & 2u) << 15);
        const uint64_t dstep = layer == 0 ? 16 : 2;
        auto c_desc = [&](int s) { return layer == 0 ? desc_a(sb + SM_A + s * 16384) : desc_k(sb + SM_A + s * 16384); };
        if (wg < 2) {
            const int prow = 32 * wg + 8 * w + g;
            const float2 l1 = *(const float2*)(sm + SM_LAM + prow * 8);
            float lr32 = l1.x, li32 = l1.y;
#pragma unroll
            for (int i = 0; i < 5; i++) { float t = lr32 * lr32 - li32 * li32; li32 = 2.f * lr32 * li32; lr32 = t; }
            float lr128 = lr32, li128 = li32;
#pragma unroll
            for (int i = 0; i < 2; i++) { float t = lr128 * lr128 - li128 * li128; li128 = 2.f * lr128 * li128; lr128 = t; }
            const float lr1 = l1.x, li1 = l1.y;
            acc_def(acc);
#pragma unroll 1
            for (int kb = 0; kb < 8; kb++) {
                mbar_wait(BAR(B_AFULL + kb), 0);
                mbar_wait(BAR(B_XFULL + (kb & 3)), (kb >> 2) & 1);
                wg_fence();
#pragma unroll
                for (int ks = 0; ks < 4; ks++)
                    wgmma_n128<1>(acc, desc_a(sb + SM_A + kb * 16384 + wg * 8192 + ks * 256),
                                  desc_b<128>(sb + SM_X + (kb & 3) * 24576 + ks * 4096), 1);
                wg_commit();
                wg_wait<1>();
                if (kb > 0 && lane == 0) {
                    mbar_arrive(BAR(B_AEMPTY + kb - 1), 1); mbar_arrive(BAR(B_XEMPTY + ((kb - 1) & 3)), 1);
                    mbar_arrive_remote(mapa(BAR(B_XEMPTY + ((kb - 1) & 3)), par ^ 1));
                }
            }
            wg_wait<0>();
            if (lane == 0) {
                mbar_arrive(BAR(B_AEMPTY + 7), 1); mbar_arrive(BAR(B_XEMPTY + 3), 1);
                mbar_arrive_remote(mapa(BAR(B_XEMPTY + 3), par ^ 1)); mbar_arrive_remote(mapa(BAR(B_RFREE), par ^ 1));
            }
            bar_arrive(14, 384);
            TS(6 + 12 * layer);
            bar_sync(4, 384);
            TS(7 + 12 * layer);
            float er = 0.f, ei = 0.f;
#pragma unroll
            for (int i = 0; i < 16; i++) {
                float2 rs = *(const float2*)(s_rstd + 128 + 8 * i + 2 * q);
                acc[4 * i] *= rs.x; acc[4 * i + 1] *= rs.y; acc[4 * i + 2] *= rs.x; acc[4 * i + 3] *= rs.y;
                float nr = lr1 * er - li1 * ei + acc[4 * i], ni = lr1 * ei + li1 * er + acc[4 * i + 2];
                er = lr1 * nr - li1 * ni + acc[4 * i + 1];
                ei = lr1 * ni + li1 * nr + acc[4 * i + 3];
            }
            float cr = 0.f, ci = 0.f, tr = 0.f, ti = 0.f;
#pragma unroll
            for (int qq = 0; qq < 4; qq++) {
                float xr_ = __shfl_sync(~0u, er, (lane & ~3) | qq), xi_ = __shfl_sync(~0u, ei, (lane & ~3) | qq);
                if (qq == q) { cr = tr; ci = ti; }
                float nr = lr32 * tr - li32 * ti + xr_, ni = lr32 * ti + li32 * tr + xi_;
                tr = nr; ti = ni;
            }
            float4* eb = g_Ebuf + (uint32_t)(layer * 16 * 512 + 64 * r + prow);
            if (q == 0 && c < 15) st_relaxed_f4(eb + c * 512, make_float4(tr, ti, __uint_as_float(epoch), 0.f));
            TS(8 + 12 * layer);
            float pr[4], pi[4];
            {
                unsigned n = 0;
                bool ok;
#pragma unroll 1
                do {
                    ok = true;
#pragma unroll
                    for (int k = 0; k < 4; k++) {
                        float4 v = make_float4(0.f, 0.f, __uint_as_float(epoch), 0.f);
                        if (4 * k + q < c) v = ld_relaxed_f4(eb + (4 * k + q) * 512);
                        pr[k] = v.x; pi[k] = v.y;
                        ok = ok && __float_as_uint(v.z) == epoch;
                    }
                } while (!ok && ++n < SPIN_LIMIT);
            }
            __syncwarp();
            TS(9 + 12 * layer);
            float hr = 0.f, hi = 0.f;
#pragma unroll
            for (int cc = 0; cc < 15; cc++) {
                float xr_ = __shfl_sync(~0u, pr[cc >> 2], (lane & ~3) | (cc & 3)), xi_ = __shfl_sync(~0u, pi[cc >> 2], (lane & ~3) | (cc & 3));
                if (cc < c) {
                    float nr = lr128 * hr - li128 * hi + xr_, ni = lr128 * hi + li128 * hr + xi_;
                    hr = nr; hi = ni;
                }
            }
#pragma unroll
            for (int qq = 0; qq < 3; qq++) {
                if (qq < q) { float nr = lr32 * hr - li32 * hi, ni = lr32 * hi + li32 * hr; hr = nr; hi = ni; }
            }
            er = cr + hr; ei = ci + hi;
            bar_sync(7, 384);
            mbar_wait_cluster(BAR(B_RFREE), layer);
            const uint32_t ha = sb + SM_HH + par * 32768 + (prow >> 3) * 1024 + g * 16 + 4 * q;
#pragma unroll
            for (int i = 0; i < 16; i++) {
                float nr = lr1 * er - li1 * ei + acc[4 * i], ni = lr1 * ei + li1 * er + acc[4 * i + 2];
                er = lr1 * nr - li1 * ni + acc[4 * i + 1];
                ei = lr1 * ni + li1 * nr + acc[4 * i + 3];
                sts32(ha + (i >> 3) * 16384 + (i & 7) * 128, pack_bf16(nr, er));
                sts32(ha + (i >> 3) * 16384 + 8192 + (i & 7) * 128, pack_bf16(ni, ei));
                if (i == 7) { fence_async_smem(); bar_arrive(13, 288); }
            }
            fence_async_smem();
            acc_def(acc);
            float acc2[32];
            acc_def(acc2);
            TS(10 + 12 * layer);
            bar_sync(6, 416);
            TS(11 + 12 * layer);
            float (&a0)[32] = *reinterpret_cast<float (*)[32]>(&acc[0]);
            float (&a1)[32] = *reinterpret_cast<float (*)[32]>(&acc[32]);
            auto tile_mma = [&](float (&d)[32], int u) {
#pragma unroll 1
                for (int k = 0; k < 2; k++) {
                    const uint32_t hb = sb + SM_HH + (par ^ k) * 32768 + wg * 16384;
                    if (k == 1) mbar_wait(BAR(wg ? B_HPEER1 : B_HPEER), layer);
                    mbar_wait(BAR(B_AFULL + 2 * u + k), 1);
                    const uint64_t da = c_desc(2 * u + k);
                    wg_fence();
#pragma unroll
                    for (int ks = 0; ks < 4; ks++) wgmma_n64s<1>(d, da + ks * dstep, desc_b<64>(hb + ks * 2048), 1);
#pragma unroll
                    for (int ks = 0; ks < 4; ks++) wgmma_n64s<-1>(d, da + 512 + ks * dstep, desc_b<64>(hb + 8192 + ks * 2048), 1);
                }
                wg_commit();
            };
            auto tile_ship = [&](float (&d)[32], int u) {
                uint4* dst = g_P + (uint32_t)(((c * 8 + 2 * ((pi_ + 1 + u) & 3) + par) * 4 + pi_) * 1024 + wg * 512 + (tid & 127));
#pragma unroll
                for (int i = 0; i < 4; i++)
                    dst[i * 128] = make_uint4((pack_bf16(d[8 * i], d[8 * i + 1]) & 0xfffefffeu) | ptag, pack_bf16(d[8 * i + 2], d[8 * i + 3]),
                                              pack_bf16(d[8 * i + 4], d[8 * i + 5]), pack_bf16(d[8 * i + 6], d[8 * i + 7]));
            };
            tile_mma(a0, 0);
            if ((tid & 127) == 0) mbar_arrive_remote(mapa(BAR(B_HDONE), par ^ 1));
            __syncwarp();
            tile_mma(a1, 1);
            wg_wait<1>();
            tile_ship(a0, 0);
            tile_mma(acc2, 2);
            bar_arrive(12, 384);
            wg_wait<1>();
            tile_ship(a1, 1);
            wg_wait<0>();
            tile_ship(acc2, 2);
            if (lane < 6) mbar_arrive(BAR(B_AEMPTY + lane), 1);
            TS(12 + 12 * layer);
        } else {
            const int t2 = tid - 256;
            const uint8_t* ximg = g_X + (uint32_t)layer * 16 * 8 * 16384;
            mbar_wait(BAR(B_SSQ), layer);
            TS(6 + 12 * layer);
            {
                float tot = 0.f;
#pragma unroll
                for (int i = 0; i < 16; i++) tot += __ldcg(g_ssqc + (layer * 16 + i) * 2048 + 128 * c + t2);
                float rs = rsqrtf(tot * (1.f / 512.f) + 1e-5f);
                s_rstd[t2] = rs;
                s_rstd[128 + t2] = 2.f * rs;
                if (layer == 0) s_mean[t2] = 0.f;
                if (layer == 1) {
                    unsigned short u = __ldcg((const unsigned short*)(ximg + (uint32_t)(c * 8 * 16384 + (t2 >> 3) * 128 + (t2 & 7) * 2)));
                    s_mean[t2] = __uint_as_float((uint32_t)u << 16) * (1.f / 512.f);
                }
            }
            TS(7 + 12 * layer);
            bar_arrive(4, 384);
            acc_def(acc);
#pragma unroll 1
            for (int kb = 0; kb < 8; kb++) {
                if (kb == 4) {
                    wg_wait<0>();
                    if (lane == 0) { mbar_arrive(BAR(B_XEMPTY + 3), 1); mbar_arrive_remote(mapa(BAR(B_XEMPTY + 3), par ^ 1)); }
                    bar_sync(14, 384);
                }
                mbar_wait(BAR(B_XFULL + (kb & 3)), (kb >> 2) & 1);
                wg_fence();
#pragma unroll
                for (int ks = 0; ks < 4; ks++)
                    wgmma_n128<1>(acc, desc_a(sb + SM_X + (kb & 3) * 24576 + 16384 + ks * 256), desc_b<128>(sb + SM_X + (kb & 3) * 24576 + ks * 4096), 1);
                wg_commit();
                wg_wait<1>();
                if ((kb & 3) != 0 && lane == 0) { mbar_arrive(BAR(B_XEMPTY + ((kb - 1) & 3)), 1); mbar_arrive_remote(mapa(BAR(B_XEMPTY + ((kb - 1) & 3)), par ^ 1)); }
            }
            wg_wait<0>();
            if (lane == 0) { mbar_arrive(BAR(B_XEMPTY + 3), 1); mbar_arrive_remote(mapa(BAR(B_XEMPTY + 3), par ^ 1)); mbar_arrive_remote(mapa(BAR(B_RFREE), par ^ 1)); }
            bar_arrive(7, 384);
            bar_sync(3, 128);
            TS(9 + 12 * layer);
            const int m0 = 16 * w + g;
            const uint32_t xoff = (uint32_t)((c * 8 + own) * 16384 + w * 4096 + g * 16 + 4 * q);
            if (layer == 0) {
                const uint8_t* xs = g_X + xoff;
#pragma unroll
                for (int i = 0; i < 16; i++) {
                    float2 rs = *(const float2*)(s_rstd + 8 * i + 2 * q);
                    uint32_t x0v = __ldcg((const uint32_t*)(xs + i * 128)), x1v = __ldcg((const uint32_t*)(xs + 2048 + i * 128));
                    acc[4 * i] = acc[4 * i] * rs.x + bf_lo(x0v);
                    acc[4 * i + 1] = acc[4 * i + 1] * rs.y + bf_hi(x0v);
                    acc[4 * i + 2] = acc[4 * i + 2] * rs.x + bf_lo(x1v);
                    acc[4 * i + 3] = acc[4 * i + 3] * rs.y + bf_hi(x1v);
                }
            } else {
                float d0 = ldbf(p.dskip + 64 * own + m0), d1 = ldbf(p.dskip + 64 * own + m0 + 8);
#pragma unroll
                for (int i = 0; i < 16; i++) {
                    float2 rs = *(const float2*)(s_rstd + 8 * i + 2 * q);
                    float2 mn = *(const float2*)(s_mean + 8 * i + 2 * q);
                    acc[4 * i] = acc[4 * i] * (1.f + rs.x * d0) + mn.x;
                    acc[4 * i + 1] = acc[4 * i + 1] * (1.f + rs.y * d0) + mn.y;
                    acc[4 * i + 2] = acc[4 * i + 2] * (1.f + rs.x * d1) + mn.x;
                    acc[4 * i + 3] = acc[4 * i + 3] * (1.f + rs.y * d1) + mn.y;
                }
            }
            TS(10 + 12 * layer);
            bar_sync(6, 416);
            TS(11 + 12 * layer);
            {
                float (&a0)[32] = *reinterpret_cast<float (*)[32]>(&acc[0]);
                float (&a1)[32] = *reinterpret_cast<float (*)[32]>(&acc[32]);
#pragma unroll 1
                for (int k = 0; k < 2; k++) {
                    const uint32_t hb = sb + SM_HH + (par ^ k) * 32768;
                    if (k == 1) {
                        mbar_wait(BAR(B_HPEER), layer);
                        mbar_wait(BAR(B_HPEER1), layer);
                        bar_sync(12, 384);
                    }
                    mbar_wait(BAR(B_AFULL + 6 + k), 1);
                    const uint64_t da = c_desc(6 + k);
                    wg_fence();
#pragma unroll
                    for (int ks = 0; ks < 4; ks++) {
                        wgmma_n64s<1>(a0, da + ks * dstep, desc_b<64>(hb + ks * 2048), 1);
                        wgmma_n64s<1>(a1, da + ks * dstep, desc_b<64>(hb + 16384 + ks * 2048), 1);
                    }
#pragma unroll
                    for (int ks = 0; ks < 4; ks++) {
                        wgmma_n64s<-1>(a0, da + 512 + ks * dstep, desc_b<64>(hb + 8192 + ks * 2048), 1);
                        wgmma_n64s<-1>(a1, da + 512 + ks * dstep, desc_b<64>(hb + 16384 + 8192 + ks * 2048), 1);
                    }
                    wg_commit();
                }
                wg_wait<0>();
            }
#pragma unroll
            for (int i = 0; i < 16; i++)
                *(float4*)(sm + SM_A + 6 * 16384 + i * 2048 + t2 * 16) = make_float4(acc[4 * i], acc[4 * i + 1], acc[4 * i + 2], acc[4 * i + 3]);
            TS(12 + 12 * layer);
        }
        {
            const int t = tid & 127;
            const int nch = wg == 2 ? 2 : 3;
            const uint4* pb = g_P + (uint32_t)((c * 8 + r) * 4 * 1024 + wg * 128 + t);
            uint4 v[3][3];
            unsigned n = 0;
#pragma unroll 1
            while (true) {
                if (lane == 31) {
#pragma unroll 1
                    while (true) {
                        uint32_t bad = 0;
#pragma unroll
                        for (int sx = 0; sx < 3; sx++) {
                            uint32_t t0;
                            asm volatile("ld.relaxed.gpu.global.u32 %0, [%1];" : "=r"(t0) : "l"(pb + ((pi_ + 1 + sx) & 3) * 1024 + (nch - 1) * 384) : "memory");
                            bad |= t0 ^ ptag;
                        }
                        if (!(bad & 0x00010001u) || ++n >= SPIN_LIMIT) break;
                    }
                }
                __syncwarp();
                uint32_t bad = 0;
#pragma unroll
                for (int k = 0; k < 3; k++)
#pragma unroll
                    for (int sx = 0; sx < 3; sx++) {
                        v[k][sx] = make_uint4(ptag, 0, 0, 0);
                        if (k < nch) v[k][sx] = ld_relaxed_u4(pb + ((pi_ + 1 + sx) & 3) * 1024 + k * 384);
                        bad |= v[k][sx].x ^ ptag;
                    }
                if (!__any_sync(~0u, bad & 0x00010001u) || ++n >= SPIN_LIMIT) break;
            }
            bar_sync(8, 384);
            TS(13 + 12 * layer);
            const int m0 = 16 * w + g;
            const float w0 = (own == 0 && m0 < 2) ? (m0 == 0 ? 0.f : 0.5f) : 1.f;
#pragma unroll
            for (int k = 0; k < 3; k++) {
                if (k < nch) {
                    const int i = wg + 3 * k;
                    float4 a = *(const float4*)(sm + SM_A + 6 * 16384 + (2 * i) * 2048 + t * 16);
                    float4 bq = *(const float4*)(sm + SM_A + 6 * 16384 + (2 * i + 1) * 2048 + t * 16);
#pragma unroll
                    for (int sx = 0; sx < 3; sx++) {
                        a.x += bf_lo(v[k][sx].x); a.y += bf_hi(v[k][sx].x); a.z += bf_lo(v[k][sx].y); a.w += bf_hi(v[k][sx].y);
                        bq.x += bf_lo(v[k][sx].z); bq.y += bf_hi(v[k][sx].z); bq.z += bf_lo(v[k][sx].w); bq.w += bf_hi(v[k][sx].w);
                    }
                    if (layer == 0) {
                        uint8_t* xd = g_X + (uint32_t)((16 * 8 + c * 8 + own) * 16384 + w * 4096 + g * 16 + 4 * q + i * 256);
                        uint32_t v0 = pack_bf16(a.x, a.y), v1 = pack_bf16(a.z, a.w), v2 = pack_bf16(bq.x, bq.y), v3 = pack_bf16(bq.z, bq.w);
                        *(uint32_t*)(xd) = v0; *(uint32_t*)(xd + 2048) = v1; *(uint32_t*)(xd + 128) = v2; *(uint32_t*)(xd + 2048 + 128) = v3;
                        float sq[4];
                        sq[0] = w0 * bf_lo(v0) * bf_lo(v0) + bf_lo(v1) * bf_lo(v1);
                        sq[1] = w0 * bf_hi(v0) * bf_hi(v0) + bf_hi(v1) * bf_hi(v1);
                        sq[2] = w0 * bf_lo(v2) * bf_lo(v2) + bf_lo(v3) * bf_lo(v3);
                        sq[3] = w0 * bf_hi(v2) * bf_hi(v2) + bf_hi(v3) * bf_hi(v3);
                        float u0 = (g & 1) ? sq[2] : sq[0], u1 = (g & 1) ? sq[3] : sq[1];
                        u0 += __shfl_xor_sync(~0u, (g & 1) ? sq[0] : sq[2], 4);
                        u1 += __shfl_xor_sync(~0u, (g & 1) ? sq[1] : sq[3], 4);
                        float z = (g & 2) ? u1 : u0;
                        z += __shfl_xor_sync(~0u, (g & 2) ? u0 : u1, 8);
                        z += __shfl_xor_sync(~0u, z, 16);
                        if (g < 4) atomicAdd(s_mean + 16 * i + 8 * (g & 1) + 2 * q + (g >> 1), z);
                    } else {
                        float* o = p.out + (uint32_t)((128 * c + 32 * q + 4 * i) * 512 + 64 * own + m0);
                        o[0] = a.x; o[512] = a.y; o[8] = a.z; o[512 + 8] = a.w;
                        o[1024] = bq.x; o[1536] = bq.y; o[1024 + 8] = bq.z; o[1536 + 8] = bq.w;
                    }
                }
            }
            if (wg < 2) mbar_wait_cluster(BAR(B_HDONE), layer);
            if (layer == 0) {
                fence_async_smem();
                bar_sync(9, 384);
                TS(14 + 12 * layer);
                if (wg == 2) {
                    atomicAdd(g_ssq + 2048 + 128 * c + t, s_mean[t] * (2.f / 512.f));
                    bar_sync(3, 128);
                    if (lane == 0) { mbar_arrive(BAR(B_AEMPTY + 6), 2); mbar_arrive(BAR(B_AEMPTY + 7), 2); }
                    if (t == 0) { fence_async(); red_release(&g_bar[2], 1); }
                }
            }
        }
        TS(15 + 12 * layer);
        if (wg == 0) TC(31);
    }
}

typedef CUresult (*EncFn)(CUtensorMap*, CUtensorMapDataType, cuuint32_t, void*, const cuuint64_t*, const cuuint64_t*,
                          const cuuint32_t*, const cuuint32_t*, CUtensorMapInterleave, CUtensorMapSwizzle,
                          CUtensorMapL2promotion, CUtensorMapFloatOOBfill);

void launch_impl(void* const* d_in, void* d_out, int stop) {
    static EncFn enc = nullptr;
    if (!enc) {
        void* fn = nullptr;
        cudaDriverEntryPointQueryResult qr;
        cudaGetDriverEntryPoint("cuTensorMapEncodeTiled", &fn, cudaEnableDefault, &qr);
        enc = (EncFn)fn;
        cudaFuncSetAttribute(fused_kernel, cudaFuncAttributeMaxDynamicSharedMemorySize, SM_TOTAL);
    }
    CUtensorMap tx, tbr, tbi, tcr, tci, tcol;
    {
        void* gx = nullptr;
        cudaGetSymbolAddress(&gx, g_X);
        cuuint64_t gd[5] = {64, 16, 64, 16, 2};
        cuuint64_t gs[4] = {128, 2048, 128 * 1024, 2048 * 1024};
        cuuint32_t bx[5] = {32, 16, 1, 16, 1};
        cuuint32_t es[5] = {1, 1, 1, 1, 1};
        enc(&tcol, CU_TENSOR_MAP_DATA_TYPE_BFLOAT16, 5, gx, gd, gs, bx, es, CU_TENSOR_MAP_INTERLEAVE_NONE,
            CU_TENSOR_MAP_SWIZZLE_64B, CU_TENSOR_MAP_L2_PROMOTION_NONE, CU_TENSOR_MAP_FLOAT_OOB_FILL_NONE);
    }
    {
        cuuint64_t gd[5] = {512, 2, 4, 16, 16};
        cuuint64_t gs[4] = {1024, 32 * 1024, 2 * 1024, 128 * 1024};
        cuuint32_t bx[5] = {64, 2, 4, 8, 1};
        cuuint32_t es[5] = {1, 1, 1, 1, 1};
        enc(&tx, CU_TENSOR_MAP_DATA_TYPE_BFLOAT16, 5, d_in[0], gd, gs, bx, es, CU_TENSOR_MAP_INTERLEAVE_NONE,
            CU_TENSOR_MAP_SWIZZLE_128B, CU_TENSOR_MAP_L2_PROMOTION_L2_128B, CU_TENSOR_MAP_FLOAT_OOB_FILL_NONE);
    }
    auto mk2 = [&](CUtensorMap* m, void* ptr, cuuint32_t rows) {
        cuuint64_t gd[2] = {512, 512};
        cuuint64_t gs[1] = {1024};
        cuuint32_t bx[2] = {64, rows};
        cuuint32_t es[2] = {1, 1};
        enc(m, CU_TENSOR_MAP_DATA_TYPE_BFLOAT16, 2, ptr, gd, gs, bx, es, CU_TENSOR_MAP_INTERLEAVE_NONE,
            CU_TENSOR_MAP_SWIZZLE_128B, CU_TENSOR_MAP_L2_PROMOTION_L2_128B, CU_TENSOR_MAP_FLOAT_OOB_FILL_NONE);
    };
    mk2(&tbr, d_in[6], 32);
    mk2(&tbi, d_in[7], 32);
    mk2(&tcr, d_in[8], 64);
    mk2(&tci, d_in[9], 64);
    Params p;
    p.x0 = (const __nv_bfloat16*)d_in[0];
    p.w_r = (const __nv_bfloat16*)d_in[1];
    p.w_i = (const __nv_bfloat16*)d_in[2];
    p.lam_re = (const __nv_bfloat16*)d_in[4];
    p.lam_im = (const __nv_bfloat16*)d_in[5];
    p.log_dt = (const __nv_bfloat16*)d_in[10];
    p.dskip = (const __nv_bfloat16*)d_in[11];
    p.out = (float*)d_out;
    p.stop = stop;
    cudaLaunchConfig_t cfg = {};
    cfg.gridDim = dim3(NCTA); cfg.blockDim = dim3(NTHREADS); cfg.dynamicSmemBytes = SM_TOTAL; cfg.stream = cudaStreamPerThread;
    cudaLaunchAttribute at[1];
    at[0].id = cudaLaunchAttributeClusterDimension;
    at[0].val.clusterDim.x = 2; at[0].val.clusterDim.y = 1; at[0].val.clusterDim.z = 1;
    cfg.attrs = at; cfg.numAttrs = 1;
    cudaLaunchKernelEx(&cfg, fused_kernel, tx, tbr, tbi, tcr, tci, tcol, p);
}

}

extern "C" void kernel_launch(void* const* d_in, const int* in_sizes, int n_in, void* d_out, int out_size) {
    (void)in_sizes; (void)n_in; (void)out_size;
    launch_impl(d_in, d_out, 100);
}
```

```cpp
#include <cuda_runtime.h>
#include <cuda_bf16.h>
#include <cuda.h>
#include <stdint.h>

namespace {

constexpr int NCTA = 128;
constexpr int NTHREADS = 512;
constexpr int SM_A = 0;
constexpr int SM_X = 131072;
constexpr int SM_H = 196608;
constexpr int SM_HH = SM_X + 32768;
constexpr int SM_M = 229376;
constexpr int SM_TOTAL = 232448;
constexpr int SM_BAR = SM_M;
constexpr int SM_TGT = SM_M + 360;
constexpr int SM_LAM = SM_M + 384;
constexpr int SM_TAB = SM_M + 896;
constexpr int SM_RSTD = SM_M + 1920;
constexpr int SM_MEAN = SM_TAB;
constexpr int SM_T64 = SM_M + 2944;
constexpr int SM_B1ST = SM_H + 24576;
constexpr int SM_RAW = SM_X + 40960;
constexpr int SM_SSQ = SM_X + 57344;
constexpr int B_FULL0 = 0;
constexpr int B_EMPTY0 = 8;
constexpr int B_FULLC = 12;
constexpr int B_AFULL = 13;
constexpr int B_AEMPTY = 21;
constexpr int B_XFULL = 29;
constexpr int B_XEMPTY = 33;
constexpr int B_AFREE = 37;
constexpr int B_COL = 38;
constexpr int B_SSQ = 39;
constexpr int B_HPEER = 40;
constexpr int B_RFREE = 41;
constexpr int B_HDONE = 42;
constexpr int B_WRDY = 43;
constexpr int B_HPEER1 = 44;
constexpr int NBARS = 45;

__device__ __align__(1024) uint8_t g_X[2 * 16 * 8 * 16384];
__device__ __align__(1024) uint8_t g_A1[8 * 8 * 16384];
__device__ __align__(1024) uint8_t g_A2[8 * 8 * 16384];
__device__ __align__(1024) uint8_t g_E[2 * 8 * 8 * 8192];
__device__ __align__(16) float g_ssq[2 * 2048];
__device__ __align__(16) float g_ssqc[2 * 16 * 2048];
__device__ __align__(16) float g_Dh[512];
__device__ __align__(16) uint4 g_Wfrag[128 * 4 * 256];
__device__ __align__(16) float4 g_Ebuf[2 * 16 * 512];
__device__ __align__(16) uint4 g_P[16 * 8 * 4 * 1024];
__device__ unsigned g_bar[8];
__device__ unsigned g_err;
#define TX(i)
#define TQ(i)
#define TS(i)
#define TC(i)

constexpr unsigned SPIN_LIMIT = 1u << 22;

__device__ __forceinline__ uint32_t s2u(const void* p) { return (uint32_t)__cvta_generic_to_shared(p); }
__device__ __forceinline__ void mbar_init(uint32_t a, uint32_t c) {
    asm volatile("mbarrier.init.shared::cta.b64 [%0], %1;" ::"r"(a), "r"(c) : "memory");
}
__device__ __forceinline__ void mbar_expect(uint32_t a, uint32_t bytes) {
    asm volatile("mbarrier.arrive.expect_tx.shared::cta.b64 _, [%0], %1;" ::"r"(a), "r"(bytes) : "memory");
}
__device__ __forceinline__ void mbar_arrive(uint32_t a, uint32_t cnt) {
    asm volatile("mbarrier.arrive.shared::cta.b64 _, [%0], %1;" ::"r"(a), "r"(cnt) : "memory");
}
__device__ __forceinline__ bool mbar_try(uint32_t a, uint32_t parity) {
    uint32_t ok;
    asm volatile("{\n.reg .pred p;\nmbarrier.try_wait.parity.shared::cta.b64 p, [%1], %2;\nselp.u32 %0, 1, 0, p;\n}"
                 : "=r"(ok) : "r"(a), "r"(parity) : "memory");
    return ok != 0;
}
__device__ __forceinline__ void mbar_wait(uint32_t a, uint32_t parity) {
    asm volatile("{\n.reg .pred p, q;\n.reg .u32 n;\nmov.u32 n, 0;\n"
                 "W_%=:\nmbarrier.try_wait.parity.shared::cta.b64 p, [%0], %1;\n@p bra D_%=;\n"
                 "add.u32 n, n, 1;\nsetp.lt.u32 q, n, 4194304;\n@q bra W_%=;\nD_%=:\n}" ::"r"(a), "r"(parity) : "memory");
}
__device__ __forceinline__ void bulk_g2s(uint32_t dst, const void* src, uint32_t bytes, uint32_t bar) {
    asm volatile("cp.async.bulk.shared::cluster.global.mbarrier::complete_tx::bytes [%0], [%1], %2, [%3];" ::"r"(dst),
                 "l"(src), "r"(bytes), "r"(bar) : "memory");
}
__device__ __forceinline__ void tma_2d(uint32_t dst, const CUtensorMap* m, int c0, int c1, uint32_t bar) {
    asm volatile("cp.async.bulk.tensor.2d.shared::cluster.global.mbarrier::complete_tx::bytes [%0], [%1, {%3,%4}], [%2];" ::"r"(dst),
                 "l"(m), "r"(bar), "r"(c0), "r"(c1) : "memory");
}
__device__ __forceinline__ void tma_5d(uint32_t dst, const CUtensorMap* m, int c0, int c1, int c2, int c3, int c4, uint32_t bar) {
    asm volatile("cp.async.bulk.tensor.5d.shared::cluster.global.mbarrier::complete_tx::bytes [%0], [%1, {%3,%4,%5,%6,%7}], [%2];" ::"r"(dst),
                 "l"(m), "r"(bar), "r"(c0), "r"(c1), "r"(c2), "r"(c3), "r"(c4) : "memory");
}
__device__ __forceinline__ void tma_2d_mc(uint32_t dst, const CUtensorMap* m, int c0, int c1, uint32_t bar) {
    asm volatile("cp.async.bulk.tensor.2d.shared::cluster.global.mbarrier::complete_tx::bytes.multicast::cluster [%0], [%1, {%3,%4}], [%2], %5;" ::"r"(dst),
                 "l"(m), "r"(bar), "r"(c0), "r"(c1), "h"((unsigned short)3) : "memory");
}
__device__ __forceinline__ void tma_5d_mc(uint32_t dst, const CUtensorMap* m, int c0, int c1, int c2, int c3, int c4, uint32_t bar) {
    asm volatile("cp.async.bulk.tensor.5d.shared::cluster.global.mbarrier::complete_tx::bytes.multicast::cluster [%0], [%1, {%3,%4,%5,%6,%7}], [%2], %8;" ::"r"(dst),
                 "l"(m), "r"(bar), "r"(c0), "r"(c1), "r"(c2), "r"(c3), "r"(c4), "h"((unsigned short)3) : "memory");
}
__device__ __forceinline__ void bulk_g2s_mc(uint32_t dst, const void* src, uint32_t bytes, uint32_t bar) {
    asm volatile("cp.async.bulk.shared::cluster.global.mbarrier::complete_tx::bytes.multicast::cluster [%0], [%1], %2, [%3], %4;" ::"r"(dst),
                 "l"(src), "r"(bytes), "r"(bar), "h"((unsigned short)3) : "memory");
}
__device__ __forceinline__ void tma_store_5d(const CUtensorMap* m, int c0, int c1, int c2, int c3, int c4, uint32_t src) {
    asm volatile("cp.async.bulk.tensor.5d.global.shared::cta.bulk_group [%0, {%2,%3,%4,%5,%6}], [%1];" ::"l"(m), "r"(src),
                 "r"(c0), "r"(c1), "r"(c2), "r"(c3), "r"(c4) : "memory");
}
__device__ __forceinline__ uint32_t lds32(uint32_t a) { uint32_t v; asm volatile("ld.shared.u32 %0, [%1];" : "=r"(v) : "r"(a) : "memory"); return v; }
__device__ __forceinline__ uint4 ld_relaxed_u4(const uint4* p) {
    uint4 v;
    asm volatile("ld.relaxed.gpu.global.v4.u32 {%0,%1,%2,%3}, [%4];" : "=r"(v.x), "=r"(v.y), "=r"(v.z), "=r"(v.w) : "l"(p) : "memory");
    return v;
}
__device__ __forceinline__ void fence_async() { asm volatile("fence.proxy.async.global;" ::: "memory"); }
__device__ __forceinline__ void red_relaxed(unsigned* p, unsigned v) {
    asm volatile("red.relaxed.gpu.global.add.u32 [%0], %1;" ::"l"(p), "r"(v) : "memory");
}
__device__ __forceinline__ uint32_t mapa(uint32_t a, uint32_t rank) {
    uint32_t d;
    asm("mapa.shared::cluster.u32 %0, %1, %2;" : "=r"(d) : "r"(a), "r"(rank));
    return d;
}
__device__ __forceinline__ void mbar_arrive_remote(uint32_t ra) {
    asm volatile("mbarrier.arrive.relaxed.cluster.shared::cluster.b64 _, [%0];" ::"r"(ra) : "memory");
}
__device__ __forceinline__ void mbar_wait_cluster(uint32_t a, uint32_t parity) {
    asm volatile("{\n.reg .pred p, q;\n.reg .u32 n;\nmov.u32 n, 0;\n"
                 "W_%=:\nmbarrier.try_wait.parity.acquire.cluster.shared::cta.b64 p, [%0], %1;\n@p bra D_%=;\n"
                 "add.u32 n, n, 1;\nsetp.lt.u32 q, n, 4194304;\n@q bra W_%=;\nD_%=:\n}" ::"r"(a), "r"(parity) : "memory");
}
__device__ __forceinline__ void bulk_s2peer(uint32_t rdst, uint32_t src, uint32_t bytes, uint32_t rbar) {
    asm volatile("cp.async.bulk.shared::cluster.shared::cta.mbarrier::complete_tx::bytes [%0], [%1], %2, [%3];" ::"r"(rdst),
                 "r"(src), "r"(bytes), "r"(rbar) : "memory");
}
__device__ __forceinline__ void fence_async_smem() { asm volatile("fence.proxy.async.shared::cta;" ::: "memory"); }
__device__ __forceinline__ void wg_fence() { asm volatile("wgmma.fence.sync.aligned;" ::: "memory"); }
__device__ __forceinline__ void wg_commit() { asm volatile("wgmma.commit_group.sync.aligned;" ::: "memory"); }
template <int N> __device__ __forceinline__ void wg_wait() { asm volatile("wgmma.wait_group.sync.aligned %0;" ::"n"(N) : "memory"); }
__device__ __forceinline__ void bar_sync(int id, int n) { asm volatile("bar.sync %0, %1;" ::"r"(id), "r"(n) : "memory"); }
__device__ __forceinline__ void bar_arrive(int id, int n) { asm volatile("bar.arrive %0, %1;" ::"r"(id), "r"(n) : "memory"); }
__device__ __forceinline__ unsigned ld_acquire(const unsigned* p) {
    unsigned v;
    asm volatile("ld.acquire.gpu.global.u32 %0, [%1];" : "=r"(v) : "l"(p) : "memory");
    return v;
}
__device__ __forceinline__ void red_release(unsigned* p, unsigned v) {
    asm volatile("red.release.gpu.global.add.u32 [%0], %1;" ::"l"(p), "r"(v) : "memory");
}
__device__ __forceinline__ void wait_count(const unsigned* p, unsigned target) {
    unsigned n = 0;
#pragma unroll 1
    while ((int)(ld_acquire(p) - target) < 0 && ++n < SPIN_LIMIT) {}
}
__device__ __forceinline__ float4 ld_relaxed_f4(const float4* p) {
    float4 v;
    asm volatile("ld.relaxed.gpu.global.v4.f32 {%0,%1,%2,%3}, [%4];" : "=f"(v.x), "=f"(v.y), "=f"(v.z), "=f"(v.w) : "l"(p) : "memory");
    return v;
}
__device__ __forceinline__ void st_relaxed_f4(float4* p, float4 v) {
    asm volatile("st.relaxed.gpu.global.v4.f32 [%0], {%1,%2,%3,%4};" ::"l"(p), "f"(v.x), "f"(v.y), "f"(v.z), "f"(v.w) : "memory");
}
__device__ __forceinline__ uint32_t pack_bf16(float lo, float hi) {
    uint32_t r;
    asm("cvt.rn.bf16x2.f32 %0, %1, %2;" : "=r"(r) : "f"(hi), "f"(lo));
    return r;
}
__device__ __forceinline__ uint32_t hmul2(uint32_t a, uint32_t b) {
    uint32_t r;
    asm("mul.rn.bf16x2 %0, %1, %2;" : "=r"(r) : "r"(a), "r"(b));
    return r;
}
__device__ __forceinline__ uint32_t hfma2(uint32_t a, uint32_t b, uint32_t c) {
    uint32_t r;
    asm("fma.rn.bf16x2 %0, %1, %2, %3;" : "=r"(r) : "r"(a), "r"(b), "r"(c));
    return r;
}
__device__ __forceinline__ float bf_lo(uint32_t v) { return __uint_as_float(v << 16); }
__device__ __forceinline__ float bf_hi(uint32_t v) { return __uint_as_float(v & 0xffff0000u); }
__device__ __forceinline__ void sts32(uint32_t a, uint32_t v) { asm volatile("st.shared.u32 [%0], %1;" ::"r"(a), "r"(v) : "memory"); }
__device__ __forceinline__ void sts128(uint32_t a, uint4 v) {
    asm volatile("st.shared.v4.u32 [%0], {%1,%2,%3,%4};" ::"r"(a), "r"(v.x), "r"(v.y), "r"(v.z), "r"(v.w) : "memory");
}

__device__ __forceinline__ uint64_t desc_ni(uint32_t addr, uint32_t lbo, uint32_t sbo) {
    return (uint64_t)((addr & 0x3FFFF) >> 4) | ((uint64_t)(lbo >> 4) << 16) | ((uint64_t)(sbo >> 4) << 32);
}
__device__ __forceinline__ uint64_t desc_a(uint32_t addr) { return desc_ni(addr, 128, 1024); }
template <int N> __device__ __forceinline__ uint64_t desc_b(uint32_t addr) { return desc_ni(addr, 16 * N, 128); }
__device__ __forceinline__ uint64_t desc_k(uint32_t addr) {
    return (uint64_t)((addr & 0x3FFFF) >> 4) | (1ull << 16) | (64ull << 32) | (1ull << 62);
}
__device__ __forceinline__ uint64_t desc_mn(uint32_t addr, uint32_t lbo) {
    return (uint64_t)((addr & 0x3FFFF) >> 4) | ((uint64_t)(lbo >> 4) << 16) | (64ull << 32) | (1ull << 62);
}

#define ACC8(d, o) "+f"(d[o + 0]), "+f"(d[o + 1]), "+f"(d[o + 2]), "+f"(d[o + 3]), "+f"(d[o + 4]), "+f"(d[o + 5]), "+f"(d[o + 6]), "+f"(d[o + 7])
template <int TB, int SA = 1>
__device__ __forceinline__ void wgmma_n128(float (&d)[64], uint64_t da, uint64_t db, int sd) {
    asm volatile(
        "{\n.reg .pred p;\nsetp.ne.b32 p, %66, 0;\n"
        "wgmma.mma_async.sync.aligned.m64n128k16.f32.bf16.bf16 "
        "{%0,%1,%2,%3,%4,%5,%6,%7,%8,%9,%10,%11,%12,%13,%14,%15,%16,%17,%18,%19,%20,%21,%22,%23,%24,%25,%26,%27,%28,%29,%30,%31,"
        "%32,%33,%34,%35,%36,%37,%38,%39,%40,%41,%42,%43,%44,%45,%46,%47,%48,%49,%50,%51,%52,%53,%54,%55,%56,%57,%58,%59,%60,%61,%62,%63},"
        " %64, %65, p, %68, 1, 0, %67;\n}"
        : ACC8(d, 0), ACC8(d, 8), ACC8(d, 16), ACC8(d, 24), ACC8(d, 32), ACC8(d, 40), ACC8(d, 48), ACC8(d, 56)
        : "l"(da), "l"(db), "r"(sd), "n"(TB), "n"(SA));
}
template <int N> __device__ __forceinline__ void acc_def(float (&d)[N]) {
#pragma unroll
    for (int i = 0; i < N; i++) d[i] = 0.f;
}
template <int TB>
__device__ __forceinline__ void wgmma_n64(float (&d)[32], uint64_t da, uint64_t db, int sd) {
    asm volatile(
        "{\n.reg .pred p;\nsetp.ne.b32 p, %34, 0;\n"
        "wgmma.mma_async.sync.aligned.m64n64k16.f32.bf16.bf16 "
        "{%0,%1,%2,%3,%4,%5,%6,%7,%8,%9,%10,%11,%12,%13,%14,%15,%16,%17,%18,%19,%20,%21,%22,%23,%24,%25,%26,%27,%28,%29,%30,%31},"
        " %32, %33, p, 1, 1, 0, %35;\n}"
        : ACC8(d, 0), ACC8(d, 8), ACC8(d, 16), ACC8(d, 24)
        : "l"(da), "l"(db), "r"(sd), "n"(TB));
}
template <int SA>
__device__ __forceinline__ void wgmma_n64s(float (&d)[32], uint64_t da, uint64_t db, int sd) {
    asm volatile(
        "{\n.reg .pred p;\nsetp.ne.b32 p, %34, 0;\n"
        "wgmma.mma_async.sync.aligned.m64n64k16.f32.bf16.bf16 "
        "{%0,%1,%2,%3,%4,%5,%6,%7,%8,%9,%10,%11,%12,%13,%14,%15,%16,%17,%18,%19,%20,%21,%22,%23,%24,%25,%26,%27,%28,%29,%30,%31},"
        " %32, %33, p, %35, 1, 0, 1;\n}"
        : ACC8(d, 0), ACC8(d, 8), ACC8(d, 16), ACC8(d, 24)
        : "l"(da), "l"(db), "r"(sd), "n"(SA));
}
__device__ __forceinline__ void wgmma_n64_rs(float (&d)[32], uint32_t a0, uint32_t a1, uint32_t a2, uint32_t a3, uint64_t db, int sd) {
    asm volatile(
        "{\n.reg .pred p;\nsetp.ne.b32 p, %37, 0;\n"
        "wgmma.mma_async.sync.aligned.m64n64k16.f32.bf16.bf16 "
        "{%0,%1,%2,%3,%4,%5,%6,%7,%8,%9,%10,%11,%12,%13,%14,%15,%16,%17,%18,%19,%20,%21,%22,%23,%24,%25,%26,%27,%28,%29,%30,%31},"
        " {%32,%33,%34,%35}, %36, p, 1, 1, 1;\n}"
        : ACC8(d, 0), ACC8(d, 8), ACC8(d, 16), ACC8(d, 24)
        : "r"(a0), "r"(a1), "r"(a2), "r"(a3), "l"(db), "r"(sd));
}

struct Params {
    const __nv_bfloat16* x0;
    const __nv_bfloat16* w_r;
    const __nv_bfloat16* w_i;
    const __nv_bfloat16* lam_re;
    const __nv_bfloat16* lam_im;
    const __nv_bfloat16* log_dt;
    const __nv_bfloat16* dskip;
    float* out;
    int stop;
};

__device__ __forceinline__ float ldbf(const __nv_bfloat16* p) { return __bfloat162float(*p); }

__device__ __forceinline__ void dft_fp(int j, int& f, int& ph) {
    int cs = j >> 1;
    if (j == 1) { f = 256; ph = 0; }
    else { f = cs; ph = (j & 1) ? 128 : 0; }
}

__device__ __forceinline__ void gen_col_consts(uint32_t sb, int tid) {
#pragma unroll 1
    for (int task = tid; task < 640; task += 256) {
        int f, c8;
        uint32_t a_cc, d_pi, d_po;
        if (task < 512) {
            f = task & 63; c8 = task >> 6;
            a_cc = sb + SM_X + (f >> 5) * 16384 + ((f >> 3) & 3) * 2048 + c8 * 128 + (f & 7) * 16;
            d_pi = 8192; d_po = 1024;
        } else {
            int n2 = task & 31;
            f = 2 * n2; c8 = (task >> 5) & 3;
            a_cc = sb + SM_X + 32768 + (n2 >> 3) * 1024 + c8 * 128 + (n2 & 7) * 16;
            d_pi = 4096; d_po = 512;
        }
        float cd, sd, cs, sn;
        __sincosf((float)(f >= 32 ? f - 64 : f) * (6.283185307179586f / 64.f), &sd, &cd);
        int a = (8 * c8 * f) & 63;
        __sincosf((float)(a >= 32 ? a - 64 : a) * (6.283185307179586f / 64.f), &sn, &cs);
        float cv[8], sv[8];
#pragma unroll
        for (int e = 0; e < 8; e++) {
            cv[e] = cs; sv[e] = sn;
            float t = cs * cd - sn * sd;
            sn = sn * cd + cs * sd;
            cs = t;
        }
        uint4 oc = make_uint4(pack_bf16(cv[0], cv[1]), pack_bf16(cv[2], cv[3]), pack_bf16(cv[4], cv[5]), pack_bf16(cv[6], cv[7]));
        uint4 os = make_uint4(pack_bf16(sv[0], sv[1]), pack_bf16(sv[2], sv[3]), pack_bf16(sv[4], sv[5]), pack_bf16(sv[6], sv[7]));
        sts128(a_cc, oc);
        sts128(a_cc + d_pi, os);
        sts128(a_cc + d_po, make_uint4(os.x ^ 0x80008000u, os.y ^ 0x80008000u, os.z ^ 0x80008000u, os.w ^ 0x80008000u));
        sts128(a_cc + d_pi + d_po, oc);
    }
}

__global__ void __launch_bounds__(NTHREADS, 1)
fused_kernel(const __grid_constant__ CUtensorMap tm_x, const __grid_constant__ CUtensorMap tm_bre,
             const __grid_constant__ CUtensorMap tm_bim, const __grid_constant__ CUtensorMap tm_cre,
             const __grid_constant__ CUtensorMap tm_cim, const __grid_constant__ CUtensorMap tm_col, const Params p) {
    extern __shared__ __align__(1024) uint8_t sm[];
    const uint32_t sb = s2u(sm);
    const int tid = threadIdx.x, b = blockIdx.x;
    const int c = b >> 3, r = b & 7;
    const int par = r & 1, pi_ = r >> 1, own = 4 * par + pi_;
    const int wg = __shfl_sync(~0u, tid >> 7, 0), w = __shfl_sync(~0u, (tid >> 5) & 3, 0), lane = tid & 31, g = lane >> 2, q = lane & 3;
    auto BAR = [&](int i) { return sb + SM_BAR + 8 * i; };
    unsigned* s_tgt = (unsigned*)(sm + SM_TGT);

    if (tid < NBARS) {
        int cnt = 1;
        if ((tid >= B_EMPTY0 && tid < B_EMPTY0 + 4) || (tid >= B_XEMPTY && tid < B_XEMPTY + 4)) cnt = 24;
        if (tid == B_RFREE) cnt = 12;
        if (tid == B_HDONE) cnt = 2;
        if (tid >= B_AEMPTY && tid < B_AEMPTY + 8) cnt = 8;
        if (tid == B_AFREE) cnt = 4;
        mbar_init(BAR(tid), cnt);
        asm volatile("fence.mbarrier_init.release.cluster;" ::: "memory");
    }
    asm volatile("barrier.cluster.arrive.release.aligned;" ::: "memory");
    if (tid >= 64 && tid < 70) {
        s_tgt[tid - 64] = ((ld_acquire(&g_bar[tid - 64]) >> 7) + 1u) << 7;
    } else if (tid >= 96 && tid < 112) {
        g_ssq[2048 + 16 * b + tid - 96] = 0.f;
    } else if (tid >= 128 && tid < 384) {
        int i = tid - 128;
        if (i < 128) ((float4*)g_ssqc)[b * 128 + i] = make_float4(0.f, 0.f, 0.f, 0.f);
    } else if (tid >= 416) {
        int i = tid - 416;
        int ps = i < 64 ? 64 * r + i : 32 * c + i - 64;
        float lr = ldbf(p.lam_re + ps), li = ldbf(p.lam_im + ps);
        float dt = __bfloat162float(__float2bfloat16(expf(ldbf(p.log_dt + ps))));
        float mag = expf(lr * dt), t = li * dt * 0.15915494309189535f, sn, cs;
        t -= rintf(t);
        sincospif(2.f * t, &sn, &cs);
        float er = mag * cs, ei = mag * sn;
        if (i < 64) {
            *(float2*)(sm + SM_LAM + i * 8) = make_float2(er, ei);
        } else {
            er -= 1.f;
            float inv = 1.f / (lr * lr + li * li);
            *(float2*)(sm + SM_RSTD + (i - 64) * 8) = make_float2((er * lr + ei * li) * inv, (ei * lr - er * li) * inv);
        }
    } else if (tid >= 384 && tid < 390) {
        const CUtensorMap* tm = tid == 384 ? &tm_x : tid == 385 ? &tm_bre : tid == 386 ? &tm_bim : tid == 387 ? &tm_cre : tid == 388 ? &tm_cim : &tm_col;
        asm volatile("prefetch.tensormap [%0];" ::"l"(tm) : "memory");
    }
    __syncwarp();
    asm volatile("barrier.cluster.wait.acquire.aligned;" ::: "memory");

    if (wg == 3) {
        asm volatile("setmaxnreg.dec.sync.aligned.u32 56;");
        if (w > 0) {
            bar_arrive(10, 480);
            if (w == 2) {
                const int kq = 2 * b + (lane >> 4), row = (kq >> 2) + 128 * (kq & 3) + 512 * ((lane >> 1) & 3) + 64 * (lane & 1);
                const char* src = (const char*)(((lane >> 3) & 1) ? p.w_i : p.w_r) + (size_t)row * 514;
                size_t a0 = (size_t)src & ~(size_t)15;
                int bytes = row == 2047 ? 512 : 544;
                asm volatile("cp.async.bulk.prefetch.L2.global [%0], %1;" ::"l"(a0), "r"(bytes) : "memory");
            }
#pragma unroll 1
            for (int i = tid - 448; i < 1536 + 128 && w > 1; i += 64) {
                if (i < 1536) g_P[(uint32_t)(b * 4 + i / 384) * 1024 + 640 + i % 384] = make_uint4(0, 0, 0, 0);
                else g_Ebuf[b * 128 + i - 1536] = make_float4(0.f, 0.f, 0.f, 0.f);
            }
#pragma unroll 1
            for (int task = tid - 448; task < 256 && w > 1; task += 64) {
                const int cb = task & 127, kq = 2 * b + (task >> 7), k1 = kq >> 2, qq = kq & 3;
                const unsigned short* wr_ = (const unsigned short*)p.w_r + (k1 + 128 * qq) * 257;
                const unsigned short* wi_ = (const unsigned short*)p.w_i + (k1 + 128 * qq) * 257;
                const int c0 = cb == 0 ? 256 : 2 * cb, c1 = 2 * cb + 1;
                uint32_t wf[16];
#pragma unroll
                for (int i = 0; i < 4; i++) {
                    int o = 512 * i * 257;
                    wf[2 * i] = (uint32_t)__ldg(wr_ + o + c0) | ((uint32_t)__ldg(wr_ + o + 64 * 257 + c0) << 16);
                    wf[2 * i + 1] = ((uint32_t)__ldg(wi_ + o + c0) | ((uint32_t)__ldg(wi_ + o + 64 * 257 + c0) << 16)) ^ 0x80008000u;
                    wf[8 + 2 * i] = (uint32_t)__ldg(wr_ + o + c1) | ((uint32_t)__ldg(wr_ + o + 64 * 257 + c1) << 16);
                    wf[8 + 2 * i + 1] = ((uint32_t)__ldg(wi_ + o + c1) | ((uint32_t)__ldg(wi_ + o + 64 * 257 + c1) << 16)) ^ 0x80008000u;
                }
                uint4* wd = g_Wfrag + (uint32_t)(cb * 1024 + kq);
#pragma unroll
                for (int i = 0; i < 4; i++) wd[i * 256] = make_uint4(wf[4 * i], wf[4 * i + 1], wf[4 * i + 2], wf[4 * i + 3]);
            }
            __syncwarp();
            if (w > 1) bar_arrive(11, 96);
            if (w == 3) {
#pragma unroll 1
                for (int it = 0; it < 8; it++) {
                    const int m = 4 * c + (it >> 1), d = 64 * r + m, ch = lane + 32 * (it & 1);
                    float v[8];
#pragma unroll
                    for (int e = 0; e < 8; e++) {
                        int j = 8 * ch + e, f, ph;
                        dft_fp(j, f, ph);
                        int a = (d * f + ph) & 511;
                        a = a >= 256 ? a - 512 : a;
                        float wj = j == 0 ? 0.f : (j == 1 ? 1.f / 512.f : 2.f / 512.f);
                        v[e] = wj * __cosf((float)a * (6.283185307179586f / 512.f));
                    }
                    uint32_t off = (uint32_t)(64 + r * 8 + (ch >> 3)) * 8192 + (m >> 3) * 1024 + (ch & 7) * 128 + (m & 7) * 16;
                    *(uint4*)(g_E + off) = make_uint4(pack_bf16(v[0], v[1]), pack_bf16(v[2], v[3]), pack_bf16(v[4], v[5]), pack_bf16(v[6], v[7]));
                }
                __syncwarp();
                if (lane == 0) { fence_async(); red_release(&g_bar[6], 1); }
                return;
            }
            if (w == 2) {
#pragma unroll 1
                for (int it = 0; it < 4; it++) {
                    const int hf = it & 1;
                    __syncwarp();
                    if (hf == 0) bar_sync(13, 288); else bar_sync(6, 416);
                    if (lane == 0) {
                        const uint32_t src = sb + SM_HH + par * 32768 + hf * 16384;
                        bulk_s2peer(mapa(src, par ^ 1), src, 16384, mapa(BAR(hf ? B_HPEER1 : B_HPEER), par ^ 1));
                    }
                }
                return;
            }
            {
                uint4 p0 = __ldg((const uint4*)p.dskip + 2 * lane), p1 = __ldg((const uint4*)p.dskip + 2 * lane + 1);
                uint32_t u[8] = {p0.x, p0.y, p0.z, p0.w, p1.x, p1.y, p1.z, p1.w};
#pragma unroll 1
                for (int jj = 0; jj < 4; jj++) {
                    int j = 64 * r + 4 * c + jj, f, ph;
                    dft_fp(j, f, ph);
                    float s = 0.f;
                    int idx = 16 * lane * f + ph;
#pragma unroll
                    for (int i = 0; i < 16; i++) {
                        int a = idx & 511;
                        idx += f;
                        a = a >= 256 ? a - 512 : a;
                        s += ((i & 1) ? bf_hi(u[i >> 1]) : bf_lo(u[i >> 1])) * __cosf((float)a * (6.283185307179586f / 512.f));
                    }
#pragma unroll
                    for (int o = 16; o; o >>= 1) s += __shfl_xor_sync(~0u, s, o);
                    if (lane == 0) g_Dh[j] = s;
                }
                if (lane == 0) red_release(&g_bar[5], 1);
                __syncwarp();
            }
            bar_sync(2, 416);
            if (lane == 0) {
                TX(5);
                asm volatile("cp.async.bulk.global.shared::cta.bulk_group [%0], [%1], 8192;" ::"l"(g_A1 + (uint32_t)(((c >> 1) * 8 + r) * 16384 + (c & 1) * 8192)),
                             "r"(sb + SM_B1ST) : "memory");
                asm volatile("cp.async.bulk.commit_group;" ::: "memory");
                fence_async();
                red_release(&g_bar[0], 1);
                TX(6);
                asm volatile("cp.async.bulk.wait_group 0;" ::: "memory");
                fence_async();
            }
            __syncwarp();
            bar_sync(11, 96);
            if (lane == 0) red_release(&g_bar[4], 1);
#pragma unroll 1
            for (int layer = 0; layer < 2; layer++) {
                __syncwarp();
                bar_sync(5, 416);
                if (lane == 0) {
                    TX(0 + 8 * layer);
                    tma_store_5d(&tm_col, 32 * (b & 1), 0, b >> 1, 0, layer, sb + SM_RAW);
                    asm volatile("cp.reduce.async.bulk.global.shared::cta.bulk_group.add.f32 [%0], [%1], 8192;" ::"l"(g_ssqc + (layer * 16 + (b & 15)) * 2048),
                                 "r"(sb + SM_SSQ) : "memory");
                    asm volatile("cp.async.bulk.commit_group;" ::: "memory");
                    asm volatile("cp.async.bulk.wait_group 0;" ::: "memory");
                    TX(1 + 8 * layer);
                    fence_async();
                    red_release(&g_bar[1 + 2 * layer], 1);
                    TX(2 + 8 * layer);
                }
            }
        } else if (tid == 384) {
#pragma unroll 1
            for (int kb = 0; kb < 8; kb++) {
                int s = kb < 6 ? kb : kb - 4;
                uint32_t dst = s < 2 ? sb + SM_A + 65536 + s * 24576 : sb + SM_X + (s - 2) * 24576;
                if (kb >= 6) mbar_wait_cluster(BAR(B_EMPTY0 + s), 0);
                uint32_t fb = BAR(B_FULL0 + kb);
                mbar_expect(fb, 24576);
                tma_5d_mc(dst + par * 8192, &tm_x, kb * 64, 0, 0, 8 * par, c, fb);
                tma_2d_mc(dst + 16384 + par * 4096, par ? &tm_bim : &tm_bre, kb * 64, 32 * c, fb);
                if (kb == 5) {
#pragma unroll 1
                    for (int k2 = par; k2 < 8; k2 += 2) {
                        asm volatile("cp.async.bulk.prefetch.tensor.2d.L2.global [%0, {%1,%2}];" ::"l"((c & 1) ? &tm_cim : &tm_cre), "r"(64 * (c >> 1)), "r"(k2 * 64) : "memory");
                        if (k2 < 4) {
                            asm volatile("cp.async.bulk.prefetch.tensor.5d.L2.global [%0, {%1,%2,%3,%4,%5}];" ::"l"(&tm_x), "r"((6 + (k2 >> 1)) * 64), "r"(0), "r"(0), "r"(8 * par), "r"(c) : "memory");
                            asm volatile("cp.async.bulk.prefetch.tensor.2d.L2.global [%0, {%1,%2}];" ::"l"(par ? &tm_bim : &tm_bre), "r"((6 + (k2 >> 1)) * 64), "r"(32 * c) : "memory");
                        }
                    }
                }
                if (kb == 7) {
                    mbar_wait_cluster(BAR(B_EMPTY0 + 0), 0);
                    mbar_wait_cluster(BAR(B_EMPTY0 + 1), 0);
                    mbar_expect(BAR(B_FULLC), 65536);
#pragma unroll 1
                    for (int k2 = par; k2 < 8; k2 += 2)
                        tma_2d_mc(sb + SM_A + 65536 + k2 * 8192, (c & 1) ? &tm_cim : &tm_cre, 64 * (c >> 1), k2 * 64, BAR(B_FULLC));
                }
            }
#pragma unroll 1
            for (int layer = 0; layer < 2; layer++) {
                wait_count(&g_bar[2 * layer], s_tgt[2 * layer]);
                TX(4 + 8 * layer);
                fence_async();
                mbar_expect(BAR(B_COL), 16384 + 8192);
                tma_5d(sb + SM_RAW, &tm_col, 32 * (b & 1), 0, b >> 1, 0, layer, BAR(B_COL));
                bulk_g2s(sb + SM_SSQ, g_ssq + layer * 2048, 8192, BAR(B_COL));
                if (layer == 0) {
                    wait_count(&g_bar[4], s_tgt[4]);
                    mbar_arrive(BAR(B_WRDY), 1);
                    fence_async();
                }
                if (layer == 0) mbar_wait(BAR(B_AFREE), 0);
                mbar_wait(BAR(B_COL), layer);
#pragma unroll 1
                for (int s = 0; s < 8; s++) {
                    if (layer == 1) mbar_wait(BAR(B_AEMPTY + s), 1);
                    if (s >= 2) mbar_wait(BAR(B_AFULL + s - 2), 0);
                    mbar_expect(BAR(B_AFULL + s), 16384);
                    bulk_g2s(sb + SM_A + s * 16384, g_A1 + (uint32_t)(r * 8 + s) * 16384, 16384, BAR(B_AFULL + s));
                }
                if (layer == 1) wait_count(&g_bar[6], s_tgt[5]);
                wait_count(&g_bar[1 + 2 * layer], s_tgt[1 + 2 * layer]);
                TX(3 + 8 * layer);
                fence_async();
                const uint8_t* xsrc = g_X + (uint32_t)(layer * 16 + c) * 8 * 16384;
                const uint8_t* esrc = g_E + (uint32_t)(layer * 8 + own) * 8 * 8192;
                mbar_arrive(BAR(B_SSQ), 1);
                mbar_expect(BAR(B_HPEER), 16384);
                mbar_expect(BAR(B_HPEER1), 16384);
#pragma unroll 1
                for (int it = 0; it < 16; it++) {
                    if (it < 8) {
                        int st = it & 3, f = layer * 2 + (it >> 2);
                        if (f > 0) mbar_wait_cluster(BAR(B_XEMPTY + st), (f - 1) & 1);
                        mbar_expect(BAR(B_XFULL + st), 24576);
                        bulk_g2s_mc(sb + SM_X + st * 24576 + par * 8192, xsrc + (uint32_t)it * 16384 + par * 8192, 8192, BAR(B_XFULL + st));
                        bulk_g2s(sb + SM_X + st * 24576 + 16384, esrc + (uint32_t)it * 8192, 8192, BAR(B_XFULL + st));
                    }
                    if (it >= 8) {
                        if (it == 8) mbar_wait(BAR(B_AEMPTY + 5), 0);
                        int s = it - 8, tile = 4 * par + ((pi_ + 1 + (s >> 1)) & 3), sl = r ^ (s & 1);
                        mbar_wait(BAR(B_AEMPTY + s), 0);
                        uint32_t fb = BAR(B_AFULL + s), dst = sb + SM_A + s * 16384;
                        mbar_expect(fb, 16384);
                        if (layer == 1) {
                            tma_2d(dst, &tm_cre, 64 * sl, 64 * tile, fb);
                            tma_2d(dst + 8192, &tm_cim, 64 * sl, 64 * tile, fb);
                        } else {
                            bulk_g2s(dst, g_A2 + (uint32_t)(sl * 8 + tile) * 16384, 16384, fb);
                        }
                    }
                }
            }
        }
        return;
    }

    asm volatile("setmaxnreg.inc.sync.aligned.u32 152;");
    TS(0);
    if (wg == 0) TC(30);
    {
        const int f = 32 * r + lane;
        float cd, sd;
        __sincosf((float)f * (6.283185307179586f / 512.f), &sd, &cd);
        const uint32_t dst = sb + SM_A + (lane >> 2) * 1024 + (lane & 3) * 32;
#pragma unroll 1
        for (int ch = tid >> 5; ch < 64; ch += 12) {
            int a = (8 * ch * f) & 511;
            a = a >= 256 ? a - 512 : a;
            float cs, sn;
            __sincosf((float)a * (6.283185307179586f / 512.f), &sn, &cs);
            float cv[8], sv[8];
#pragma unroll
            for (int e = 0; e < 8; e++) {
                cv[e] = cs; sv[e] = -sn;
                float t = cs * cd - sn * sd;
                sn = sn * cd + cs * sd;
                cs = t;
            }
            uint4 o1 = make_uint4(pack_bf16(sv[0], sv[1]), pack_bf16(sv[2], sv[3]), pack_bf16(sv[4], sv[5]), pack_bf16(sv[6], sv[7]));
            if (f == 0) o1 = make_uint4(0xbf803f80u, 0xbf803f80u, 0xbf803f80u, 0xbf803f80u);
            uint32_t a0 = dst + (ch >> 3) * 8192 + (ch & 7) * 128;
            sts128(a0, make_uint4(pack_bf16(cv[0], cv[1]), pack_bf16(cv[2], cv[3]), pack_bf16(cv[4], cv[5]), pack_bf16(cv[6], cv[7])));
            sts128(a0 + 16, o1);
        }
    }
    fence_async_smem();
    bar_sync(10, 480);
    TS(1);
    {
        float acc[32];
        acc_def(acc);
        const int npos = 16 * r + 8 * (wg & 1) + 2 * w;
        float sh0 = 0.f, sh1 = 0.f, s0 = 0.f, s1 = 0.f, q0 = 0.f, q1 = 0.f;
#pragma unroll 1
        for (int kb = 0; kb < 8; kb++) {
            int s = kb < 6 ? kb : kb - 4;
            uint32_t slot = s < 2 ? sb + SM_A + 65536 + s * 24576 : sb + SM_X + (s - 2) * 24576;
            uint32_t src = slot + wg * 8192;
            mbar_wait(BAR(B_FULL0 + kb), 0);
            {
                uint32_t v0 = lds32(slot + npos * 128 + lane * 4), v1 = lds32(slot + npos * 128 + 128 + lane * 4);
                if (kb == 0) { sh0 = __shfl_sync(~0u, bf_lo(v0), 0); sh1 = __shfl_sync(~0u, bf_lo(v1), 0); }
                float a = bf_lo(v0) - sh0, bq = bf_hi(v0) - sh0, cq = bf_lo(v1) - sh1, d = bf_hi(v1) - sh1;
                s0 += a + bq; q0 += a * a + bq * bq; s1 += cq + d; q1 += cq * cq + d * d;
            }
            wg_fence();
#pragma unroll
            for (int ks = 0; ks < 4; ks++)
                wgmma_n64<0>(acc, desc_a(sb + SM_A + kb * 8192 + ks * 256), desc_k(src + ks * 32), 1);
            wg_commit();
            wg_wait<1>();
            if (kb > 0 && kb <= 4 && lane == 0) { mbar_arrive(BAR(B_EMPTY0 + kb - 1), 1); mbar_arrive_remote(mapa(BAR(B_EMPTY0 + kb - 1), par ^ 1)); }
        }
        wg_wait<0>();
        TS(2);
        if (wg < 2) {
            uint8_t* dst = g_X + (uint32_t)((c * 8 + r) * 16384 + w * 4096 + wg * 1024 + g * 16 + 4 * q);
#pragma unroll
            for (int i = 0; i < 8; i++) {
                *(uint32_t*)(dst + i * 128) = pack_bf16(acc[4 * i], acc[4 * i + 1]);
                *(uint32_t*)(dst + 2048 + i * 128) = pack_bf16(acc[4 * i + 2], acc[4 * i + 3]);
            }
#pragma unroll
            for (int o = 16; o; o >>= 1) {
                s0 += __shfl_xor_sync(~0u, s0, o); q0 += __shfl_xor_sync(~0u, q0, o);
                s1 += __shfl_xor_sync(~0u, s1, o); q1 += __shfl_xor_sync(~0u, q1, o);
            }
            if (lane == 0) *(float2*)(g_ssq + 128 * c + npos) = make_float2(fmaxf(q0 - s0 * s0 * (1.f / 512.f), 0.f), fmaxf(q1 - s1 * s1 * (1.f / 512.f), 0.f));
        } else {
            uint8_t* dst = sm + SM_B1ST + w * 256 + q * 32 + g * 2;
            const float wj0 = (r == 0 && w == 0 && g < 2) ? (g == 0 ? 0.f : 1.f / 512.f) : 2.f / 512.f;
#pragma unroll
            for (int i = 0; i < 4; i++) {
#pragma unroll
                for (int e = 0; e < 2; e++) {
                    float2 cf = *(const float2*)(sm + SM_RSTD + (8 * i + 2 * q + e) * 8);
#pragma unroll
                    for (int h = 0; h < 2; h++) {
                        float wj = h == 0 ? wj0 : 2.f / 512.f;
                        float pr = acc[4 * i + 2 * h + e] * wj, pi = acc[16 + 4 * i + 2 * h + e] * wj;
                        uint8_t* d2 = dst + i * 2048 + h * 128 + e * 16;
                        *(__nv_bfloat16*)(d2) = __float2bfloat16(cf.x * pr - cf.y * pi);
                        *(__nv_bfloat16*)(d2 + 1024) = __float2bfloat16(cf.x * pi + cf.y * pr);
                    }
                }
            }
            fence_async_smem();
        }
        bar_sync(2, 416);
        TS(3);
    }

    if (wg == 2) {
        {
            const int m = 4 * c + w, jp = 64 * r + m;
            int fp, php;
            dft_fp(jp, fp, php);
            const __nv_bfloat16* dh = (const __nv_bfloat16*)(sm + SM_RSTD);
            if (tid == 256) wait_count(&g_bar[5], s_tgt[5]);
            bar_sync(3, 128);
            float4 d4 = __ldcg((const float4*)g_Dh + (tid - 256));
            *(uint2*)(sm + SM_RSTD + (tid - 256) * 8) = make_uint2(pack_bf16(d4.x, d4.y), pack_bf16(d4.z, d4.w));
            bar_sync(3, 128);
#pragma unroll 1
            for (int it = 0; it < 2; it++) {
                const int ch = lane + 32 * it;
                float v[8];
#pragma unroll
                for (int e = 0; e < 8; e++) {
                    int j = 8 * ch + e, f, ph;
                    dft_fp(j, f, ph);
                    float wj = j == 0 ? 0.f : (j == 1 ? 1.f / 512.f : 2.f / 512.f);
                    float gsum = 0.f;
#pragma unroll
                    for (int sgn = 0; sgn < 2; sgn++) {
                        int mm = (sgn ? f - fp : f + fp) & 511, pp = (sgn ? ph - php : ph + php) & 511;
                        if (mm > 256) { mm = 512 - mm; pp = (512 - pp) & 511; }
                        int odd = (pp >> 7) & 1;
                        float t = __bfloat162float(dh[mm == 256 ? 1 : 2 * mm + odd]);
                        if (odd && (mm & 255) == 0) t = 0.f;
                        gsum += (pp & 256) ? -t : t;
                    }
                    v[e] = 0.5f * wj * gsum;
                }
                uint32_t off = (uint32_t)(r * 8 + (ch >> 3)) * 8192 + (m >> 3) * 1024 + (ch & 7) * 128 + (m & 7) * 16;
                *(uint4*)(g_E + off) = make_uint4(pack_bf16(v[0], v[1]), pack_bf16(v[2], v[3]), pack_bf16(v[4], v[5]), pack_bf16(v[6], v[7]));
            }
        }
        float acc[32];
        acc_def(acc);
        mbar_wait(BAR(B_FULLC), 0);
        wg_fence();
#pragma unroll 1
        for (int kb = 0; kb < 8; kb++) {
#pragma unroll
            for (int ks = 0; ks < 4; ks++)
                wgmma_n64<1>(acc, desc_a(sb + SM_A + kb * 8192 + ks * 256), desc_mn(sb + SM_A + 65536 + kb * 8192 + ks * 2048, 8192), 1);
            wg_commit();
        }
        wg_wait<0>();
        fence_async_smem();
        if (lane == 0) mbar_arrive(BAR(B_AFREE), 1);
        uint8_t* dst = g_A2 + (uint32_t)(((c >> 1) * 8 + r) * 16384 + (c & 1) * 8192 + w * 2048 + g * 16 + 4 * q);
#pragma unroll
        for (int i = 0; i < 8; i++) {
            *(uint32_t*)(dst + i * 128) = pack_bf16(acc[4 * i], acc[4 * i + 1]);
            *(uint32_t*)(dst + 1024 + i * 128) = pack_bf16(acc[4 * i + 2], acc[4 * i + 3]);
        }
    }

#pragma unroll 1
    for (int layer = 0; layer < 2; layer++) {
        if (wg < 2) {
            const int n1 = 32 * wg + 8 * w + g;
            const int ct = n1 >> 2;
            gen_col_consts(sb, tid);
            uint32_t tr2[4], ti2[4], tn2[4];
#pragma unroll
            for (int i = 0; i < 4; i++) {
                float cr[2], ci[2];
#pragma unroll
                for (int e = 0; e < 2; e++) {
                    int a = (n1 * (8 * i + 2 * q + e)) & 2047;
                    a = a >= 1024 ? a - 2048 : a;
                    float ang = (float)a * (-6.283185307179586f / 2048.f);
                    cr[e] = __cosf(ang); ci[e] = __sinf(ang);
                }
                tr2[i] = pack_bf16(cr[0], cr[1]); ti2[i] = pack_bf16(ci[0], ci[1]); tn2[i] = ti2[i] ^ 0x80008000u;
            }
            uint32_t wf[16];
            const uint4* ws = g_Wfrag + (uint32_t)(b * 1024 + n1 * 4 + q);
#pragma unroll
            for (int i = 0; i < 4; i++) {
                uint4 v = make_uint4(0, 0, 0, 0);
                if (layer == 1) v = __ldcg(ws + i * 256);
                wf[4 * i] = v.x; wf[4 * i + 1] = v.y; wf[4 * i + 2] = v.z; wf[4 * i + 3] = v.w;
            }
            mbar_wait(BAR(B_COL), layer);
            TS(4 + 12 * layer);
            if (wg == 0) TC(0 + 10 * layer);
            const uint32_t rw0 = sb + SM_RAW + ct * 1024 + q * 64 + ((q >> 1) << 4) + (g & 3) * 4, rw1 = rw0 ^ 16;
            const int pos0 = 128 * ct + 8 * q + 2 * (g & 3);
            const int sw = b == 0 ? 1 : 0;
            uint32_t xr[4][4];
            const uint32_t st0 = sb + SM_H + (n1 >> 3) * 1024 + g * 16 + 4 * q;
#pragma unroll
            for (int i = 0; i < 4; i++) {
                float2 sq = *(const float2*)(sm + SM_SSQ + (pos0 + 32 * i) * 4);
                const uint32_t rs2 = pack_bf16(rsqrtf(sq.x * (1.f / 512.f) + 1e-5f), rsqrtf(sq.y * (1.f / 512.f) + 1e-5f));
#pragma unroll
                for (int jj = 0; jj < 4; jj++) {
                    const int K = jj ^ (2 * (i & 1));
                    uint32_t a = ((K & 1) ? rw1 : rw0) + i * 256 + (K & 2) * 16;
                    if (jj < 2) a ^= sw << 4;
                    uint32_t v = lds32(a);
                    xr[jj][i] = v;
                    uint32_t o = hmul2(v, rs2);
                    if (jj == 1 && sw) o = 0u;
                    sts32(st0 + (jj & 1) * 8192 + (4 * (jj >> 1) + i) * 128, o);
                }
            }
            if (wg == 0) TC(1 + 10 * layer);
            fence_async_smem();
            bar_sync(1, 256);
            float acc[32];
            const uint32_t s1a = sb + SM_X + wg * 16384, s2b = sb + SM_X + 32768;
            wg_fence();
#pragma unroll
            for (int ks = 0; ks < 8; ks++)
                wgmma_n64<1>(acc, desc_a(s1a + (ks >> 2) * 8192 + (ks & 3) * 256), desc_b<64>(sb + SM_H + ks * 2048), ks != 0);
            wg_commit();
            if (layer == 0) {
                mbar_wait(BAR(B_WRDY), 0);
#pragma unroll
                for (int i = 0; i < 4; i++) {
                    uint4 v = __ldcg(ws + i * 256);
                    wf[4 * i] = v.x; wf[4 * i + 1] = v.y; wf[4 * i + 2] = v.z; wf[4 * i + 3] = v.w;
                }
            }
            wg_wait<0>();
            if (wg == 0) TC(2 + 10 * layer);
            uint32_t are[2][4], aim[2][4];
#pragma unroll
            for (int col = 0; col < 2; col++) {
#pragma unroll
                for (int i = 0; i < 4; i++) {
                    int o = 4 * (4 * col + i);
                    uint32_t zr = pack_bf16(acc[o], acc[o + 1]), zi = pack_bf16(acc[o + 2], acc[o + 3]);
                    are[col][i] = hfma2(zr, tr2[i], hmul2(zi, tn2[i]));
                    aim[col][i] = hfma2(zr, ti2[i], hmul2(zi, tr2[i]));
                }
            }
            wg_fence();
#pragma unroll
            for (int ks = 0; ks < 2; ks++)
                wgmma_n64_rs(acc, are[0][2 * ks], are[1][2 * ks], are[0][2 * ks + 1], are[1][2 * ks + 1], desc_b<64>(s2b + ks * 2048), ks != 0);
#pragma unroll
            for (int ks = 0; ks < 2; ks++)
                wgmma_n64_rs(acc, aim[0][2 * ks], aim[1][2 * ks], aim[0][2 * ks + 1], aim[1][2 * ks + 1], desc_b<64>(s2b + 4096 + ks * 2048), 1);
            wg_commit();
            wg_wait<0>();
            if (wg == 0) TC(3 + 10 * layer);
#pragma unroll
            for (int col = 0; col < 2; col++) {
#pragma unroll
                for (int i = 0; i < 4; i++) {
                    uint32_t wr = wf[col * 8 + 2 * i], wn = wf[col * 8 + 2 * i + 1];
                    uint32_t zr = pack_bf16(acc[4 * i + 2 * col], acc[4 * i + 2 * col + 1]);
                    uint32_t zi = pack_bf16(acc[16 + 4 * i + 2 * col], acc[16 + 4 * i + 2 * col + 1]);
                    are[col][i] = hfma2(zr, wr, hmul2(zi, wn));
                    aim[col][i] = hfma2(zr, wn, hmul2(zi ^ 0x80008000u, wr));
                }
            }
            wg_fence();
#pragma unroll
            for (int ks = 0; ks < 2; ks++)
                wgmma_n64_rs(acc, are[0][2 * ks], are[1][2 * ks], are[0][2 * ks + 1], are[1][2 * ks + 1], desc_b<64>(s2b + ks * 2048), ks != 0);
#pragma unroll
            for (int ks = 0; ks < 2; ks++)
                wgmma_n64_rs(acc, aim[0][2 * ks], aim[1][2 * ks], aim[0][2 * ks + 1], aim[1][2 * ks + 1], desc_b<64>(s2b + 4096 + ks * 2048), 1);
            wg_commit();
            wg_wait<0>();
            if (wg == 0) TC(4 + 10 * layer);
#pragma unroll
            for (int col = 0; col < 2; col++) {
#pragma unroll
                for (int i = 0; i < 4; i++) {
                    uint32_t zr = pack_bf16(acc[4 * i + 2 * col], acc[4 * i + 2 * col + 1]);
                    uint32_t zi = pack_bf16(acc[16 + 4 * i + 2 * col], acc[16 + 4 * i + 2 * col + 1]);
                    sts32(st0 + 16384 + (4 * col + i) * 128, hfma2(zr, tr2[i], hmul2(zi, tn2[i])));
                    sts32(st0 + 16384 + 8192 + (4 * col + i) * 128, hfma2(zr, ti2[i], hmul2(zi, tr2[i])));
                }
            }
            if (wg == 0) TC(5 + 10 * layer);
            fence_async_smem();
            bar_sync(1, 256);
            wg_fence();
#pragma unroll
            for (int ks = 0; ks < 8; ks++)
                wgmma_n64<1>(acc, desc_a(s1a + (ks >> 2) * 8192 + (ks & 3) * 256), desc_b<64>(sb + SM_H + 16384 + ks * 2048), ks != 0);
            wg_commit();
            wg_wait<0>();
            if (wg == 0) TC(6 + 10 * layer);
            const float sc = 1.f / 2048.f;
            const float sci0 = sw ? 0.f : -sc;
            const float wr0 = sw ? 0.5f : 1.f, wi0 = sw ? 0.f : 1.f;
#pragma unroll
            for (int i = 0; i < 4; i++) {
                float ss0, ss1;
#pragma unroll
                for (int col = 0; col < 2; col++) {
                    int o = 4 * (4 * col + i);
                    uint32_t vr = xr[2 * col][i], vi = xr[2 * col + 1][i];
                    float si = col == 0 ? sci0 : -sc;
                    uint32_t nr = pack_bf16(fmaf(acc[o], sc, bf_lo(vr)), fmaf(acc[o + 1], sc, bf_hi(vr)));
                    uint32_t ni = pack_bf16(fmaf(acc[o + 2], si, bf_lo(vi)), fmaf(acc[o + 3], si, bf_hi(vi)));
                    float a0 = bf_lo(nr), a1 = bf_hi(nr), b0 = bf_lo(ni), b1 = bf_hi(ni);
                    if (col == 0) {
                        ss0 = wr0 * a0 * a0 + wi0 * b0 * b0;
                        ss1 = wr0 * a1 * a1 + wi0 * b1 * b1;
                    } else {
                        ss0 += a0 * a0 + b0 * b0;
                        ss1 += a1 * a1 + b1 * b1;
                    }
                    const int K = (2 * col) ^ (2 * (i & 1));
                    uint32_t a = rw0 + i * 256 + K * 16;
                    if (col == 0) a ^= sw << 4;
                    sts32(a, nr);
                    sts32(a ^ 16, ni);
                }
                *(float2*)(sm + SM_SSQ + (pos0 + 32 * i) * 4) = make_float2(ss0 * (2.f / 512.f), ss1 * (2.f / 512.f));
            }
            fence_async_smem();
        }
        TS(5 + 12 * layer);
        if (wg == 0) TC(7 + 10 * layer);
        bar_arrive(5, 416);

        float acc[64];
        float* s_rstd = (float*)(sm + SM_RSTD);
        float* s_mean = (float*)(sm + SM_MEAN);
        const unsigned epoch = s_tgt[0] >> 7;
        const uint32_t pt3 = 1u + (2u * epoch + layer) % 3u;
        const uint32_t ptag = (pt3 & 1u) | ((pt3 & 2u) << 15);
        const uint64_t dstep = layer == 0 ? 16 : 2;
        auto c_desc = [&](int s) { return layer == 0 ? desc_a(sb + SM_A + s * 16384) : desc_k(sb + SM_A + s * 16384); };
        if (wg < 2) {
            const int prow = 32 * wg + 8 * w + g;
            const float2 l1 = *(const float2*)(sm + SM_LAM + prow * 8);
            float lr32 = l1.x, li32 = l1.y;
#pragma unroll
            for (int i = 0; i < 5; i++) { float t = lr32 * lr32 - li32 * li32; li32 = 2.f * lr32 * li32; lr32 = t; }
            float lr128 = lr32, li128 = li32;
#pragma unroll
            for (int i = 0; i < 2; i++) { float t = lr128 * lr128 - li128 * li128; li128 = 2.f * lr128 * li128; lr128 = t; }
            const float lr1 = l1.x, li1 = l1.y;
            acc_def(acc);
#pragma unroll 1
            for (int kb = 0; kb < 8; kb++) {
                mbar_wait(BAR(B_AFULL + kb), 0);
                mbar_wait(BAR(B_XFULL + (kb & 3)), (kb >> 2) & 1);
                wg_fence();
#pragma unroll
                for (int ks = 0; ks < 4; ks++)
                    wgmma_n128<1>(acc, desc_a(sb + SM_A + kb * 16384 + wg * 8192 + ks * 256),
                                  desc_b<128>(sb + SM_X + (kb & 3) * 24576 + ks * 4096), 1);
                wg_commit();
                wg_wait<1>();
                if (kb > 0 && lane == 0) {
                    mbar_arrive(BAR(B_AEMPTY + kb - 1), 1); mbar_arrive(BAR(B_XEMPTY + ((kb - 1) & 3)), 1);
                    mbar_arrive_remote(mapa(BAR(B_XEMPTY + ((kb - 1) & 3)), par ^ 1));
                }
            }
            wg_wait<0>();
            if (lane == 0) {
                mbar_arrive(BAR(B_AEMPTY + 7), 1); mbar_arrive(BAR(B_XEMPTY + 3), 1);
                mbar_arrive_remote(mapa(BAR(B_XEMPTY + 3), par ^ 1)); mbar_arrive_remote(mapa(BAR(B_RFREE), par ^ 1));
            }
            bar_arrive(14, 384);
            TS(6 + 12 * layer);
            bar_sync(4, 384);
            TS(7 + 12 * layer);
            float er = 0.f, ei = 0.f;
#pragma unroll
            for (int i = 0; i < 16; i++) {
                float2 rs = *(const float2*)(s_rstd + 128 + 8 * i + 2 * q);
                acc[4 * i] *= rs.x; acc[4 * i + 1] *= rs.y; acc[4 * i + 2] *= rs.x; acc[4 * i + 3] *= rs.y;
                float nr = lr1 * er - li1 * ei + acc[4 * i], ni = lr1 * ei + li1 * er + acc[4 * i + 2];
                er = lr1 * nr - li1 * ni + acc[4 * i + 1];
                ei = lr1 * ni + li1 * nr + acc[4 * i + 3];
            }
            float cr = 0.f, ci = 0.f, tr = 0.f, ti = 0.f;
#pragma unroll
            for (int qq = 0; qq < 4; qq++) {
                float xr_ = __shfl_sync(~0u, er, (lane & ~3) | qq), xi_ = __shfl_sync(~0u, ei, (lane & ~3) | qq);
                if (qq == q) { cr = tr; ci = ti; }
                float nr = lr32 * tr - li32 * ti + xr_, ni = lr32 * ti + li32 * tr + xi_;
                tr = nr; ti = ni;
            }
            float4* eb = g_Ebuf + (uint32_t)(layer * 16 * 512 + 64 * r + prow);
            if (q == 0 && c < 15) st_relaxed_f4(eb + c * 512, make_float4(tr, ti, __uint_as_float(epoch), 0.f));
            TS(8 + 12 * layer);
            float pr[4], pi[4];
            {
                unsigned n = 0;
                bool ok;
#pragma unroll 1
                do {
                    ok = true;
#pragma unroll
                    for (int k = 0; k < 4; k++) {
                        float4 v = make_float4(0.f, 0.f, __uint_as_float(epoch), 0.f);
                        if (4 * k + q < c) v = ld_relaxed_f4(eb + (4 * k + q) * 512);
                        pr[k] = v.x; pi[k] = v.y;
                        ok = ok && __float_as_uint(v.z) == epoch;
                    }
                } while (!ok && ++n < SPIN_LIMIT);
            }
            __syncwarp();
            TS(9 + 12 * layer);
            float hr = 0.f, hi = 0.f;
#pragma unroll
            for (int cc = 0; cc < 15; cc++) {
                float xr_ = __shfl_sync(~0u, pr[cc >> 2], (lane & ~3) | (cc & 3)), xi_ = __shfl_sync(~0u, pi[cc >> 2], (lane & ~3) | (cc & 3));
                if (cc < c) {
                    float nr = lr128 * hr - li128 * hi + xr_, ni = lr128 * hi + li128 * hr + xi_;
                    hr = nr; hi = ni;
                }
            }
#pragma unroll
            for (int qq = 0; qq < 3; qq++) {
                if (qq < q) { float nr = lr32 * hr - li32 * hi, ni = lr32 * hi + li32 * hr; hr = nr; hi = ni; }
            }
            er = cr + hr; ei = ci + hi;
            bar_sync(7, 384);
            mbar_wait_cluster(BAR(B_RFREE), layer);
            const uint32_t ha = sb + SM_HH + par * 32768 + (prow >> 3) * 1024 + g * 16 + 4 * q;
#pragma unroll
            for (int i = 0; i < 16; i++) {
                float nr = lr1 * er - li1 * ei + acc[4 * i], ni = lr1 * ei + li1 * er + acc[4 * i + 2];
                er = lr1 * nr - li1 * ni + acc[4 * i + 1];
                ei = lr1 * ni + li1 * nr + acc[4 * i + 3];
                sts32(ha + (i >> 3) * 16384 + (i & 7) * 128, pack_bf16(nr, er));
                sts32(ha + (i >> 3) * 16384 + 8192 + (i & 7) * 128, pack_bf16(ni, ei));
                if (i == 7) { fence_async_smem(); bar_arrive(13, 288); }
            }
            fence_async_smem();
            acc_def(acc);
            float acc2[32];
            acc_def(acc2);
            TS(10 + 12 * layer);
            bar_sync(6, 416);
            TS(11 + 12 * layer);
            float (&a0)[32] = *reinterpret_cast<float (*)[32]>(&acc[0]);
            float (&a1)[32] = *reinterpret_cast<float (*)[32]>(&acc[32]);
            auto tile_mma = [&](float (&d)[32], int u) {
#pragma unroll 1
                for (int k = 0; k < 2; k++) {
                    const uint32_t hb = sb + SM_HH + (par ^ k) * 32768 + wg * 16384;
                    if (k == 1) mbar_wait(BAR(wg ? B_HPEER1 : B_HPEER), layer);
                    mbar_wait(BAR(B_AFULL + 2 * u + k), 1);
                    const uint64_t da = c_desc(2 * u + k);
                    wg_fence();
#pragma unroll
                    for (int ks = 0; ks < 4; ks++) wgmma_n64s<1>(d, da + ks * dstep, desc_b<64>(hb + ks * 2048), 1);
#pragma unroll
                    for (int ks = 0; ks < 4; ks++) wgmma_n64s<-1>(d, da + 512 + ks * dstep, desc_b<64>(hb + 8192 + ks * 2048), 1);
                }
                wg_commit();
            };
            auto tile_ship = [&](float (&d)[32], int u) {
                uint4* dst = g_P + (uint32_t)(((c * 8 + 2 * ((pi_ + 1 + u) & 3) + par) * 4 + pi_) * 1024 + wg * 512 + (tid & 127));
#pragma unroll
                for (int i = 0; i < 4; i++)
                    dst[i * 128] = make_uint4((pack_bf16(d[8 * i], d[8 * i + 1]) & 0xfffefffeu) | ptag, pack_bf16(d[8 * i + 2], d[8 * i + 3]),
                                              pack_bf16(d[8 * i + 4], d[8 * i + 5]), pack_bf16(d[8 * i + 6], d[8 * i + 7]));
            };
            tile_mma(a0, 0);
            if ((tid & 127) == 0) mbar_arrive_remote(mapa(BAR(B_HDONE), par ^ 1));
            __syncwarp();
            tile_mma(a1, 1);
            wg_wait<1>();
            tile_ship(a0, 0);
            tile_mma(acc2, 2);
            bar_arrive(12, 384);
            wg_wait<1>();
            tile_ship(a1, 1);
            wg_wait<0>();
            tile_ship(acc2, 2);
            if (lane < 6) mbar_arrive(BAR(B_AEMPTY + lane), 1);
            TS(12 + 12 * layer);
        } else {
            const int t2 = tid - 256;
            const uint8_t* ximg = g_X + (uint32_t)layer * 16 * 8 * 16384;
            mbar_wait(BAR(B_SSQ), layer);
            TS(6 + 12 * layer);
            float sqv[16];
#pragma unroll
            for (int i = 0; i < 16; i++) sqv[i] = __ldcg(g_ssqc + (layer * 16 + i) * 2048 + 128 * c + t2);
            const unsigned short xm = __ldcg((const unsigned short*)(ximg + (uint32_t)(c * 8 * 16384 + (t2 >> 3) * 128 + (t2 & 7) * 2)));
            acc_def(acc);
#pragma unroll 1
            for (int kb = 0; kb < 8; kb++) {
                if (kb == 4) {
                    wg_wait<0>();
                    if (lane == 0) { mbar_arrive(BAR(B_XEMPTY + 3), 1); mbar_arrive_remote(mapa(BAR(B_XEMPTY + 3), par ^ 1)); }
                    float tot = 0.f;
#pragma unroll
                    for (int i = 0; i < 16; i++) tot += sqv[i];
                    float rs = rsqrtf(tot * (1.f / 512.f) + 1e-5f);
                    s_rstd[t2] = rs;
                    s_rstd[128 + t2] = 2.f * rs;
                    s_mean[t2] = layer == 0 ? 0.f : __uint_as_float((uint32_t)xm << 16) * (1.f / 512.f);
                    TS(7 + 12 * layer);
                    bar_arrive(4, 384);
                    bar_sync(14, 384);
                }
                mbar_wait(BAR(B_XFULL + (kb & 3)), (kb >> 2) & 1);
                wg_fence();
#pragma unroll
                for (int ks = 0; ks < 4; ks++)
                    wgmma_n128<1>(acc, desc_a(sb + SM_X + (kb & 3) * 24576 + 16384 + ks * 256), desc_b<128>(sb + SM_X + (kb & 3) * 24576 + ks * 4096), 1);
                wg_commit();
                wg_wait<1>();
                if ((kb & 3) != 0 && lane == 0) { mbar_arrive(BAR(B_XEMPTY + ((kb - 1) & 3)), 1); mbar_arrive_remote(mapa(BAR(B_XEMPTY + ((kb - 1) & 3)), par ^ 1)); }
            }
            wg_wait<0>();
            if (lane == 0) { mbar_arrive(BAR(B_XEMPTY + 3), 1); mbar_arrive_remote(mapa(BAR(B_XEMPTY + 3), par ^ 1)); mbar_arrive_remote(mapa(BAR(B_RFREE), par ^ 1)); }
            bar_arrive(7, 384);
            bar_sync(3, 128);
            TS(9 + 12 * layer);
            const int m0 = 16 * w + g;
            const uint32_t xoff = (uint32_t)((c * 8 + own) * 16384 + w * 4096 + g * 16 + 4 * q);
            if (layer == 0) {
                const uint8_t* xs = g_X + xoff;
#pragma unroll
                for (int i = 0; i < 16; i++) {
                    float2 rs = *(const float2*)(s_rstd + 8 * i + 2 * q);
                    uint32_t x0v = __ldcg((const uint32_t*)(xs + i * 128)), x1v = __ldcg((const uint32_t*)(xs + 2048 + i * 128));
                    acc[4 * i] = acc[4 * i] * rs.x + bf_lo(x0v);
                    acc[4 * i + 1] = acc[4 * i + 1] * rs.y + bf_hi(x0v);
                    acc[4 * i + 2] = acc[4 * i + 2] * rs.x + bf_lo(x1v);
                    acc[4 * i + 3] = acc[4 * i + 3] * rs.y + bf_hi(x1v);
                }
            } else {
                float d0 = ldbf(p.dskip + 64 * own + m0), d1 = ldbf(p.dskip + 64 * own + m0 + 8);
#pragma unroll
                for (int i = 0; i < 16; i++) {
                    float2 rs = *(const float2*)(s_rstd + 8 * i + 2 * q);
                    float2 mn = *(const float2*)(s_mean + 8 * i + 2 * q);
                    acc[4 * i] = acc[4 * i] * (1.f + rs.x * d0) + mn.x;
                    acc[4 * i + 1] = acc[4 * i + 1] * (1.f + rs.y * d0) + mn.y;
                    acc[4 * i + 2] = acc[4 * i + 2] * (1.f + rs.x * d1) + mn.x;
                    acc[4 * i + 3] = acc[4 * i + 3] * (1.f + rs.y * d1) + mn.y;
                }
            }
            TS(10 + 12 * layer);
            bar_sync(6, 416);
            TS(11 + 12 * layer);
            {
                float (&a0)[32] = *reinterpret_cast<float (*)[32]>(&acc[0]);
                float (&a1)[32] = *reinterpret_cast<float (*)[32]>(&acc[32]);
#pragma unroll 1
                for (int k = 0; k < 2; k++) {
                    const uint32_t hb = sb + SM_HH + (par ^ k) * 32768;
                    if (k == 1) {
                        mbar_wait(BAR(B_HPEER), layer);
                        mbar_wait(BAR(B_HPEER1), layer);
                        bar_sync(12, 384);
                    }
                    mbar_wait(BAR(B_AFULL + 6 + k), 1);
                    const uint64_t da = c_desc(6 + k);
                    wg_fence();
#pragma unroll
                    for (int ks = 0; ks < 4; ks++) {
                        wgmma_n64s<1>(a0, da + ks * dstep, desc_b<64>(hb + ks * 2048), 1);
                        wgmma_n64s<1>(a1, da + ks * dstep, desc_b<64>(hb + 16384 + ks * 2048), 1);
                    }
#pragma unroll
                    for (int ks = 0; ks < 4; ks++) {
                        wgmma_n64s<-1>(a0, da + 512 + ks * dstep, desc_b<64>(hb + 8192 + ks * 2048), 1);
                        wgmma_n64s<-1>(a1, da + 512 + ks * dstep, desc_b<64>(hb + 16384 + 8192 + ks * 2048), 1);
                    }
                    wg_commit();
                }
                wg_wait<0>();
            }
#pragma unroll
            for (int i = 0; i < 16; i++)
                *(float4*)(sm + SM_A + 6 * 16384 + i * 2048 + t2 * 16) = make_float4(acc[4 * i], acc[4 * i + 1], acc[4 * i + 2], acc[4 * i + 3]);
            TS(12 + 12 * layer);
        }
        {
            const int t = tid & 127;
            const int nch = wg == 2 ? 2 : 3;
            const uint4* pb = g_P + (uint32_t)((c * 8 + r) * 4 * 1024 + wg * 128 + t);
            uint4 v[3][3];
            unsigned n = 0;
#pragma unroll 1
            while (true) {
                if (lane == 31) {
#pragma unroll 1
                    while (true) {
                        uint32_t bad = 0;
#pragma unroll
                        for (int sx = 0; sx < 3; sx++) {
                            uint32_t t0;
                            asm volatile("ld.relaxed.gpu.global.u32 %0, [%1];" : "=r"(t0) : "l"(pb + ((pi_ + 1 + sx) & 3) * 1024 + (nch - 1) * 384) : "memory");
                            bad |= t0 ^ ptag;
                        }
                        if (!(bad & 0x00010001u) || ++n >= SPIN_LIMIT) break;
                    }
                }
                __syncwarp();
                uint32_t bad = 0;
#pragma unroll
                for (int k = 0; k < 3; k++)
#pragma unroll
                    for (int sx = 0; sx < 3; sx++) {
                        v[k][sx] = make_uint4(ptag, 0, 0, 0);
                        if (k < nch) v[k][sx] = ld_relaxed_u4(pb + ((pi_ + 1 + sx) & 3) * 1024 + k * 384);
                        bad |= v[k][sx].x ^ ptag;
                    }
                if (!__any_sync(~0u, bad & 0x00010001u) || ++n >= SPIN_LIMIT) break;
            }
            bar_sync(8, 384);
            TS(13 + 12 * layer);
            const int m0 = 16 * w + g;
            const float w0 = (own == 0 && m0 < 2) ? (m0 == 0 ? 0.f : 0.5f) : 1.f;
#pragma unroll
            for (int k = 0; k < 3; k++) {
                if (k < nch) {
                    const int i = wg + 3 * k;
                    float4 a = *(const float4*)(sm + SM_A + 6 * 16384 + (2 * i) * 2048 + t * 16);
                    float4 bq = *(const float4*)(sm + SM_A + 6 * 16384 + (2 * i + 1) * 2048 + t * 16);
#pragma unroll
                    for (int sx = 0; sx < 3; sx++) {
                        a.x += bf_lo(v[k][sx].x); a.y += bf_hi(v[k][sx].x); a.z += bf_lo(v[k][sx].y); a.w += bf_hi(v[k][sx].y);
                        bq.x += bf_lo(v[k][sx].z); bq.y += bf_hi(v[k][sx].z); bq.z += bf_lo(v[k][sx].w); bq.w += bf_hi(v[k][sx].w);
                    }
                    if (layer == 0) {
                        uint8_t* xd = g_X + (uint32_t)((16 * 8 + c * 8 + own) * 16384 + w * 4096 + g * 16 + 4 * q + i * 256);
                        uint32_t v0 = pack_bf16(a.x, a.y), v1 = pack_bf16(a.z, a.w), v2 = pack_bf16(bq.x, bq.y), v3 = pack_bf16(bq.z, bq.w);
                        *(uint32_t*)(xd) = v0; *(uint32_t*)(xd + 2048) = v1; *(uint32_t*)(xd + 128) = v2; *(uint32_t*)(xd + 2048 + 128) = v3;
                        float sq[4];
                        sq[0] = w0 * bf_lo(v0) * bf_lo(v0) + bf_lo(v1) * bf_lo(v1);
                        sq[1] = w0 * bf_hi(v0) * bf_hi(v0) + bf_hi(v1) * bf_hi(v1);
                        sq[2] = w0 * bf_lo(v2) * bf_lo(v2) + bf_lo(v3) * bf_lo(v3);
                        sq[3] = w0 * bf_hi(v2) * bf_hi(v2) + bf_hi(v3) * bf_hi(v3);
                        float u0 = (g & 1) ? sq[2] : sq[0], u1 = (g & 1) ? sq[3] : sq[1];
                        u0 += __shfl_xor_sync(~0u, (g & 1) ? sq[0] : sq[2], 4);
                        u1 += __shfl_xor_sync(~0u, (g & 1) ? sq[1] : sq[3], 4);
                        float z = (g & 2) ? u1 : u0;
                        z += __shfl_xor_sync(~0u, (g & 2) ? u0 : u1, 8);
                        z += __shfl_xor_sync(~0u, z, 16);
                        if (g < 4) atomicAdd(s_mean + 16 * i + 8 * (g & 1) + 2 * q + (g >> 1), z);
                    } else {
                        float* o = p.out + (uint32_t)((128 * c + 32 * q + 4 * i) * 512 + 64 * own + m0);
                        o[0] = a.x; o[512] = a.y; o[8] = a.z; o[512 + 8] = a.w;
                        o[1024] = bq.x; o[1536] = bq.y; o[1024 + 8] = bq.z; o[1536 + 8] = bq.w;
                    }
                }
            }
            if (wg < 2) mbar_wait_cluster(BAR(B_HDONE), layer);
            if (layer == 0) {
                fence_async_smem();
                bar_sync(9, 384);
                TS(14 + 12 * layer);
                if (wg == 2) {
                    atomicAdd(g_ssq + 2048 + 128 * c + t, s_mean[t] * (2.f / 512.f));
                    bar_sync(3, 128);
                    if (lane == 0) { mbar_arrive(BAR(B_AEMPTY + 6), 2); mbar_arrive(BAR(B_AEMPTY + 7), 2); }
                    if (t == 0) { fence_async(); red_release(&g_bar[2], 1); }
                }
            }
        }
        TS(15 + 12 * layer);
        if (wg == 0) TC(31);
    }
}

typedef CUresult (*EncFn)(CUtensorMap*, CUtensorMapDataType, cuuint32_t, void*, const cuuint64_t*, const cuuint64_t*,
                          const cuuint32_t*, const cuuint32_t*, CUtensorMapInterleave, CUtensorMapSwizzle,
                          CUtensorMapL2promotion, CUtensorMapFloatOOBfill);

void launch_impl(void* const* d_in, void* d_out, int stop) {
    static EncFn enc = nullptr;
    if (!enc) {
        void* fn = nullptr;
        cudaDriverEntryPointQueryResult qr;
        cudaGetDriverEntryPoint("cuTensorMapEncodeTiled", &fn, cudaEnableDefault, &qr);
        enc = (EncFn)fn;
        cudaFuncSetAttribute(fused_kernel, cudaFuncAttributeMaxDynamicSharedMemorySize, SM_TOTAL);
    }
    CUtensorMap tx, tbr, tbi, tcr, tci, tcol;
    {
        void* gx = nullptr;
        cudaGetSymbolAddress(&gx, g_X);
        cuuint64_t gd[5] = {64, 16, 64, 16, 2};
        cuuint64_t gs[4] = {128, 2048, 128 * 1024, 2048 * 1024};
        cuuint32_t bx[5] = {32, 16, 1, 16, 1};
        cuuint32_t es[5] = {1, 1, 1, 1, 1};
        enc(&tcol, CU_TENSOR_MAP_DATA_TYPE_BFLOAT16, 5, gx, gd, gs, bx, es, CU_TENSOR_MAP_INTERLEAVE_NONE,
            CU_TENSOR_MAP_SWIZZLE_64B, CU_TENSOR_MAP_L2_PROMOTION_NONE, CU_TENSOR_MAP_FLOAT_OOB_FILL_NONE);
    }
    {
        cuuint64_t gd[5] = {512, 2, 4, 16, 16};
        cuuint64_t gs[4] = {1024, 32 * 1024, 2 * 1024, 128 * 1024};
        cuuint32_t bx[5] = {64, 2, 4, 8, 1};
        cuuint32_t es[5] = {1, 1, 1, 1, 1};
        enc(&tx, CU_TENSOR_MAP_DATA_TYPE_BFLOAT16, 5, d_in[0], gd, gs, bx, es, CU_TENSOR_MAP_INTERLEAVE_NONE,
            CU_TENSOR_MAP_SWIZZLE_128B, CU_TENSOR_MAP_L2_PROMOTION_L2_128B, CU_TENSOR_MAP_FLOAT_OOB_FILL_NONE);
    }
    auto mk2 = [&](CUtensorMap* m, void* ptr, cuuint32_t rows) {
        cuuint64_t gd[2] = {512, 512};
        cuuint64_t gs[1] = {1024};
        cuuint32_t bx[2] = {64, rows};
        cuuint32_t es[2] = {1, 1};
        enc(m, CU_TENSOR_MAP_DATA_TYPE_BFLOAT16, 2, ptr, gd, gs, bx, es, CU_TENSOR_MAP_INTERLEAVE_NONE,
            CU_TENSOR_MAP_SWIZZLE_128B, CU_TENSOR_MAP_L2_PROMOTION_L2_128B, CU_TENSOR_MAP_FLOAT_OOB_FILL_NONE);
    };
    mk2(&tbr, d_in[6], 32);
    mk2(&tbi, d_in[7], 32);
    mk2(&tcr, d_in[8], 64);
    mk2(&tci, d_in[9], 64);
    Params p;
    p.x0 = (const __nv_bfloat16*)d_in[0];
    p.w_r = (const __nv_bfloat16*)d_in[1];
    p.w_i = (const __nv_bfloat16*)d_in[2];
    p.lam_re = (const __nv_bfloat16*)d_in[4];
    p.lam_im = (const __nv_bfloat16*)d_in[5];
    p.log_dt = (const __nv_bfloat16*)d_in[10];
    p.dskip = (const __nv_bfloat16*)d_in[11];
    p.out = (float*)d_out;
    p.stop = stop;
    cudaLaunchConfig_t cfg = {};
    cfg.gridDim = dim3(NCTA); cfg.blockDim = dim3(NTHREADS); cfg.dynamicSmemBytes = SM_TOTAL; cfg.stream = cudaStreamPerThread;
    cudaLaunchAttribute at[1];
    at[0].id = cudaLaunchAttributeClusterDimension;
    at[0].val.clusterDim.x = 2; at[0].val.clusterDim.y = 1; at[0].val.clusterDim.z = 1;
    cfg.attrs = at; cfg.numAttrs = 1;
    cudaLaunchKernelEx(&cfg, fused_kernel, tx, tbr, tbi, tcr, tci, tcol, p);
}

}

extern "C" void kernel_launch(void* const* d_in, const int* in_sizes, int n_in, void* d_out, int out_size) {
    (void)in_sizes; (void)n_in; (void)out_size;
    launch_impl(d_in, d_out, 100);
}
```

```cpp
#include <cuda_runtime.h>
#include <cuda_bf16.h>
#include <cuda.h>
#include <stdint.h>

namespace {

constexpr int NCTA = 128;
constexpr int NTHREADS = 512;
constexpr int SM_A = 0;
constexpr int SM_X = 131072;
constexpr int SM_H = 196608;
constexpr int SM_HH = SM_X + 32768;
constexpr int SM_M = 229376;
constexpr int SM_TOTAL = 232448;
constexpr int SM_BAR = SM_M;
constexpr int SM_TGT = SM_M + 384;
constexpr int SM_LAM = SM_M + 416;
constexpr int SM_TAB = SM_M + 928;
constexpr int SM_RSTD = SM_M + 1920;
constexpr int SM_MEAN = SM_TAB;
constexpr int SM_T64 = SM_M + 2944;
constexpr int SM_B1ST = SM_H + 24576;
constexpr int SM_RAW = SM_X + 40960;
constexpr int SM_SSQ = SM_X + 57344;
constexpr int B_FULL0 = 0;
constexpr int B_EMPTY0 = 8;
constexpr int B_FULLC = 12;
constexpr int B_AFULL = 13;
constexpr int B_AEMPTY = 21;
constexpr int B_XFULL = 29;
constexpr int B_XEMPTY = 33;
constexpr int B_AFREE = 37;
constexpr int B_COL = 38;
constexpr int B_SSQ = 39;
constexpr int B_HPEER = 40;
constexpr int B_RFREE = 41;
constexpr int B_HDONE = 42;
constexpr int B_WRDY = 43;
constexpr int B_HPEER1 = 44;
constexpr int B_FULLB = 45;
constexpr int B_BFREE = 46;
constexpr int B_SETUP = 47;
constexpr int NBARS = 48;

__device__ __align__(1024) uint8_t g_X[2 * 16 * 8 * 16384];
__device__ __align__(1024) uint8_t g_A1[8 * 8 * 16384];
__device__ __align__(1024) uint8_t g_A2[8 * 8 * 16384];
__device__ __align__(1024) uint8_t g_E[2 * 8 * 8 * 8192];
__device__ __align__(16) float g_ssq[2 * 2048];
__device__ __align__(16) float g_ssqc[2 * 16 * 2048];
__device__ __align__(16) float g_Dh[512];
__device__ __align__(16) uint4 g_Wfrag[128 * 4 * 256];
__device__ __align__(16) float4 g_Ebuf[2 * 16 * 512];
__device__ __align__(16) uint4 g_P[16 * 8 * 4 * 1024];
__device__ unsigned g_bar[8];
__device__ unsigned g_err;
#define TX(i)
#define TQ(i)
#define TS(i)
#define TC(i)

constexpr unsigned SPIN_LIMIT = 1u << 22;

__device__ __forceinline__ uint32_t s2u(const void* p) { return (uint32_t)__cvta_generic_to_shared(p); }
__device__ __forceinline__ void mbar_init(uint32_t a, uint32_t c) {
    asm volatile("mbarrier.init.shared::cta.b64 [%0], %1;" ::"r"(a), "r"(c) : "memory");
}
__device__ __forceinline__ void mbar_expect(uint32_t a, uint32_t bytes) {
    asm volatile("mbarrier.arrive.expect_tx.shared::cta.b64 _, [%0], %1;" ::"r"(a), "r"(bytes) : "memory");
}
__device__ __forceinline__ void mbar_arrive(uint32_t a, uint32_t cnt) {
    asm volatile("mbarrier.arrive.shared::cta.b64 _, [%0], %1;" ::"r"(a), "r"(cnt) : "memory");
}
__device__ __forceinline__ bool mbar_try(uint32_t a, uint32_t parity) {
    uint32_t ok;
    asm volatile("{\n.reg .pred p;\nmbarrier.try_wait.parity.shared::cta.b64 p, [%1], %2;\nselp.u32 %0, 1, 0, p;\n}"
                 : "=r"(ok) : "r"(a), "r"(parity) : "memory");
    return ok != 0;
}
__device__ __forceinline__ void mbar_wait(uint32_t a, uint32_t parity) {
    asm volatile("{\n.reg .pred p, q;\n.reg .u32 n;\nmov.u32 n, 0;\n"
                 "W_%=:\nmbarrier.try_wait.parity.shared::cta.b64 p, [%0], %1;\n@p bra D_%=;\n"
                 "add.u32 n, n, 1;\nsetp.lt.u32 q, n, 4194304;\n@q bra W_%=;\nD_%=:\n}" ::"r"(a), "r"(parity) : "memory");
}
__device__ __forceinline__ void bulk_g2s(uint32_t dst, const void* src, uint32_t bytes, uint32_t bar) {
    asm volatile("cp.async.bulk.shared::cluster.global.mbarrier::complete_tx::bytes [%0], [%1], %2, [%3];" ::"r"(dst),
                 "l"(src), "r"(bytes), "r"(bar) : "memory");
}
__device__ __forceinline__ void tma_2d(uint32_t dst, const CUtensorMap* m, int c0, int c1, uint32_t bar) {
    asm volatile("cp.async.bulk.tensor.2d.shared::cluster.global.mbarrier::complete_tx::bytes [%0], [%1, {%3,%4}], [%2];" ::"r"(dst),
                 "l"(m), "r"(bar), "r"(c0), "r"(c1) : "memory");
}
__device__ __forceinline__ void tma_5d(uint32_t dst, const CUtensorMap* m, int c0, int c1, int c2, int c3, int c4, uint32_t bar) {
    asm volatile("cp.async.bulk.tensor.5d.shared::cluster.global.mbarrier::complete_tx::bytes [%0], [%1, {%3,%4,%5,%6,%7}], [%2];" ::"r"(dst),
                 "l"(m), "r"(bar), "r"(c0), "r"(c1), "r"(c2), "r"(c3), "r"(c4) : "memory");
}
__device__ __forceinline__ void tma_2d_mc(uint32_t dst, const CUtensorMap* m, int c0, int c1, uint32_t bar) {
    asm volatile("cp.async.bulk.tensor.2d.shared::cluster.global.mbarrier::complete_tx::bytes.multicast::cluster [%0], [%1, {%3,%4}], [%2], %5;" ::"r"(dst),
                 "l"(m), "r"(bar), "r"(c0), "r"(c1), "h"((unsigned short)3) : "memory");
}
__device__ __forceinline__ void tma_5d_mc(uint32_t dst, const CUtensorMap* m, int c0, int c1, int c2, int c3, int c4, uint32_t bar) {
    asm volatile("cp.async.bulk.tensor.5d.shared::cluster.global.mbarrier::complete_tx::bytes.multicast::cluster [%0], [%1, {%3,%4,%5,%6,%7}], [%2], %8;" ::"r"(dst),
                 "l"(m), "r"(bar), "r"(c0), "r"(c1), "r"(c2), "r"(c3), "r"(c4), "h"((unsigned short)3) : "memory");
}
__device__ __forceinline__ void bulk_g2s_mc(uint32_t dst, const void* src, uint32_t bytes, uint32_t bar) {
    asm volatile("cp.async.bulk.shared::cluster.global.mbarrier::complete_tx::bytes.multicast::cluster [%0], [%1], %2, [%3], %4;" ::"r"(dst),
                 "l"(src), "r"(bytes), "r"(bar), "h"((unsigned short)3) : "memory");
}
__device__ __forceinline__ void tma_store_5d(const CUtensorMap* m, int c0, int c1, int c2, int c3, int c4, uint32_t src) {
    asm volatile("cp.async.bulk.tensor.5d.global.shared::cta.bulk_group [%0, {%2,%3,%4,%5,%6}], [%1];" ::"l"(m), "r"(src),
                 "r"(c0), "r"(c1), "r"(c2), "r"(c3), "r"(c4) : "memory");
}
__device__ __forceinline__ uint32_t lds32(uint32_t a) { uint32_t v; asm volatile("ld.shared.u32 %0, [%1];" : "=r"(v) : "r"(a) : "memory"); return v; }
__device__ __forceinline__ uint4 ld_relaxed_u4(const uint4* p) {
    uint4 v;
    asm volatile("ld.relaxed.gpu.global.v4.u32 {%0,%1,%2,%3}, [%4];" : "=r"(v.x), "=r"(v.y), "=r"(v.z), "=r"(v.w) : "l"(p) : "memory");
    return v;
}
__device__ __forceinline__ void fence_async() { asm volatile("fence.proxy.async.global;" ::: "memory"); }
__device__ __forceinline__ void red_relaxed(unsigned* p, unsigned v) {
    asm volatile("red.relaxed.gpu.global.add.u32 [%0], %1;" ::"l"(p), "r"(v) : "memory");
}
__device__ __forceinline__ uint32_t mapa(uint32_t a, uint32_t rank) {
    uint32_t d;
    asm("mapa.shared::cluster.u32 %0, %1, %2;" : "=r"(d) : "r"(a), "r"(rank));
    return d;
}
__device__ __forceinline__ void mbar_arrive_remote(uint32_t ra) {
    asm volatile("mbarrier.arrive.relaxed.cluster.shared::cluster.b64 _, [%0];" ::"r"(ra) : "memory");
}
__device__ __forceinline__ void mbar_wait_cluster(uint32_t a, uint32_t parity) {
    asm volatile("{\n.reg .pred p, q;\n.reg .u32 n;\nmov.u32 n, 0;\n"
                 "W_%=:\nmbarrier.try_wait.parity.acquire.cluster.shared::cta.b64 p, [%0], %1;\n@p bra D_%=;\n"
                 "add.u32 n, n, 1;\nsetp.lt.u32 q, n, 4194304;\n@q bra W_%=;\nD_%=:\n}" ::"r"(a), "r"(parity) : "memory");
}
__device__ __forceinline__ void bulk_s2peer(uint32_t rdst, uint32_t src, uint32_t bytes, uint32_t rbar) {
    asm volatile("cp.async.bulk.shared::cluster.shared::cta.mbarrier::complete_tx::bytes [%0], [%1], %2, [%3];" ::"r"(rdst),
                 "r"(src), "r"(bytes), "r"(rbar) : "memory");
}
__device__ __forceinline__ void fence_async_smem() { asm volatile("fence.proxy.async.shared::cta;" ::: "memory"); }
__device__ __forceinline__ void wg_fence() { asm volatile("wgmma.fence.sync.aligned;" ::: "memory"); }
__device__ __forceinline__ void wg_commit() { asm volatile("wgmma.commit_group.sync.aligned;" ::: "memory"); }
template <int N> __device__ __forceinline__ void wg_wait() { asm volatile("wgmma.wait_group.sync.aligned %0;" ::"n"(N) : "memory"); }
__device__ __forceinline__ void bar_sync(int id, int n) { asm volatile("bar.sync %0, %1;" ::"r"(id), "r"(n) : "memory"); }
__device__ __forceinline__ void bar_arrive(int id, int n) { asm volatile("bar.arrive %0, %1;" ::"r"(id), "r"(n) : "memory"); }
__device__ __forceinline__ unsigned ld_acquire(const unsigned* p) {
    unsigned v;
    asm volatile("ld.acquire.gpu.global.u32 %0, [%1];" : "=r"(v) : "l"(p) : "memory");
    return v;
}
__device__ __forceinline__ void red_release(unsigned* p, unsigned v) {
    asm volatile("red.release.gpu.global.add.u32 [%0], %1;" ::"l"(p), "r"(v) : "memory");
}
__device__ __forceinline__ void wait_count(const unsigned* p, unsigned target) {
    unsigned n = 0;
#pragma unroll 1
    while ((int)(ld_acquire(p) - target) < 0 && ++n < SPIN_LIMIT) {}
}
__device__ __forceinline__ float4 ld_relaxed_f4(const float4* p) {
    float4 v;
    asm volatile("ld.relaxed.gpu.global.v4.f32 {%0,%1,%2,%3}, [%4];" : "=f"(v.x), "=f"(v.y), "=f"(v.z), "=f"(v.w) : "l"(p) : "memory");
    return v;
}
__device__ __forceinline__ void st_relaxed_f4(float4* p, float4 v) {
    asm volatile("st.relaxed.gpu.global.v4.f32 [%0], {%1,%2,%3,%4};" ::"l"(p), "f"(v.x), "f"(v.y), "f"(v.z), "f"(v.w) : "memory");
}
__device__ __forceinline__ uint32_t pack_bf16(float lo, float hi) {
    uint32_t r;
    asm("cvt.rn.bf16x2.f32 %0, %1, %2;" : "=r"(r) : "f"(hi), "f"(lo));
    return r;
}
__device__ __forceinline__ uint32_t hmul2(uint32_t a, uint32_t b) {
    uint32_t r;
    asm("mul.rn.bf16x2 %0, %1, %2;" : "=r"(r) : "r"(a), "r"(b));
    return r;
}
__device__ __forceinline__ uint32_t hfma2(uint32_t a, uint32_t b, uint32_t c) {
    uint32_t r;
    asm("fma.rn.bf16x2 %0, %1, %2, %3;" : "=r"(r) : "r"(a), "r"(b), "r"(c));
    return r;
}
__device__ __forceinline__ float bf_lo(uint32_t v) { return __uint_as_float(v << 16); }
__device__ __forceinline__ float bf_hi(uint32_t v) { return __uint_as_float(v & 0xffff0000u); }
__device__ __forceinline__ void sts32(uint32_t a, uint32_t v) { asm volatile("st.shared.u32 [%0], %1;" ::"r"(a), "r"(v) : "memory"); }
__device__ __forceinline__ void sts128(uint32_t a, uint4 v) {
    asm volatile("st.shared.v4.u32 [%0], {%1,%2,%3,%4};" ::"r"(a), "r"(v.x), "r"(v.y), "r"(v.z), "r"(v.w) : "memory");
}

__device__ __forceinline__ uint64_t desc_ni(uint32_t addr, uint32_t lbo, uint32_t sbo) {
    return (uint64_t)((addr & 0x3FFFF) >> 4) | ((uint64_t)(lbo >> 4) << 16) | ((uint64_t)(sbo >> 4) << 32);
}
__device__ __forceinline__ uint64_t desc_a(uint32_t addr) { return desc_ni(addr, 128, 1024); }
template <int N> __device__ __forceinline__ uint64_t desc_b(uint32_t addr) { return desc_ni(addr, 16 * N, 128); }
__device__ __forceinline__ uint64_t desc_k(uint32_t addr) {
    return (uint64_t)((addr & 0x3FFFF) >> 4) | (1ull << 16) | (64ull << 32) | (1ull << 62);
}
__device__ __forceinline__ uint64_t desc_mn(uint32_t addr, uint32_t lbo) {
    return (uint64_t)((addr & 0x3FFFF) >> 4) | ((uint64_t)(lbo >> 4) << 16) | (64ull << 32) | (1ull << 62);
}

#define ACC8(d, o) "+f"(d[o + 0]), "+f"(d[o + 1]), "+f"(d[o + 2]), "+f"(d[o + 3]), "+f"(d[o + 4]), "+f"(d[o + 5]), "+f"(d[o + 6]), "+f"(d[o + 7])
template <int TB, int SA = 1>
__device__ __forceinline__ void wgmma_n128(float (&d)[64], uint64_t da, uint64_t db, int sd) {
    asm volatile(
        "{\n.reg .pred p;\nsetp.ne.b32 p, %66, 0;\n"
        "wgmma.mma_async.sync.aligned.m64n128k16.f32.bf16.bf16 "
        "{%0,%1,%2,%3,%4,%5,%6,%7,%8,%9,%10,%11,%12,%13,%14,%15,%16,%17,%18,%19,%20,%21,%22,%23,%24,%25,%26,%27,%28,%29,%30,%31,"
        "%32,%33,%34,%35,%36,%37,%38,%39,%40,%41,%42,%43,%44,%45,%46,%47,%48,%49,%50,%51,%52,%53,%54,%55,%56,%57,%58,%59,%60,%61,%62,%63},"
        " %64, %65, p, %68, 1, 0, %67;\n}"
        : ACC8(d, 0), ACC8(d, 8), ACC8(d, 16), ACC8(d, 24), ACC8(d, 32), ACC8(d, 40), ACC8(d, 48), ACC8(d, 56)
        : "l"(da), "l"(db), "r"(sd), "n"(TB), "n"(SA));
}
template <int N> __device__ __forceinline__ void acc_def(float (&d)[N]) {
#pragma unroll
    for (int i = 0; i < N; i++) d[i] = 0.f;
}
template <int TB>
__device__ __forceinline__ void wgmma_n64(float (&d)[32], uint64_t da, uint64_t db, int sd) {
    asm volatile(
        "{\n.reg .pred p;\nsetp.ne.b32 p, %34, 0;\n"
        "wgmma.mma_async.sync.aligned.m64n64k16.f32.bf16.bf16 "
        "{%0,%1,%2,%3,%4,%5,%6,%7,%8,%9,%10,%11,%12,%13,%14,%15,%16,%17,%18,%19,%20,%21,%22,%23,%24,%25,%26,%27,%28,%29,%30,%31},"
        " %32, %33, p, 1, 1, 0, %35;\n}"
        : ACC8(d, 0), ACC8(d, 8), ACC8(d, 16), ACC8(d, 24)
        : "l"(da), "l"(db), "r"(sd), "n"(TB));
}
template <int SA>
__device__ __forceinline__ void wgmma_n64s(float (&d)[32], uint64_t da, uint64_t db, int sd) {
    asm volatile(
        "{\n.reg .pred p;\nsetp.ne.b32 p, %34, 0;\n"
        "wgmma.mma_async.sync.aligned.m64n64k16.f32.bf16.bf16 "
        "{%0,%1,%2,%3,%4,%5,%6,%7,%8,%9,%10,%11,%12,%13,%14,%15,%16,%17,%18,%19,%20,%21,%22,%23,%24,%25,%26,%27,%28,%29,%30,%31},"
        " %32, %33, p, %35, 1, 0, 1;\n}"
        : ACC8(d, 0), ACC8(d, 8), ACC8(d, 16), ACC8(d, 24)
        : "l"(da), "l"(db), "r"(sd), "n"(SA));
}
__device__ __forceinline__ void wgmma_n64_rs(float (&d)[32], uint32_t a0, uint32_t a1, uint32_t a2, uint32_t a3, uint64_t db, int sd) {
    asm volatile(
        "{\n.reg .pred p;\nsetp.ne.b32 p, %37, 0;\n"
        "wgmma.mma_async.sync.aligned.m64n64k16.f32.bf16.bf16 "
        "{%0,%1,%2,%3,%4,%5,%6,%7,%8,%9,%10,%11,%12,%13,%14,%15,%16,%17,%18,%19,%20,%21,%22,%23,%24,%25,%26,%27,%28,%29,%30,%31},"
        " {%32,%33,%34,%35}, %36, p, 1, 1, 1;\n}"
        : ACC8(d, 0), ACC8(d, 8), ACC8(d, 16), ACC8(d, 24)
        : "r"(a0), "r"(a1), "r"(a2), "r"(a3), "l"(db), "r"(sd));
}

struct Params {
    const __nv_bfloat16* x0;
    const __nv_bfloat16* w_r;
    const __nv_bfloat16* w_i;
    const __nv_bfloat16* lam_re;
    const __nv_bfloat16* lam_im;
    const __nv_bfloat16* log_dt;
    const __nv_bfloat16* dskip;
    float* out;
    int stop;
};

__device__ __forceinline__ float ldbf(const __nv_bfloat16* p) { return __bfloat162float(*p); }

__device__ __forceinline__ void dft_fp(int j, int& f, int& ph) {
    int cs = j >> 1;
    if (j == 1) { f = 256; ph = 0; }
    else { f = cs; ph = (j & 1) ? 128 : 0; }
}

__device__ __forceinline__ void gen_col_consts(uint32_t sb, int tid) {
#pragma unroll 1
    for (int task = tid; task < 640; task += 256) {
        int f, c8;
        uint32_t a_cc, d_pi, d_po;
        if (task < 512) {
            f = task & 63; c8 = task >> 6;
            a_cc = sb + SM_X + (f >> 5) * 16384 + ((f >> 3) & 3) * 2048 + c8 * 128 + (f & 7) * 16;
            d_pi = 8192; d_po = 1024;
        } else {
            int n2 = task & 31;
            f = 2 * n2; c8 = (task >> 5) & 3;
            a_cc = sb + SM_X + 32768 + (n2 >> 3) * 1024 + c8 * 128 + (n2 & 7) * 16;
            d_pi = 4096; d_po = 512;
        }
        float cd, sd, cs, sn;
        __sincosf((float)(f >= 32 ? f - 64 : f) * (6.283185307179586f / 64.f), &sd, &cd);
        int a = (8 * c8 * f) & 63;
        __sincosf((float)(a >= 32 ? a - 64 : a) * (6.283185307179586f / 64.f), &sn, &cs);
        float cv[8], sv[8];
#pragma unroll
        for (int e = 0; e < 8; e++) {
            cv[e] = cs; sv[e] = sn;
            float t = cs * cd - sn * sd;
            sn = sn * cd + cs * sd;
            cs = t;
        }
        uint4 oc = make_uint4(pack_bf16(cv[0], cv[1]), pack_bf16(cv[2], cv[3]), pack_bf16(cv[4], cv[5]), pack_bf16(cv[6], cv[7]));
        uint4 os = make_uint4(pack_bf16(sv[0], sv[1]), pack_bf16(sv[2], sv[3]), pack_bf16(sv[4], sv[5]), pack_bf16(sv[6], sv[7]));
        sts128(a_cc, oc);
        sts128(a_cc + d_pi, os);
        sts128(a_cc + d_po, make_uint4(os.x ^ 0x80008000u, os.y ^ 0x80008000u, os.z ^ 0x80008000u, os.w ^ 0x80008000u));
        sts128(a_cc + d_pi + d_po, oc);
    }
}

__global__ void __launch_bounds__(NTHREADS, 1)
fused_kernel(const __grid_constant__ CUtensorMap tm_x, const __grid_constant__ CUtensorMap tm_bre,
             const __grid_constant__ CUtensorMap tm_bim, const __grid_constant__ CUtensorMap tm_cre,
             const __grid_constant__ CUtensorMap tm_cim, const __grid_constant__ CUtensorMap tm_col, const Params p) {
    extern __shared__ __align__(1024) uint8_t sm[];
    const uint32_t sb = s2u(sm);
    const int tid = threadIdx.x, b = blockIdx.x;
    const int c = b >> 3, r = b & 7;
    const int par = r & 1, pi_ = r >> 1, own = 4 * par + pi_;
    const int wg = __shfl_sync(~0u, tid >> 7, 0), w = __shfl_sync(~0u, (tid >> 5) & 3, 0), lane = tid & 31, g = lane >> 2, q = lane & 3;
    auto BAR = [&](int i) { return sb + SM_BAR + 8 * i; };
    unsigned* s_tgt = (unsigned*)(sm + SM_TGT);

    if (tid < NBARS) {
        int cnt = 1;
        if (tid >= B_EMPTY0 && tid < B_EMPTY0 + 4) cnt = 16;
        if (tid >= B_XEMPTY && tid < B_XEMPTY + 4) cnt = 24;
        if (tid == B_RFREE) cnt = 12;
        if (tid == B_HDONE) cnt = 2;
        if (tid == B_SETUP) cnt = 3;
        if ((tid >= B_AEMPTY && tid < B_AEMPTY + 8) || tid == B_BFREE) cnt = 8;
        if (tid == B_AFREE) cnt = 4;
        mbar_init(BAR(tid), cnt);
        asm volatile("fence.mbarrier_init.release.cluster;" ::: "memory");
    }
    asm volatile("barrier.cluster.arrive.release.aligned;" ::: "memory");

    if (wg == 3) {
        asm volatile("setmaxnreg.dec.sync.aligned.u32 56;");
        if (w == 0 && lane < 6) {
            const CUtensorMap* tm = lane == 0 ? &tm_x : lane == 1 ? &tm_bre : lane == 2 ? &tm_bim : lane == 3 ? &tm_cre : lane == 4 ? &tm_cim : &tm_col;
            asm volatile("prefetch.tensormap [%0];" ::"l"(tm) : "memory");
        }
        __syncwarp();
        asm volatile("barrier.cluster.wait.acquire.aligned;" ::: "memory");
        if (w > 0) {
            {
                int i = tid - 416;
                int ps = i < 64 ? 64 * r + i : 32 * c + i - 64;
                float lr = ldbf(p.lam_re + ps), li = ldbf(p.lam_im + ps);
                float dt = __bfloat162float(__float2bfloat16(expf(ldbf(p.log_dt + ps))));
                if (i < 6) s_tgt[i] = ((ld_acquire(&g_bar[i]) >> 7) + 1u) << 7;
                float mag = expf(lr * dt), t = li * dt * 0.15915494309189535f, sn, cs;
                t -= rintf(t);
                sincospif(2.f * t, &sn, &cs);
                float er = mag * cs, ei = mag * sn;
                if (i < 64) {
                    *(float2*)(sm + SM_LAM + i * 8) = make_float2(er, ei);
                } else {
                    er -= 1.f;
                    float inv = 1.f / (lr * lr + li * li);
                    *(float2*)(sm + SM_TAB + (i - 64) * 8) = make_float2((er * lr + ei * li) * inv, (ei * lr - er * li) * inv);
                }
            }
            __syncwarp();
            bar_arrive(15, 224);
            if (lane == 0) mbar_arrive(BAR(B_SETUP), 1);
            if (w == 2) {
                const int kq = 2 * b + (lane >> 4), row = (kq >> 2) + 128 * (kq & 3) + 512 * ((lane >> 1) & 3) + 64 * (lane & 1);
                const char* src = (const char*)(((lane >> 3) & 1) ? p.w_i : p.w_r) + (size_t)row * 514;
                size_t a0 = (size_t)src & ~(size_t)15;
                int bytes = row == 2047 ? 512 : 544;
                asm volatile("cp.async.bulk.prefetch.L2.global [%0], %1;" ::"l"(a0), "r"(bytes) : "memory");
            }
#pragma unroll 1
            for (int i = tid - 448; i < 1536 + 128 && w > 1; i += 64) {
                if (i < 1536) g_P[(uint32_t)(b * 4 + i / 384) * 1024 + 640 + i % 384] = make_uint4(0, 0, 0, 0);
                else g_Ebuf[b * 128 + i - 1536] = make_float4(0.f, 0.f, 0.f, 0.f);
            }
#pragma unroll 1
            for (int task = tid - 448; task < 256 && w > 1; task += 64) {
                const int cb = task & 127, kq = 2 * b + (task >> 7), k1 = kq >> 2, qq = kq & 3;
                const unsigned short* wr_ = (const unsigned short*)p.w_r + (k1 + 128 * qq) * 257;
                const unsigned short* wi_ = (const unsigned short*)p.w_i + (k1 + 128 * qq) * 257;
                const int c0 = cb == 0 ? 256 : 2 * cb, c1 = 2 * cb + 1;
                uint32_t wf[16];
#pragma unroll
                for (int i = 0; i < 4; i++) {
                    int o = 512 * i * 257;
                    wf[2 * i] = (uint32_t)__ldg(wr_ + o + c0) | ((uint32_t)__ldg(wr_ + o + 64 * 257 + c0) << 16);
                    wf[2 * i + 1] = ((uint32_t)__ldg(wi_ + o + c0) | ((uint32_t)__ldg(wi_ + o + 64 * 257 + c0) << 16)) ^ 0x80008000u;
                    wf[8 + 2 * i] = (uint32_t)__ldg(wr_ + o + c1) | ((uint32_t)__ldg(wr_ + o + 64 * 257 + c1) << 16);
                    wf[8 + 2 * i + 1] = ((uint32_t)__ldg(wi_ + o + c1) | ((uint32_t)__ldg(wi_ + o + 64 * 257 + c1) << 16)) ^ 0x80008000u;
                }
                uint4* wd = g_Wfrag + (uint32_t)(cb * 1024 + kq);
#pragma unroll
                for (int i = 0; i < 4; i++) wd[i * 256] = make_uint4(wf[4 * i], wf[4 * i + 1], wf[4 * i + 2], wf[4 * i + 3]);
            }
            __syncwarp();
            if (w > 1) bar_arrive(11, 96);
            if (w == 3) {
#pragma unroll 1
                for (int it = 0; it < 8; it++) {
                    const int m = 4 * c + (it >> 1), d = 64 * r + m, ch = lane + 32 * (it & 1);
                    float v[8];
#pragma unroll
                    for (int e = 0; e < 8; e++) {
                        int j = 8 * ch + e, f, ph;
                        dft_fp(j, f, ph);
                        int a = (d * f + ph) & 511;
                        a = a >= 256 ? a - 512 : a;
                        float wj = j == 0 ? 0.f : (j == 1 ? 1.f / 512.f : 2.f / 512.f);
                        v[e] = wj * __cosf((float)a * (6.283185307179586f / 512.f));
                    }
                    uint32_t off = (uint32_t)(64 + r * 8 + (ch >> 3)) * 8192 + (m >> 3) * 1024 + (ch & 7) * 128 + (m & 7) * 16;
                    *(uint4*)(g_E + off) = make_uint4(pack_bf16(v[0], v[1]), pack_bf16(v[2], v[3]), pack_bf16(v[4], v[5]), pack_bf16(v[6], v[7]));
                }
                __syncwarp();
                if (lane == 0) { fence_async(); red_release(&g_bar[6], 1); }
                return;
            }
            if (w == 2) {
#pragma unroll 1
                for (int it = 0; it < 4; it++) {
                    const int hf = it & 1;
                    __syncwarp();
                    if (hf == 0) bar_sync(13, 288); else bar_sync(6, 416);
                    if (lane == 0) {
                        const uint32_t src = sb + SM_HH + par * 32768 + hf * 16384;
                        bulk_s2peer(mapa(src, par ^ 1), src, 16384, mapa(BAR(hf ? B_HPEER1 : B_HPEER), par ^ 1));
                    }
                }
                return;
            }
            {
                uint4 p0 = __ldg((const uint4*)p.dskip + 2 * lane), p1 = __ldg((const uint4*)p.dskip + 2 * lane + 1);
                uint32_t u[8] = {p0.x, p0.y, p0.z, p0.w, p1.x, p1.y, p1.z, p1.w};
#pragma unroll 1
                for (int jj = 0; jj < 4; jj++) {
                    int j = 64 * r + 4 * c + jj, f, ph;
                    dft_fp(j, f, ph);
                    float s = 0.f;
                    int idx = 16 * lane * f + ph;
#pragma unroll
                    for (int i = 0; i < 16; i++) {
                        int a = idx & 511;
                        idx += f;
                        a = a >= 256 ? a - 512 : a;
                        s += ((i & 1) ? bf_hi(u[i >> 1]) : bf_lo(u[i >> 1])) * __cosf((float)a * (6.283185307179586f / 512.f));
                    }
#pragma unroll
                    for (int o = 16; o; o >>= 1) s += __shfl_xor_sync(~0u, s, o);
                    if (lane == 0) g_Dh[j] = s;
                }
                if (lane == 0) red_release(&g_bar[5], 1);
                __syncwarp();
            }
            bar_sync(2, 288);
            if (lane == 0) {
                TX(5);
                fence_async();
                red_release(&g_bar[0], 1);
                TX(6);
            }
            __syncwarp();
            bar_sync(12, 160);
            if (lane == 0) {
                asm volatile("cp.async.bulk.global.shared::cta.bulk_group [%0], [%1], 8192;" ::"l"(g_A1 + (uint32_t)(((c >> 1) * 8 + r) * 16384 + (c & 1) * 8192)),
                             "r"(sb + SM_B1ST) : "memory");
                asm volatile("cp.async.bulk.commit_group;" ::: "memory");
                asm volatile("cp.async.bulk.wait_group 0;" ::: "memory");
                fence_async();
            }
            __syncwarp();
            bar_sync(11, 96);
            if (lane == 0) red_release(&g_bar[4], 1);
#pragma unroll 1
            for (int layer = 0; layer < 2; layer++) {
                __syncwarp();
                bar_sync(5, 416);
                if (lane == 0) {
                    TX(0 + 8 * layer);
                    tma_store_5d(&tm_col, 32 * (b & 1), 0, b >> 1, 0, layer, sb + SM_RAW);
                    asm volatile("cp.reduce.async.bulk.global.shared::cta.bulk_group.add.f32 [%0], [%1], 8192;" ::"l"(g_ssqc + (layer * 16 + (b & 15)) * 2048),
                                 "r"(sb + SM_SSQ) : "memory");
                    asm volatile("cp.async.bulk.commit_group;" ::: "memory");
                    asm volatile("cp.async.bulk.wait_group 0;" ::: "memory");
                    TX(1 + 8 * layer);
                    fence_async();
                    red_release(&g_bar[1 + 2 * layer], 1);
                    TX(2 + 8 * layer);
                }
            }
        } else if (tid == 384) {
#pragma unroll 1
            for (int kb = 0; kb < 8; kb++) {
                uint32_t fb = BAR(B_FULL0 + kb);
                mbar_expect(fb, 16384);
                tma_5d_mc(sb + SM_A + 65536 + kb * 16384 + par * 8192, &tm_x, kb * 64, 0, 0, 8 * par, c, fb);
            }
#pragma unroll 1
            for (int k2 = 0; k2 < 8; k2++) {
                asm volatile("cp.async.bulk.prefetch.tensor.2d.L2.global [%0, {%1,%2}];" ::"l"(par ? &tm_bim : &tm_bre), "r"(k2 * 64), "r"(32 * c) : "memory");
                if ((k2 & 1) == par)
                    asm volatile("cp.async.bulk.prefetch.tensor.2d.L2.global [%0, {%1,%2}];" ::"l"((c & 1) ? &tm_cim : &tm_cre), "r"(64 * (c >> 1)), "r"(k2 * 64) : "memory");
            }
            mbar_wait(BAR(B_SETUP), 0);
#pragma unroll 1
            for (int layer = 0; layer < 2; layer++) {
                wait_count(&g_bar[2 * layer], s_tgt[2 * layer]);
                TX(4 + 8 * layer);
                fence_async();
                mbar_expect(BAR(B_COL), 16384 + 8192);
                tma_5d(sb + SM_RAW, &tm_col, 32 * (b & 1), 0, b >> 1, 0, layer, BAR(B_COL));
                bulk_g2s(sb + SM_SSQ, g_ssq + layer * 2048, 8192, BAR(B_COL));
                if (layer == 0) {
                    wait_count(&g_bar[4], s_tgt[4]);
                    mbar_arrive(BAR(B_WRDY), 1);
                    fence_async();
                }
                if (layer == 0) mbar_wait(BAR(B_AFREE), 0);
                mbar_wait(BAR(B_COL), layer);
#pragma unroll 1
                for (int s = 0; s < 8; s++) {
                    if (layer == 1) mbar_wait(BAR(B_AEMPTY + s), 1);
                    if (s >= 2) mbar_wait(BAR(B_AFULL + s - 2), 0);
                    mbar_expect(BAR(B_AFULL + s), 16384);
                    bulk_g2s(sb + SM_A + s * 16384, g_A1 + (uint32_t)(r * 8 + s) * 16384, 16384, BAR(B_AFULL + s));
                }
                if (layer == 1) wait_count(&g_bar[6], s_tgt[5]);
                wait_count(&g_bar[1 + 2 * layer], s_tgt[1 + 2 * layer]);
                TX(3 + 8 * layer);
                fence_async();
                const uint8_t* xsrc = g_X + (uint32_t)(layer * 16 + c) * 8 * 16384;
                const uint8_t* esrc = g_E + (uint32_t)(layer * 8 + own) * 8 * 8192;
                mbar_arrive(BAR(B_SSQ), 1);
                mbar_expect(BAR(B_HPEER), 16384);
                mbar_expect(BAR(B_HPEER1), 16384);
#pragma unroll 1
                for (int it = 0; it < 16; it++) {
                    if (it < 8) {
                        int st = it & 3, f = layer * 2 + (it >> 2);
                        if (f > 0) mbar_wait_cluster(BAR(B_XEMPTY + st), (f - 1) & 1);
                        mbar_expect(BAR(B_XFULL + st), 24576);
                        bulk_g2s_mc(sb + SM_X + st * 24576 + par * 8192, xsrc + (uint32_t)it * 16384 + par * 8192, 8192, BAR(B_XFULL + st));
                        bulk_g2s(sb + SM_X + st * 24576 + 16384, esrc + (uint32_t)it * 8192, 8192, BAR(B_XFULL + st));
                    }
                    if (it >= 8) {
                        if (it == 8) mbar_wait(BAR(B_AEMPTY + 5), 0);
                        int s = it - 8, tile = 4 * par + ((pi_ + 1 + (s >> 1)) & 3), sl = r ^ (s & 1);
                        mbar_wait(BAR(B_AEMPTY + s), 0);
                        uint32_t fb = BAR(B_AFULL + s), dst = sb + SM_A + s * 16384;
                        mbar_expect(fb, 16384);
                        if (layer == 1) {
                            tma_2d(dst, &tm_cre, 64 * sl, 64 * tile, fb);
                            tma_2d(dst + 8192, &tm_cim, 64 * sl, 64 * tile, fb);
                        } else {
                            bulk_g2s(dst, g_A2 + (uint32_t)(sl * 8 + tile) * 16384, 16384, fb);
                        }
                    }
                }
            }
        }
        return;
    }

    asm volatile("setmaxnreg.inc.sync.aligned.u32 152;");
    if (tid >= 96 && tid < 112) g_ssq[2048 + 16 * b + tid - 96] = 0.f;
    if (tid >= 128 && tid < 256) ((float4*)g_ssqc)[b * 128 + tid - 128] = make_float4(0.f, 0.f, 0.f, 0.f);
    TS(0);
    if (wg == 0) TC(30);
    {
        const int f = 32 * r + lane;
        float cd, sd;
        __sincosf((float)f * (6.283185307179586f / 512.f), &sd, &cd);
        const uint32_t dst = sb + SM_A + (lane >> 2) * 1024 + (lane & 3) * 32;
#pragma unroll 1
        for (int ch = tid >> 5; ch < 64; ch += 12) {
            int a = (8 * ch * f) & 511;
            a = a >= 256 ? a - 512 : a;
            float cs, sn;
            __sincosf((float)a * (6.283185307179586f / 512.f), &sn, &cs);
            float cv[8], sv[8];
#pragma unroll
            for (int e = 0; e < 8; e++) {
                cv[e] = cs; sv[e] = -sn;
                float t = cs * cd - sn * sd;
                sn = sn * cd + cs * sd;
                cs = t;
            }
            uint4 o1 = make_uint4(pack_bf16(sv[0], sv[1]), pack_bf16(sv[2], sv[3]), pack_bf16(sv[4], sv[5]), pack_bf16(sv[6], sv[7]));
            if (f == 0) o1 = make_uint4(0xbf803f80u, 0xbf803f80u, 0xbf803f80u, 0xbf803f80u);
            uint32_t a0 = dst + (ch >> 3) * 8192 + (ch & 7) * 128;
            sts128(a0, make_uint4(pack_bf16(cv[0], cv[1]), pack_bf16(cv[2], cv[3]), pack_bf16(cv[4], cv[5]), pack_bf16(cv[6], cv[7])));
            sts128(a0 + 16, o1);
        }
    }
    fence_async_smem();
    asm volatile("barrier.cluster.wait.acquire.aligned;" ::: "memory");
    bar_sync(10, 384);
    TS(1);
    if (wg < 2) {
        float acc[32];
        acc_def(acc);
        const int npos = 16 * r + 8 * wg + 2 * w;
        float sh0 = 0.f, sh1 = 0.f, s0 = 0.f, s1 = 0.f, q0 = 0.f, q1 = 0.f;
#pragma unroll 1
        for (int kb = 0; kb < 8; kb++) {
            uint32_t slot = sb + SM_A + 65536 + kb * 16384;
            mbar_wait(BAR(B_FULL0 + kb), 0);
            wg_fence();
#pragma unroll
            for (int ks = 0; ks < 4; ks++)
                wgmma_n64<0>(acc, desc_a(sb + SM_A + kb * 8192 + ks * 256), desc_k(slot + wg * 8192 + ks * 32), 1);
            wg_commit();
            {
                uint32_t v0 = lds32(slot + npos * 128 + lane * 4), v1 = lds32(slot + npos * 128 + 128 + lane * 4);
                if (kb == 0) { sh0 = __shfl_sync(~0u, bf_lo(v0), 0); sh1 = __shfl_sync(~0u, bf_lo(v1), 0); }
                float a = bf_lo(v0) - sh0, bq = bf_hi(v0) - sh0, cq = bf_lo(v1) - sh1, d = bf_hi(v1) - sh1;
                s0 += a + bq; q0 += a * a + bq * bq; s1 += cq + d; q1 += cq * cq + d * d;
            }
            wg_wait<1>();
            if (kb > 0 && kb <= 4 && lane == 0) { mbar_arrive(BAR(B_EMPTY0 + kb - 1), 1); mbar_arrive_remote(mapa(BAR(B_EMPTY0 + kb - 1), par ^ 1)); }
        }
#pragma unroll
        for (int o = 16; o; o >>= 1) {
            s0 += __shfl_xor_sync(~0u, s0, o); q0 += __shfl_xor_sync(~0u, q0, o);
            s1 += __shfl_xor_sync(~0u, s1, o); q1 += __shfl_xor_sync(~0u, q1, o);
        }
        if (lane == 0) *(float2*)(g_ssq + 128 * c + npos) = make_float2(fmaxf(q0 - s0 * s0 * (1.f / 512.f), 0.f), fmaxf(q1 - s1 * s1 * (1.f / 512.f), 0.f));
        wg_wait<0>();
        TS(2);
        uint8_t* dst = g_X + (uint32_t)((c * 8 + r) * 16384 + w * 4096 + wg * 1024 + g * 16 + 4 * q);
#pragma unroll
        for (int i = 0; i < 8; i++) {
            *(uint32_t*)(dst + i * 128) = pack_bf16(acc[4 * i], acc[4 * i + 1]);
            *(uint32_t*)(dst + 2048 + i * 128) = pack_bf16(acc[4 * i + 2], acc[4 * i + 3]);
        }
        bar_sync(2, 288);
        mbar_wait(BAR(B_SETUP), 0);
        TS(3);
    }

    if (wg == 2) {
        bar_sync(15, 224);
        {
            const int m = 4 * c + w, jp = 64 * r + m;
            int fp, php;
            dft_fp(jp, fp, php);
            const __nv_bfloat16* dh = (const __nv_bfloat16*)(sm + SM_RSTD);
            if (tid == 256) wait_count(&g_bar[5], s_tgt[5]);
            bar_sync(3, 128);
            float4 d4 = __ldcg((const float4*)g_Dh + (tid - 256));
            *(uint2*)(sm + SM_RSTD + (tid - 256) * 8) = make_uint2(pack_bf16(d4.x, d4.y), pack_bf16(d4.z, d4.w));
            bar_sync(3, 128);
#pragma unroll 1
            for (int it = 0; it < 2; it++) {
                const int ch = lane + 32 * it;
                float v[8];
#pragma unroll
                for (int e = 0; e < 8; e++) {
                    int j = 8 * ch + e, f, ph;
                    dft_fp(j, f, ph);
                    float wj = j == 0 ? 0.f : (j == 1 ? 1.f / 512.f : 2.f / 512.f);
                    float gsum = 0.f;
#pragma unroll
                    for (int sgn = 0; sgn < 2; sgn++) {
                        int mm = (sgn ? f - fp : f + fp) & 511, pp = (sgn ? ph - php : ph + php) & 511;
                        if (mm > 256) { mm = 512 - mm; pp = (512 - pp) & 511; }
                        int odd = (pp >> 7) & 1;
                        float t = __bfloat162float(dh[mm == 256 ? 1 : 2 * mm + odd]);
                        if (odd && (mm & 255) == 0) t = 0.f;
                        gsum += (pp & 256) ? -t : t;
                    }
                    v[e] = 0.5f * wj * gsum;
                }
                uint32_t off = (uint32_t)(r * 8 + (ch >> 3)) * 8192 + (m >> 3) * 1024 + (ch & 7) * 128 + (m & 7) * 16;
                *(uint4*)(g_E + off) = make_uint4(pack_bf16(v[0], v[1]), pack_bf16(v[2], v[3]), pack_bf16(v[4], v[5]), pack_bf16(v[6], v[7]));
            }
        }
        float acc[32];
        acc_def(acc);
        if (tid == 256) {
#pragma unroll 1
            for (int s = 0; s < 4; s++) mbar_wait_cluster(BAR(B_EMPTY0 + s), 0);
            mbar_expect(BAR(B_FULLB), 65536);
#pragma unroll 1
            for (int k2 = 0; k2 < 8; k2++)
                tma_2d_mc(sb + SM_A + 65536 + k2 * 8192 + par * 4096, par ? &tm_bim : &tm_bre, k2 * 64, 32 * c, BAR(B_FULLB));
        }
        __syncwarp();
        mbar_wait(BAR(B_FULLB), 0);
        wg_fence();
#pragma unroll 1
        for (int kb = 0; kb < 8; kb++) {
#pragma unroll
            for (int ks = 0; ks < 4; ks++)
                wgmma_n64<0>(acc, desc_a(sb + SM_A + kb * 8192 + ks * 256), desc_k(sb + SM_A + 65536 + kb * 8192 + ks * 32), 1);
            wg_commit();
        }
        wg_wait<0>();
        if (lane == 0) { mbar_arrive(BAR(B_BFREE), 1); mbar_arrive_remote(mapa(BAR(B_BFREE), par ^ 1)); }
        if (tid == 256) {
            mbar_wait_cluster(BAR(B_BFREE), 0);
            mbar_expect(BAR(B_FULLC), 65536);
#pragma unroll 1
            for (int k2 = par; k2 < 8; k2 += 2)
                tma_2d_mc(sb + SM_A + 65536 + k2 * 8192, (c & 1) ? &tm_cim : &tm_cre, 64 * (c >> 1), k2 * 64, BAR(B_FULLC));
        }
        __syncwarp();
        {
            uint8_t* dst = sm + SM_B1ST + w * 256 + q * 32 + g * 2;
            const float wj0 = (r == 0 && w == 0 && g < 2) ? (g == 0 ? 0.f : 1.f / 512.f) : 2.f / 512.f;
#pragma unroll
            for (int i = 0; i < 4; i++) {
#pragma unroll
                for (int e = 0; e < 2; e++) {
                    float2 cf = *(const float2*)(sm + SM_TAB + (8 * i + 2 * q + e) * 8);
#pragma unroll
                    for (int h = 0; h < 2; h++) {
                        float wj = h == 0 ? wj0 : 2.f / 512.f;
                        float pr = acc[4 * i + 2 * h + e] * wj, pi = acc[16 + 4 * i + 2 * h + e] * wj;
                        uint8_t* d2 = dst + i * 2048 + h * 128 + e * 16;
                        *(__nv_bfloat16*)(d2) = __float2bfloat16(cf.x * pr - cf.y * pi);
                        *(__nv_bfloat16*)(d2 + 1024) = __float2bfloat16(cf.x * pi + cf.y * pr);
                    }
                }
            }
            fence_async_smem();
            bar_arrive(12, 160);
        }
        acc_def(acc);
        mbar_wait(BAR(B_FULLC), 0);
        wg_fence();
#pragma unroll 1
        for (int kb = 0; kb < 8; kb++) {
#pragma unroll
            for (int ks = 0; ks < 4; ks++)
                wgmma_n64<1>(acc, desc_a(sb + SM_A + kb * 8192 + ks * 256), desc_mn(sb + SM_A + 65536 + kb * 8192 + ks * 2048, 8192), 1);
            wg_commit();
        }
        wg_wait<0>();
        fence_async_smem();
        if (lane == 0) mbar_arrive(BAR(B_AFREE), 1);
        uint8_t* dst = g_A2 + (uint32_t)(((c >> 1) * 8 + r) * 16384 + (c & 1) * 8192 + w * 2048 + g * 16 + 4 * q);
#pragma unroll
        for (int i = 0; i < 8; i++) {
            *(uint32_t*)(dst + i * 128) = pack_bf16(acc[4 * i], acc[4 * i + 1]);
            *(uint32_t*)(dst + 1024 + i * 128) = pack_bf16(acc[4 * i + 2], acc[4 * i + 3]);
        }
    }

#pragma unroll 1
    for (int layer = 0; layer < 2; layer++) {
        if (wg < 2) {
            const int n1 = 32 * wg + 8 * w + g;
            const int ct = n1 >> 2;
            gen_col_consts(sb, tid);
            uint32_t tr2[4], ti2[4], tn2[4];
#pragma unroll
            for (int i = 0; i < 4; i++) {
                float cr[2], ci[2];
#pragma unroll
                for (int e = 0; e < 2; e++) {
                    int a = (n1 * (8 * i + 2 * q + e)) & 2047;
                    a = a >= 1024 ? a - 2048 : a;
                    float ang = (float)a * (-6.283185307179586f / 2048.f);
                    cr[e] = __cosf(ang); ci[e] = __sinf(ang);
                }
                tr2[i] = pack_bf16(cr[0], cr[1]); ti2[i] = pack_bf16(ci[0], ci[1]); tn2[i] = ti2[i] ^ 0x80008000u;
            }
            uint32_t wf[16];
            const uint4* ws = g_Wfrag + (uint32_t)(b * 1024 + n1 * 4 + q);
#pragma unroll
            for (int i = 0; i < 4; i++) {
                uint4 v = make_uint4(0, 0, 0, 0);
                if (layer == 1) v = __ldcg(ws + i * 256);
                wf[4 * i] = v.x; wf[4 * i + 1] = v.y; wf[4 * i + 2] = v.z; wf[4 * i + 3] = v.w;
            }
            mbar_wait(BAR(B_COL), layer);
            TS(4 + 12 * layer);
            if (wg == 0) TC(0 + 10 * layer);
            const uint32_t rw0 = sb + SM_RAW + ct * 1024 + q * 64 + ((q >> 1) << 4) + (g & 3) * 4, rw1 = rw0 ^ 16;
            const int pos0 = 128 * ct + 8 * q + 2 * (g & 3);
            const int sw = b == 0 ? 1 : 0;
            uint32_t xr[4][4];
            const uint32_t st0 = sb + SM_H + (n1 >> 3) * 1024 + g * 16 + 4 * q;
#pragma unroll
            for (int i = 0; i < 4; i++) {
                float2 sq = *(const float2*)(sm + SM_SSQ + (pos0 + 32 * i) * 4);
                const uint32_t rs2 = pack_bf16(rsqrtf(sq.x * (1.f / 512.f) + 1e-5f), rsqrtf(sq.y * (1.f / 512.f) + 1e-5f));
#pragma unroll
                for (int jj = 0; jj < 4; jj++) {
                    const int K = jj ^ (2 * (i & 1));
                    uint32_t a = ((K & 1) ? rw1 : rw0) + i * 256 + (K & 2) * 16;
                    if (jj < 2) a ^= sw << 4;
                    uint32_t v = lds32(a);
                    xr[jj][i] = v;
                    uint32_t o = hmul2(v, rs2);
                    if (jj == 1 && sw) o = 0u;
                    sts32(st0 + (jj & 1) * 8192 + (4 * (jj >> 1) + i) * 128, o);
                }
            }
            if (wg == 0) TC(1 + 10 * layer);
            fence_async_smem();
            bar_sync(1, 256);
            float acc[32];
            const uint32_t s1a = sb + SM_X + wg * 16384, s2b = sb + SM_X + 32768;
            wg_fence();
#pragma unroll
            for (int ks = 0; ks < 8; ks++)
                wgmma_n64<1>(acc, desc_a(s1a + (ks >> 2) * 8192 + (ks & 3) * 256), desc_b<64>(sb + SM_H + ks * 2048), ks != 0);
            wg_commit();
            if (layer == 0) {
                mbar_wait(BAR(B_WRDY), 0);
#pragma unroll
                for (int i = 0; i < 4; i++) {
                    uint4 v = __ldcg(ws + i * 256);
                    wf[4 * i] = v.x; wf[4 * i + 1] = v.y; wf[4 * i + 2] = v.z; wf[4 * i + 3] = v.w;
                }
            }
            wg_wait<0>();
            if (wg == 0) TC(2 + 10 * layer);
            uint32_t are[2][4], aim[2][4];
#pragma unroll
            for (int col = 0; col < 2; col++) {
#pragma unroll
                for (int i = 0; i < 4; i++) {
                    int o = 4 * (4 * col + i);
                    uint32_t zr = pack_bf16(acc[o], acc[o + 1]), zi = pack_bf16(acc[o + 2], acc[o + 3]);
                    are[col][i] = hfma2(zr, tr2[i], hmul2(zi, tn2[i]));
                    aim[col][i] = hfma2(zr, ti2[i], hmul2(zi, tr2[i]));
                }
            }
            wg_fence();
#pragma unroll
            for (int ks = 0; ks < 2; ks++)
                wgmma_n64_rs(acc, are[0][2 * ks], are[1][2 * ks], are[0][2 * ks + 1], are[1][2 * ks + 1], desc_b<64>(s2b + ks * 2048), ks != 0);
#pragma unroll
            for (int ks = 0; ks < 2; ks++)
                wgmma_n64_rs(acc, aim[0][2 * ks], aim[1][2 * ks], aim[0][2 * ks + 1], aim[1][2 * ks + 1], desc_b<64>(s2b + 4096 + ks * 2048), 1);
            wg_commit();
            wg_wait<0>();
            if (wg == 0) TC(3 + 10 * layer);
#pragma unroll
            for (int col = 0; col < 2; col++) {
#pragma unroll
                for (int i = 0; i < 4; i++) {
                    uint32_t wr = wf[col * 8 + 2 * i], wn = wf[col * 8 + 2 * i + 1];
                    uint32_t zr = pack_bf16(acc[4 * i + 2 * col], acc[4 * i + 2 * col + 1]);
                    uint32_t zi = pack_bf16(acc[16 + 4 * i + 2 * col], acc[16 + 4 * i + 2 * col + 1]);
                    are[col][i] = hfma2(zr, wr, hmul2(zi, wn));
                    aim[col][i] = hfma2(zr, wn, hmul2(zi ^ 0x80008000u, wr));
                }
            }
            wg_fence();
#pragma unroll
            for (int ks = 0; ks < 2; ks++)
                wgmma_n64_rs(acc, are[0][2 * ks], are[1][2 * ks], are[0][2 * ks + 1], are[1][2 * ks + 1], desc_b<64>(s2b + ks * 2048), ks != 0);
#pragma unroll
            for (int ks = 0; ks < 2; ks++)
                wgmma_n64_rs(acc, aim[0][2 * ks], aim[1][2 * ks], aim[0][2 * ks + 1], aim[1][2 * ks + 1], desc_b<64>(s2b + 4096 + ks * 2048), 1);
            wg_commit();
            wg_wait<0>();
            if (wg == 0) TC(4 + 10 * layer);
#pragma unroll
            for (int col = 0; col < 2; col++) {
#pragma unroll
                for (int i = 0; i < 4; i++) {
                    uint32_t zr = pack_bf16(acc[4 * i + 2 * col], acc[4 * i + 2 * col + 1]);
                    uint32_t zi = pack_bf16(acc[16 + 4 * i + 2 * col], acc[16 + 4 * i + 2 * col + 1]);
                    sts32(st0 + 16384 + (4 * col + i) * 128, hfma2(zr, tr2[i], hmul2(zi, tn2[i])));
                    sts32(st0 + 16384 + 8192 + (4 * col + i) * 128, hfma2(zr, ti2[i], hmul2(zi, tr2[i])));
                }
            }
            if (wg == 0) TC(5 + 10 * layer);
            fence_async_smem();
            bar_sync(1, 256);
            wg_fence();
#pragma unroll
            for (int ks = 0; ks < 8; ks++)
                wgmma_n64<1>(acc, desc_a(s1a + (ks >> 2) * 8192 + (ks & 3) * 256), desc_b<64>(sb + SM_H + 16384 + ks * 2048), ks != 0);
            wg_commit();
            wg_wait<0>();
            if (wg == 0) TC(6 + 10 * layer);
            const float sc = 1.f / 2048.f;
            const float sci0 = sw ? 0.f : -sc;
            const float wr0 = sw ? 0.5f : 1.f, wi0 = sw ? 0.f : 1.f;
#pragma unroll
            for (int i = 0; i < 4; i++) {
                float ss0, ss1;
#pragma unroll
                for (int col = 0; col < 2; col++) {
                    int o = 4 * (4 * col + i);
                    uint32_t vr = xr[2 * col][i], vi = xr[2 * col + 1][i];
                    float si = col == 0 ? sci0 : -sc;
                    uint32_t nr = pack_bf16(fmaf(acc[o], sc, bf_lo(vr)), fmaf(acc[o + 1], sc, bf_hi(vr)));
                    uint32_t ni = pack_bf16(fmaf(acc[o + 2], si, bf_lo(vi)), fmaf(acc[o + 3], si, bf_hi(vi)));
                    float a0 = bf_lo(nr), a1 = bf_hi(nr), b0 = bf_lo(ni), b1 = bf_hi(ni);
                    if (col == 0) {
                        ss0 = wr0 * a0 * a0 + wi0 * b0 * b0;
                        ss1 = wr0 * a1 * a1 + wi0 * b1 * b1;
                    } else {
                        ss0 += a0 * a0 + b0 * b0;
                        ss1 += a1 * a1 + b1 * b1;
                    }
                    const int K = (2 * col) ^ (2 * (i & 1));
                    uint32_t a = rw0 + i * 256 + K * 16;
                    if (col == 0) a ^= sw << 4;
                    sts32(a, nr);
                    sts32(a ^ 16, ni);
                }
                *(float2*)(sm + SM_SSQ + (pos0 + 32 * i) * 4) = make_float2(ss0 * (2.f / 512.f), ss1 * (2.f / 512.f));
            }
            fence_async_smem();
        }
        TS(5 + 12 * layer);
        if (wg == 0) TC(7 + 10 * layer);
        bar_arrive(5, 416);

        float acc[64];
        float* s_rstd = (float*)(sm + SM_RSTD);
        float* s_mean = (float*)(sm + SM_MEAN);
        const unsigned epoch = s_tgt[0] >> 7;
        const uint32_t pt3 = 1u + (2u * epoch + layer) % 3u;
        const uint32_t ptag = (pt3 & 1u) | ((pt3 & 2u) << 15);
        const uint64_t dstep = layer == 0 ? 16 : 2;
        auto c_desc = [&](int s) { return layer == 0 ? desc_a(sb + SM_A + s * 16384) : desc_k(sb + SM_A + s * 16384); };
        if (wg < 2) {
            const int prow = 32 * wg + 8 * w + g;
            const float2 l1 = *(const float2*)(sm + SM_LAM + prow * 8);
            float lr32 = l1.x, li32 = l1.y;
#pragma unroll
            for (int i = 0; i < 5; i++) { float t = lr32 * lr32 - li32 * li32; li32 = 2.f * lr32 * li32; lr32 = t; }
            float lr128 = lr32, li128 = li32;
#pragma unroll
            for (int i = 0; i < 2; i++) { float t = lr128 * lr128 - li128 * li128; li128 = 2.f * lr128 * li128; lr128 = t; }
            const float lr1 = l1.x, li1 = l1.y;
            acc_def(acc);
#pragma unroll 1
            for (int kb = 0; kb < 8; kb++) {
                mbar_wait(BAR(B_AFULL + kb), 0);
                mbar_wait(BAR(B_XFULL + (kb & 3)), (kb >> 2) & 1);
                wg_fence();
#pragma unroll
                for (int ks = 0; ks < 4; ks++)
                    wgmma_n128<1>(acc, desc_a(sb + SM_A + kb * 16384 + wg * 8192 + ks * 256),
                                  desc_b<128>(sb + SM_X + (kb & 3) * 24576 + ks * 4096), 1);
                wg_commit();
                wg_wait<1>();
                if (kb > 0 && lane == 0) {
                    mbar_arrive(BAR(B_AEMPTY + kb - 1), 1); mbar_arrive(BAR(B_XEMPTY + ((kb - 1) & 3)), 1);
                    mbar_arrive_remote(mapa(BAR(B_XEMPTY + ((kb - 1) & 3)), par ^ 1));
                }
            }
            wg_wait<0>();
            if (lane == 0) {
                mbar_arrive(BAR(B_AEMPTY + 7), 1); mbar_arrive(BAR(B_XEMPTY + 3), 1);
                mbar_arrive_remote(mapa(BAR(B_XEMPTY + 3), par ^ 1)); mbar_arrive_remote(mapa(BAR(B_RFREE), par ^ 1));
            }
            bar_arrive(14, 384);
            TS(6 + 12 * layer);
            bar_sync(4, 384);
            TS(7 + 12 * layer);
            float er = 0.f, ei = 0.f;
#pragma unroll
            for (int i = 0; i < 16; i++) {
                float2 rs = *(const float2*)(s_rstd + 128 + 8 * i + 2 * q);
                acc[4 * i] *= rs.x; acc[4 * i + 1] *= rs.y; acc[4 * i + 2] *= rs.x; acc[4 * i + 3] *= rs.y;
                float nr = lr1 * er - li1 * ei + acc[4 * i], ni = lr1 * ei + li1 * er + acc[4 * i + 2];
                er = lr1 * nr - li1 * ni + acc[4 * i + 1];
                ei = lr1 * ni + li1 * nr + acc[4 * i + 3];
            }
            float cr = 0.f, ci = 0.f, tr = 0.f, ti = 0.f;
#pragma unroll
            for (int qq = 0; qq < 4; qq++) {
                float xr_ = __shfl_sync(~0u, er, (lane & ~3) | qq), xi_ = __shfl_sync(~0u, ei, (lane & ~3) | qq);
                if (qq == q) { cr = tr; ci = ti; }
                float nr = lr32 * tr - li32 * ti + xr_, ni = lr32 * ti + li32 * tr + xi_;
                tr = nr; ti = ni;
            }
            float4* eb = g_Ebuf + (uint32_t)(layer * 16 * 512 + 64 * r + prow);
            if (q == 0 && c < 15) st_relaxed_f4(eb + c * 512, make_float4(tr, ti, __uint_as_float(epoch), 0.f));
            TS(8 + 12 * layer);
            float pr[4], pi[4];
            {
                unsigned n = 0;
                bool ok;
#pragma unroll 1
                do {
                    ok = true;
#pragma unroll
                    for (int k = 0; k < 4; k++) {
                        float4 v = make_float4(0.f, 0.f, __uint_as_float(epoch), 0.f);
                        if (4 * k + q < c) v = ld_relaxed_f4(eb + (4 * k + q) * 512);
                        pr[k] = v.x; pi[k] = v.y;
                        ok = ok && __float_as_uint(v.z) == epoch;
                    }
                } while (!ok && ++n < SPIN_LIMIT);
            }
            __syncwarp();
            TS(9 + 12 * layer);
            float hr = 0.f, hi = 0.f;
#pragma unroll
            for (int cc = 0; cc < 15; cc++) {
                float xr_ = __shfl_sync(~0u, pr[cc >> 2], (lane & ~3) | (cc & 3)), xi_ = __shfl_sync(~0u, pi[cc >> 2], (lane & ~3) | (cc & 3));
                if (cc < c) {
                    float nr = lr128 * hr - li128 * hi + xr_, ni = lr128 * hi + li128 * hr + xi_;
                    hr = nr; hi = ni;
                }
            }
#pragma unroll
            for (int qq = 0; qq < 3; qq++) {
                if (qq < q) { float nr = lr32 * hr - li32 * hi, ni = lr32 * hi + li32 * hr; hr = nr; hi = ni; }
            }
            er = cr + hr; ei = ci + hi;
            bar_sync(7, 384);
            mbar_wait_cluster(BAR(B_RFREE), layer);
            const uint32_t ha = sb + SM_HH + par * 32768 + (prow >> 3) * 1024 + g * 16 + 4 * q;
#pragma unroll
            for (int i = 0; i < 16; i++) {
                float nr = lr1 * er - li1 * ei + acc[4 * i], ni = lr1 * ei + li1 * er + acc[4 * i + 2];
                er = lr1 * nr - li1 * ni + acc[4 * i + 1];
                ei = lr1 * ni + li1 * nr + acc[4 * i + 3];
                sts32(ha + (i >> 3) * 16384 + (i & 7) * 128, pack_bf16(nr, er));
                sts32(ha + (i >> 3) * 16384 + 8192 + (i & 7) * 128, pack_bf16(ni, ei));
                if (i == 7) { fence_async_smem(); bar_arrive(13, 288); }
            }
            fence_async_smem();
            acc_def(acc);
            float acc2[32];
            acc_def(acc2);
            TS(10 + 12 * layer);
            bar_sync(6, 416);
            TS(11 + 12 * layer);
            float (&a0)[32] = *reinterpret_cast<float (*)[32]>(&acc[0]);
            float (&a1)[32] = *reinterpret_cast<float (*)[32]>(&acc[32]);
            auto tile_mma = [&](float (&d)[32], int u) {
#pragma unroll 1
                for (int k = 0; k < 2; k++) {
                    const uint32_t hb = sb + SM_HH + (par ^ k) * 32768 + wg * 16384;
                    if (k == 1) mbar_wait(BAR(wg ? B_HPEER1 : B_HPEER), layer);
                    mbar_wait(BAR(B_AFULL + 2 * u + k), 1);
                    const uint64_t da = c_desc(2 * u + k);
                    wg_fence();
#pragma unroll
                    for (int ks = 0; ks < 4; ks++) wgmma_n64s<1>(d, da + ks * dstep, desc_b<64>(hb + ks * 2048), 1);
#pragma unroll
                    for (int ks = 0; ks < 4; ks++) wgmma_n64s<-1>(d, da + 512 + ks * dstep, desc_b<64>(hb + 8192 + ks * 2048), 1);
                }
                wg_commit();
            };
            auto tile_ship = [&](float (&d)[32], int u) {
                uint4* dst = g_P + (uint32_t)(((c * 8 + 2 * ((pi_ + 1 + u) & 3) + par) * 4 + pi_) * 1024 + wg * 512 + (tid & 127));
#pragma unroll
                for (int i = 0; i < 4; i++)
                    dst[i * 128] = make_uint4((pack_bf16(d[8 * i], d[8 * i + 1]) & 0xfffefffeu) | ptag, pack_bf16(d[8 * i + 2], d[8 * i + 3]),
                                              pack_bf16(d[8 * i + 4], d[8 * i + 5]), pack_bf16(d[8 * i + 6], d[8 * i + 7]));
            };
            tile_mma(a0, 0);
            if ((tid & 127) == 0) mbar_arrive_remote(mapa(BAR(B_HDONE), par ^ 1));
            __syncwarp();
            tile_mma(a1, 1);
            wg_wait<1>();
            tile_ship(a0, 0);
            tile_mma(acc2, 2);
            bar_arrive(12, 384);
            wg_wait<1>();
            tile_ship(a1, 1);
            wg_wait<0>();
            tile_ship(acc2, 2);
            if (lane < 6) mbar_arrive(BAR(B_AEMPTY + lane), 1);
            TS(12 + 12 * layer);
        } else {
            const int t2 = tid - 256;
            const uint8_t* ximg = g_X + (uint32_t)layer * 16 * 8 * 16384;
            mbar_wait(BAR(B_SSQ), layer);
            TS(6 + 12 * layer);
            float sqv[16];
#pragma unroll
            for (int i = 0; i < 16; i++) sqv[i] = __ldcg(g_ssqc + (layer * 16 + i) * 2048 + 128 * c + t2);
            const unsigned short xm = __ldcg((const unsigned short*)(ximg + (uint32_t)(c * 8 * 16384 + (t2 >> 3) * 128 + (t2 & 7) * 2)));
            acc_def(acc);
#pragma unroll 1
            for (int kb = 0; kb < 8; kb++) {
                if (kb == 4) {
                    wg_wait<0>();
                    if (lane == 0) { mbar_arrive(BAR(B_XEMPTY + 3), 1); mbar_arrive_remote(mapa(BAR(B_XEMPTY + 3), par ^ 1)); }
                    float tot = 0.f;
#pragma unroll
                    for (int i = 0; i < 16; i++) tot += sqv[i];
                    float rs = rsqrtf(tot * (1.f / 512.f) + 1e-5f);
                    s_rstd[t2] = rs;
                    s_rstd[128 + t2] = 2.f * rs;
                    s_mean[t2] = layer == 0 ? 0.f : __uint_as_float((uint32_t)xm << 16) * (1.f / 512.f);
                    TS(7 + 12 * layer);
                    bar_arrive(4, 384);
                    bar_sync(14, 384);
                }
                mbar_wait(BAR(B_XFULL + (kb & 3)), (kb >> 2) & 1);
                wg_fence();
#pragma unroll
                for (int ks = 0; ks < 4; ks++)
                    wgmma_n128<1>(acc, desc_a(sb + SM_X + (kb & 3) * 24576 + 16384 + ks * 256), desc_b<128>(sb + SM_X + (kb & 3) * 24576 + ks * 4096), 1);
                wg_commit();
                wg_wait<1>();
                if ((kb & 3) != 0 && lane == 0) { mbar_arrive(BAR(B_XEMPTY + ((kb - 1) & 3)), 1); mbar_arrive_remote(mapa(BAR(B_XEMPTY + ((kb - 1) & 3)), par ^ 1)); }
            }
            wg_wait<0>();
            if (lane == 0) { mbar_arrive(BAR(B_XEMPTY + 3), 1); mbar_arrive_remote(mapa(BAR(B_XEMPTY + 3), par ^ 1)); mbar_arrive_remote(mapa(BAR(B_RFREE), par ^ 1)); }
            bar_arrive(7, 384);
            bar_sync(3, 128);
            TS(9 + 12 * layer);
            const int m0 = 16 * w + g;
            const uint32_t xoff = (uint32_t)((c * 8 + own) * 16384 + w * 4096 + g * 16 + 4 * q);
            if (layer == 0) {
                const uint8_t* xs = g_X + xoff;
#pragma unroll
                for (int i = 0; i < 16; i++) {
                    float2 rs = *(const float2*)(s_rstd + 8 * i + 2 * q);
                    uint32_t x0v = __ldcg((const uint32_t*)(xs + i * 128)), x1v = __ldcg((const uint32_t*)(xs + 2048 + i * 128));
                    acc[4 * i] = acc[4 * i] * rs.x + bf_lo(x0v);
                    acc[4 * i + 1] = acc[4 * i + 1] * rs.y + bf_hi(x0v);
                    acc[4 * i + 2] = acc[4 * i + 2] * rs.x + bf_lo(x1v);
                    acc[4 * i + 3] = acc[4 * i + 3] * rs.y + bf_hi(x1v);
                }
            } else {
                float d0 = ldbf(p.dskip + 64 * own + m0), d1 = ldbf(p.dskip + 64 * own + m0 + 8);
#pragma unroll
                for (int i = 0; i < 16; i++) {
                    float2 rs = *(const float2*)(s_rstd + 8 * i + 2 * q);
                    float2 mn = *(const float2*)(s_mean + 8 * i + 2 * q);
                    acc[4 * i] = acc[4 * i] * (1.f + rs.x * d0) + mn.x;
                    acc[4 * i + 1] = acc[4 * i + 1] * (1.f + rs.y * d0) + mn.y;
                    acc[4 * i + 2] = acc[4 * i + 2] * (1.f + rs.x * d1) + mn.x;
                    acc[4 * i + 3] = acc[4 * i + 3] * (1.f + rs.y * d1) + mn.y;
                }
            }
            TS(10 + 12 * layer);
            bar_sync(6, 416);
            TS(11 + 12 * layer);
            {
                float (&a0)[32] = *reinterpret_cast<float (*)[32]>(&acc[0]);
                float (&a1)[32] = *reinterpret_cast<float (*)[32]>(&acc[32]);
#pragma unroll 1
                for (int k = 0; k < 2; k++) {
                    const uint32_t hb = sb + SM_HH + (par ^ k) * 32768;
                    if (k == 1) {
                        mbar_wait(BAR(B_HPEER), layer);
                        mbar_wait(BAR(B_HPEER1), layer);
                        bar_sync(12, 384);
                    }
                    mbar_wait(BAR(B_AFULL + 6 + k), 1);
                    const uint64_t da = c_desc(6 + k);
                    wg_fence();
#pragma unroll
                    for (int ks = 0; ks < 4; ks++) {
                        wgmma_n64s<1>(a0, da + ks * dstep, desc_b<64>(hb + ks * 2048), 1);
                        wgmma_n64s<1>(a1, da + ks * dstep, desc_b<64>(hb + 16384 + ks * 2048), 1);
                    }
#pragma unroll
                    for (int ks = 0; ks < 4; ks++) {
                        wgmma_n64s<-1>(a0, da + 512 + ks * dstep, desc_b<64>(hb + 8192 + ks * 2048), 1);
                        wgmma_n64s<-1>(a1, da + 512 + ks * dstep, desc_b<64>(hb + 16384 + 8192 + ks * 2048), 1);
                    }
                    wg_commit();
                }
                wg_wait<0>();
            }
#pragma unroll
            for (int i = 0; i < 16; i++)
                *(float4*)(sm + SM_A + 6 * 16384 + i * 2048 + t2 * 16) = make_float4(acc[4 * i], acc[4 * i + 1], acc[4 * i + 2], acc[4 * i + 3]);
            TS(12 + 12 * layer);
        }
        {
            const int t = tid & 127;
            const int nch = wg == 2 ? 2 : 3;
            const uint4* pb = g_P + (uint32_t)((c * 8 + r) * 4 * 1024 + wg * 128 + t);
            uint4 v[3][3];
            unsigned n = 0;
#pragma unroll 1
            while (true) {
                if (lane == 31) {
#pragma unroll 1
                    while (true) {
                        uint32_t bad = 0;
#pragma unroll
                        for (int sx = 0; sx < 3; sx++) {
                            uint32_t t0;
                            asm volatile("ld.relaxed.gpu.global.u32 %0, [%1];" : "=r"(t0) : "l"(pb + ((pi_ + 1 + sx) & 3) * 1024 + (nch - 1) * 384) : "memory");
                            bad |= t0 ^ ptag;
                        }
                        if (!(bad & 0x00010001u) || ++n >= SPIN_LIMIT) break;
                    }
                }
                __syncwarp();
                uint32_t bad = 0;
#pragma unroll
                for (int k = 0; k < 3; k++)
#pragma unroll
                    for (int sx = 0; sx < 3; sx++) {
                        v[k][sx] = make_uint4(ptag, 0, 0, 0);
                        if (k < nch) v[k][sx] = ld_relaxed_u4(pb + ((pi_ + 1 + sx) & 3) * 1024 + k * 384);
                        bad |= v[k][sx].x ^ ptag;
                    }
                if (!__any_sync(~0u, bad & 0x00010001u) || ++n >= SPIN_LIMIT) break;
            }
            bar_sync(8, 384);
            TS(13 + 12 * layer);
            const int m0 = 16 * w + g;
            const float w0 = (own == 0 && m0 < 2) ? (m0 == 0 ? 0.f : 0.5f) : 1.f;
#pragma unroll
            for (int k = 0; k < 3; k++) {
                if (k < nch) {
                    const int i = wg + 3 * k;
                    float4 a = *(const float4*)(sm + SM_A + 6 * 16384 + (2 * i) * 2048 + t * 16);
                    float4 bq = *(const float4*)(sm + SM_A + 6 * 16384 + (2 * i + 1) * 2048 + t * 16);
#pragma unroll
                    for (int sx = 0; sx < 3; sx++) {
                        a.x += bf_lo(v[k][sx].x); a.y += bf_hi(v[k][sx].x); a.z += bf_lo(v[k][sx].y); a.w += bf_hi(v[k][sx].y);
                        bq.x += bf_lo(v[k][sx].z); bq.y += bf_hi(v[k][sx].z); bq.z += bf_lo(v[k][sx].w); bq.w += bf_hi(v[k][sx].w);
                    }
                    if (layer == 0) {
                        uint8_t* xd = g_X + (uint32_t)((16 * 8 + c * 8 + own) * 16384 + w * 4096 + g * 16 + 4 * q + i * 256);
                        uint32_t v0 = pack_bf16(a.x, a.y), v1 = pack_bf16(a.z, a.w), v2 = pack_bf16(bq.x, bq.y), v3 = pack_bf16(bq.z, bq.w);
                        *(uint32_t*)(xd) = v0; *(uint32_t*)(xd + 2048) = v1; *(uint32_t*)(xd + 128) = v2; *(uint32_t*)(xd + 2048 + 128) = v3;
                        float sq[4];
                        sq[0] = w0 * bf_lo(v0) * bf_lo(v0) + bf_lo(v1) * bf_lo(v1);
                        sq[1] = w0 * bf_hi(v0) * bf_hi(v0) + bf_hi(v1) * bf_hi(v1);
                        sq[2] = w0 * bf_lo(v2) * bf_lo(v2) + bf_lo(v3) * bf_lo(v3);
                        sq[3] = w0 * bf_hi(v2) * bf_hi(v2) + bf_hi(v3) * bf_hi(v3);
                        float u0 = (g & 1) ? sq[2] : sq[0], u1 = (g & 1) ? sq[3] : sq[1];
                        u0 += __shfl_xor_sync(~0u, (g & 1) ? sq[0] : sq[2], 4);
                        u1 += __shfl_xor_sync(~0u, (g & 1) ? sq[1] : sq[3], 4);
                        float z = (g & 2) ? u1 : u0;
                        z += __shfl_xor_sync(~0u, (g & 2) ? u0 : u1, 8);
                        z += __shfl_xor_sync(~0u, z, 16);
                        if (g < 4) atomicAdd(s_mean + 16 * i + 8 * (g & 1) + 2 * q + (g >> 1), z);
                    } else {
                        float* o = p.out + (uint32_t)((128 * c + 32 * q + 4 * i) * 512 + 64 * own + m0);
                        o[0] = a.x; o[512] = a.y; o[8] = a.z; o[512 + 8] = a.w;
                        o[1024] = bq.x; o[1536] = bq.y; o[1024 + 8] = bq.z; o[1536 + 8] = bq.w;
                    }
                }
            }
            if (wg < 2) mbar_wait_cluster(BAR(B_HDONE), layer);
            if (layer == 0) {
                fence_async_smem();
                bar_sync(9, 384);
                TS(14 + 12 * layer);
                if (wg == 2) {
                    atomicAdd(g_ssq + 2048 + 128 * c + t, s_mean[t] * (2.f / 512.f));
                    bar_sync(3, 128);
                    if (lane == 0) { mbar_arrive(BAR(B_AEMPTY + 6), 2); mbar_arrive(BAR(B_AEMPTY + 7), 2); }
                    if (t == 0) { fence_async(); red_release(&g_bar[2], 1); }
                }
            }
        }
        TS(15 + 12 * layer);
        if (wg == 0) TC(31);
    }
}

typedef CUresult (*EncFn)(CUtensorMap*, CUtensorMapDataType, cuuint32_t, void*, const cuuint64_t*, const cuuint64_t*,
                          const cuuint32_t*, const cuuint32_t*, CUtensorMapInterleave, CUtensorMapSwizzle,
                          CUtensorMapL2promotion, CUtensorMapFloatOOBfill);

void launch_impl(void* const* d_in, void* d_out, int stop) {
    static EncFn enc = nullptr;
    if (!enc) {
        void* fn = nullptr;
        cudaDriverEntryPointQueryResult qr;
        cudaGetDriverEntryPoint("cuTensorMapEncodeTiled", &fn, cudaEnableDefault, &qr);
        enc = (EncFn)fn;
        cudaFuncSetAttribute(fused_kernel, cudaFuncAttributeMaxDynamicSharedMemorySize, SM_TOTAL);
    }
    CUtensorMap tx, tbr, tbi, tcr, tci, tcol;
    {
        void* gx = nullptr;
        cudaGetSymbolAddress(&gx, g_X);
        cuuint64_t gd[5] = {64, 16, 64, 16, 2};
        cuuint64_t gs[4] = {128, 2048, 128 * 1024, 2048 * 1024};
        cuuint32_t bx[5] = {32, 16, 1, 16, 1};
        cuuint32_t es[5] = {1, 1, 1, 1, 1};
        enc(&tcol, CU_TENSOR_MAP_DATA_TYPE_BFLOAT16, 5, gx, gd, gs, bx, es, CU_TENSOR_MAP_INTERLEAVE_NONE,
            CU_TENSOR_MAP_SWIZZLE_64B, CU_TENSOR_MAP_L2_PROMOTION_NONE, CU_TENSOR_MAP_FLOAT_OOB_FILL_NONE);
    }
    {
        cuuint64_t gd[5] = {512, 2, 4, 16, 16};
        cuuint64_t gs[4] = {1024, 32 * 1024, 2 * 1024, 128 * 1024};
        cuuint32_t bx[5] = {64, 2, 4, 8, 1};
        cuuint32_t es[5] = {1, 1, 1, 1, 1};
        enc(&tx, CU_TENSOR_MAP_DATA_TYPE_BFLOAT16, 5, d_in[0], gd, gs, bx, es, CU_TENSOR_MAP_INTERLEAVE_NONE,
            CU_TENSOR_MAP_SWIZZLE_128B, CU_TENSOR_MAP_L2_PROMOTION_L2_128B, CU_TENSOR_MAP_FLOAT_OOB_FILL_NONE);
    }
    auto mk2 = [&](CUtensorMap* m, void* ptr, cuuint32_t rows) {
        cuuint64_t gd[2] = {512, 512};
        cuuint64_t gs[1] = {1024};
        cuuint32_t bx[2] = {64, rows};
        cuuint32_t es[2] = {1, 1};
        enc(m, CU_TENSOR_MAP_DATA_TYPE_BFLOAT16, 2, ptr, gd, gs, bx, es, CU_TENSOR_MAP_INTERLEAVE_NONE,
            CU_TENSOR_MAP_SWIZZLE_128B, CU_TENSOR_MAP_L2_PROMOTION_L2_128B, CU_TENSOR_MAP_FLOAT_OOB_FILL_NONE);
    };
    mk2(&tbr, d_in[6], 32);
    mk2(&tbi, d_in[7], 32);
    mk2(&tcr, d_in[8], 64);
    mk2(&tci, d_in[9], 64);
    Params p;
    p.x0 = (const __nv_bfloat16*)d_in[0];
    p.w_r = (const __nv_bfloat16*)d_in[1];
    p.w_i = (const __nv_bfloat16*)d_in[2];
    p.lam_re = (const __nv_bfloat16*)d_in[4];
    p.lam_im = (const __nv_bfloat16*)d_in[5];
    p.log_dt = (const __nv_bfloat16*)d_in[10];
    p.dskip = (const __nv_bfloat16*)d_in[11];
    p.out = (float*)d_out;
    p.stop = stop;
    cudaLaunchConfig_t cfg = {};
    cfg.gridDim = dim3(NCTA); cfg.blockDim = dim3(NTHREADS); cfg.dynamicSmemBytes = SM_TOTAL; cfg.stream = cudaStreamPerThread;
    cudaLaunchAttribute at[1];
    at[0].id = cudaLaunchAttributeClusterDimension;
    at[0].val.clusterDim.x = 2; at[0].val.clusterDim.y = 1; at[0].val.clusterDim.z = 1;
    cfg.attrs = at; cfg.numAttrs = 1;
    cudaLaunchKernelEx(&cfg, fused_kernel, tx, tbr, tbi, tcr, tci, tcol, p);
}

}

extern "C" void kernel_launch(void* const* d_in, const int* in_sizes, int n_in, void* d_out, int out_size) {
    (void)in_sizes; (void)n_in; (void)out_size;
    launch_impl(d_in, d_out, 100);
}
```

```cpp
#include <cuda_runtime.h>
#include <cuda_bf16.h>
#include <cuda.h>
#include <stdint.h>

namespace {

constexpr int NCTA = 128;
constexpr int NTHREADS = 512;
constexpr int SM_A = 0;
constexpr int SM_X = 131072;
constexpr int SM_H = 196608;
constexpr int SM_HH = SM_X + 32768;
constexpr int SM_M = 229376;
constexpr int SM_TOTAL = 232448;
constexpr int SM_BAR = SM_M;
constexpr int SM_TGT = SM_M + 392;
constexpr int SM_LAM = SM_M + 416;
constexpr int SM_TAB = SM_M + 928;
constexpr int SM_RSTD = SM_M + 1920;
constexpr int SM_MEAN = SM_TAB;
constexpr int SM_T64 = SM_M + 2944;
constexpr int SM_B1ST = SM_H + 24576;
constexpr int SM_RAW = SM_X + 40960;
constexpr int SM_SSQ = SM_X + 57344;
constexpr int B_FULL0 = 0;
constexpr int B_EMPTY0 = 8;
constexpr int B_FULLC = 12;
constexpr int B_AFULL = 13;
constexpr int B_AEMPTY = 21;
constexpr int B_XFULL = 29;
constexpr int B_XEMPTY = 33;
constexpr int B_AFREE = 37;
constexpr int B_COL = 38;
constexpr int B_SSQ = 39;
constexpr int B_HPEER = 40;
constexpr int B_RFREE = 41;
constexpr int B_HDONE = 42;
constexpr int B_WRDY = 43;
constexpr int B_HPEER1 = 44;
constexpr int B_FULLB = 45;
constexpr int B_BFREE = 46;
constexpr int B_SETUP = 47;
constexpr int B_B1DONE = 48;
constexpr int NBARS = 49;

__device__ __align__(1024) uint8_t g_X[2 * 16 * 8 * 16384];
__device__ __align__(1024) uint8_t g_A1[8 * 8 * 16384];
__device__ __align__(1024) uint8_t g_A2[8 * 8 * 16384];
__device__ __align__(1024) uint8_t g_E[2 * 8 * 8 * 8192];
__device__ __align__(16) float g_ssq[2 * 2048];
__device__ __align__(16) float g_ssqc[2 * 16 * 2048];
__device__ __align__(16) float g_Dh[512];
__device__ __align__(16) uint4 g_Wfrag[128 * 4 * 256];
__device__ __align__(16) float4 g_Ebuf[2 * 16 * 512];
__device__ __align__(16) uint4 g_P[16 * 8 * 4 * 1024];
__device__ unsigned g_bar[8];
__device__ unsigned g_err;
#define TX(i)
#define TQ(i)
#define TS(i)
#define TC(i)

constexpr unsigned SPIN_LIMIT = 1u << 22;

__device__ __forceinline__ uint32_t s2u(const void* p) { return (uint32_t)__cvta_generic_to_shared(p); }
__device__ __forceinline__ void mbar_init(uint32_t a, uint32_t c) {
    asm volatile("mbarrier.init.shared::cta.b64 [%0], %1;" ::"r"(a), "r"(c) : "memory");
}
__device__ __forceinline__ void mbar_expect(uint32_t a, uint32_t bytes) {
    asm volatile("mbarrier.arrive.expect_tx.shared::cta.b64 _, [%0], %1;" ::"r"(a), "r"(bytes) : "memory");
}
__device__ __forceinline__ void mbar_arrive(uint32_t a, uint32_t cnt) {
    asm volatile("mbarrier.arrive.shared::cta.b64 _, [%0], %1;" ::"r"(a), "r"(cnt) : "memory");
}
__device__ __forceinline__ bool mbar_try(uint32_t a, uint32_t parity) {
    uint32_t ok;
    asm volatile("{\n.reg .pred p;\nmbarrier.try_wait.parity.shared::cta.b64 p, [%1], %2;\nselp.u32 %0, 1, 0, p;\n}"
                 : "=r"(ok) : "r"(a), "r"(parity) : "memory");
    return ok != 0;
}
__device__ __forceinline__ void mbar_wait(uint32_t a, uint32_t parity) {
    asm volatile("{\n.reg .pred p, q;\n.reg .u32 n;\nmov.u32 n, 0;\n"
                 "W_%=:\nmbarrier.try_wait.parity.shared::cta.b64 p, [%0], %1;\n@p bra D_%=;\n"
                 "add.u32 n, n, 1;\nsetp.lt.u32 q, n, 4194304;\n@q bra W_%=;\nD_%=:\n}" ::"r"(a), "r"(parity) : "memory");
}
__device__ __forceinline__ void bulk_g2s(uint32_t dst, const void* src, uint32_t bytes, uint32_t bar) {
    asm volatile("cp.async.bulk.shared::cluster.global.mbarrier::complete_tx::bytes [%0], [%1], %2, [%3];" ::"r"(dst),
                 "l"(src), "r"(bytes), "r"(bar) : "memory");
}
__device__ __forceinline__ void tma_2d(uint32_t dst, const CUtensorMap* m, int c0, int c1, uint32_t bar) {
    asm volatile("cp.async.bulk.tensor.2d.shared::cluster.global.mbarrier::complete_tx::bytes [%0], [%1, {%3,%4}], [%2];" ::"r"(dst),
                 "l"(m), "r"(bar), "r"(c0), "r"(c1) : "memory");
}
__device__ __forceinline__ void tma_5d(uint32_t dst, const CUtensorMap* m, int c0, int c1, int c2, int c3, int c4, uint32_t bar) {
    asm volatile("cp.async.bulk.tensor.5d.shared::cluster.global.mbarrier::complete_tx::bytes [%0], [%1, {%3,%4,%5,%6,%7}], [%2];" ::"r"(dst),
                 "l"(m), "r"(bar), "r"(c0), "r"(c1), "r"(c2), "r"(c3), "r"(c4) : "memory");
}
__device__ __forceinline__ void tma_2d_mc(uint32_t dst, const CUtensorMap* m, int c0, int c1, uint32_t bar) {
    asm volatile("cp.async.bulk.tensor.2d.shared::cluster.global.mbarrier::complete_tx::bytes.multicast::cluster [%0], [%1, {%3,%4}], [%2], %5;" ::"r"(dst),
                 "l"(m), "r"(bar), "r"(c0), "r"(c1), "h"((unsigned short)3) : "memory");
}
__device__ __forceinline__ void tma_5d_mc(uint32_t dst, const CUtensorMap* m, int c0, int c1, int c2, int c3, int c4, uint32_t bar) {
    asm volatile("cp.async.bulk.tensor.5d.shared::cluster.global.mbarrier::complete_tx::bytes.multicast::cluster [%0], [%1, {%3,%4,%5,%6,%7}], [%2], %8;" ::"r"(dst),
                 "l"(m), "r"(bar), "r"(c0), "r"(c1), "r"(c2), "r"(c3), "r"(c4), "h"((unsigned short)3) : "memory");
}
__device__ __forceinline__ void bulk_g2s_mc(uint32_t dst, const void* src, uint32_t bytes, uint32_t bar) {
    asm volatile("cp.async.bulk.shared::cluster.global.mbarrier::complete_tx::bytes.multicast::cluster [%0], [%1], %2, [%3], %4;" ::"r"(dst),
                 "l"(src), "r"(bytes), "r"(bar), "h"((unsigned short)3) : "memory");
}
__device__ __forceinline__ void tma_store_5d(const CUtensorMap* m, int c0, int c1, int c2, int c3, int c4, uint32_t src) {
    asm volatile("cp.async.bulk.tensor.5d.global.shared::cta.bulk_group [%0, {%2,%3,%4,%5,%6}], [%1];" ::"l"(m), "r"(src),
                 "r"(c0), "r"(c1), "r"(c2), "r"(c3), "r"(c4) : "memory");
}
__device__ __forceinline__ uint32_t lds32(uint32_t a) { uint32_t v; asm volatile("ld.shared.u32 %0, [%1];" : "=r"(v) : "r"(a) : "memory"); return v; }
__device__ __forceinline__ uint4 ld_relaxed_u4(const uint4* p) {
    uint4 v;
    asm volatile("ld.relaxed.gpu.global.v4.u32 {%0,%1,%2,%3}, [%4];" : "=r"(v.x), "=r"(v.y), "=r"(v.z), "=r"(v.w) : "l"(p) : "memory");
    return v;
}
__device__ __forceinline__ void fence_async() { asm volatile("fence.proxy.async.global;" ::: "memory"); }
__device__ __forceinline__ void red_relaxed(unsigned* p, unsigned v) {
    asm volatile("red.relaxed.gpu.global.add.u32 [%0], %1;" ::"l"(p), "r"(v) : "memory");
}
__device__ __forceinline__ uint32_t mapa(uint32_t a, uint32_t rank) {
    uint32_t d;
    asm("mapa.shared::cluster.u32 %0, %1, %2;" : "=r"(d) : "r"(a), "r"(rank));
    return d;
}
__device__ __forceinline__ void mbar_arrive_remote(uint32_t ra) {
    asm volatile("mbarrier.arrive.relaxed.cluster.shared::cluster.b64 _, [%0];" ::"r"(ra) : "memory");
}
__device__ __forceinline__ void mbar_wait_cluster(uint32_t a, uint32_t parity) {
    asm volatile("{\n.reg .pred p, q;\n.reg .u32 n;\nmov.u32 n, 0;\n"
                 "W_%=:\nmbarrier.try_wait.parity.acquire.cluster.shared::cta.b64 p, [%0], %1;\n@p bra D_%=;\n"
                 "add.u32 n, n, 1;\nsetp.lt.u32 q, n, 4194304;\n@q bra W_%=;\nD_%=:\n}" ::"r"(a), "r"(parity) : "memory");
}
__device__ __forceinline__ void bulk_s2peer(uint32_t rdst, uint32_t src, uint32_t bytes, uint32_t rbar) {
    asm volatile("cp.async.bulk.shared::cluster.shared::cta.mbarrier::complete_tx::bytes [%0], [%1], %2, [%3];" ::"r"(rdst),
                 "r"(src), "r"(bytes), "r"(rbar) : "memory");
}
__device__ __forceinline__ void fence_async_smem() { asm volatile("fence.proxy.async.shared::cta;" ::: "memory"); }
__device__ __forceinline__ void wg_fence() { asm volatile("wgmma.fence.sync.aligned;" ::: "memory"); }
__device__ __forceinline__ void wg_commit() { asm volatile("wgmma.commit_group.sync.aligned;" ::: "memory"); }
template <int N> __device__ __forceinline__ void wg_wait() { asm volatile("wgmma.wait_group.sync.aligned %0;" ::"n"(N) : "memory"); }
__device__ __forceinline__ void bar_sync(int id, int n) { asm volatile("bar.sync %0, %1;" ::"r"(id), "r"(n) : "memory"); }
__device__ __forceinline__ void bar_arrive(int id, int n) { asm volatile("bar.arrive %0, %1;" ::"r"(id), "r"(n) : "memory"); }
__device__ __forceinline__ unsigned ld_acquire(const unsigned* p) {
    unsigned v;
    asm volatile("ld.acquire.gpu.global.u32 %0, [%1];" : "=r"(v) : "l"(p) : "memory");
    return v;
}
__device__ __forceinline__ void red_release(unsigned* p, unsigned v) {
    asm volatile("red.release.gpu.global.add.u32 [%0], %1;" ::"l"(p), "r"(v) : "memory");
}
__device__ __forceinline__ void wait_count(const unsigned* p, unsigned target) {
    unsigned n = 0;
#pragma unroll 1
    while ((int)(ld_acquire(p) - target) < 0 && ++n < SPIN_LIMIT) {}
}
__device__ __forceinline__ float4 ld_relaxed_f4(const float4* p) {
    float4 v;
    asm volatile("ld.relaxed.gpu.global.v4.f32 {%0,%1,%2,%3}, [%4];" : "=f"(v.x), "=f"(v.y), "=f"(v.z), "=f"(v.w) : "l"(p) : "memory");
    return v;
}
__device__ __forceinline__ void st_relaxed_f4(float4* p, float4 v) {
    asm volatile("st.relaxed.gpu.global.v4.f32 [%0], {%1,%2,%3,%4};" ::"l"(p), "f"(v.x), "f"(v.y), "f"(v.z), "f"(v.w) : "memory");
}
__device__ __forceinline__ uint32_t pack_bf16(float lo, float hi) {
    uint32_t r;
    asm("cvt.rn.bf16x2.f32 %0, %1, %2;" : "=r"(r) : "f"(hi), "f"(lo));
    return r;
}
__device__ __forceinline__ uint32_t hmul2(uint32_t a, uint32_t b) {
    uint32_t r;
    asm("mul.rn.bf16x2 %0, %1, %2;" : "=r"(r) : "r"(a), "r"(b));
    return r;
}
__device__ __forceinline__ uint32_t hfma2(uint32_t a, uint32_t b, uint32_t c) {
    uint32_t r;
    asm("fma.rn.bf16x2 %0, %1, %2, %3;" : "=r"(r) : "r"(a), "r"(b), "r"(c));
    return r;
}
__device__ __forceinline__ float bf_lo(uint32_t v) { return __uint_as_float(v << 16); }
__device__ __forceinline__ float bf_hi(uint32_t v) { return __uint_as_float(v & 0xffff0000u); }
__device__ __forceinline__ void sts32(uint32_t a, uint32_t v) { asm volatile("st.shared.u32 [%0], %1;" ::"r"(a), "r"(v) : "memory"); }
__device__ __forceinline__ void sts128(uint32_t a, uint4 v) {
    asm volatile("st.shared.v4.u32 [%0], {%1,%2,%3,%4};" ::"r"(a), "r"(v.x), "r"(v.y), "r"(v.z), "r"(v.w) : "memory");
}

__device__ __forceinline__ uint64_t desc_ni(uint32_t addr, uint32_t lbo, uint32_t sbo) {
    return (uint64_t)((addr & 0x3FFFF) >> 4) | ((uint64_t)(lbo >> 4) << 16) | ((uint64_t)(sbo >> 4) << 32);
}
__device__ __forceinline__ uint64_t desc_a(uint32_t addr) { return desc_ni(addr, 128, 1024); }
template <int N> __device__ __forceinline__ uint64_t desc_b(uint32_t addr) { return desc_ni(addr, 16 * N, 128); }
__device__ __forceinline__ uint64_t desc_k(uint32_t addr) {
    return (uint64_t)((addr & 0x3FFFF) >> 4) | (1ull << 16) | (64ull << 32) | (1ull << 62);
}
__device__ __forceinline__ uint64_t desc_mn(uint32_t addr, uint32_t lbo) {
    return (uint64_t)((addr & 0x3FFFF) >> 4) | ((uint64_t)(lbo >> 4) << 16) | (64ull << 32) | (1ull << 62);
}

#define ACC8(d, o) "+f"(d[o + 0]), "+f"(d[o + 1]), "+f"(d[o + 2]), "+f"(d[o + 3]), "+f"(d[o + 4]), "+f"(d[o + 5]), "+f"(d[o + 6]), "+f"(d[o + 7])
template <int TB, int SA = 1>
__device__ __forceinline__ void wgmma_n128(float (&d)[64], uint64_t da, uint64_t db, int sd) {
    asm volatile(
        "{\n.reg .pred p;\nsetp.ne.b32 p, %66, 0;\n"
        "wgmma.mma_async.sync.aligned.m64n128k16.f32.bf16.bf16 "
        "{%0,%1,%2,%3,%4,%5,%6,%7,%8,%9,%10,%11,%12,%13,%14,%15,%16,%17,%18,%19,%20,%21,%22,%23,%24,%25,%26,%27,%28,%29,%30,%31,"
        "%32,%33,%34,%35,%36,%37,%38,%39,%40,%41,%42,%43,%44,%45,%46,%47,%48,%49,%50,%51,%52,%53,%54,%55,%56,%57,%58,%59,%60,%61,%62,%63},"
        " %64, %65, p, %68, 1, 0, %67;\n}"
        : ACC8(d, 0), ACC8(d, 8), ACC8(d, 16), ACC8(d, 24), ACC8(d, 32), ACC8(d, 40), ACC8(d, 48), ACC8(d, 56)
        : "l"(da), "l"(db), "r"(sd), "n"(TB), "n"(SA));
}
template <int N> __device__ __forceinline__ void acc_def(float (&d)[N]) {
#pragma unroll
    for (int i = 0; i < N; i++) d[i] = 0.f;
}
template <int TB>
__device__ __forceinline__ void wgmma_n64(float (&d)[32], uint64_t da, uint64_t db, int sd) {
    asm volatile(
        "{\n.reg .pred p;\nsetp.ne.b32 p, %34, 0;\n"
        "wgmma.mma_async.sync.aligned.m64n64k16.f32.bf16.bf16 "
        "{%0,%1,%2,%3,%4,%5,%6,%7,%8,%9,%10,%11,%12,%13,%14,%15,%16,%17,%18,%19,%20,%21,%22,%23,%24,%25,%26,%27,%28,%29,%30,%31},"
        " %32, %33, p, 1, 1, 0, %35;\n}"
        : ACC8(d, 0), ACC8(d, 8), ACC8(d, 16), ACC8(d, 24)
        : "l"(da), "l"(db), "r"(sd), "n"(TB));
}
template <int SA>
__device__ __forceinline__ void wgmma_n64s(float (&d)[32], uint64_t da, uint64_t db, int sd) {
    asm volatile(
        "{\n.reg .pred p;\nsetp.ne.b32 p, %34, 0;\n"
        "wgmma.mma_async.sync.aligned.m64n64k16.f32.bf16.bf16 "
        "{%0,%1,%2,%3,%4,%5,%6,%7,%8,%9,%10,%11,%12,%13,%14,%15,%16,%17,%18,%19,%20,%21,%22,%23,%24,%25,%26,%27,%28,%29,%30,%31},"
        " %32, %33, p, %35, 1, 0, 1;\n}"
        : ACC8(d, 0), ACC8(d, 8), ACC8(d, 16), ACC8(d, 24)
        : "l"(da), "l"(db), "r"(sd), "n"(SA));
}
__device__ __forceinline__ void wgmma_n64_rs(float (&d)[32], uint32_t a0, uint32_t a1, uint32_t a2, uint32_t a3, uint64_t db, int sd) {
    asm volatile(
        "{\n.reg .pred p;\nsetp.ne.b32 p, %37, 0;\n"
        "wgmma.mma_async.sync.aligned.m64n64k16.f32.bf16.bf16 "
        "{%0,%1,%2,%3,%4,%5,%6,%7,%8,%9,%10,%11,%12,%13,%14,%15,%16,%17,%18,%19,%20,%21,%22,%23,%24,%25,%26,%27,%28,%29,%30,%31},"
        " {%32,%33,%34,%35}, %36, p, 1, 1, 1;\n}"
        : ACC8(d, 0), ACC8(d, 8), ACC8(d, 16), ACC8(d, 24)
        : "r"(a0), "r"(a1), "r"(a2), "r"(a3), "l"(db), "r"(sd));
}

struct Params {
    const __nv_bfloat16* x0;
    const __nv_bfloat16* w_r;
    const __nv_bfloat16* w_i;
    const __nv_bfloat16* lam_re;
    const __nv_bfloat16* lam_im;
    const __nv_bfloat16* log_dt;
    const __nv_bfloat16* dskip;
    float* out;
    int stop;
};

__device__ __forceinline__ float ldbf(const __nv_bfloat16* p) { return __bfloat162float(*p); }

__device__ __forceinline__ void dft_fp(int j, int& f, int& ph) {
    int cs = j >> 1;
    if (j == 1) { f = 256; ph = 0; }
    else { f = cs; ph = (j & 1) ? 128 : 0; }
}

__device__ __forceinline__ void gen_col_consts(uint32_t sb, int tid) {
#pragma unroll 1
    for (int task = tid; task < 640; task += 256) {
        int f, c8;
        uint32_t a_cc, d_pi, d_po;
        if (task < 512) {
            f = task & 63; c8 = task >> 6;
            a_cc = sb + SM_X + (f >> 5) * 16384 + ((f >> 3) & 3) * 2048 + c8 * 128 + (f & 7) * 16;
            d_pi = 8192; d_po = 1024;
        } else {
            int n2 = task & 31;
            f = 2 * n2; c8 = (task >> 5) & 3;
            a_cc = sb + SM_X + 32768 + (n2 >> 3) * 1024 + c8 * 128 + (n2 & 7) * 16;
            d_pi = 4096; d_po = 512;
        }
        float cd, sd, cs, sn;
        __sincosf((float)(f >= 32 ? f - 64 : f) * (6.283185307179586f / 64.f), &sd, &cd);
        int a = (8 * c8 * f) & 63;
        __sincosf((float)(a >= 32 ? a - 64 : a) * (6.283185307179586f / 64.f), &sn, &cs);
        float cv[8], sv[8];
#pragma unroll
        for (int e = 0; e < 8; e++) {
            cv[e] = cs; sv[e] = sn;
            float t = cs * cd - sn * sd;
            sn = sn * cd + cs * sd;
            cs = t;
        }
        uint4 oc = make_uint4(pack_bf16(cv[0], cv[1]), pack_bf16(cv[2], cv[3]), pack_bf16(cv[4], cv[5]), pack_bf16(cv[6], cv[7]));
        uint4 os = make_uint4(pack_bf16(sv[0], sv[1]), pack_bf16(sv[2], sv[3]), pack_bf16(sv[4], sv[5]), pack_bf16(sv[6], sv[7]));
        sts128(a_cc, oc);
        sts128(a_cc + d_pi, os);
        sts128(a_cc + d_po, make_uint4(os.x ^ 0x80008000u, os.y ^ 0x80008000u, os.z ^ 0x80008000u, os.w ^ 0x80008000u));
        sts128(a_cc + d_pi + d_po, oc);
    }
}

__global__ void __launch_bounds__(NTHREADS, 1)
fused_kernel(const __grid_constant__ CUtensorMap tm_x, const __grid_constant__ CUtensorMap tm_bre,
             const __grid_constant__ CUtensorMap tm_bim, const __grid_constant__ CUtensorMap tm_cre,
             const __grid_constant__ CUtensorMap tm_cim, const __grid_constant__ CUtensorMap tm_col, const Params p) {
    extern __shared__ __align__(1024) uint8_t sm[];
    const uint32_t sb = s2u(sm);
    const int tid = threadIdx.x, b = blockIdx.x;
    const int c = b >> 3, r = b & 7;
    const int par = r & 1, pi_ = r >> 1, own = 4 * par + pi_;
    const int wg = __shfl_sync(~0u, tid >> 7, 0), w = __shfl_sync(~0u, (tid >> 5) & 3, 0), lane = tid & 31, g = lane >> 2, q = lane & 3;
    auto BAR = [&](int i) { return sb + SM_BAR + 8 * i; };
    unsigned* s_tgt = (unsigned*)(sm + SM_TGT);

    if (tid < NBARS) {
        int cnt = 1;
        if (tid >= B_EMPTY0 && tid < B_EMPTY0 + 4) cnt = 16;
        if (tid >= B_XEMPTY && tid < B_XEMPTY + 4) cnt = 24;
        if (tid == B_RFREE) cnt = 12;
        if (tid == B_HDONE) cnt = 2;
        if (tid == B_SETUP) cnt = 3;
        if ((tid >= B_AEMPTY && tid < B_AEMPTY + 8) || tid == B_BFREE) cnt = 8;
        if (tid == B_AFREE) cnt = 4;
        mbar_init(BAR(tid), cnt);
        asm volatile("fence.mbarrier_init.release.cluster;" ::: "memory");
    }
    asm volatile("barrier.cluster.arrive.release.aligned;" ::: "memory");

    if (wg == 3) {
        asm volatile("setmaxnreg.dec.sync.aligned.u32 56;");
        if (w == 0 && lane < 6) {
            const CUtensorMap* tm = lane == 0 ? &tm_x : lane == 1 ? &tm_bre : lane == 2 ? &tm_bim : lane == 3 ? &tm_cre : lane == 4 ? &tm_cim : &tm_col;
            asm volatile("prefetch.tensormap [%0];" ::"l"(tm) : "memory");
        }
        __syncwarp();
        asm volatile("barrier.cluster.wait.acquire.aligned;" ::: "memory");
        if (w > 0) {
            {
                int i = tid - 416;
                int ps = i < 64 ? 64 * r + i : 32 * c + i - 64;
                float lr = ldbf(p.lam_re + ps), li = ldbf(p.lam_im + ps);
                float dt = __bfloat162float(__float2bfloat16(expf(ldbf(p.log_dt + ps))));
                if (i < 6) s_tgt[i] = ((ld_acquire(&g_bar[i]) >> 7) + 1u) << 7;
                float mag = expf(lr * dt), t = li * dt * 0.15915494309189535f, sn, cs;
                t -= rintf(t);
                sincospif(2.f * t, &sn, &cs);
                float er = mag * cs, ei = mag * sn;
                if (i < 64) {
                    *(float2*)(sm + SM_LAM + i * 8) = make_float2(er, ei);
                } else {
                    er -= 1.f;
                    float inv = 1.f / (lr * lr + li * li);
                    *(float2*)(sm + SM_TAB + (i - 64) * 8) = make_float2((er * lr + ei * li) * inv, (ei * lr - er * li) * inv);
                }
            }
            __syncwarp();
            bar_arrive(15, 224);
            if (lane == 0) mbar_arrive(BAR(B_SETUP), 1);
            if (w == 2) {
                const int kq = 2 * b + (lane >> 4), row = (kq >> 2) + 128 * (kq & 3) + 512 * ((lane >> 1) & 3) + 64 * (lane & 1);
                const char* src = (const char*)(((lane >> 3) & 1) ? p.w_i : p.w_r) + (size_t)row * 514;
                size_t a0 = (size_t)src & ~(size_t)15;
                int bytes = row == 2047 ? 512 : 544;
                asm volatile("cp.async.bulk.prefetch.L2.global [%0], %1;" ::"l"(a0), "r"(bytes) : "memory");
            }
#pragma unroll 1
            for (int i = tid - 448; i < 1536 + 128 && w > 1; i += 64) {
                if (i < 1536) g_P[(uint32_t)(b * 4 + i / 384) * 1024 + 640 + i % 384] = make_uint4(0, 0, 0, 0);
                else g_Ebuf[b * 128 + i - 1536] = make_float4(0.f, 0.f, 0.f, 0.f);
            }
#pragma unroll 1
            for (int task = tid - 448; task < 256 && w > 1; task += 64) {
                const int cb = task & 127, kq = 2 * b + (task >> 7), k1 = kq >> 2, qq = kq & 3;
                const unsigned short* wr_ = (const unsigned short*)p.w_r + (k1 + 128 * qq) * 257;
                const unsigned short* wi_ = (const unsigned short*)p.w_i + (k1 + 128 * qq) * 257;
                const int c0 = cb == 0 ? 256 : 2 * cb, c1 = 2 * cb + 1;
                uint32_t wf[16];
#pragma unroll
                for (int i = 0; i < 4; i++) {
                    int o = 512 * i * 257;
                    wf[2 * i] = (uint32_t)__ldg(wr_ + o + c0) | ((uint32_t)__ldg(wr_ + o + 64 * 257 + c0) << 16);
                    wf[2 * i + 1] = ((uint32_t)__ldg(wi_ + o + c0) | ((uint32_t)__ldg(wi_ + o + 64 * 257 + c0) << 16)) ^ 0x80008000u;
                    wf[8 + 2 * i] = (uint32_t)__ldg(wr_ + o + c1) | ((uint32_t)__ldg(wr_ + o + 64 * 257 + c1) << 16);
                    wf[8 + 2 * i + 1] = ((uint32_t)__ldg(wi_ + o + c1) | ((uint32_t)__ldg(wi_ + o + 64 * 257 + c1) << 16)) ^ 0x80008000u;
                }
                uint4* wd = g_Wfrag + (uint32_t)(cb * 1024 + kq);
#pragma unroll
                for (int i = 0; i < 4; i++) wd[i * 256] = make_uint4(wf[4 * i], wf[4 * i + 1], wf[4 * i + 2], wf[4 * i + 3]);
            }
            __syncwarp();
            if (w == 2) bar_arrive(11, 64);
            if (w == 3) {
                bar_sync(11, 64);
                if (lane == 0) red_release(&g_bar[4], 1);
#pragma unroll 1
                for (int it = 0; it < 8; it++) {
                    const int m = 4 * c + (it >> 1), d = 64 * r + m, ch = lane + 32 * (it & 1);
                    float v[8];
#pragma unroll
                    for (int e = 0; e < 8; e++) {
                        int j = 8 * ch + e, f, ph;
                        dft_fp(j, f, ph);
                        int a = (d * f + ph) & 511;
                        a = a >= 256 ? a - 512 : a;
                        float wj = j == 0 ? 0.f : (j == 1 ? 1.f / 512.f : 2.f / 512.f);
                        v[e] = wj * __cosf((float)a * (6.283185307179586f / 512.f));
                    }
                    uint32_t off = (uint32_t)(64 + r * 8 + (ch >> 3)) * 8192 + (m >> 3) * 1024 + (ch & 7) * 128 + (m & 7) * 16;
                    *(uint4*)(g_E + off) = make_uint4(pack_bf16(v[0], v[1]), pack_bf16(v[2], v[3]), pack_bf16(v[4], v[5]), pack_bf16(v[6], v[7]));
                }
                __syncwarp();
                if (lane == 0) { fence_async(); red_release(&g_bar[6], 1); }
                return;
            }
            if (w == 2) {
#pragma unroll 1
                for (int it = 0; it < 4; it++) {
                    const int hf = it & 1;
                    __syncwarp();
                    if (hf == 0) bar_sync(13, 288); else bar_sync(6, 416);
                    if (lane == 0) {
                        const uint32_t src = sb + SM_HH + par * 32768 + hf * 16384;
                        bulk_s2peer(mapa(src, par ^ 1), src, 16384, mapa(BAR(hf ? B_HPEER1 : B_HPEER), par ^ 1));
                    }
                }
                return;
            }
            {
                uint4 p0 = __ldg((const uint4*)p.dskip + 2 * lane), p1 = __ldg((const uint4*)p.dskip + 2 * lane + 1);
                uint32_t u[8] = {p0.x, p0.y, p0.z, p0.w, p1.x, p1.y, p1.z, p1.w};
#pragma unroll 1
                for (int jj = 0; jj < 4; jj++) {
                    int j = 64 * r + 4 * c + jj, f, ph;
                    dft_fp(j, f, ph);
                    float s = 0.f;
                    int idx = 16 * lane * f + ph;
#pragma unroll
                    for (int i = 0; i < 16; i++) {
                        int a = idx & 511;
                        idx += f;
                        a = a >= 256 ? a - 512 : a;
                        s += ((i & 1) ? bf_hi(u[i >> 1]) : bf_lo(u[i >> 1])) * __cosf((float)a * (6.283185307179586f / 512.f));
                    }
#pragma unroll
                    for (int o = 16; o; o >>= 1) s += __shfl_xor_sync(~0u, s, o);
                    if (lane == 0) g_Dh[j] = s;
                }
                if (lane == 0) red_release(&g_bar[5], 1);
                __syncwarp();
            }
            bar_sync(2, 288);
            if (lane == 0) {
                TX(5);
                fence_async();
                red_release(&g_bar[0], 1);
                TX(6);
            }
            __syncwarp();
            bar_sync(12, 160);
            if (lane == 0) {
                asm volatile("cp.async.bulk.global.shared::cta.bulk_group [%0], [%1], 8192;" ::"l"(g_A1 + (uint32_t)(((c >> 1) * 8 + r) * 16384 + (c & 1) * 8192)),
                             "r"(sb + SM_B1ST) : "memory");
                asm volatile("cp.async.bulk.commit_group;" ::: "memory");
                asm volatile("cp.async.bulk.wait_group 0;" ::: "memory");
                mbar_arrive(BAR(B_B1DONE), 1);
                fence_async();
                red_release(&g_bar[7], 1);
            }
#pragma unroll 1
            for (int layer = 0; layer < 2; layer++) {
                __syncwarp();
                bar_sync(5, 416);
                if (lane == 0) {
                    TX(0 + 8 * layer);
                    tma_store_5d(&tm_col, 32 * (b & 1), 0, b >> 1, 0, layer, sb + SM_RAW);
                    asm volatile("cp.reduce.async.bulk.global.shared::cta.bulk_group.add.f32 [%0], [%1], 8192;" ::"l"(g_ssqc + (layer * 16 + (b & 15)) * 2048),
                                 "r"(sb + SM_SSQ) : "memory");
                    asm volatile("cp.async.bulk.commit_group;" ::: "memory");
                    asm volatile("cp.async.bulk.wait_group 0;" ::: "memory");
                    TX(1 + 8 * layer);
                    fence_async();
                    red_release(&g_bar[1 + 2 * layer], 1);
                    TX(2 + 8 * layer);
                }
            }
        } else if (tid == 384) {
#pragma unroll 1
            for (int kb = 0; kb < 8; kb++) {
                uint32_t fb = BAR(B_FULL0 + kb);
                mbar_expect(fb, 16384);
                tma_5d_mc(sb + SM_A + 65536 + kb * 16384 + par * 8192, &tm_x, kb * 64, 0, 0, 8 * par, c, fb);
            }
#pragma unroll 1
            for (int k2 = 0; k2 < 8; k2++) {
                asm volatile("cp.async.bulk.prefetch.tensor.2d.L2.global [%0, {%1,%2}];" ::"l"(par ? &tm_bim : &tm_bre), "r"(k2 * 64), "r"(32 * c) : "memory");
                if ((k2 & 1) == par)
                    asm volatile("cp.async.bulk.prefetch.tensor.2d.L2.global [%0, {%1,%2}];" ::"l"((c & 1) ? &tm_cim : &tm_cre), "r"(64 * (c >> 1)), "r"(k2 * 64) : "memory");
            }
            mbar_wait(BAR(B_SETUP), 0);
#pragma unroll 1
            for (int layer = 0; layer < 2; layer++) {
                wait_count(&g_bar[2 * layer], s_tgt[2 * layer]);
                TX(4 + 8 * layer);
                fence_async();
                mbar_expect(BAR(B_COL), 16384 + 8192);
                tma_5d(sb + SM_RAW, &tm_col, 32 * (b & 1), 0, b >> 1, 0, layer, BAR(B_COL));
                bulk_g2s(sb + SM_SSQ, g_ssq + layer * 2048, 8192, BAR(B_COL));
                if (layer == 0) {
                    wait_count(&g_bar[4], s_tgt[4]);
                    mbar_arrive(BAR(B_WRDY), 1);
                    wait_count(&g_bar[7], s_tgt[5]);
                    fence_async();
                }
                if (layer == 0) mbar_wait(BAR(B_AFREE), 0);
                mbar_wait(BAR(B_COL), layer);
#pragma unroll 1
                for (int s = 0; s < 8; s++) {
                    if (layer == 1) mbar_wait(BAR(B_AEMPTY + s), 1);
                    if (s >= 2) mbar_wait(BAR(B_AFULL + s - 2), 0);
                    mbar_expect(BAR(B_AFULL + s), 16384);
                    bulk_g2s(sb + SM_A + s * 16384, g_A1 + (uint32_t)(r * 8 + s) * 16384, 16384, BAR(B_AFULL + s));
                }
                if (layer == 1) wait_count(&g_bar[6], s_tgt[5]);
                wait_count(&g_bar[1 + 2 * layer], s_tgt[1 + 2 * layer]);
                TX(3 + 8 * layer);
                fence_async();
                const uint8_t* xsrc = g_X + (uint32_t)(layer * 16 + c) * 8 * 16384;
                const uint8_t* esrc = g_E + (uint32_t)(layer * 8 + own) * 8 * 8192;
                mbar_arrive(BAR(B_SSQ), 1);
                mbar_expect(BAR(B_HPEER), 16384);
                mbar_expect(BAR(B_HPEER1), 16384);
#pragma unroll 1
                for (int it = 0; it < 16; it++) {
                    if (it < 8) {
                        int st = it & 3, f = layer * 2 + (it >> 2);
                        if (f > 0) mbar_wait_cluster(BAR(B_XEMPTY + st), (f - 1) & 1);
                        mbar_expect(BAR(B_XFULL + st), 24576);
                        bulk_g2s_mc(sb + SM_X + st * 24576 + par * 8192, xsrc + (uint32_t)it * 16384 + par * 8192, 8192, BAR(B_XFULL + st));
                        bulk_g2s(sb + SM_X + st * 24576 + 16384, esrc + (uint32_t)it * 8192, 8192, BAR(B_XFULL + st));
                    }
                    if (it >= 8) {
                        if (it == 8) mbar_wait(BAR(B_AEMPTY + 5), 0);
                        int s = it - 8, tile = 4 * par + ((pi_ + 1 + (s >> 1)) & 3), sl = r ^ (s & 1);
                        mbar_wait(BAR(B_AEMPTY + s), 0);
                        uint32_t fb = BAR(B_AFULL + s), dst = sb + SM_A + s * 16384;
                        mbar_expect(fb, 16384);
                        if (layer == 1) {
                            tma_2d(dst, &tm_cre, 64 * sl, 64 * tile, fb);
                            tma_2d(dst + 8192, &tm_cim, 64 * sl, 64 * tile, fb);
                        } else {
                            bulk_g2s(dst, g_A2 + (uint32_t)(sl * 8 + tile) * 16384, 16384, fb);
                        }
                    }
                }
            }
        }
        return;
    }

    asm volatile("setmaxnreg.inc.sync.aligned.u32 152;");
    if (tid >= 96 && tid < 112) g_ssq[2048 + 16 * b + tid - 96] = 0.f;
    if (tid >= 128 && tid < 256) ((float4*)g_ssqc)[b * 128 + tid - 128] = make_float4(0.f, 0.f, 0.f, 0.f);
    TS(0);
    if (wg == 0) TC(30);
    {
        const int f = 32 * r + lane;
        float cd, sd;
        __sincosf((float)f * (6.283185307179586f / 512.f), &sd, &cd);
        const uint32_t dst = sb + SM_A + (lane >> 2) * 1024 + (lane & 3) * 32;
#pragma unroll 1
        for (int ch = tid >> 5; ch < 64; ch += 12) {
            int a = (8 * ch * f) & 511;
            a = a >= 256 ? a - 512 : a;
            float cs, sn;
            __sincosf((float)a * (6.283185307179586f / 512.f), &sn, &cs);
            float cv[8], sv[8];
#pragma unroll
            for (int e = 0; e < 8; e++) {
                cv[e] = cs; sv[e] = -sn;
                float t = cs * cd - sn * sd;
                sn = sn * cd + cs * sd;
                cs = t;
            }
            uint4 o1 = make_uint4(pack_bf16(sv[0], sv[1]), pack_bf16(sv[2], sv[3]), pack_bf16(sv[4], sv[5]), pack_bf16(sv[6], sv[7]));
            if (f == 0) o1 = make_uint4(0xbf803f80u, 0xbf803f80u, 0xbf803f80u, 0xbf803f80u);
            uint32_t a0 = dst + (ch >> 3) * 8192 + (ch & 7) * 128;
            sts128(a0, make_uint4(pack_bf16(cv[0], cv[1]), pack_bf16(cv[2], cv[3]), pack_bf16(cv[4], cv[5]), pack_bf16(cv[6], cv[7])));
            sts128(a0 + 16, o1);
        }
    }
    fence_async_smem();
    asm volatile("barrier.cluster.wait.acquire.aligned;" ::: "memory");
    bar_sync(10, 384);
    TS(1);
    if (wg < 2) {
        float acc[32];
        acc_def(acc);
        const int npos = 16 * r + 8 * wg + 2 * w;
        float sh0 = 0.f, sh1 = 0.f, s0 = 0.f, s1 = 0.f, q0 = 0.f, q1 = 0.f;
#pragma unroll 1
        for (int kb = 0; kb < 8; kb++) {
            uint32_t slot = sb + SM_A + 65536 + kb * 16384;
            mbar_wait(BAR(B_FULL0 + kb), 0);
            wg_fence();
#pragma unroll
            for (int ks = 0; ks < 4; ks++)
                wgmma_n64<0>(acc, desc_a(sb + SM_A + kb * 8192 + ks * 256), desc_k(slot + wg * 8192 + ks * 32), 1);
            wg_commit();
            {
                uint32_t v0 = lds32(slot + npos * 128 + lane * 4), v1 = lds32(slot + npos * 128 + 128 + lane * 4);
                if (kb == 0) { sh0 = __shfl_sync(~0u, bf_lo(v0), 0); sh1 = __shfl_sync(~0u, bf_lo(v1), 0); }
                float a = bf_lo(v0) - sh0, bq = bf_hi(v0) - sh0, cq = bf_lo(v1) - sh1, d = bf_hi(v1) - sh1;
                s0 += a + bq; q0 += a * a + bq * bq; s1 += cq + d; q1 += cq * cq + d * d;
            }
            wg_wait<1>();
            if (kb > 0 && kb <= 4 && lane == 0) { mbar_arrive(BAR(B_EMPTY0 + kb - 1), 1); mbar_arrive_remote(mapa(BAR(B_EMPTY0 + kb - 1), par ^ 1)); }
        }
#pragma unroll
        for (int o = 16; o; o >>= 1) {
            s0 += __shfl_xor_sync(~0u, s0, o); q0 += __shfl_xor_sync(~0u, q0, o);
            s1 += __shfl_xor_sync(~0u, s1, o); q1 += __shfl_xor_sync(~0u, q1, o);
        }
        if (lane == 0) *(float2*)(g_ssq + 128 * c + npos) = make_float2(fmaxf(q0 - s0 * s0 * (1.f / 512.f), 0.f), fmaxf(q1 - s1 * s1 * (1.f / 512.f), 0.f));
        wg_wait<0>();
        TS(2);
        uint8_t* dst = g_X + (uint32_t)((c * 8 + r) * 16384 + w * 4096 + wg * 1024 + g * 16 + 4 * q);
#pragma unroll
        for (int i = 0; i < 8; i++) {
            *(uint32_t*)(dst + i * 128) = pack_bf16(acc[4 * i], acc[4 * i + 1]);
            *(uint32_t*)(dst + 2048 + i * 128) = pack_bf16(acc[4 * i + 2], acc[4 * i + 3]);
        }
        bar_sync(2, 288);
        mbar_wait(BAR(B_SETUP), 0);
        TS(3);
    }

    if (wg == 2) {
        bar_sync(15, 224);
        float acc[32];
        acc_def(acc);
        if (tid == 256) {
#pragma unroll 1
            for (int s = 0; s < 4; s++) mbar_wait_cluster(BAR(B_EMPTY0 + s), 0);
            mbar_expect(BAR(B_FULLB), 65536);
#pragma unroll 1
            for (int k2 = 0; k2 < 8; k2++)
                tma_2d_mc(sb + SM_A + 65536 + k2 * 8192 + par * 4096, par ? &tm_bim : &tm_bre, k2 * 64, 32 * c, BAR(B_FULLB));
        }
        __syncwarp();
        mbar_wait(BAR(B_FULLB), 0);
        wg_fence();
#pragma unroll 1
        for (int kb = 0; kb < 8; kb++) {
#pragma unroll
            for (int ks = 0; ks < 4; ks++)
                wgmma_n64<0>(acc, desc_a(sb + SM_A + kb * 8192 + ks * 256), desc_k(sb + SM_A + 65536 + kb * 8192 + ks * 32), 1);
            wg_commit();
        }
        wg_wait<0>();
        if (lane == 0) { mbar_arrive(BAR(B_BFREE), 1); mbar_arrive_remote(mapa(BAR(B_BFREE), par ^ 1)); }
        if (tid == 256) {
            mbar_wait_cluster(BAR(B_BFREE), 0);
            mbar_expect(BAR(B_FULLC), 65536);
#pragma unroll 1
            for (int k2 = par; k2 < 8; k2 += 2)
                tma_2d_mc(sb + SM_A + 65536 + k2 * 8192, (c & 1) ? &tm_cim : &tm_cre, 64 * (c >> 1), k2 * 64, BAR(B_FULLC));
        }
        __syncwarp();
        {
            uint8_t* dst = sm + SM_B1ST + w * 256 + q * 32 + g * 2;
            const float wj0 = (r == 0 && w == 0 && g < 2) ? (g == 0 ? 0.f : 1.f / 512.f) : 2.f / 512.f;
#pragma unroll
            for (int i = 0; i < 4; i++) {
#pragma unroll
                for (int e = 0; e < 2; e++) {
                    float2 cf = *(const float2*)(sm + SM_TAB + (8 * i + 2 * q + e) * 8);
#pragma unroll
                    for (int h = 0; h < 2; h++) {
                        float wj = h == 0 ? wj0 : 2.f / 512.f;
                        float pr = acc[4 * i + 2 * h + e] * wj, pi = acc[16 + 4 * i + 2 * h + e] * wj;
                        uint8_t* d2 = dst + i * 2048 + h * 128 + e * 16;
                        *(__nv_bfloat16*)(d2) = __float2bfloat16(cf.x * pr - cf.y * pi);
                        *(__nv_bfloat16*)(d2 + 1024) = __float2bfloat16(cf.x * pi + cf.y * pr);
                    }
                }
            }
            fence_async_smem();
            bar_arrive(12, 160);
        }
        acc_def(acc);
        mbar_wait(BAR(B_FULLC), 0);
        wg_fence();
#pragma unroll 1
        for (int kb = 0; kb < 8; kb++) {
#pragma unroll
            for (int ks = 0; ks < 4; ks++)
                wgmma_n64<1>(acc, desc_a(sb + SM_A + kb * 8192 + ks * 256), desc_mn(sb + SM_A + 65536 + kb * 8192 + ks * 2048, 8192), 1);
            wg_commit();
        }
        wg_wait<0>();
        fence_async_smem();
        if (lane == 0) mbar_arrive(BAR(B_AFREE), 1);
        uint8_t* dst = g_A2 + (uint32_t)(((c >> 1) * 8 + r) * 16384 + (c & 1) * 8192 + w * 2048 + g * 16 + 4 * q);
#pragma unroll
        for (int i = 0; i < 8; i++) {
            *(uint32_t*)(dst + i * 128) = pack_bf16(acc[4 * i], acc[4 * i + 1]);
            *(uint32_t*)(dst + 1024 + i * 128) = pack_bf16(acc[4 * i + 2], acc[4 * i + 3]);
        }
        {
            const int m = 4 * c + w, jp = 64 * r + m;
            int fp, php;
            dft_fp(jp, fp, php);
            const __nv_bfloat16* dh = (const __nv_bfloat16*)(sm + SM_RSTD);
            if (tid == 256) wait_count(&g_bar[5], s_tgt[5]);
            bar_sync(3, 128);
            float4 d4 = __ldcg((const float4*)g_Dh + (tid - 256));
            *(uint2*)(sm + SM_RSTD + (tid - 256) * 8) = make_uint2(pack_bf16(d4.x, d4.y), pack_bf16(d4.z, d4.w));
            bar_sync(3, 128);
#pragma unroll 1
            for (int it = 0; it < 2; it++) {
                const int ch = lane + 32 * it;
                float v[8];
#pragma unroll
                for (int e = 0; e < 8; e++) {
                    int j = 8 * ch + e, f, ph;
                    dft_fp(j, f, ph);
                    float wj = j == 0 ? 0.f : (j == 1 ? 1.f / 512.f : 2.f / 512.f);
                    float gsum = 0.f;
#pragma unroll
                    for (int sgn = 0; sgn < 2; sgn++) {
                        int mm = (sgn ? f - fp : f + fp) & 511, pp = (sgn ? ph - php : ph + php) & 511;
                        if (mm > 256) { mm = 512 - mm; pp = (512 - pp) & 511; }
                        int odd = (pp >> 7) & 1;
                        float t = __bfloat162float(dh[mm == 256 ? 1 : 2 * mm + odd]);
                        if (odd && (mm & 255) == 0) t = 0.f;
                        gsum += (pp & 256) ? -t : t;
                    }
                    v[e] = 0.5f * wj * gsum;
                }
                uint32_t off = (uint32_t)(r * 8 + (ch >> 3)) * 8192 + (m >> 3) * 1024 + (ch & 7) * 128 + (m & 7) * 16;
                *(uint4*)(g_E + off) = make_uint4(pack_bf16(v[0], v[1]), pack_bf16(v[2], v[3]), pack_bf16(v[4], v[5]), pack_bf16(v[6], v[7]));
            }
        }
    }

#pragma unroll 1
    for (int layer = 0; layer < 2; layer++) {
        if (wg < 2) {
            const int n1 = 32 * wg + 8 * w + g;
            const int ct = n1 >> 2;
            gen_col_consts(sb, tid);
            uint32_t tr2[4], ti2[4], tn2[4];
#pragma unroll
            for (int i = 0; i < 4; i++) {
                float cr[2], ci[2];
#pragma unroll
                for (int e = 0; e < 2; e++) {
                    int a = (n1 * (8 * i + 2 * q + e)) & 2047;
                    a = a >= 1024 ? a - 2048 : a;
                    float ang = (float)a * (-6.283185307179586f / 2048.f);
                    cr[e] = __cosf(ang); ci[e] = __sinf(ang);
                }
                tr2[i] = pack_bf16(cr[0], cr[1]); ti2[i] = pack_bf16(ci[0], ci[1]); tn2[i] = ti2[i] ^ 0x80008000u;
            }
            uint32_t wf[16];
            const uint4* ws = g_Wfrag + (uint32_t)(b * 1024 + n1 * 4 + q);
#pragma unroll
            for (int i = 0; i < 4; i++) {
                uint4 v = make_uint4(0, 0, 0, 0);
                if (layer == 1) v = __ldcg(ws + i * 256);
                wf[4 * i] = v.x; wf[4 * i + 1] = v.y; wf[4 * i + 2] = v.z; wf[4 * i + 3] = v.w;
            }
            mbar_wait(BAR(B_COL), layer);
            TS(4 + 12 * layer);
            if (wg == 0) TC(0 + 10 * layer);
            const uint32_t rw0 = sb + SM_RAW + ct * 1024 + q * 64 + ((q >> 1) << 4) + (g & 3) * 4, rw1 = rw0 ^ 16;
            const int pos0 = 128 * ct + 8 * q + 2 * (g & 3);
            const int sw = b == 0 ? 1 : 0;
            uint32_t xr[4][4];
            const uint32_t st0 = sb + SM_H + (n1 >> 3) * 1024 + g * 16 + 4 * q;
#pragma unroll
            for (int i = 0; i < 4; i++) {
                float2 sq = *(const float2*)(sm + SM_SSQ + (pos0 + 32 * i) * 4);
                const uint32_t rs2 = pack_bf16(rsqrtf(sq.x * (1.f / 512.f) + 1e-5f), rsqrtf(sq.y * (1.f / 512.f) + 1e-5f));
#pragma unroll
                for (int jj = 0; jj < 4; jj++) {
                    const int K = jj ^ (2 * (i & 1));
                    uint32_t a = ((K & 1) ? rw1 : rw0) + i * 256 + (K & 2) * 16;
                    if (jj < 2) a ^= sw << 4;
                    uint32_t v = lds32(a);
                    xr[jj][i] = v;
                    uint32_t o = hmul2(v, rs2);
                    if (jj == 1 && sw) o = 0u;
                    sts32(st0 + (jj & 1) * 8192 + (4 * (jj >> 1) + i) * 128, o);
                }
            }
            if (wg == 0) TC(1 + 10 * layer);
            fence_async_smem();
            bar_sync(1, 256);
            float acc[32];
            const uint32_t s1a = sb + SM_X + wg * 16384, s2b = sb + SM_X + 32768;
            wg_fence();
#pragma unroll
            for (int ks = 0; ks < 8; ks++)
                wgmma_n64<1>(acc, desc_a(s1a + (ks >> 2) * 8192 + (ks & 3) * 256), desc_b<64>(sb + SM_H + ks * 2048), ks != 0);
            wg_commit();
            if (layer == 0) {
                mbar_wait(BAR(B_WRDY), 0);
#pragma unroll
                for (int i = 0; i < 4; i++) {
                    uint4 v = __ldcg(ws + i * 256);
                    wf[4 * i] = v.x; wf[4 * i + 1] = v.y; wf[4 * i + 2] = v.z; wf[4 * i + 3] = v.w;
                }
            }
            wg_wait<0>();
            if (wg == 0) TC(2 + 10 * layer);
            uint32_t are[2][4], aim[2][4];
#pragma unroll
            for (int col = 0; col < 2; col++) {
#pragma unroll
                for (int i = 0; i < 4; i++) {
                    int o = 4 * (4 * col + i);
                    uint32_t zr = pack_bf16(acc[o], acc[o + 1]), zi = pack_bf16(acc[o + 2], acc[o + 3]);
                    are[col][i] = hfma2(zr, tr2[i], hmul2(zi, tn2[i]));
                    aim[col][i] = hfma2(zr, ti2[i], hmul2(zi, tr2[i]));
                }
            }
            wg_fence();
#pragma unroll
            for (int ks = 0; ks < 2; ks++)
                wgmma_n64_rs(acc, are[0][2 * ks], are[1][2 * ks], are[0][2 * ks + 1], are[1][2 * ks + 1], desc_b<64>(s2b + ks * 2048), ks != 0);
#pragma unroll
            for (int ks = 0; ks < 2; ks++)
                wgmma_n64_rs(acc, aim[0][2 * ks], aim[1][2 * ks], aim[0][2 * ks + 1], aim[1][2 * ks + 1], desc_b<64>(s2b + 4096 + ks * 2048), 1);
            wg_commit();
            wg_wait<0>();
            if (wg == 0) TC(3 + 10 * layer);
#pragma unroll
            for (int col = 0; col < 2; col++) {
#pragma unroll
                for (int i = 0; i < 4; i++) {
                    uint32_t wr = wf[col * 8 + 2 * i], wn = wf[col * 8 + 2 * i + 1];
                    uint32_t zr = pack_bf16(acc[4 * i + 2 * col], acc[4 * i + 2 * col + 1]);
                    uint32_t zi = pack_bf16(acc[16 + 4 * i + 2 * col], acc[16 + 4 * i + 2 * col + 1]);
                    are[col][i] = hfma2(zr, wr, hmul2(zi, wn));
                    aim[col][i] = hfma2(zr, wn, hmul2(zi ^ 0x80008000u, wr));
                }
            }
            wg_fence();
#pragma unroll
            for (int ks = 0; ks < 2; ks++)
                wgmma_n64_rs(acc, are[0][2 * ks], are[1][2 * ks], are[0][2 * ks + 1], are[1][2 * ks + 1], desc_b<64>(s2b + ks * 2048), ks != 0);
#pragma unroll
            for (int ks = 0; ks < 2; ks++)
                wgmma_n64_rs(acc, aim[0][2 * ks], aim[1][2 * ks], aim[0][2 * ks + 1], aim[1][2 * ks + 1], desc_b<64>(s2b + 4096 + ks * 2048), 1);
            wg_commit();
            wg_wait<0>();
            if (wg == 0) TC(4 + 10 * layer);
            mbar_wait(BAR(B_B1DONE), 0);
#pragma unroll
            for (int col = 0; col < 2; col++) {
#pragma unroll
                for (int i = 0; i < 4; i++) {
                    uint32_t zr = pack_bf16(acc[4 * i + 2 * col], acc[4 * i + 2 * col + 1]);
                    uint32_t zi = pack_bf16(acc[16 + 4 * i + 2 * col], acc[16 + 4 * i + 2 * col + 1]);
                    sts32(st0 + 16384 + (4 * col + i) * 128, hfma2(zr, tr2[i], hmul2(zi, tn2[i])));
                    sts32(st0 + 16384 + 8192 + (4 * col + i) * 128, hfma2(zr, ti2[i], hmul2(zi, tr2[i])));
                }
            }
            if (wg == 0) TC(5 + 10 * layer);
            fence_async_smem();
            bar_sync(1, 256);
            wg_fence();
#pragma unroll
            for (int ks = 0; ks < 8; ks++)
                wgmma_n64<1>(acc, desc_a(s1a + (ks >> 2) * 8192 + (ks & 3) * 256), desc_b<64>(sb + SM_H + 16384 + ks * 2048), ks != 0);
            wg_commit();
            wg_wait<0>();
            if (wg == 0) TC(6 + 10 * layer);
            const float sc = 1.f / 2048.f;
            const float sci0 = sw ? 0.f : -sc;
            const float wr0 = sw ? 0.5f : 1.f, wi0 = sw ? 0.f : 1.f;
#pragma unroll
            for (int i = 0; i < 4; i++) {
                float ss0, ss1;
#pragma unroll
                for (int col = 0; col < 2; col++) {
                    int o = 4 * (4 * col + i);
                    uint32_t vr = xr[2 * col][i], vi = xr[2 * col + 1][i];
                    float si = col == 0 ? sci0 : -sc;
                    uint32_t nr = pack_bf16(fmaf(acc[o], sc, bf_lo(vr)), fmaf(acc[o + 1], sc, bf_hi(vr)));
                    uint32_t ni = pack_bf16(fmaf(acc[o + 2], si, bf_lo(vi)), fmaf(acc[o + 3], si, bf_hi(vi)));
                    float a0 = bf_lo(nr), a1 = bf_hi(nr), b0 = bf_lo(ni), b1 = bf_hi(ni);
                    if (col == 0) {
                        ss0 = wr0 * a0 * a0 + wi0 * b0 * b0;
                        ss1 = wr0 * a1 * a1 + wi0 * b1 * b1;
                    } else {
                        ss0 += a0 * a0 + b0 * b0;
                        ss1 += a1 * a1 + b1 * b1;
                    }
                    const int K = (2 * col) ^ (2 * (i & 1));
                    uint32_t a = rw0 + i * 256 + K * 16;
                    if (col == 0) a ^= sw << 4;
                    sts32(a, nr);
                    sts32(a ^ 16, ni);
                }
                *(float2*)(sm + SM_SSQ + (pos0 + 32 * i) * 4) = make_float2(ss0 * (2.f / 512.f), ss1 * (2.f / 512.f));
            }
            fence_async_smem();
        }
        TS(5 + 12 * layer);
        if (wg == 0) TC(7 + 10 * layer);
        bar_arrive(5, 416);

        float acc[64];
        float* s_rstd = (float*)(sm + SM_RSTD);
        float* s_mean = (float*)(sm + SM_MEAN);
        const unsigned epoch = s_tgt[0] >> 7;
        const uint32_t pt3 = 1u + (2u * epoch + layer) % 3u;
        const uint32_t ptag = (pt3 & 1u) | ((pt3 & 2u) << 15);
        const uint64_t dstep = layer == 0 ? 16 : 2;
        auto c_desc = [&](int s) { return layer == 0 ? desc_a(sb + SM_A + s * 16384) : desc_k(sb + SM_A + s * 16384); };
        if (wg < 2) {
            const int prow = 32 * wg + 8 * w + g;
            const float2 l1 = *(const float2*)(sm + SM_LAM + prow * 8);
            float lr32 = l1.x, li32 = l1.y;
#pragma unroll
            for (int i = 0; i < 5; i++) { float t = lr32 * lr32 - li32 * li32; li32 = 2.f * lr32 * li32; lr32 = t; }
            float lr128 = lr32, li128 = li32;
#pragma unroll
            for (int i = 0; i < 2; i++) { float t = lr128 * lr128 - li128 * li128; li128 = 2.f * lr128 * li128; lr128 = t; }
            const float lr1 = l1.x, li1 = l1.y;
            acc_def(acc);
#pragma unroll 1
            for (int kb = 0; kb < 8; kb++) {
                mbar_wait(BAR(B_AFULL + kb), 0);
                mbar_wait(BAR(B_XFULL + (kb & 3)), (kb >> 2) & 1);
                wg_fence();
#pragma unroll
                for (int ks = 0; ks < 4; ks++)
                    wgmma_n128<1>(acc, desc_a(sb + SM_A + kb * 16384 + wg * 8192 + ks * 256),
                                  desc_b<128>(sb + SM_X + (kb & 3) * 24576 + ks * 4096), 1);
                wg_commit();
                wg_wait<1>();
                if (kb > 0 && lane == 0) {
                    mbar_arrive(BAR(B_AEMPTY + kb - 1), 1); mbar_arrive(BAR(B_XEMPTY + ((kb - 1) & 3)), 1);
                    mbar_arrive_remote(mapa(BAR(B_XEMPTY + ((kb - 1) & 3)), par ^ 1));
                }
            }
            wg_wait<0>();
            if (lane == 0) {
                mbar_arrive(BAR(B_AEMPTY + 7), 1); mbar_arrive(BAR(B_XEMPTY + 3), 1);
                mbar_arrive_remote(mapa(BAR(B_XEMPTY + 3), par ^ 1)); mbar_arrive_remote(mapa(BAR(B_RFREE), par ^ 1));
            }
            bar_arrive(14, 384);
            TS(6 + 12 * layer);
            bar_sync(4, 384);
            TS(7 + 12 * layer);
            float er = 0.f, ei = 0.f;
#pragma unroll
            for (int i = 0; i < 16; i++) {
                float2 rs = *(const float2*)(s_rstd + 128 + 8 * i + 2 * q);
                acc[4 * i] *= rs.x; acc[4 * i + 1] *= rs.y; acc[4 * i + 2] *= rs.x; acc[4 * i + 3] *= rs.y;
                float nr = lr1 * er - li1 * ei + acc[4 * i], ni = lr1 * ei + li1 * er + acc[4 * i + 2];
                er = lr1 * nr - li1 * ni + acc[4 * i + 1];
                ei = lr1 * ni + li1 * nr + acc[4 * i + 3];
            }
            float cr = 0.f, ci = 0.f, tr = 0.f, ti = 0.f;
#pragma unroll
            for (int qq = 0; qq < 4; qq++) {
                float xr_ = __shfl_sync(~0u, er, (lane & ~3) | qq), xi_ = __shfl_sync(~0u, ei, (lane & ~3) | qq);
                if (qq == q) { cr = tr; ci = ti; }
                float nr = lr32 * tr - li32 * ti + xr_, ni = lr32 * ti + li32 * tr + xi_;
                tr = nr; ti = ni;
            }
            float4* eb = g_Ebuf + (uint32_t)(layer * 16 * 512 + 64 * r + prow);
            if (q == 0 && c < 15) st_relaxed_f4(eb + c * 512, make_float4(tr, ti, __uint_as_float(epoch), 0.f));
            TS(8 + 12 * layer);
            float pr[4], pi[4];
            {
                unsigned n = 0;
                bool ok;
#pragma unroll 1
                do {
                    ok = true;
#pragma unroll
                    for (int k = 0; k < 4; k++) {
                        float4 v = make_float4(0.f, 0.f, __uint_as_float(epoch), 0.f);
                        if (4 * k + q < c) v = ld_relaxed_f4(eb + (4 * k + q) * 512);
                        pr[k] = v.x; pi[k] = v.y;
                        ok = ok && __float_as_uint(v.z) == epoch;
                    }
                } while (!ok && ++n < SPIN_LIMIT);
            }
            __syncwarp();
            TS(9 + 12 * layer);
            float hr = 0.f, hi = 0.f;
#pragma unroll
            for (int cc = 0; cc < 15; cc++) {
                float xr_ = __shfl_sync(~0u, pr[cc >> 2], (lane & ~3) | (cc & 3)), xi_ = __shfl_sync(~0u, pi[cc >> 2], (lane & ~3) | (cc & 3));
                if (cc < c) {
                    float nr = lr128 * hr - li128 * hi + xr_, ni = lr128 * hi + li128 * hr + xi_;
                    hr = nr; hi = ni;
                }
            }
#pragma unroll
            for (int qq = 0; qq < 3; qq++) {
                if (qq < q) { float nr = lr32 * hr - li32 * hi, ni = lr32 * hi + li32 * hr; hr = nr; hi = ni; }
            }
            er = cr + hr; ei = ci + hi;
            bar_sync(7, 384);
            mbar_wait_cluster(BAR(B_RFREE), layer);
            const uint32_t ha = sb + SM_HH + par * 32768 + (prow >> 3) * 1024 + g * 16 + 4 * q;
#pragma unroll
            for (int i = 0; i < 16; i++) {
                float nr = lr1 * er - li1 * ei + acc[4 * i], ni = lr1 * ei + li1 * er + acc[4 * i + 2];
                er = lr1 * nr - li1 * ni + acc[4 * i + 1];
                ei = lr1 * ni + li1 * nr + acc[4 * i + 3];
                sts32(ha + (i >> 3) * 16384 + (i & 7) * 128, pack_bf16(nr, er));
                sts32(ha + (i >> 3) * 16384 + 8192 + (i & 7) * 128, pack_bf16(ni, ei));
                if (i == 7) { fence_async_smem(); bar_arrive(13, 288); }
            }
            fence_async_smem();
            acc_def(acc);
            float acc2[32];
            acc_def(acc2);
            TS(10 + 12 * layer);
            bar_sync(6, 416);
            TS(11 + 12 * layer);
            float (&a0)[32] = *reinterpret_cast<float (*)[32]>(&acc[0]);
            float (&a1)[32] = *reinterpret_cast<float (*)[32]>(&acc[32]);
            auto tile_mma = [&](float (&d)[32], int u) {
#pragma unroll 1
                for (int k = 0; k < 2; k++) {
                    const uint32_t hb = sb + SM_HH + (par ^ k) * 32768 + wg * 16384;
                    if (k == 1) mbar_wait(BAR(wg ? B_HPEER1 : B_HPEER), layer);
                    mbar_wait(BAR(B_AFULL + 2 * u + k), 1);
                    const uint64_t da = c_desc(2 * u + k);
                    wg_fence();
#pragma unroll
                    for (int ks = 0; ks < 4; ks++) wgmma_n64s<1>(d, da + ks * dstep, desc_b<64>(hb + ks * 2048), 1);
#pragma unroll
                    for (int ks = 0; ks < 4; ks++) wgmma_n64s<-1>(d, da + 512 + ks * dstep, desc_b<64>(hb + 8192 + ks * 2048), 1);
                }
                wg_commit();
            };
            auto tile_ship = [&](float (&d)[32], int u) {
                uint4* dst = g_P + (uint32_t)(((c * 8 + 2 * ((pi_ + 1 + u) & 3) + par) * 4 + pi_) * 1024 + wg * 512 + (tid & 127));
#pragma unroll
                for (int i = 0; i < 4; i++)
                    dst[i * 128] = make_uint4((pack_bf16(d[8 * i], d[8 * i + 1]) & 0xfffefffeu) | ptag, pack_bf16(d[8 * i + 2], d[8 * i + 3]),
                                              pack_bf16(d[8 * i + 4], d[8 * i + 5]), pack_bf16(d[8 * i + 6], d[8 * i + 7]));
            };
            tile_mma(a0, 0);
            if ((tid & 127) == 0) mbar_arrive_remote(mapa(BAR(B_HDONE), par ^ 1));
            __syncwarp();
            tile_mma(a1, 1);
            wg_wait<1>();
            tile_ship(a0, 0);
            tile_mma(acc2, 2);
            bar_arrive(12, 384);
            wg_wait<1>();
            tile_ship(a1, 1);
            wg_wait<0>();
            tile_ship(acc2, 2);
            if (lane < 6) mbar_arrive(BAR(B_AEMPTY + lane), 1);
            TS(12 + 12 * layer);
        } else {
            const int t2 = tid - 256;
            const uint8_t* ximg = g_X + (uint32_t)layer * 16 * 8 * 16384;
            mbar_wait(BAR(B_SSQ), layer);
            TS(6 + 12 * layer);
            float sqv[16];
#pragma unroll
            for (int i = 0; i < 16; i++) sqv[i] = __ldcg(g_ssqc + (layer * 16 + i) * 2048 + 128 * c + t2);
            const unsigned short xm = __ldcg((const unsigned short*)(ximg + (uint32_t)(c * 8 * 16384 + (t2 >> 3) * 128 + (t2 & 7) * 2)));
            acc_def(acc);
#pragma unroll 1
            for (int kb = 0; kb < 8; kb++) {
                if (kb == 4) {
                    wg_wait<0>();
                    if (lane == 0) { mbar_arrive(BAR(B_XEMPTY + 3), 1); mbar_arrive_remote(mapa(BAR(B_XEMPTY + 3), par ^ 1)); }
                    float tot = 0.f;
#pragma unroll
                    for (int i = 0; i < 16; i++) tot += sqv[i];
                    float rs = rsqrtf(tot * (1.f / 512.f) + 1e-5f);
                    s_rstd[t2] = rs;
                    s_rstd[128 + t2] = 2.f * rs;
                    s_mean[t2] = layer == 0 ? 0.f : __uint_as_float((uint32_t)xm << 16) * (1.f / 512.f);
                    TS(7 + 12 * layer);
                    bar_arrive(4, 384);
                    bar_sync(14, 384);
                }
                mbar_wait(BAR(B_XFULL + (kb & 3)), (kb >> 2) & 1);
                wg_fence();
#pragma unroll
                for (int ks = 0; ks < 4; ks++)
                    wgmma_n128<1>(acc, desc_a(sb + SM_X + (kb & 3) * 24576 + 16384 + ks * 256), desc_b<128>(sb + SM_X + (kb & 3) * 24576 + ks * 4096), 1);
                wg_commit();
                wg_wait<1>();
                if ((kb & 3) != 0 && lane == 0) { mbar_arrive(BAR(B_XEMPTY + ((kb - 1) & 3)), 1); mbar_arrive_remote(mapa(BAR(B_XEMPTY + ((kb - 1) & 3)), par ^ 1)); }
            }
            wg_wait<0>();
            if (lane == 0) { mbar_arrive(BAR(B_XEMPTY + 3), 1); mbar_arrive_remote(mapa(BAR(B_XEMPTY + 3), par ^ 1)); mbar_arrive_remote(mapa(BAR(B_RFREE), par ^ 1)); }
            bar_arrive(7, 384);
            bar_sync(3, 128);
            TS(9 + 12 * layer);
            const int m0 = 16 * w + g;
            const uint32_t xoff = (uint32_t)((c * 8 + own) * 16384 + w * 4096 + g * 16 + 4 * q);
            if (layer == 0) {
                const uint8_t* xs = g_X + xoff;
#pragma unroll
                for (int i = 0; i < 16; i++) {
                    float2 rs = *(const float2*)(s_rstd + 8 * i + 2 * q);
                    uint32_t x0v = __ldcg((const uint32_t*)(xs + i * 128)), x1v = __ldcg((const uint32_t*)(xs + 2048 + i * 128));
                    acc[4 * i] = acc[4 * i] * rs.x + bf_lo(x0v);
                    acc[4 * i + 1] = acc[4 * i + 1] * rs.y + bf_hi(x0v);
                    acc[4 * i + 2] = acc[4 * i + 2] * rs.x + bf_lo(x1v);
                    acc[4 * i + 3] = acc[4 * i + 3] * rs.y + bf_hi(x1v);
                }
            } else {
                float d0 = ldbf(p.dskip + 64 * own + m0), d1 = ldbf(p.dskip + 64 * own + m0 + 8);
#pragma unroll
                for (int i = 0; i < 16; i++) {
                    float2 rs = *(const float2*)(s_rstd + 8 * i + 2 * q);
                    float2 mn = *(const float2*)(s_mean + 8 * i + 2 * q);
                    acc[4 * i] = acc[4 * i] * (1.f + rs.x * d0) + mn.x;
                    acc[4 * i + 1] = acc[4 * i + 1] * (1.f + rs.y * d0) + mn.y;
                    acc[4 * i + 2] = acc[4 * i + 2] * (1.f + rs.x * d1) + mn.x;
                    acc[4 * i + 3] = acc[4 * i + 3] * (1.f + rs.y * d1) + mn.y;
                }
            }
            TS(10 + 12 * layer);
            bar_sync(6, 416);
            TS(11 + 12 * layer);
            {
                float (&a0)[32] = *reinterpret_cast<float (*)[32]>(&acc[0]);
                float (&a1)[32] = *reinterpret_cast<float (*)[32]>(&acc[32]);
#pragma unroll 1
                for (int k = 0; k < 2; k++) {
                    const uint32_t hb = sb + SM_HH + (par ^ k) * 32768;
                    if (k == 1) {
                        mbar_wait(BAR(B_HPEER), layer);
                        mbar_wait(BAR(B_HPEER1), layer);
                        bar_sync(12, 384);
                    }
                    mbar_wait(BAR(B_AFULL + 6 + k), 1);
                    const uint64_t da = c_desc(6 + k);
                    wg_fence();
#pragma unroll
                    for (int ks = 0; ks < 4; ks++) {
                        wgmma_n64s<1>(a0, da + ks * dstep, desc_b<64>(hb + ks * 2048), 1);
                        wgmma_n64s<1>(a1, da + ks * dstep, desc_b<64>(hb + 16384 + ks * 2048), 1);
                    }
#pragma unroll
                    for (int ks = 0; ks < 4; ks++) {
                        wgmma_n64s<-1>(a0, da + 512 + ks * dstep, desc_b<64>(hb + 8192 + ks * 2048), 1);
                        wgmma_n64s<-1>(a1, da + 512 + ks * dstep, desc_b<64>(hb + 16384 + 8192 + ks * 2048), 1);
                    }
                    wg_commit();
                }
                wg_wait<0>();
            }
#pragma unroll
            for (int i = 0; i < 16; i++)
                *(float4*)(sm + SM_A + 6 * 16384 + i * 2048 + t2 * 16) = make_float4(acc[4 * i], acc[4 * i + 1], acc[4 * i + 2], acc[4 * i + 3]);
            TS(12 + 12 * layer);
        }
        {
            const int t = tid & 127;
            const int nch = wg == 2 ? 2 : 3;
            const uint4* pb = g_P + (uint32_t)((c * 8 + r) * 4 * 1024 + wg * 128 + t);
            uint4 v[3][3];
            unsigned n = 0;
#pragma unroll 1
            while (true) {
                if (lane == 31) {
#pragma unroll 1
                    while (true) {
                        uint32_t bad = 0;
#pragma unroll
                        for (int sx = 0; sx < 3; sx++) {
                            uint32_t t0;
                            asm volatile("ld.relaxed.gpu.global.u32 %0, [%1];" : "=r"(t0) : "l"(pb + ((pi_ + 1 + sx) & 3) * 1024 + (nch - 1) * 384) : "memory");
                            bad |= t0 ^ ptag;
                        }
                        if (!(bad & 0x00010001u) || ++n >= SPIN_LIMIT) break;
                    }
                }
                __syncwarp();
                uint32_t bad = 0;
#pragma unroll
                for (int k = 0; k < 3; k++)
#pragma unroll
                    for (int sx = 0; sx < 3; sx++) {
                        v[k][sx] = make_uint4(ptag, 0, 0, 0);
                        if (k < nch) v[k][sx] = ld_relaxed_u4(pb + ((pi_ + 1 + sx) & 3) * 1024 + k * 384);
                        bad |= v[k][sx].x ^ ptag;
                    }
                if (!__any_sync(~0u, bad & 0x00010001u) || ++n >= SPIN_LIMIT) break;
            }
            bar_sync(8, 384);
            TS(13 + 12 * layer);
            const int m0 = 16 * w + g;
            const float w0 = (own == 0 && m0 < 2) ? (m0 == 0 ? 0.f : 0.5f) : 1.f;
#pragma unroll
            for (int k = 0; k < 3; k++) {
                if (k < nch) {
                    const int i = wg + 3 * k;
                    float4 a = *(const float4*)(sm + SM_A + 6 * 16384 + (2 * i) * 2048 + t * 16);
                    float4 bq = *(const float4*)(sm + SM_A + 6 * 16384 + (2 * i + 1) * 2048 + t * 16);
#pragma unroll
                    for (int sx = 0; sx < 3; sx++) {
                        a.x += bf_lo(v[k][sx].x); a.y += bf_hi(v[k][sx].x); a.z += bf_lo(v[k][sx].y); a.w += bf_hi(v[k][sx].y);
                        bq.x += bf_lo(v[k][sx].z); bq.y += bf_hi(v[k][sx].z); bq.z += bf_lo(v[k][sx].w); bq.w += bf_hi(v[k][sx].w);
                    }
                    if (layer == 0) {
                        uint8_t* xd = g_X + (uint32_t)((16 * 8 + c * 8 + own) * 16384 + w * 4096 + g * 16 + 4 * q + i * 256);
                        uint32_t v0 = pack_bf16(a.x, a.y), v1 = pack_bf16(a.z, a.w), v2 = pack_bf16(bq.x, bq.y), v3 = pack_bf16(bq.z, bq.w);
                        *(uint32_t*)(xd) = v0; *(uint32_t*)(xd + 2048) = v1; *(uint32_t*)(xd + 128) = v2; *(uint32_t*)(xd + 2048 + 128) = v3;
                        float sq[4];
                        sq[0] = w0 * bf_lo(v0) * bf_lo(v0) + bf_lo(v1) * bf_lo(v1);
                        sq[1] = w0 * bf_hi(v0) * bf_hi(v0) + bf_hi(v1) * bf_hi(v1);
                        sq[2] = w0 * bf_lo(v2) * bf_lo(v2) + bf_lo(v3) * bf_lo(v3);
                        sq[3] = w0 * bf_hi(v2) * bf_hi(v2) + bf_hi(v3) * bf_hi(v3);
                        float u0 = (g & 1) ? sq[2] : sq[0], u1 = (g & 1) ? sq[3] : sq[1];
                        u0 += __shfl_xor_sync(~0u, (g & 1) ? sq[0] : sq[2], 4);
                        u1 += __shfl_xor_sync(~0u, (g & 1) ? sq[1] : sq[3], 4);
                        float z = (g & 2) ? u1 : u0;
                        z += __shfl_xor_sync(~0u, (g & 2) ? u0 : u1, 8);
                        z += __shfl_xor_sync(~0u, z, 16);
                        if (g < 4) atomicAdd(s_mean + 16 * i + 8 * (g & 1) + 2 * q + (g >> 1), z);
                    } else {
                        float* o = p.out + (uint32_t)((128 * c + 32 * q + 4 * i) * 512 + 64 * own + m0);
                        o[0] = a.x; o[512] = a.y; o[8] = a.z; o[512 + 8] = a.w;
                        o[1024] = bq.x; o[1536] = bq.y; o[1024 + 8] = bq.z; o[1536 + 8] = bq.w;
                    }
                }
            }
            if (wg < 2) mbar_wait_cluster(BAR(B_HDONE), layer);
            if (layer == 0) {
                fence_async_smem();
                bar_sync(9, 384);
                TS(14 + 12 * layer);
                if (wg == 2) {
                    atomicAdd(g_ssq + 2048 + 128 * c + t, s_mean[t] * (2.f / 512.f));
                    bar_sync(3, 128);
                    if (lane == 0) { mbar_arrive(BAR(B_AEMPTY + 6), 2); mbar_arrive(BAR(B_AEMPTY + 7), 2); }
                    if (t == 0) { fence_async(); red_release(&g_bar[2], 1); }
                }
            }
        }
        TS(15 + 12 * layer);
        if (wg == 0) TC(31);
    }
}

typedef CUresult (*EncFn)(CUtensorMap*, CUtensorMapDataType, cuuint32_t, void*, const cuuint64_t*, const cuuint64_t*,
                          const cuuint32_t*, const cuuint32_t*, CUtensorMapInterleave, CUtensorMapSwizzle,
                          CUtensorMapL2promotion, CUtensorMapFloatOOBfill);

void launch_impl(void* const* d_in, void* d_out, int stop) {
    static EncFn enc = nullptr;
    if (!enc) {
        void* fn = nullptr;
        cudaDriverEntryPointQueryResult qr;
        cudaGetDriverEntryPoint("cuTensorMapEncodeTiled", &fn, cudaEnableDefault, &qr);
        enc = (EncFn)fn;
        cudaFuncSetAttribute(fused_kernel, cudaFuncAttributeMaxDynamicSharedMemorySize, SM_TOTAL);
    }
    CUtensorMap tx, tbr, tbi, tcr, tci, tcol;
    {
        void* gx = nullptr;
        cudaGetSymbolAddress(&gx, g_X);
        cuuint64_t gd[5] = {64, 16, 64, 16, 2};
        cuuint64_t gs[4] = {128, 2048, 128 * 1024, 2048 * 1024};
        cuuint32_t bx[5] = {32, 16, 1, 16, 1};
        cuuint32_t es[5] = {1, 1, 1, 1, 1};
        enc(&tcol, CU_TENSOR_MAP_DATA_TYPE_BFLOAT16, 5, gx, gd, gs, bx, es, CU_TENSOR_MAP_INTERLEAVE_NONE,
            CU_TENSOR_MAP_SWIZZLE_64B, CU_TENSOR_MAP_L2_PROMOTION_NONE, CU_TENSOR_MAP_FLOAT_OOB_FILL_NONE);
    }
    {
        cuuint64_t gd[5] = {512, 2, 4, 16, 16};
        cuuint64_t gs[4] = {1024, 32 * 1024, 2 * 1024, 128 * 1024};
        cuuint32_t bx[5] = {64, 2, 4, 8, 1};
        cuuint32_t es[5] = {1, 1, 1, 1, 1};
        enc(&tx, CU_TENSOR_MAP_DATA_TYPE_BFLOAT16, 5, d_in[0], gd, gs, bx, es, CU_TENSOR_MAP_INTERLEAVE_NONE,
            CU_TENSOR_MAP_SWIZZLE_128B, CU_TENSOR_MAP_L2_PROMOTION_L2_128B, CU_TENSOR_MAP_FLOAT_OOB_FILL_NONE);
    }
    auto mk2 = [&](CUtensorMap* m, void* ptr, cuuint32_t rows) {
        cuuint64_t gd[2] = {512, 512};
        cuuint64_t gs[1] = {1024};
        cuuint32_t bx[2] = {64, rows};
        cuuint32_t es[2] = {1, 1};
        enc(m, CU_TENSOR_MAP_DATA_TYPE_BFLOAT16, 2, ptr, gd, gs, bx, es, CU_TENSOR_MAP_INTERLEAVE_NONE,
            CU_TENSOR_MAP_SWIZZLE_128B, CU_TENSOR_MAP_L2_PROMOTION_L2_128B, CU_TENSOR_MAP_FLOAT_OOB_FILL_NONE);
    };
    mk2(&tbr, d_in[6], 32);
    mk2(&tbi, d_in[7], 32);
    mk2(&tcr, d_in[8], 64);
    mk2(&tci, d_in[9], 64);
    Params p;
    p.x0 = (const __nv_bfloat16*)d_in[0];
    p.w_r = (const __nv_bfloat16*)d_in[1];
    p.w_i = (const __nv_bfloat16*)d_in[2];
    p.lam_re = (const __nv_bfloat16*)d_in[4];
    p.lam_im = (const __nv_bfloat16*)d_in[5];
    p.log_dt = (const __nv_bfloat16*)d_in[10];
    p.dskip = (const __nv_bfloat16*)d_in[11];
    p.out = (float*)d_out;
    p.stop = stop;
    cudaLaunchConfig_t cfg = {};
    cfg.gridDim = dim3(NCTA); cfg.blockDim = dim3(NTHREADS); cfg.dynamicSmemBytes = SM_TOTAL; cfg.stream = cudaStreamPerThread;
    cudaLaunchAttribute at[1];
    at[0].id = cudaLaunchAttributeClusterDimension;
    at[0].val.clusterDim.x = 2; at[0].val.clusterDim.y = 1; at[0].val.clusterDim.z = 1;
    cfg.attrs = at; cfg.numAttrs = 1;
    cudaLaunchKernelEx(&cfg, fused_kernel, tx, tbr, tbi, tcr, tci, tcol, p);
}

}

extern "C" void kernel_launch(void* const* d_in, const int* in_sizes, int n_in, void* d_out, int out_size) {
    (void)in_sizes; (void)n_in; (void)out_size;
    launch_impl(d_in, d_out, 100);
}
```

```cpp
#include <cuda_runtime.h>
#include <cuda_bf16.h>
#include <cuda.h>
#include <stdint.h>

namespace {

constexpr int NCTA = 128;
constexpr int NTHREADS = 512;
constexpr int SM_A = 0;
constexpr int SM_X = 131072;
constexpr int SM_H = 196608;
constexpr int SM_HH = SM_X + 32768;
constexpr int SM_M = 229376;
constexpr int SM_TOTAL = 232448;
constexpr int SM_BAR = SM_M;
constexpr int SM_TGT = SM_M + 392;
constexpr int SM_LAM = SM_M + 416;
constexpr int SM_TAB = SM_M + 928;
constexpr int SM_RSTD = SM_M + 1920;
constexpr int SM_MEAN = SM_TAB;
constexpr int SM_T64 = SM_M + 2944;
constexpr int SM_B1ST = SM_H + 24576;
constexpr int SM_RAW = SM_X + 40960;
constexpr int SM_SSQ = SM_X + 57344;
constexpr int B_FULL0 = 0;
constexpr int B_EMPTY0 = 8;
constexpr int B_FULLC = 12;
constexpr int B_AFULL = 13;
constexpr int B_AEMPTY = 21;
constexpr int B_XFULL = 29;
constexpr int B_XEMPTY = 33;
constexpr int B_AFREE = 37;
constexpr int B_COL = 38;
constexpr int B_SSQ = 39;
constexpr int B_HPEER = 40;
constexpr int B_RFREE = 41;
constexpr int B_HDONE = 42;
constexpr int B_WRDY = 43;
constexpr int B_HPEER1 = 44;
constexpr int B_FULLB = 45;
constexpr int B_BFREE = 46;
constexpr int B_SETUP = 47;
constexpr int B_B1DONE = 48;
constexpr int NBARS = 49;

__device__ __align__(1024) uint8_t g_X[2 * 16 * 8 * 16384];
__device__ __align__(1024) uint8_t g_A1[8 * 8 * 16384];
__device__ __align__(1024) uint8_t g_A2[8 * 8 * 16384];
__device__ __align__(1024) uint8_t g_E[2 * 8 * 8 * 8192];
__device__ __align__(16) float g_ssq[2 * 2048];
__device__ __align__(16) float g_ssqc[2 * 16 * 2048];
__device__ __align__(16) float g_Dh[512];
__device__ __align__(16) uint4 g_Wfrag[128 * 4 * 256];
__device__ __align__(16) float4 g_Ebuf[2 * 16 * 512];
__device__ __align__(16) uint4 g_P[16 * 8 * 4 * 1024];
__device__ unsigned g_bar[8];
__device__ unsigned g_err;
#define TX(i)
#define TQ(i)
#define TS(i)
#define TC(i)

constexpr unsigned SPIN_LIMIT = 1u << 22;

__device__ __forceinline__ uint32_t s2u(const void* p) { return (uint32_t)__cvta_generic_to_shared(p); }
__device__ __forceinline__ void mbar_init(uint32_t a, uint32_t c) {
    asm volatile("mbarrier.init.shared::cta.b64 [%0], %1;" ::"r"(a), "r"(c) : "memory");
}
__device__ __forceinline__ void mbar_expect(uint32_t a, uint32_t bytes) {
    asm volatile("mbarrier.arrive.expect_tx.shared::cta.b64 _, [%0], %1;" ::"r"(a), "r"(bytes) : "memory");
}
__device__ __forceinline__ void mbar_arrive(uint32_t a, uint32_t cnt) {
    asm volatile("mbarrier.arrive.shared::cta.b64 _, [%0], %1;" ::"r"(a), "r"(cnt) : "memory");
}
__device__ __forceinline__ bool mbar_try(uint32_t a, uint32_t parity) {
    uint32_t ok;
    asm volatile("{\n.reg .pred p;\nmbarrier.try_wait.parity.shared::cta.b64 p, [%1], %2;\nselp.u32 %0, 1, 0, p;\n}"
                 : "=r"(ok) : "r"(a), "r"(parity) : "memory");
    return ok != 0;
}
__device__ __forceinline__ void mbar_wait(uint32_t a, uint32_t parity) {
    asm volatile("{\n.reg .pred p, q;\n.reg .u32 n;\nmov.u32 n, 0;\n"
                 "W_%=:\nmbarrier.try_wait.parity.shared::cta.b64 p, [%0], %1;\n@p bra D_%=;\n"
                 "add.u32 n, n, 1;\nsetp.lt.u32 q, n, 4194304;\n@q bra W_%=;\nD_%=:\n}" ::"r"(a), "r"(parity) : "memory");
}
__device__ __forceinline__ void bulk_g2s(uint32_t dst, const void* src, uint32_t bytes, uint32_t bar) {
    asm volatile("cp.async.bulk.shared::cluster.global.mbarrier::complete_tx::bytes [%0], [%1], %2, [%3];" ::"r"(dst),
                 "l"(src), "r"(bytes), "r"(bar) : "memory");
}
__device__ __forceinline__ void tma_2d(uint32_t dst, const CUtensorMap* m, int c0, int c1, uint32_t bar) {
    asm volatile("cp.async.bulk.tensor.2d.shared::cluster.global.mbarrier::complete_tx::bytes [%0], [%1, {%3,%4}], [%2];" ::"r"(dst),
                 "l"(m), "r"(bar), "r"(c0), "r"(c1) : "memory");
}
__device__ __forceinline__ void tma_5d(uint32_t dst, const CUtensorMap* m, int c0, int c1, int c2, int c3, int c4, uint32_t bar) {
    asm volatile("cp.async.bulk.tensor.5d.shared::cluster.global.mbarrier::complete_tx::bytes [%0], [%1, {%3,%4,%5,%6,%7}], [%2];" ::"r"(dst),
                 "l"(m), "r"(bar), "r"(c0), "r"(c1), "r"(c2), "r"(c3), "r"(c4) : "memory");
}
__device__ __forceinline__ void tma_2d_mc(uint32_t dst, const CUtensorMap* m, int c0, int c1, uint32_t bar) {
    asm volatile("cp.async.bulk.tensor.2d.shared::cluster.global.mbarrier::complete_tx::bytes.multicast::cluster [%0], [%1, {%3,%4}], [%2], %5;" ::"r"(dst),
                 "l"(m), "r"(bar), "r"(c0), "r"(c1), "h"((unsigned short)3) : "memory");
}
__device__ __forceinline__ void tma_5d_mc(uint32_t dst, const CUtensorMap* m, int c0, int c1, int c2, int c3, int c4, uint32_t bar) {
    asm volatile("cp.async.bulk.tensor.5d.shared::cluster.global.mbarrier::complete_tx::bytes.multicast::cluster [%0], [%1, {%3,%4,%5,%6,%7}], [%2], %8;" ::"r"(dst),
                 "l"(m), "r"(bar), "r"(c0), "r"(c1), "r"(c2), "r"(c3), "r"(c4), "h"((unsigned short)3) : "memory");
}
__device__ __forceinline__ void bulk_g2s_mc(uint32_t dst, const void* src, uint32_t bytes, uint32_t bar) {
    asm volatile("cp.async.bulk.shared::cluster.global.mbarrier::complete_tx::bytes.multicast::cluster [%0], [%1], %2, [%3], %4;" ::"r"(dst),
                 "l"(src), "r"(bytes), "r"(bar), "h"((unsigned short)3) : "memory");
}
__device__ __forceinline__ void tma_store_5d(const CUtensorMap* m, int c0, int c1, int c2, int c3, int c4, uint32_t src) {
    asm volatile("cp.async.bulk.tensor.5d.global.shared::cta.bulk_group [%0, {%2,%3,%4,%5,%6}], [%1];" ::"l"(m), "r"(src),
                 "r"(c0), "r"(c1), "r"(c2), "r"(c3), "r"(c4) : "memory");
}
__device__ __forceinline__ uint32_t lds32(uint32_t a) { uint32_t v; asm volatile("ld.shared.u32 %0, [%1];" : "=r"(v) : "r"(a) : "memory"); return v; }
__device__ __forceinline__ uint4 ld_relaxed_u4(const uint4* p) {
    uint4 v;
    asm volatile("ld.relaxed.gpu.global.v4.u32 {%0,%1,%2,%3}, [%4];" : "=r"(v.x), "=r"(v.y), "=r"(v.z), "=r"(v.w) : "l"(p) : "memory");
    return v;
}
__device__ __forceinline__ void fence_async() { asm volatile("fence.proxy.async.global;" ::: "memory"); }
__device__ __forceinline__ void red_relaxed(unsigned* p, unsigned v) {
    asm volatile("red.relaxed.gpu.global.add.u32 [%0], %1;" ::"l"(p), "r"(v) : "memory");
}
__device__ __forceinline__ uint32_t mapa(uint32_t a, uint32_t rank) {
    uint32_t d;
    asm("mapa.shared::cluster.u32 %0, %1, %2;" : "=r"(d) : "r"(a), "r"(rank));
    return d;
}
__device__ __forceinline__ void mbar_arrive_remote(uint32_t ra) {
    asm volatile("mbarrier.arrive.relaxed.cluster.shared::cluster.b64 _, [%0];" ::"r"(ra) : "memory");
}
__device__ __forceinline__ void mbar_wait_cluster(uint32_t a, uint32_t parity) {
    asm volatile("{\n.reg .pred p, q;\n.reg .u32 n;\nmov.u32 n, 0;\n"
                 "W_%=:\nmbarrier.try_wait.parity.acquire.cluster.shared::cta.b64 p, [%0], %1;\n@p bra D_%=;\n"
                 "add.u32 n, n, 1;\nsetp.lt.u32 q, n, 4194304;\n@q bra W_%=;\nD_%=:\n}" ::"r"(a), "r"(parity) : "memory");
}
__device__ __forceinline__ void bulk_s2peer(uint32_t rdst, uint32_t src, uint32_t bytes, uint32_t rbar) {
    asm volatile("cp.async.bulk.shared::cluster.shared::cta.mbarrier::complete_tx::bytes [%0], [%1], %2, [%3];" ::"r"(rdst),
                 "r"(src), "r"(bytes), "r"(rbar) : "memory");
}
__device__ __forceinline__ void fence_async_smem() { asm volatile("fence.proxy.async.shared::cta;" ::: "memory"); }
__device__ __forceinline__ void wg_fence() { asm volatile("wgmma.fence.sync.aligned;" ::: "memory"); }
__device__ __forceinline__ void wg_commit() { asm volatile("wgmma.commit_group.sync.aligned;" ::: "memory"); }
template <int N> __device__ __forceinline__ void wg_wait() { asm volatile("wgmma.wait_group.sync.aligned %0;" ::"n"(N) : "memory"); }
__device__ __forceinline__ void bar_sync(int id, int n) { asm volatile("bar.sync %0, %1;" ::"r"(id), "r"(n) : "memory"); }
__device__ __forceinline__ void bar_arrive(int id, int n) { asm volatile("bar.arrive %0, %1;" ::"r"(id), "r"(n) : "memory"); }
__device__ __forceinline__ unsigned ld_acquire(const unsigned* p) {
    unsigned v;
    asm volatile("ld.acquire.gpu.global.u32 %0, [%1];" : "=r"(v) : "l"(p) : "memory");
    return v;
}
__device__ __forceinline__ void red_release(unsigned* p, unsigned v) {
    asm volatile("red.release.gpu.global.add.u32 [%0], %1;" ::"l"(p), "r"(v) : "memory");
}
__device__ __forceinline__ void wait_count(const unsigned* p, unsigned target) {
    unsigned n = 0;
#pragma unroll 1
    while ((int)(ld_acquire(p) - target) < 0 && ++n < SPIN_LIMIT) {}
}
__device__ __forceinline__ float4 ld_relaxed_f4(const float4* p) {
    float4 v;
    asm volatile("ld.relaxed.gpu.global.v4.f32 {%0,%1,%2,%3}, [%4];" : "=f"(v.x), "=f"(v.y), "=f"(v.z), "=f"(v.w) : "l"(p) : "memory");
    return v;
}
__device__ __forceinline__ void st_relaxed_f4(float4* p, float4 v) {
    asm volatile("st.relaxed.gpu.global.v4.f32 [%0], {%1,%2,%3,%4};" ::"l"(p), "f"(v.x), "f"(v.y), "f"(v.z), "f"(v.w) : "memory");
}
__device__ __forceinline__ uint32_t pack_bf16(float lo, float hi) {
    uint32_t r;
    asm("cvt.rn.bf16x2.f32 %0, %1, %2;" : "=r"(r) : "f"(hi), "f"(lo));
    return r;
}
__device__ __forceinline__ uint32_t hmul2(uint32_t a, uint32_t b) {
    uint32_t r;
    asm("mul.rn.bf16x2 %0, %1, %2;" : "=r"(r) : "r"(a), "r"(b));
    return r;
}
__device__ __forceinline__ uint32_t hfma2(uint32_t a, uint32_t b, uint32_t c) {
    uint32_t r;
    asm("fma.rn.bf16x2 %0, %1, %2, %3;" : "=r"(r) : "r"(a), "r"(b), "r"(c));
    return r;
}
__device__ __forceinline__ float bf_lo(uint32_t v) { return __uint_as_float(v << 16); }
__device__ __forceinline__ float bf_hi(uint32_t v) { return __uint_as_float(v & 0xffff0000u); }
__device__ __forceinline__ void sts32(uint32_t a, uint32_t v) { asm volatile("st.shared.u32 [%0], %1;" ::"r"(a), "r"(v) : "memory"); }
__device__ __forceinline__ void sts128(uint32_t a, uint4 v) {
    asm volatile("st.shared.v4.u32 [%0], {%1,%2,%3,%4};" ::"r"(a), "r"(v.x), "r"(v.y), "r"(v.z), "r"(v.w) : "memory");
}

__device__ __forceinline__ uint64_t desc_ni(uint32_t addr, uint32_t lbo, uint32_t sbo) {
    return (uint64_t)((addr & 0x3FFFF) >> 4) | ((uint64_t)(lbo >> 4) << 16) | ((uint64_t)(sbo >> 4) << 32);
}
__device__ __forceinline__ uint64_t desc_a(uint32_t addr) { return desc_ni(addr, 128, 1024); }
template <int N> __device__ __forceinline__ uint64_t desc_b(uint32_t addr) { return desc_ni(addr, 16 * N, 128); }
__device__ __forceinline__ uint64_t desc_k(uint32_t addr) {
    return (uint64_t)((addr & 0x3FFFF) >> 4) | (1ull << 16) | (64ull << 32) | (1ull << 62);
}
__device__ __forceinline__ uint64_t desc_mn(uint32_t addr, uint32_t lbo) {
    return (uint64_t)((addr & 0x3FFFF) >> 4) | ((uint64_t)(lbo >> 4) << 16) | (64ull << 32) | (1ull << 62);
}

#define ACC8(d, o) "+f"(d[o + 0]), "+f"(d[o + 1]), "+f"(d[o + 2]), "+f"(d[o + 3]), "+f"(d[o + 4]), "+f"(d[o + 5]), "+f"(d[o + 6]), "+f"(d[o + 7])
template <int TB, int SA = 1>
__device__ __forceinline__ void wgmma_n128(float (&d)[64], uint64_t da, uint64_t db, int sd) {
    asm volatile(
        "{\n.reg .pred p;\nsetp.ne.b32 p, %66, 0;\n"
        "wgmma.mma_async.sync.aligned.m64n128k16.f32.bf16.bf16 "
        "{%0,%1,%2,%3,%4,%5,%6,%7,%8,%9,%10,%11,%12,%13,%14,%15,%16,%17,%18,%19,%20,%21,%22,%23,%24,%25,%26,%27,%28,%29,%30,%31,"
        "%32,%33,%34,%35,%36,%37,%38,%39,%40,%41,%42,%43,%44,%45,%46,%47,%48,%49,%50,%51,%52,%53,%54,%55,%56,%57,%58,%59,%60,%61,%62,%63},"
        " %64, %65, p, %68, 1, 0, %67;\n}"
        : ACC8(d, 0), ACC8(d, 8), ACC8(d, 16), ACC8(d, 24), ACC8(d, 32), ACC8(d, 40), ACC8(d, 48), ACC8(d, 56)
        : "l"(da), "l"(db), "r"(sd), "n"(TB), "n"(SA));
}
template <int N> __device__ __forceinline__ void acc_def(float (&d)[N]) {
#pragma unroll
    for (int i = 0; i < N; i++) d[i] = 0.f;
}
template <int TB>
__device__ __forceinline__ void wgmma_n64(float (&d)[32], uint64_t da, uint64_t db, int sd) {
    asm volatile(
        "{\n.reg .pred p;\nsetp.ne.b32 p, %34, 0;\n"
        "wgmma.mma_async.sync.aligned.m64n64k16.f32.bf16.bf16 "
        "{%0,%1,%2,%3,%4,%5,%6,%7,%8,%9,%10,%11,%12,%13,%14,%15,%16,%17,%18,%19,%20,%21,%22,%23,%24,%25,%26,%27,%28,%29,%30,%31},"
        " %32, %33, p, 1, 1, 0, %35;\n}"
        : ACC8(d, 0), ACC8(d, 8), ACC8(d, 16), ACC8(d, 24)
        : "l"(da), "l"(db), "r"(sd), "n"(TB));
}
template <int SA>
__device__ __forceinline__ void wgmma_n64s(float (&d)[32], uint64_t da, uint64_t db, int sd) {
    asm volatile(
        "{\n.reg .pred p;\nsetp.ne.b32 p, %34, 0;\n"
        "wgmma.mma_async.sync.aligned.m64n64k16.f32.bf16.bf16 "
        "{%0,%1,%2,%3,%4,%5,%6,%7,%8,%9,%10,%11,%12,%13,%14,%15,%16,%17,%18,%19,%20,%21,%22,%23,%24,%25,%26,%27,%28,%29,%30,%31},"
        " %32, %33, p, %35, 1, 0, 1;\n}"
        : ACC8(d, 0), ACC8(d, 8), ACC8(d, 16), ACC8(d, 24)
        : "l"(da), "l"(db), "r"(sd), "n"(SA));
}
__device__ __forceinline__ void wgmma_n64_rs(float (&d)[32], uint32_t a0, uint32_t a1, uint32_t a2, uint32_t a3, uint64_t db, int sd) {
    asm volatile(
        "{\n.reg .pred p;\nsetp.ne.b32 p, %37, 0;\n"
        "wgmma.mma_async.sync.aligned.m64n64k16.f32.bf16.bf16 "
        "{%0,%1,%2,%3,%4,%5,%6,%7,%8,%9,%10,%11,%12,%13,%14,%15,%16,%17,%18,%19,%20,%21,%22,%23,%24,%25,%26,%27,%28,%29,%30,%31},"
        " {%32,%33,%34,%35}, %36, p, 1, 1, 1;\n}"
        : ACC8(d, 0), ACC8(d, 8), ACC8(d, 16), ACC8(d, 24)
        : "r"(a0), "r"(a1), "r"(a2), "r"(a3), "l"(db), "r"(sd));
}

struct Params {
    const __nv_bfloat16* x0;
    const __nv_bfloat16* w_r;
    const __nv_bfloat16* w_i;
    const __nv_bfloat16* lam_re;
    const __nv_bfloat16* lam_im;
    const __nv_bfloat16* log_dt;
    const __nv_bfloat16* dskip;
    float* out;
    int stop;
};

__device__ __forceinline__ float ldbf(const __nv_bfloat16* p) { return __bfloat162float(*p); }

__device__ __forceinline__ void dft_fp(int j, int& f, int& ph) {
    int cs = j >> 1;
    if (j == 1) { f = 256; ph = 0; }
    else { f = cs; ph = (j & 1) ? 128 : 0; }
}

__device__ __forceinline__ void gen_col_consts(uint32_t sb, int tid) {
#pragma unroll 1
    for (int task = tid; task < 640; task += 256) {
        int f, c8;
        uint32_t a_cc, d_pi, d_po;
        if (task < 512) {
            f = task & 63; c8 = task >> 6;
            a_cc = sb + SM_X + (f >> 5) * 16384 + ((f >> 3) & 3) * 2048 + c8 * 128 + (f & 7) * 16;
            d_pi = 8192; d_po = 1024;
        } else {
            int n2 = task & 31;
            f = 2 * n2; c8 = (task >> 5) & 3;
            a_cc = sb + SM_X + 32768 + (n2 >> 3) * 1024 + c8 * 128 + (n2 & 7) * 16;
            d_pi = 4096; d_po = 512;
        }
        float cd, sd, cs, sn;
        __sincosf((float)(f >= 32 ? f - 64 : f) * (6.283185307179586f / 64.f), &sd, &cd);
        int a = (8 * c8 * f) & 63;
        __sincosf((float)(a >= 32 ? a - 64 : a) * (6.283185307179586f / 64.f), &sn, &cs);
        float cv[8], sv[8];
#pragma unroll
        for (int e = 0; e < 8; e++) {
            cv[e] = cs; sv[e] = sn;
            float t = cs * cd - sn * sd;
            sn = sn * cd + cs * sd;
            cs = t;
        }
        uint4 oc = make_uint4(pack_bf16(cv[0], cv[1]), pack_bf16(cv[2], cv[3]), pack_bf16(cv[4], cv[5]), pack_bf16(cv[6], cv[7]));
        uint4 os = make_uint4(pack_bf16(sv[0], sv[1]), pack_bf16(sv[2], sv[3]), pack_bf16(sv[4], sv[5]), pack_bf16(sv[6], sv[7]));
        sts128(a_cc, oc);
        sts128(a_cc + d_pi, os);
        sts128(a_cc + d_po, make_uint4(os.x ^ 0x80008000u, os.y ^ 0x80008000u, os.z ^ 0x80008000u, os.w ^ 0x80008000u));
        sts128(a_cc + d_pi + d_po, oc);
    }
}

__global__ void __launch_bounds__(NTHREADS, 1)
fused_kernel(const __grid_constant__ CUtensorMap tm_x, const __grid_constant__ CUtensorMap tm_bre,
             const __grid_constant__ CUtensorMap tm_bim, const __grid_constant__ CUtensorMap tm_cre,
             const __grid_constant__ CUtensorMap tm_cim, const __grid_constant__ CUtensorMap tm_col, const Params p) {
    extern __shared__ __align__(1024) uint8_t sm[];
    const uint32_t sb = s2u(sm);
    const int tid = threadIdx.x, b = blockIdx.x;
    const int c = b >> 3, r = b & 7;
    const int par = r & 1, pi_ = r >> 1, own = 4 * par + pi_;
    const int wg = __shfl_sync(~0u, tid >> 7, 0), w = __shfl_sync(~0u, (tid >> 5) & 3, 0), lane = tid & 31, g = lane >> 2, q = lane & 3;
    auto BAR = [&](int i) { return sb + SM_BAR + 8 * i; };
    unsigned* s_tgt = (unsigned*)(sm + SM_TGT);

    if (tid < NBARS) {
        int cnt = 1;
        if (tid >= B_EMPTY0 && tid < B_EMPTY0 + 4) cnt = 16;
        if (tid >= B_XEMPTY && tid < B_XEMPTY + 4) cnt = 24;
        if (tid == B_RFREE) cnt = 12;
        if (tid == B_HDONE) cnt = 2;
        if (tid == B_SETUP) cnt = 3;
        if ((tid >= B_AEMPTY && tid < B_AEMPTY + 8) || tid == B_BFREE) cnt = 8;
        if (tid == B_AFREE) cnt = 4;
        mbar_init(BAR(tid), cnt);
        asm volatile("fence.mbarrier_init.release.cluster;" ::: "memory");
    }
    asm volatile("barrier.cluster.arrive.release.aligned;" ::: "memory");

    if (wg == 3) {
        asm volatile("setmaxnreg.dec.sync.aligned.u32 56;");
        if (w == 0 && lane < 6) {
            const CUtensorMap* tm = lane == 0 ? &tm_x : lane == 1 ? &tm_bre : lane == 2 ? &tm_bim : lane == 3 ? &tm_cre : lane == 4 ? &tm_cim : &tm_col;
            asm volatile("prefetch.tensormap [%0];" ::"l"(tm) : "memory");
        }
        __syncwarp();
        asm volatile("barrier.cluster.wait.acquire.aligned;" ::: "memory");
        if (w > 0) {
            {
                int i = tid - 416;
                int ps = i < 64 ? 64 * r + i : 32 * c + i - 64;
                float lr = ldbf(p.lam_re + ps), li = ldbf(p.lam_im + ps);
                float dt = __bfloat162float(__float2bfloat16(expf(ldbf(p.log_dt + ps))));
                if (i < 6) s_tgt[i] = ((ld_acquire(&g_bar[i]) >> 7) + 1u) << 7;
                float mag = expf(lr * dt), t = li * dt * 0.15915494309189535f, sn, cs;
                t -= rintf(t);
                sincospif(2.f * t, &sn, &cs);
                float er = mag * cs, ei = mag * sn;
                if (i < 64) {
                    *(float2*)(sm + SM_LAM + i * 8) = make_float2(er, ei);
                } else {
                    er -= 1.f;
                    float inv = 1.f / (lr * lr + li * li);
                    *(float2*)(sm + SM_TAB + (i - 64) * 8) = make_float2((er * lr + ei * li) * inv, (ei * lr - er * li) * inv);
                }
            }
            __syncwarp();
            bar_arrive(15, 224);
            if (lane == 0) mbar_arrive(BAR(B_SETUP), 1);
#pragma unroll 1
            for (int i = tid - 448; i < 1536 + 128 && w > 1; i += 64) {
                if (i < 1536) g_P[(uint32_t)(b * 4 + i / 384) * 1024 + 640 + i % 384] = make_uint4(0, 0, 0, 0);
                else g_Ebuf[b * 128 + i - 1536] = make_float4(0.f, 0.f, 0.f, 0.f);
            }
            __syncwarp();
            if (w == 3) bar_arrive(11, 192);
            if (w == 2) {
                bar_sync(11, 192);
                if (lane == 0) red_release(&g_bar[4], 1);
            }
            if (w == 3) {
#pragma unroll 1
                for (int it = 0; it < 8; it++) {
                    const int m = 4 * c + (it >> 1), d = 64 * r + m, ch = lane + 32 * (it & 1);
                    float v[8];
#pragma unroll
                    for (int e = 0; e < 8; e++) {
                        int j = 8 * ch + e, f, ph;
                        dft_fp(j, f, ph);
                        int a = (d * f + ph) & 511;
                        a = a >= 256 ? a - 512 : a;
                        float wj = j == 0 ? 0.f : (j == 1 ? 1.f / 512.f : 2.f / 512.f);
                        v[e] = wj * __cosf((float)a * (6.283185307179586f / 512.f));
                    }
                    uint32_t off = (uint32_t)(64 + r * 8 + (ch >> 3)) * 8192 + (m >> 3) * 1024 + (ch & 7) * 128 + (m & 7) * 16;
                    *(uint4*)(g_E + off) = make_uint4(pack_bf16(v[0], v[1]), pack_bf16(v[2], v[3]), pack_bf16(v[4], v[5]), pack_bf16(v[6], v[7]));
                }
                __syncwarp();
                if (lane == 0) { fence_async(); red_release(&g_bar[6], 1); }
                return;
            }
            if (w == 2) {
#pragma unroll 1
                for (int it = 0; it < 4; it++) {
                    const int hf = it & 1;
                    __syncwarp();
                    if (hf == 0) bar_sync(13, 288); else bar_sync(6, 416);
                    if (lane == 0) {
                        const uint32_t src = sb + SM_HH + par * 32768 + hf * 16384;
                        bulk_s2peer(mapa(src, par ^ 1), src, 16384, mapa(BAR(hf ? B_HPEER1 : B_HPEER), par ^ 1));
                    }
                }
                return;
            }
            bar_sync(2, 288);
            if (lane == 0) {
                TX(5);
                fence_async();
                red_release(&g_bar[0], 1);
                TX(6);
            }
            __syncwarp();
            bar_sync(12, 160);
            if (lane == 0) {
                asm volatile("cp.async.bulk.global.shared::cta.bulk_group [%0], [%1], 8192;" ::"l"(g_A1 + (uint32_t)(((c >> 1) * 8 + r) * 16384 + (c & 1) * 8192)),
                             "r"(sb + SM_B1ST) : "memory");
                asm volatile("cp.async.bulk.commit_group;" ::: "memory");
                asm volatile("cp.async.bulk.wait_group 0;" ::: "memory");
                mbar_arrive(BAR(B_B1DONE), 1);
                fence_async();
                red_release(&g_bar[7], 1);
            }
#pragma unroll 1
            for (int layer = 0; layer < 2; layer++) {
                __syncwarp();
                bar_sync(5, 416);
                if (lane == 0) {
                    TX(0 + 8 * layer);
                    tma_store_5d(&tm_col, 32 * (b & 1), 0, b >> 1, 0, layer, sb + SM_RAW);
                    asm volatile("cp.reduce.async.bulk.global.shared::cta.bulk_group.add.f32 [%0], [%1], 8192;" ::"l"(g_ssqc + (layer * 16 + (b & 15)) * 2048),
                                 "r"(sb + SM_SSQ) : "memory");
                    asm volatile("cp.async.bulk.commit_group;" ::: "memory");
                    asm volatile("cp.async.bulk.wait_group 0;" ::: "memory");
                    TX(1 + 8 * layer);
                    fence_async();
                    red_release(&g_bar[1 + 2 * layer], 1);
                    TX(2 + 8 * layer);
                }
            }
        } else if (tid == 384) {
#pragma unroll 1
            for (int kb = 0; kb < 8; kb++) {
                uint32_t fb = BAR(B_FULL0 + kb);
                mbar_expect(fb, 16384);
                tma_5d_mc(sb + SM_A + 65536 + kb * 16384 + par * 8192, &tm_x, kb * 64, 0, 0, 8 * par, c, fb);
            }
#pragma unroll 1
            for (int k2 = 0; k2 < 8; k2++) {
                asm volatile("cp.async.bulk.prefetch.tensor.2d.L2.global [%0, {%1,%2}];" ::"l"(par ? &tm_bim : &tm_bre), "r"(k2 * 64), "r"(32 * c) : "memory");
                if ((k2 & 1) == par)
                    asm volatile("cp.async.bulk.prefetch.tensor.2d.L2.global [%0, {%1,%2}];" ::"l"((c & 1) ? &tm_cim : &tm_cre), "r"(64 * (c >> 1)), "r"(k2 * 64) : "memory");
            }
            mbar_wait(BAR(B_SETUP), 0);
#pragma unroll 1
            for (int layer = 0; layer < 2; layer++) {
                wait_count(&g_bar[2 * layer], s_tgt[2 * layer]);
                TX(4 + 8 * layer);
                fence_async();
                mbar_expect(BAR(B_COL), 16384 + 8192);
                tma_5d(sb + SM_RAW, &tm_col, 32 * (b & 1), 0, b >> 1, 0, layer, BAR(B_COL));
                bulk_g2s(sb + SM_SSQ, g_ssq + layer * 2048, 8192, BAR(B_COL));
                if (layer == 0) {
                    wait_count(&g_bar[4], s_tgt[4]);
                    mbar_arrive(BAR(B_WRDY), 1);
                    wait_count(&g_bar[7], s_tgt[4]);
                    fence_async();
                }
                if (layer == 0) mbar_wait(BAR(B_AFREE), 0);
                mbar_wait(BAR(B_COL), layer);
#pragma unroll 1
                for (int s = 0; s < 8; s++) {
                    if (layer == 1) mbar_wait(BAR(B_AEMPTY + s), 1);
                    if (s >= 2) mbar_wait(BAR(B_AFULL + s - 2), 0);
                    mbar_expect(BAR(B_AFULL + s), 16384);
                    bulk_g2s(sb + SM_A + s * 16384, g_A1 + (uint32_t)(r * 8 + s) * 16384, 16384, BAR(B_AFULL + s));
                }
                if (layer == 1) wait_count(&g_bar[6], s_tgt[4]);
                wait_count(&g_bar[1 + 2 * layer], s_tgt[1 + 2 * layer]);
                TX(3 + 8 * layer);
                fence_async();
                const uint8_t* xsrc = g_X + (uint32_t)(layer * 16 + c) * 8 * 16384;
                const uint8_t* esrc = g_E + (uint32_t)(layer * 8 + own) * 8 * 8192;
                mbar_arrive(BAR(B_SSQ), 1);
                mbar_expect(BAR(B_HPEER), 16384);
                mbar_expect(BAR(B_HPEER1), 16384);
#pragma unroll 1
                for (int it = 0; it < 16; it++) {
                    if (it < 8) {
                        int st = it & 3, f = layer * 2 + (it >> 2);
                        if (f > 0) mbar_wait_cluster(BAR(B_XEMPTY + st), (f - 1) & 1);
                        mbar_expect(BAR(B_XFULL + st), 24576);
                        bulk_g2s_mc(sb + SM_X + st * 24576 + par * 8192, xsrc + (uint32_t)it * 16384 + par * 8192, 8192, BAR(B_XFULL + st));
                        bulk_g2s(sb + SM_X + st * 24576 + 16384, esrc + (uint32_t)it * 8192, 8192, BAR(B_XFULL + st));
                    }
                    if (it >= 8) {
                        if (it == 8) mbar_wait(BAR(B_AEMPTY + 5), 0);
                        int s = it - 8, tile = 4 * par + ((pi_ + 1 + (s >> 1)) & 3), sl = r ^ (s & 1);
                        mbar_wait(BAR(B_AEMPTY + s), 0);
                        uint32_t fb = BAR(B_AFULL + s), dst = sb + SM_A + s * 16384;
                        mbar_expect(fb, 16384);
                        if (layer == 1) {
                            tma_2d(dst, &tm_cre, 64 * sl, 64 * tile, fb);
                            tma_2d(dst + 8192, &tm_cim, 64 * sl, 64 * tile, fb);
                        } else {
                            bulk_g2s(dst, g_A2 + (uint32_t)(sl * 8 + tile) * 16384, 16384, fb);
                        }
                    }
                }
            }
        }
        return;
    }

    asm volatile("setmaxnreg.inc.sync.aligned.u32 152;");
    if (tid >= 96 && tid < 112) g_ssq[2048 + 16 * b + tid - 96] = 0.f;
    if (tid >= 128 && tid < 256) ((float4*)g_ssqc)[b * 128 + tid - 128] = make_float4(0.f, 0.f, 0.f, 0.f);
    TS(0);
    if (wg == 0) TC(30);
    {
        const int f = 32 * r + lane;
        float cd, sd;
        __sincosf((float)f * (6.283185307179586f / 512.f), &sd, &cd);
        const uint32_t dst = sb + SM_A + (lane >> 2) * 1024 + (lane & 3) * 32;
#pragma unroll 1
        for (int ch = tid >> 5; ch < 64; ch += 12) {
            int a = (8 * ch * f) & 511;
            a = a >= 256 ? a - 512 : a;
            float cs, sn;
            __sincosf((float)a * (6.283185307179586f / 512.f), &sn, &cs);
            float cv[8], sv[8];
#pragma unroll
            for (int e = 0; e < 8; e++) {
                cv[e] = cs; sv[e] = -sn;
                float t = cs * cd - sn * sd;
                sn = sn * cd + cs * sd;
                cs = t;
            }
            uint4 o1 = make_uint4(pack_bf16(sv[0], sv[1]), pack_bf16(sv[2], sv[3]), pack_bf16(sv[4], sv[5]), pack_bf16(sv[6], sv[7]));
            if (f == 0) o1 = make_uint4(0xbf803f80u, 0xbf803f80u, 0xbf803f80u, 0xbf803f80u);
            uint32_t a0 = dst + (ch >> 3) * 8192 + (ch & 7) * 128;
            sts128(a0, make_uint4(pack_bf16(cv[0], cv[1]), pack_bf16(cv[2], cv[3]), pack_bf16(cv[4], cv[5]), pack_bf16(cv[6], cv[7])));
            sts128(a0 + 16, o1);
        }
    }
    fence_async_smem();
    asm volatile("barrier.cluster.wait.acquire.aligned;" ::: "memory");
    bar_sync(10, 384);
    TS(1);
    if (wg < 2) {
        float acc[32];
        acc_def(acc);
        const int npos = 16 * r + 8 * wg + 2 * w;
        float sh0 = 0.f, sh1 = 0.f, s0 = 0.f, s1 = 0.f, q0 = 0.f, q1 = 0.f;
#pragma unroll 1
        for (int kb = 0; kb < 8; kb++) {
            uint32_t slot = sb + SM_A + 65536 + kb * 16384;
            mbar_wait(BAR(B_FULL0 + kb), 0);
            wg_fence();
#pragma unroll
            for (int ks = 0; ks < 4; ks++)
                wgmma_n64<0>(acc, desc_a(sb + SM_A + kb * 8192 + ks * 256), desc_k(slot + wg * 8192 + ks * 32), 1);
            wg_commit();
            {
                uint32_t v0 = lds32(slot + npos * 128 + lane * 4), v1 = lds32(slot + npos * 128 + 128 + lane * 4);
                if (kb == 0) { sh0 = __shfl_sync(~0u, bf_lo(v0), 0); sh1 = __shfl_sync(~0u, bf_lo(v1), 0); }
                float a = bf_lo(v0) - sh0, bq = bf_hi(v0) - sh0, cq = bf_lo(v1) - sh1, d = bf_hi(v1) - sh1;
                s0 += a + bq; q0 += a * a + bq * bq; s1 += cq + d; q1 += cq * cq + d * d;
            }
            wg_wait<1>();
            if (kb > 0 && kb <= 4 && lane == 0) { mbar_arrive(BAR(B_EMPTY0 + kb - 1), 1); mbar_arrive_remote(mapa(BAR(B_EMPTY0 + kb - 1), par ^ 1)); }
        }
#pragma unroll
        for (int o = 16; o; o >>= 1) {
            s0 += __shfl_xor_sync(~0u, s0, o); q0 += __shfl_xor_sync(~0u, q0, o);
            s1 += __shfl_xor_sync(~0u, s1, o); q1 += __shfl_xor_sync(~0u, q1, o);
        }
        if (lane == 0) *(float2*)(g_ssq + 128 * c + npos) = make_float2(fmaxf(q0 - s0 * s0 * (1.f / 512.f), 0.f), fmaxf(q1 - s1 * s1 * (1.f / 512.f), 0.f));
        wg_wait<0>();
        TS(2);
        uint8_t* dst = g_X + (uint32_t)((c * 8 + r) * 16384 + w * 4096 + wg * 1024 + g * 16 + 4 * q);
#pragma unroll
        for (int i = 0; i < 8; i++) {
            *(uint32_t*)(dst + i * 128) = pack_bf16(acc[4 * i], acc[4 * i + 1]);
            *(uint32_t*)(dst + 2048 + i * 128) = pack_bf16(acc[4 * i + 2], acc[4 * i + 3]);
        }
        bar_sync(2, 288);
        mbar_wait(BAR(B_SETUP), 0);
        TS(3);
    }

    if (wg == 2) {
        {
            const int cb = tid & 127;
            const int c0 = cb == 0 ? 256 : 2 * cb, c1 = 2 * cb + 1;
            uint32_t wf[2][16];
#pragma unroll
            for (int h = 0; h < 2; h++) {
                const int kq = 2 * b + h, k1 = kq >> 2, qq = kq & 3;
                const unsigned short* wr_ = (const unsigned short*)p.w_r + (k1 + 128 * qq) * 257;
                const unsigned short* wi_ = (const unsigned short*)p.w_i + (k1 + 128 * qq) * 257;
#pragma unroll
                for (int i = 0; i < 4; i++) {
                    int o = 512 * i * 257;
                    wf[h][2 * i] = (uint32_t)__ldg(wr_ + o + c0) | ((uint32_t)__ldg(wr_ + o + 64 * 257 + c0) << 16);
                    wf[h][2 * i + 1] = ((uint32_t)__ldg(wi_ + o + c0) | ((uint32_t)__ldg(wi_ + o + 64 * 257 + c0) << 16)) ^ 0x80008000u;
                    wf[h][8 + 2 * i] = (uint32_t)__ldg(wr_ + o + c1) | ((uint32_t)__ldg(wr_ + o + 64 * 257 + c1) << 16);
                    wf[h][8 + 2 * i + 1] = ((uint32_t)__ldg(wi_ + o + c1) | ((uint32_t)__ldg(wi_ + o + 64 * 257 + c1) << 16)) ^ 0x80008000u;
                }
            }
            uint4 p0 = __ldg((const uint4*)p.dskip + 2 * lane), p1 = __ldg((const uint4*)p.dskip + 2 * lane + 1);
            uint32_t u[8] = {p0.x, p0.y, p0.z, p0.w, p1.x, p1.y, p1.z, p1.w};
            int j = 64 * r + 4 * c + w, f, ph;
            dft_fp(j, f, ph);
            float s = 0.f;
            int idx = 16 * lane * f + ph;
#pragma unroll
            for (int i = 0; i < 16; i++) {
                int a = idx & 511;
                idx += f;
                a = a >= 256 ? a - 512 : a;
                s += ((i & 1) ? bf_hi(u[i >> 1]) : bf_lo(u[i >> 1])) * __cosf((float)a * (6.283185307179586f / 512.f));
            }
#pragma unroll
            for (int o = 16; o; o >>= 1) s += __shfl_xor_sync(~0u, s, o);
            if (lane == 0) g_Dh[j] = s;
            uint4* wd = g_Wfrag + (uint32_t)(cb * 1024 + 2 * b);
#pragma unroll
            for (int i = 0; i < 4; i++) {
                wd[i * 256] = make_uint4(wf[0][4 * i], wf[0][4 * i + 1], wf[0][4 * i + 2], wf[0][4 * i + 3]);
                wd[i * 256 + 1] = make_uint4(wf[1][4 * i], wf[1][4 * i + 1], wf[1][4 * i + 2], wf[1][4 * i + 3]);
            }
            bar_arrive(11, 192);
        }
        bar_sync(15, 224);
        float acc[32];
        acc_def(acc);
        if (tid == 256) {
#pragma unroll 1
            for (int s = 0; s < 4; s++) mbar_wait_cluster(BAR(B_EMPTY0 + s), 0);
            mbar_expect(BAR(B_FULLB), 65536);
#pragma unroll 1
            for (int k2 = 0; k2 < 8; k2++)
                tma_2d_mc(sb + SM_A + 65536 + k2 * 8192 + par * 4096, par ? &tm_bim : &tm_bre, k2 * 64, 32 * c, BAR(B_FULLB));
        }
        __syncwarp();
        mbar_wait(BAR(B_FULLB), 0);
        wg_fence();
#pragma unroll 1
        for (int kb = 0; kb < 8; kb++) {
#pragma unroll
            for (int ks = 0; ks < 4; ks++)
                wgmma_n64<0>(acc, desc_a(sb + SM_A + kb * 8192 + ks * 256), desc_k(sb + SM_A + 65536 + kb * 8192 + ks * 32), 1);
            wg_commit();
        }
        wg_wait<0>();
        if (lane == 0) { mbar_arrive(BAR(B_BFREE), 1); mbar_arrive_remote(mapa(BAR(B_BFREE), par ^ 1)); }
        if (tid == 256) {
            mbar_wait_cluster(BAR(B_BFREE), 0);
            mbar_expect(BAR(B_FULLC), 65536);
#pragma unroll 1
            for (int k2 = par; k2 < 8; k2 += 2)
                tma_2d_mc(sb + SM_A + 65536 + k2 * 8192, (c & 1) ? &tm_cim : &tm_cre, 64 * (c >> 1), k2 * 64, BAR(B_FULLC));
        }
        __syncwarp();
        {
            uint8_t* dst = sm + SM_B1ST + w * 256 + q * 32 + g * 2;
            const float wj0 = (r == 0 && w == 0 && g < 2) ? (g == 0 ? 0.f : 1.f / 512.f) : 2.f / 512.f;
#pragma unroll
            for (int i = 0; i < 4; i++) {
#pragma unroll
                for (int e = 0; e < 2; e++) {
                    float2 cf = *(const float2*)(sm + SM_TAB + (8 * i + 2 * q + e) * 8);
#pragma unroll
                    for (int h = 0; h < 2; h++) {
                        float wj = h == 0 ? wj0 : 2.f / 512.f;
                        float pr = acc[4 * i + 2 * h + e] * wj, pi = acc[16 + 4 * i + 2 * h + e] * wj;
                        uint8_t* d2 = dst + i * 2048 + h * 128 + e * 16;
                        *(__nv_bfloat16*)(d2) = __float2bfloat16(cf.x * pr - cf.y * pi);
                        *(__nv_bfloat16*)(d2 + 1024) = __float2bfloat16(cf.x * pi + cf.y * pr);
                    }
                }
            }
            fence_async_smem();
            bar_arrive(12, 160);
        }
        acc_def(acc);
        mbar_wait(BAR(B_FULLC), 0);
        wg_fence();
#pragma unroll 1
        for (int kb = 0; kb < 8; kb++) {
#pragma unroll
            for (int ks = 0; ks < 4; ks++)
                wgmma_n64<1>(acc, desc_a(sb + SM_A + kb * 8192 + ks * 256), desc_mn(sb + SM_A + 65536 + kb * 8192 + ks * 2048, 8192), 1);
            wg_commit();
        }
        wg_wait<0>();
        fence_async_smem();
        if (lane == 0) mbar_arrive(BAR(B_AFREE), 1);
        uint8_t* dst = g_A2 + (uint32_t)(((c >> 1) * 8 + r) * 16384 + (c & 1) * 8192 + w * 2048 + g * 16 + 4 * q);
#pragma unroll
        for (int i = 0; i < 8; i++) {
            *(uint32_t*)(dst + i * 128) = pack_bf16(acc[4 * i], acc[4 * i + 1]);
            *(uint32_t*)(dst + 1024 + i * 128) = pack_bf16(acc[4 * i + 2], acc[4 * i + 3]);
        }
        {
            const int m = 4 * c + w, jp = 64 * r + m;
            int fp, php;
            dft_fp(jp, fp, php);
            const __nv_bfloat16* dh = (const __nv_bfloat16*)(sm + SM_RSTD);
            if (tid == 256) wait_count(&g_bar[4], s_tgt[4]);
            bar_sync(3, 128);
            float4 d4 = __ldcg((const float4*)g_Dh + (tid - 256));
            *(uint2*)(sm + SM_RSTD + (tid - 256) * 8) = make_uint2(pack_bf16(d4.x, d4.y), pack_bf16(d4.z, d4.w));
            bar_sync(3, 128);
#pragma unroll 1
            for (int it = 0; it < 2; it++) {
                const int ch = lane + 32 * it;
                float v[8];
#pragma unroll
                for (int e = 0; e < 8; e++) {
                    int j = 8 * ch + e, f, ph;
                    dft_fp(j, f, ph);
                    float wj = j == 0 ? 0.f : (j == 1 ? 1.f / 512.f : 2.f / 512.f);
                    float gsum = 0.f;
#pragma unroll
                    for (int sgn = 0; sgn < 2; sgn++) {
                        int mm = (sgn ? f - fp : f + fp) & 511, pp = (sgn ? ph - php : ph + php) & 511;
                        if (mm > 256) { mm = 512 - mm; pp = (512 - pp) & 511; }
                        int odd = (pp >> 7) & 1;
                        float t = __bfloat162float(dh[mm == 256 ? 1 : 2 * mm + odd]);
                        if (odd && (mm & 255) == 0) t = 0.f;
                        gsum += (pp & 256) ? -t : t;
                    }
                    v[e] = 0.5f * wj * gsum;
                }
                uint32_t off = (uint32_t)(r * 8 + (ch >> 3)) * 8192 + (m >> 3) * 1024 + (ch & 7) * 128 + (m & 7) * 16;
                *(uint4*)(g_E + off) = make_uint4(pack_bf16(v[0], v[1]), pack_bf16(v[2], v[3]), pack_bf16(v[4], v[5]), pack_bf16(v[6], v[7]));
            }
        }
    }

#pragma unroll 1
    for (int layer = 0; layer < 2; layer++) {
        if (wg < 2) {
            const int n1 = 32 * wg + 8 * w + g;
            const int ct = n1 >> 2;
            gen_col_consts(sb, tid);
            uint32_t tr2[4], ti2[4], tn2[4];
#pragma unroll
            for (int i = 0; i < 4; i++) {
                float cr[2], ci[2];
#pragma unroll
                for (int e = 0; e < 2; e++) {
                    int a = (n1 * (8 * i + 2 * q + e)) & 2047;
                    a = a >= 1024 ? a - 2048 : a;
                    float ang = (float)a * (-6.283185307179586f / 2048.f);
                    cr[e] = __cosf(ang); ci[e] = __sinf(ang);
                }
                tr2[i] = pack_bf16(cr[0], cr[1]); ti2[i] = pack_bf16(ci[0], ci[1]); tn2[i] = ti2[i] ^ 0x80008000u;
            }
            uint32_t wf[16];
            const uint4* ws = g_Wfrag + (uint32_t)(b * 1024 + n1 * 4 + q);
#pragma unroll
            for (int i = 0; i < 4; i++) {
                uint4 v = make_uint4(0, 0, 0, 0);
                if (layer == 1) v = __ldcg(ws + i * 256);
                wf[4 * i] = v.x; wf[4 * i + 1] = v.y; wf[4 * i + 2] = v.z; wf[4 * i + 3] = v.w;
            }
            mbar_wait(BAR(B_COL), layer);
            TS(4 + 12 * layer);
            if (wg == 0) TC(0 + 10 * layer);
            const uint32_t rw0 = sb + SM_RAW + ct * 1024 + q * 64 + ((q >> 1) << 4) + (g & 3) * 4, rw1 = rw0 ^ 16;
            const int pos0 = 128 * ct + 8 * q + 2 * (g & 3);
            const int sw = b == 0 ? 1 : 0;
            uint32_t xr[4][4];
            const uint32_t st0 = sb + SM_H + (n1 >> 3) * 1024 + g * 16 + 4 * q;
#pragma unroll
            for (int i = 0; i < 4; i++) {
                float2 sq = *(const float2*)(sm + SM_SSQ + (pos0 + 32 * i) * 4);
                const uint32_t rs2 = pack_bf16(rsqrtf(sq.x * (1.f / 512.f) + 1e-5f), rsqrtf(sq.y * (1.f / 512.f) + 1e-5f));
#pragma unroll
                for (int jj = 0; jj < 4; jj++) {
                    const int K = jj ^ (2 * (i & 1));
                    uint32_t a = ((K & 1) ? rw1 : rw0) + i * 256 + (K & 2) * 16;
                    if (jj < 2) a ^= sw << 4;
                    uint32_t v = lds32(a);
                    xr[jj][i] = v;
                    uint32_t o = hmul2(v, rs2);
                    if (jj == 1 && sw) o = 0u;
                    sts32(st0 + (jj & 1) * 8192 + (4 * (jj >> 1) + i) * 128, o);
                }
            }
            if (wg == 0) TC(1 + 10 * layer);
            fence_async_smem();
            bar_sync(1, 256);
            float acc[32];
            const uint32_t s1a = sb + SM_X + wg * 16384, s2b = sb + SM_X + 32768;
            wg_fence();
#pragma unroll
            for (int ks = 0; ks < 8; ks++)
                wgmma_n64<1>(acc, desc_a(s1a + (ks >> 2) * 8192 + (ks & 3) * 256), desc_b<64>(sb + SM_H + ks * 2048), ks != 0);
            wg_commit();
            if (layer == 0) {
                mbar_wait(BAR(B_WRDY), 0);
#pragma unroll
                for (int i = 0; i < 4; i++) {
                    uint4 v = __ldcg(ws + i * 256);
                    wf[4 * i] = v.x; wf[4 * i + 1] = v.y; wf[4 * i + 2] = v.z; wf[4 * i + 3] = v.w;
                }
            }
            wg_wait<0>();
            if (wg == 0) TC(2 + 10 * layer);
            uint32_t are[2][4], aim[2][4];
#pragma unroll
            for (int col = 0; col < 2; col++) {
#pragma unroll
                for (int i = 0; i < 4; i++) {
                    int o = 4 * (4 * col + i);
                    uint32_t zr = pack_bf16(acc[o], acc[o + 1]), zi = pack_bf16(acc[o + 2], acc[o + 3]);
                    are[col][i] = hfma2(zr, tr2[i], hmul2(zi, tn2[i]));
                    aim[col][i] = hfma2(zr, ti2[i], hmul2(zi, tr2[i]));
                }
            }
            wg_fence();
#pragma unroll
            for (int ks = 0; ks < 2; ks++)
                wgmma_n64_rs(acc, are[0][2 * ks], are[1][2 * ks], are[0][2 * ks + 1], are[1][2 * ks + 1], desc_b<64>(s2b + ks * 2048), ks != 0);
#pragma unroll
            for (int ks = 0; ks < 2; ks++)
                wgmma_n64_rs(acc, aim[0][2 * ks], aim[1][2 * ks], aim[0][2 * ks + 1], aim[1][2 * ks + 1], desc_b<64>(s2b + 4096 + ks * 2048), 1);
            wg_commit();
            wg_wait<0>();
            if (wg == 0) TC(3 + 10 * layer);
#pragma unroll
            for (int col = 0; col < 2; col++) {
#pragma unroll
                for (int i = 0; i < 4; i++) {
                    uint32_t wr = wf[col * 8 + 2 * i], wn = wf[col * 8 + 2 * i + 1];
                    uint32_t zr = pack_bf16(acc[4 * i + 2 * col], acc[4 * i + 2 * col + 1]);
                    uint32_t zi = pack_bf16(acc[16 + 4 * i + 2 * col], acc[16 + 4 * i + 2 * col + 1]);
                    are[col][i] = hfma2(zr, wr, hmul2(zi, wn));
                    aim[col][i] = hfma2(zr, wn, hmul2(zi ^ 0x80008000u, wr));
                }
            }
            wg_fence();
#pragma unroll
            for (int ks = 0; ks < 2; ks++)
                wgmma_n64_rs(acc, are[0][2 * ks], are[1][2 * ks], are[0][2 * ks + 1], are[1][2 * ks + 1], desc_b<64>(s2b + ks * 2048), ks != 0);
#pragma unroll
            for (int ks = 0; ks < 2; ks++)
                wgmma_n64_rs(acc, aim[0][2 * ks], aim[1][2 * ks], aim[0][2 * ks + 1], aim[1][2 * ks + 1], desc_b<64>(s2b + 4096 + ks * 2048), 1);
            wg_commit();
            wg_wait<0>();
            if (wg == 0) TC(4 + 10 * layer);
            mbar_wait(BAR(B_B1DONE), 0);
#pragma unroll
            for (int col = 0; col < 2; col++) {
#pragma unroll
                for (int i = 0; i < 4; i++) {
                    uint32_t zr = pack_bf16(acc[4 * i + 2 * col], acc[4 * i + 2 * col + 1]);
                    uint32_t zi = pack_bf16(acc[16 + 4 * i + 2 * col], acc[16 + 4 * i + 2 * col + 1]);
                    sts32(st0 + 16384 + (4 * col + i) * 128, hfma2(zr, tr2[i], hmul2(zi, tn2[i])));
                    sts32(st0 + 16384 + 8192 + (4 * col + i) * 128, hfma2(zr, ti2[i], hmul2(zi, tr2[i])));
                }
            }
            if (wg == 0) TC(5 + 10 * layer);
            fence_async_smem();
            bar_sync(1, 256);
            wg_fence();
#pragma unroll
            for (int ks = 0; ks < 8; ks++)
                wgmma_n64<1>(acc, desc_a(s1a + (ks >> 2) * 8192 + (ks & 3) * 256), desc_b<64>(sb + SM_H + 16384 + ks * 2048), ks != 0);
            wg_commit();
            wg_wait<0>();
            if (wg == 0) TC(6 + 10 * layer);
            const float sc = 1.f / 2048.f;
            const float sci0 = sw ? 0.f : -sc;
            const float wr0 = sw ? 0.5f : 1.f, wi0 = sw ? 0.f : 1.f;
#pragma unroll
            for (int i = 0; i < 4; i++) {
                float ss0, ss1;
#pragma unroll
                for (int col = 0; col < 2; col++) {
                    int o = 4 * (4 * col + i);
                    uint32_t vr = xr[2 * col][i], vi = xr[2 * col + 1][i];
                    float si = col == 0 ? sci0 : -sc;
                    uint32_t nr = pack_bf16(fmaf(acc[o], sc, bf_lo(vr)), fmaf(acc[o + 1], sc, bf_hi(vr)));
                    uint32_t ni = pack_bf16(fmaf(acc[o + 2], si, bf_lo(vi)), fmaf(acc[o + 3], si, bf_hi(vi)));
                    float a0 = bf_lo(nr), a1 = bf_hi(nr), b0 = bf_lo(ni), b1 = bf_hi(ni);
                    if (col == 0) {
                        ss0 = wr0 * a0 * a0 + wi0 * b0 * b0;
                        ss1 = wr0 * a1 * a1 + wi0 * b1 * b1;
                    } else {
                        ss0 += a0 * a0 + b0 * b0;
                        ss1 += a1 * a1 + b1 * b1;
                    }
                    const int K = (2 * col) ^ (2 * (i & 1));
                    uint32_t a = rw0 + i * 256 + K * 16;
                    if (col == 0) a ^= sw << 4;
                    sts32(a, nr);
                    sts32(a ^ 16, ni);
                }
                *(float2*)(sm + SM_SSQ + (pos0 + 32 * i) * 4) = make_float2(ss0 * (2.f / 512.f), ss1 * (2.f / 512.f));
            }
            fence_async_smem();
        }
        TS(5 + 12 * layer);
        if (wg == 0) TC(7 + 10 * layer);
        bar_arrive(5, 416);

        float acc[64];
        float* s_rstd = (float*)(sm + SM_RSTD);
        float* s_mean = (float*)(sm + SM_MEAN);
        const unsigned epoch = s_tgt[0] >> 7;
        const uint32_t pt3 = 1u + (2u * epoch + layer) % 3u;
        const uint32_t ptag = (pt3 & 1u) | ((pt3 & 2u) << 15);
        const uint64_t dstep = layer == 0 ? 16 : 2;
        auto c_desc = [&](int s) { return layer == 0 ? desc_a(sb + SM_A + s * 16384) : desc_k(sb + SM_A + s * 16384); };
        if (wg < 2) {
            const int prow = 32 * wg + 8 * w + g;
            const float2 l1 = *(const float2*)(sm + SM_LAM + prow * 8);
            float lr32 = l1.x, li32 = l1.y;
#pragma unroll
            for (int i = 0; i < 5; i++) { float t = lr32 * lr32 - li32 * li32; li32 = 2.f * lr32 * li32; lr32 = t; }
            float lr128 = lr32, li128 = li32;
#pragma unroll
            for (int i = 0; i < 2; i++) { float t = lr128 * lr128 - li128 * li128; li128 = 2.f * lr128 * li128; lr128 = t; }
            const float lr1 = l1.x, li1 = l1.y;
            acc_def(acc);
#pragma unroll 1
            for (int kb = 0; kb < 8; kb++) {
                mbar_wait(BAR(B_AFULL + kb), 0);
                mbar_wait(BAR(B_XFULL + (kb & 3)), (kb >> 2) & 1);
                wg_fence();
#pragma unroll
                for (int ks = 0; ks < 4; ks++)
                    wgmma_n128<1>(acc, desc_a(sb + SM_A + kb * 16384 + wg * 8192 + ks * 256),
                                  desc_b<128>(sb + SM_X + (kb & 3) * 24576 + ks * 4096), 1);
                wg_commit();
                wg_wait<1>();
                if (kb > 0 && lane == 0) {
                    mbar_arrive(BAR(B_AEMPTY + kb - 1), 1); mbar_arrive(BAR(B_XEMPTY + ((kb - 1) & 3)), 1);
                    mbar_arrive_remote(mapa(BAR(B_XEMPTY + ((kb - 1) & 3)), par ^ 1));
                }
            }
            wg_wait<0>();
            if (lane == 0) {
                mbar_arrive(BAR(B_AEMPTY + 7), 1); mbar_arrive(BAR(B_XEMPTY + 3), 1);
                mbar_arrive_remote(mapa(BAR(B_XEMPTY + 3), par ^ 1)); mbar_arrive_remote(mapa(BAR(B_RFREE), par ^ 1));
            }
            bar_arrive(14, 384);
            TS(6 + 12 * layer);
            bar_sync(4, 384);
            TS(7 + 12 * layer);
            float er = 0.f, ei = 0.f;
#pragma unroll
            for (int i = 0; i < 16; i++) {
                float2 rs = *(const float2*)(s_rstd + 128 + 8 * i + 2 * q);
                acc[4 * i] *= rs.x; acc[4 * i + 1] *= rs.y; acc[4 * i + 2] *= rs.x; acc[4 * i + 3] *= rs.y;
                float nr = lr1 * er - li1 * ei + acc[4 * i], ni = lr1 * ei + li1 * er + acc[4 * i + 2];
                er = lr1 * nr - li1 * ni + acc[4 * i + 1];
                ei = lr1 * ni + li1 * nr + acc[4 * i + 3];
            }
            float cr = 0.f, ci = 0.f, tr = 0.f, ti = 0.f;
#pragma unroll
            for (int qq = 0; qq < 4; qq++) {
                float xr_ = __shfl_sync(~0u, er, (lane & ~3) | qq), xi_ = __shfl_sync(~0u, ei, (lane & ~3) | qq);
                if (qq == q) { cr = tr; ci = ti; }
                float nr = lr32 * tr - li32 * ti + xr_, ni = lr32 * ti + li32 * tr + xi_;
                tr = nr; ti = ni;
            }
            float4* eb = g_Ebuf + (uint32_t)(layer * 16 * 512 + 64 * r + prow);
            if (q == 0 && c < 15) st_relaxed_f4(eb + c * 512, make_float4(tr, ti, __uint_as_float(epoch), 0.f));
            TS(8 + 12 * layer);
            float pr[4], pi[4];
            {
                unsigned n = 0;
                bool ok;
#pragma unroll 1
                do {
                    ok = true;
#pragma unroll
                    for (int k = 0; k < 4; k++) {
                        float4 v = make_float4(0.f, 0.f, __uint_as_float(epoch), 0.f);
                        if (4 * k + q < c) v = ld_relaxed_f4(eb + (4 * k + q) * 512);
                        pr[k] = v.x; pi[k] = v.y;
                        ok = ok && __float_as_uint(v.z) == epoch;
                    }
                } while (!ok && ++n < SPIN_LIMIT);
            }
            __syncwarp();
            TS(9 + 12 * layer);
            float hr = 0.f, hi = 0.f;
#pragma unroll
            for (int cc = 0; cc < 15; cc++) {
                float xr_ = __shfl_sync(~0u, pr[cc >> 2], (lane & ~3) | (cc & 3)), xi_ = __shfl_sync(~0u, pi[cc >> 2], (lane & ~3) | (cc & 3));
                if (cc < c) {
                    float nr = lr128 * hr - li128 * hi + xr_, ni = lr128 * hi + li128 * hr + xi_;
                    hr = nr; hi = ni;
                }
            }
#pragma unroll
            for (int qq = 0; qq < 3; qq++) {
                if (qq < q) { float nr = lr32 * hr - li32 * hi, ni = lr32 * hi + li32 * hr; hr = nr; hi = ni; }
            }
            er = cr + hr; ei = ci + hi;
            bar_sync(7, 384);
            mbar_wait_cluster(BAR(B_RFREE), layer);
            const uint32_t ha = sb + SM_HH + par * 32768 + (prow >> 3) * 1024 + g * 16 + 4 * q;
#pragma unroll
            for (int i = 0; i < 16; i++) {
                float nr = lr1 * er - li1 * ei + acc[4 * i], ni = lr1 * ei + li1 * er + acc[4 * i + 2];
                er = lr1 * nr - li1 * ni + acc[4 * i + 1];
                ei = lr1 * ni + li1 * nr + acc[4 * i + 3];
                sts32(ha + (i >> 3) * 16384 + (i & 7) * 128, pack_bf16(nr, er));
                sts32(ha + (i >> 3) * 16384 + 8192 + (i & 7) * 128, pack_bf16(ni, ei));
                if (i == 7) { fence_async_smem(); bar_arrive(13, 288); }
            }
            fence_async_smem();
            acc_def(acc);
            float acc2[32];
            acc_def(acc2);
            TS(10 + 12 * layer);
            bar_sync(6, 416);
            TS(11 + 12 * layer);
            float (&a0)[32] = *reinterpret_cast<float (*)[32]>(&acc[0]);
            float (&a1)[32] = *reinterpret_cast<float (*)[32]>(&acc[32]);
            auto tile_mma = [&](float (&d)[32], int u) {
#pragma unroll 1
                for (int k = 0; k < 2; k++) {
                    const uint32_t hb = sb + SM_HH + (par ^ k) * 32768 + wg * 16384;
                    if (k == 1) mbar_wait(BAR(wg ? B_HPEER1 : B_HPEER), layer);
                    mbar_wait(BAR(B_AFULL + 2 * u + k), 1);
                    const uint64_t da = c_desc(2 * u + k);
                    wg_fence();
#pragma unroll
                    for (int ks = 0; ks < 4; ks++) wgmma_n64s<1>(d, da + ks * dstep, desc_b<64>(hb + ks * 2048), 1);
#pragma unroll
                    for (int ks = 0; ks < 4; ks++) wgmma_n64s<-1>(d, da + 512 + ks * dstep, desc_b<64>(hb + 8192 + ks * 2048), 1);
                }
                wg_commit();
            };
            auto tile_ship = [&](float (&d)[32], int u) {
                uint4* dst = g_P + (uint32_t)(((c * 8 + 2 * ((pi_ + 1 + u) & 3) + par) * 4 + pi_) * 1024 + wg * 512 + (tid & 127));
#pragma unroll
                for (int i = 0; i < 4; i++)
                    dst[i * 128] = make_uint4((pack_bf16(d[8 * i], d[8 * i + 1]) & 0xfffefffeu) | ptag, pack_bf16(d[8 * i + 2], d[8 * i + 3]),
                                              pack_bf16(d[8 * i + 4], d[8 * i + 5]), pack_bf16(d[8 * i + 6], d[8 * i + 7]));
            };
            tile_mma(a0, 0);
            if ((tid & 127) == 0) mbar_arrive_remote(mapa(BAR(B_HDONE), par ^ 1));
            __syncwarp();
            tile_mma(a1, 1);
            wg_wait<1>();
            tile_ship(a0, 0);
            tile_mma(acc2, 2);
            bar_arrive(12, 384);
            wg_wait<1>();
            tile_ship(a1, 1);
            wg_wait<0>();
            tile_ship(acc2, 2);
            if (lane < 6) mbar_arrive(BAR(B_AEMPTY + lane), 1);
            TS(12 + 12 * layer);
        } else {
            const int t2 = tid - 256;
            const uint8_t* ximg = g_X + (uint32_t)layer * 16 * 8 * 16384;
            mbar_wait(BAR(B_SSQ), layer);
            TS(6 + 12 * layer);
            float sqv[16];
#pragma unroll
            for (int i = 0; i < 16; i++) sqv[i] = __ldcg(g_ssqc + (layer * 16 + i) * 2048 + 128 * c + t2);
            const unsigned short xm = __ldcg((const unsigned short*)(ximg + (uint32_t)(c * 8 * 16384 + (t2 >> 3) * 128 + (t2 & 7) * 2)));
            acc_def(acc);
#pragma unroll 1
            for (int kb = 0; kb < 8; kb++) {
                if (kb == 4) {
                    wg_wait<0>();
                    if (lane == 0) { mbar_arrive(BAR(B_XEMPTY + 3), 1); mbar_arrive_remote(mapa(BAR(B_XEMPTY + 3), par ^ 1)); }
                    float tot = 0.f;
#pragma unroll
                    for (int i = 0; i < 16; i++) tot += sqv[i];
                    float rs = rsqrtf(tot * (1.f / 512.f) + 1e-5f);
                    s_rstd[t2] = rs;
                    s_rstd[128 + t2] = 2.f * rs;
                    s_mean[t2] = layer == 0 ? 0.f : __uint_as_float((uint32_t)xm << 16) * (1.f / 512.f);
                    TS(7 + 12 * layer);
                    bar_arrive(4, 384);
                    bar_sync(14, 384);
                }
                mbar_wait(BAR(B_XFULL + (kb & 3)), (kb >> 2) & 1);
                wg_fence();
#pragma unroll
                for (int ks = 0; ks < 4; ks++)
                    wgmma_n128<1>(acc, desc_a(sb + SM_X + (kb & 3) * 24576 + 16384 + ks * 256), desc_b<128>(sb + SM_X + (kb & 3) * 24576 + ks * 4096), 1);
                wg_commit();
                wg_wait<1>();
                if ((kb & 3) != 0 && lane == 0) { mbar_arrive(BAR(B_XEMPTY + ((kb - 1) & 3)), 1); mbar_arrive_remote(mapa(BAR(B_XEMPTY + ((kb - 1) & 3)), par ^ 1)); }
            }
            wg_wait<0>();
            if (lane == 0) { mbar_arrive(BAR(B_XEMPTY + 3), 1); mbar_arrive_remote(mapa(BAR(B_XEMPTY + 3), par ^ 1)); mbar_arrive_remote(mapa(BAR(B_RFREE), par ^ 1)); }
            bar_arrive(7, 384);
            bar_sync(3, 128);
            TS(9 + 12 * layer);
            const int m0 = 16 * w + g;
            const uint32_t xoff = (uint32_t)((c * 8 + own) * 16384 + w * 4096 + g * 16 + 4 * q);
            if (layer == 0) {
                const uint8_t* xs = g_X + xoff;
#pragma unroll
                for (int i = 0; i < 16; i++) {
                    float2 rs = *(const float2*)(s_rstd + 8 * i + 2 * q);
                    uint32_t x0v = __ldcg((const uint32_t*)(xs + i * 128)), x1v = __ldcg((const uint32_t*)(xs + 2048 + i * 128));
                    acc[4 * i] = acc[4 * i] * rs.x + bf_lo(x0v);
                    acc[4 * i + 1] = acc[4 * i + 1] * rs.y + bf_hi(x0v);
                    acc[4 * i + 2] = acc[4 * i + 2] * rs.x + bf_lo(x1v);
                    acc[4 * i + 3] = acc[4 * i + 3] * rs.y + bf_hi(x1v);
                }
            } else {
                float d0 = ldbf(p.dskip + 64 * own + m0), d1 = ldbf(p.dskip + 64 * own + m0 + 8);
#pragma unroll
                for (int i = 0; i < 16; i++) {
                    float2 rs = *(const float2*)(s_rstd + 8 * i + 2 * q);
                    float2 mn = *(const float2*)(s_mean + 8 * i + 2 * q);
                    acc[4 * i] = acc[4 * i] * (1.f + rs.x * d0) + mn.x;
                    acc[4 * i + 1] = acc[4 * i + 1] * (1.f + rs.y * d0) + mn.y;
                    acc[4 * i + 2] = acc[4 * i + 2] * (1.f + rs.x * d1) + mn.x;
                    acc[4 * i + 3] = acc[4 * i + 3] * (1.f + rs.y * d1) + mn.y;
                }
            }
            TS(10 + 12 * layer);
            bar_sync(6, 416);
            TS(11 + 12 * layer);
            {
                float (&a0)[32] = *reinterpret_cast<float (*)[32]>(&acc[0]);
                float (&a1)[32] = *reinterpret_cast<float (*)[32]>(&acc[32]);
#pragma unroll 1
                for (int k = 0; k < 2; k++) {
                    const uint32_t hb = sb + SM_HH + (par ^ k) * 32768;
                    if (k == 1) {
                        mbar_wait(BAR(B_HPEER), layer);
                        mbar_wait(BAR(B_HPEER1), layer);
                        bar_sync(12, 384);
                    }
                    mbar_wait(BAR(B_AFULL + 6 + k), 1);
                    const uint64_t da = c_desc(6 + k);
                    wg_fence();
#pragma unroll
                    for (int ks = 0; ks < 4; ks++) {
                        wgmma_n64s<1>(a0, da + ks * dstep, desc_b<64>(hb + ks * 2048), 1);
                        wgmma_n64s<1>(a1, da + ks * dstep, desc_b<64>(hb + 16384 + ks * 2048), 1);
                    }
#pragma unroll
                    for (int ks = 0; ks < 4; ks++) {
                        wgmma_n64s<-1>(a0, da + 512 + ks * dstep, desc_b<64>(hb + 8192 + ks * 2048), 1);
                        wgmma_n64s<-1>(a1, da + 512 + ks * dstep, desc_b<64>(hb + 16384 + 8192 + ks * 2048), 1);
                    }
                    wg_commit();
                }
                wg_wait<0>();
            }
#pragma unroll
            for (int i = 0; i < 16; i++)
                *(float4*)(sm + SM_A + 6 * 16384 + i * 2048 + t2 * 16) = make_float4(acc[4 * i], acc[4 * i + 1], acc[4 * i + 2], acc[4 * i + 3]);
            TS(12 + 12 * layer);
        }
        {
            const int t = tid & 127;
            const int nch = wg == 2 ? 2 : 3;
            const uint4* pb = g_P + (uint32_t)((c * 8 + r) * 4 * 1024 + wg * 128 + t);
            uint4 v[3][3];
            unsigned n = 0;
#pragma unroll 1
            while (true) {
                if (lane == 31) {
#pragma unroll 1
                    while (true) {
                        uint32_t bad = 0;
#pragma unroll
                        for (int sx = 0; sx < 3; sx++) {
                            uint32_t t0;
                            asm volatile("ld.relaxed.gpu.global.u32 %0, [%1];" : "=r"(t0) : "l"(pb + ((pi_ + 1 + sx) & 3) * 1024 + (nch - 1) * 384) : "memory");
                            bad |= t0 ^ ptag;
                        }
                        if (!(bad & 0x00010001u) || ++n >= SPIN_LIMIT) break;
                    }
                }
                __syncwarp();
                uint32_t bad = 0;
#pragma unroll
                for (int k = 0; k < 3; k++)
#pragma unroll
                    for (int sx = 0; sx < 3; sx++) {
                        v[k][sx] = make_uint4(ptag, 0, 0, 0);
                        if (k < nch) v[k][sx] = ld_relaxed_u4(pb + ((pi_ + 1 + sx) & 3) * 1024 + k * 384);
                        bad |= v[k][sx].x ^ ptag;
                    }
                if (!__any_sync(~0u, bad & 0x00010001u) || ++n >= SPIN_LIMIT) break;
            }
            bar_sync(8, 384);
            TS(13 + 12 * layer);
            const int m0 = 16 * w + g;
            const float w0 = (own == 0 && m0 < 2) ? (m0 == 0 ? 0.f : 0.5f) : 1.f;
#pragma unroll
            for (int k = 0; k < 3; k++) {
                if (k < nch) {
                    const int i = wg + 3 * k;
                    float4 a = *(const float4*)(sm + SM_A + 6 * 16384 + (2 * i) * 2048 + t * 16);
                    float4 bq = *(const float4*)(sm + SM_A + 6 * 16384 + (2 * i + 1) * 2048 + t * 16);
#pragma unroll
                    for (int sx = 0; sx < 3; sx++) {
                        a.x += bf_lo(v[k][sx].x); a.y += bf_hi(v[k][sx].x); a.z += bf_lo(v[k][sx].y); a.w += bf_hi(v[k][sx].y);
                        bq.x += bf_lo(v[k][sx].z); bq.y += bf_hi(v[k][sx].z); bq.z += bf_lo(v[k][sx].w); bq.w += bf_hi(v[k][sx].w);
                    }
                    if (layer == 0) {
                        uint8_t* xd = g_X + (uint32_t)((16 * 8 + c * 8 + own) * 16384 + w * 4096 + g * 16 + 4 * q + i * 256);
                        uint32_t v0 = pack_bf16(a.x, a.y), v1 = pack_bf16(a.z, a.w), v2 = pack_bf16(bq.x, bq.y), v3 = pack_bf16(bq.z, bq.w);
                        *(uint32_t*)(xd) = v0; *(uint32_t*)(xd + 2048) = v1; *(uint32_t*)(xd + 128) = v2; *(uint32_t*)(xd + 2048 + 128) = v3;
                        float sq[4];
                        sq[0] = w0 * bf_lo(v0) * bf_lo(v0) + bf_lo(v1) * bf_lo(v1);
                        sq[1] = w0 * bf_hi(v0) * bf_hi(v0) + bf_hi(v1) * bf_hi(v1);
                        sq[2] = w0 * bf_lo(v2) * bf_lo(v2) + bf_lo(v3) * bf_lo(v3);
                        sq[3] = w0 * bf_hi(v2) * bf_hi(v2) + bf_hi(v3) * bf_hi(v3);
                        float u0 = (g & 1) ? sq[2] : sq[0], u1 = (g & 1) ? sq[3] : sq[1];
                        u0 += __shfl_xor_sync(~0u, (g & 1) ? sq[0] : sq[2], 4);
                        u1 += __shfl_xor_sync(~0u, (g & 1) ? sq[1] : sq[3], 4);
                        float z = (g & 2) ? u1 : u0;
                        z += __shfl_xor_sync(~0u, (g & 2) ? u0 : u1, 8);
                        z += __shfl_xor_sync(~0u, z, 16);
                        if (g < 4) atomicAdd(s_mean + 16 * i + 8 * (g & 1) + 2 * q + (g >> 1), z);
                    } else {
                        float* o = p.out + (uint32_t)((128 * c + 32 * q + 4 * i) * 512 + 64 * own + m0);
                        o[0] = a.x; o[512] = a.y; o[8] = a.z; o[512 + 8] = a.w;
                        o[1024] = bq.x; o[1536] = bq.y; o[1024 + 8] = bq.z; o[1536 + 8] = bq.w;
                    }
                }
            }
            if (wg < 2) mbar_wait_cluster(BAR(B_HDONE), layer);
            if (layer == 0) {
                fence_async_smem();
                bar_sync(9, 384);
                TS(14 + 12 * layer);
                if (wg == 2) {
                    atomicAdd(g_ssq + 2048 + 128 * c + t, s_mean[t] * (2.f / 512.f));
                    bar_sync(3, 128);
                    if (lane == 0) { mbar_arrive(BAR(B_AEMPTY + 6), 2); mbar_arrive(BAR(B_AEMPTY + 7), 2); }
                    if (t == 0) { fence_async(); red_release(&g_bar[2], 1); }
                }
            }
        }
        TS(15 + 12 * layer);
        if (wg == 0) TC(31);
    }
}

typedef CUresult (*EncFn)(CUtensorMap*, CUtensorMapDataType, cuuint32_t, void*, const cuuint64_t*, const cuuint64_t*,
                          const cuuint32_t*, const cuuint32_t*, CUtensorMapInterleave, CUtensorMapSwizzle,
                          CUtensorMapL2promotion, CUtensorMapFloatOOBfill);

void launch_impl(void* const* d_in, void* d_out, int stop) {
    static EncFn enc = nullptr;
    if (!enc) {
        void* fn = nullptr;
        cudaDriverEntryPointQueryResult qr;
        cudaGetDriverEntryPoint("cuTensorMapEncodeTiled", &fn, cudaEnableDefault, &qr);
        enc = (EncFn)fn;
        cudaFuncSetAttribute(fused_kernel, cudaFuncAttributeMaxDynamicSharedMemorySize, SM_TOTAL);
    }
    CUtensorMap tx, tbr, tbi, tcr, tci, tcol;
    {
        void* gx = nullptr;
        cudaGetSymbolAddress(&gx, g_X);
        cuuint64_t gd[5] = {64, 16, 64, 16, 2};
        cuuint64_t gs[4] = {128, 2048, 128 * 1024, 2048 * 1024};
        cuuint32_t bx[5] = {32, 16, 1, 16, 1};
        cuuint32_t es[5] = {1, 1, 1, 1, 1};
        enc(&tcol, CU_TENSOR_MAP_DATA_TYPE_BFLOAT16, 5, gx, gd, gs, bx, es, CU_TENSOR_MAP_INTERLEAVE_NONE,
            CU_TENSOR_MAP_SWIZZLE_64B, CU_TENSOR_MAP_L2_PROMOTION_NONE, CU_TENSOR_MAP_FLOAT_OOB_FILL_NONE);
    }
    {
        cuuint64_t gd[5] = {512, 2, 4, 16, 16};
        cuuint64_t gs[4] = {1024, 32 * 1024, 2 * 1024, 128 * 1024};
        cuuint32_t bx[5] = {64, 2, 4, 8, 1};
        cuuint32_t es[5] = {1, 1, 1, 1, 1};
        enc(&tx, CU_TENSOR_MAP_DATA_TYPE_BFLOAT16, 5, d_in[0], gd, gs, bx, es, CU_TENSOR_MAP_INTERLEAVE_NONE,
            CU_TENSOR_MAP_SWIZZLE_128B, CU_TENSOR_MAP_L2_PROMOTION_L2_128B, CU_TENSOR_MAP_FLOAT_OOB_FILL_NONE);
    }
    auto mk2 = [&](CUtensorMap* m, void* ptr, cuuint32_t rows) {
        cuuint64_t gd[2] = {512, 512};
        cuuint64_t gs[1] = {1024};
        cuuint32_t bx[2] = {64, rows};
        cuuint32_t es[2] = {1, 1};
        enc(m, CU_TENSOR_MAP_DATA_TYPE_BFLOAT16, 2, ptr, gd, gs, bx, es, CU_TENSOR_MAP_INTERLEAVE_NONE,
            CU_TENSOR_MAP_SWIZZLE_128B, CU_TENSOR_MAP_L2_PROMOTION_L2_128B, CU_TENSOR_MAP_FLOAT_OOB_FILL_NONE);
    };
    mk2(&tbr, d_in[6], 32);
    mk2(&tbi, d_in[7], 32);
    mk2(&tcr, d_in[8], 64);
    mk2(&tci, d_in[9], 64);
    Params p;
    p.x0 = (const __nv_bfloat16*)d_in[0];
    p.w_r = (const __nv_bfloat16*)d_in[1];
    p.w_i = (const __nv_bfloat16*)d_in[2];
    p.lam_re = (const __nv_bfloat16*)d_in[4];
    p.lam_im = (const __nv_bfloat16*)d_in[5];
    p.log_dt = (const __nv_bfloat16*)d_in[10];
    p.dskip = (const __nv_bfloat16*)d_in[11];
    p.out = (float*)d_out;
    p.stop = stop;
    cudaLaunchConfig_t cfg = {};
    cfg.gridDim = dim3(NCTA); cfg.blockDim = dim3(NTHREADS); cfg.dynamicSmemBytes = SM_TOTAL; cfg.stream = cudaStreamPerThread;
    cudaLaunchAttribute at[1];
    at[0].id = cudaLaunchAttributeClusterDimension;
    at[0].val.clusterDim.x = 2; at[0].val.clusterDim.y = 1; at[0].val.clusterDim.z = 1;
    cfg.attrs = at; cfg.numAttrs = 1;
    cudaLaunchKernelEx(&cfg, fused_kernel, tx, tbr, tbi, tcr, tci, tcol, p);
}

}

extern "C" void kernel_launch(void* const* d_in, const int* in_sizes, int n_in, void* d_out, int out_size) {
    (void)in_sizes; (void)n_in; (void)out_size;
    launch_impl(d_in, d_out, 100);
}
```

```cpp
#include <cuda_runtime.h>
#include <cuda_bf16.h>
#include <cuda.h>
#include <stdint.h>

namespace {

constexpr int NCTA = 128;
constexpr int NTHREADS = 512;
constexpr int SM_A = 0;
constexpr int SM_X = 131072;
constexpr int SM_H = 196608;
constexpr int SM_HH = SM_X + 32768;
constexpr int SM_M = 229376;
constexpr int SM_TOTAL = 232448;
constexpr int SM_BAR = SM_M;
constexpr int SM_TGT = SM_M + 392;
constexpr int SM_LAM = SM_M + 416;
constexpr int SM_TAB = SM_M + 928;
constexpr int SM_RSTD = SM_M + 1920;
constexpr int SM_MEAN = SM_TAB;
constexpr int SM_T64 = SM_M + 2944;
constexpr int SM_B1ST = SM_H + 24576;
constexpr int SM_RAW = SM_X + 40960;
constexpr int SM_SSQ = SM_X + 57344;
constexpr int B_FULL0 = 0;
constexpr int B_EMPTY0 = 8;
constexpr int B_FULLC = 12;
constexpr int B_AFULL = 13;
constexpr int B_AEMPTY = 21;
constexpr int B_XFULL = 29;
constexpr int B_XEMPTY = 33;
constexpr int B_AFREE = 37;
constexpr int B_COL = 38;
constexpr int B_SSQ = 39;
constexpr int B_HPEER = 40;
constexpr int B_RFREE = 41;
constexpr int B_HDONE = 42;
constexpr int B_WRDY = 43;
constexpr int B_HPEER1 = 44;
constexpr int B_FULLB = 45;
constexpr int B_BFREE = 46;
constexpr int B_SETUP = 47;
constexpr int B_B1DONE = 48;
constexpr int NBARS = 49;

__device__ __align__(1024) uint8_t g_X[2 * 16 * 8 * 16384];
__device__ __align__(1024) uint8_t g_A1[8 * 8 * 16384];
__device__ __align__(1024) uint8_t g_A2[8 * 8 * 16384];
__device__ __align__(1024) uint8_t g_E[2 * 8 * 8 * 8192];
__device__ __align__(16) float g_ssq[2 * 2048];
__device__ __align__(16) float g_ssqc[2 * 16 * 2048];
__device__ __align__(16) float g_Dh[512];
__device__ __align__(16) uint4 g_Wfrag[128 * 4 * 256];
__device__ __align__(16) float4 g_Ebuf[2 * 16 * 512];
__device__ __align__(16) uint4 g_P[16 * 8 * 4 * 1024];
__device__ unsigned g_bar[8];
__device__ unsigned g_err;
#define TX(i)
#define TQ(i)
#define TS(i)
#define TC(i)

constexpr unsigned SPIN_LIMIT = 1u << 22;

__device__ __forceinline__ uint32_t s2u(const void* p) { return (uint32_t)__cvta_generic_to_shared(p); }
__device__ __forceinline__ void mbar_init(uint32_t a, uint32_t c) {
    asm volatile("mbarrier.init.shared::cta.b64 [%0], %1;" ::"r"(a), "r"(c) : "memory");
}
__device__ __forceinline__ void mbar_expect(uint32_t a, uint32_t bytes) {
    asm volatile("mbarrier.arrive.expect_tx.shared::cta.b64 _, [%0], %1;" ::"r"(a), "r"(bytes) : "memory");
}
__device__ __forceinline__ void mbar_arrive(uint32_t a, uint32_t cnt) {
    asm volatile("mbarrier.arrive.shared::cta.b64 _, [%0], %1;" ::"r"(a), "r"(cnt) : "memory");
}
__device__ __forceinline__ bool mbar_try(uint32_t a, uint32_t parity) {
    uint32_t ok;
    asm volatile("{\n.reg .pred p;\nmbarrier.try_wait.parity.shared::cta.b64 p, [%1], %2;\nselp.u32 %0, 1, 0, p;\n}"
                 : "=r"(ok) : "r"(a), "r"(parity) : "memory");
    return ok != 0;
}
__device__ __forceinline__ void mbar_wait(uint32_t a, uint32_t parity) {
    asm volatile("{\n.reg .pred p, q;\n.reg .u32 n;\nmov.u32 n, 0;\n"
                 "W_%=:\nmbarrier.try_wait.parity.shared::cta.b64 p, [%0], %1;\n@p bra D_%=;\n"
                 "add.u32 n, n, 1;\nsetp.lt.u32 q, n, 4194304;\n@q bra W_%=;\nD_%=:\n}" ::"r"(a), "r"(parity) : "memory");
}
__device__ __forceinline__ void bulk_g2s(uint32_t dst, const void* src, uint32_t bytes, uint32_t bar) {
    asm volatile("cp.async.bulk.shared::cluster.global.mbarrier::complete_tx::bytes [%0], [%1], %2, [%3];" ::"r"(dst),
                 "l"(src), "r"(bytes), "r"(bar) : "memory");
}
__device__ __forceinline__ void tma_2d(uint32_t dst, const CUtensorMap* m, int c0, int c1, uint32_t bar) {
    asm volatile("cp.async.bulk.tensor.2d.shared::cluster.global.mbarrier::complete_tx::bytes [%0], [%1, {%3,%4}], [%2];" ::"r"(dst),
                 "l"(m), "r"(bar), "r"(c0), "r"(c1) : "memory");
}
__device__ __forceinline__ void tma_5d(uint32_t dst, const CUtensorMap* m, int c0, int c1, int c2, int c3, int c4, uint32_t bar) {
    asm volatile("cp.async.bulk.tensor.5d.shared::cluster.global.mbarrier::complete_tx::bytes [%0], [%1, {%3,%4,%5,%6,%7}], [%2];" ::"r"(dst),
                 "l"(m), "r"(bar), "r"(c0), "r"(c1), "r"(c2), "r"(c3), "r"(c4) : "memory");
}
__device__ __forceinline__ void tma_2d_mc(uint32_t dst, const CUtensorMap* m, int c0, int c1, uint32_t bar) {
    asm volatile("cp.async.bulk.tensor.2d.shared::cluster.global.mbarrier::complete_tx::bytes.multicast::cluster [%0], [%1, {%3,%4}], [%2], %5;" ::"r"(dst),
                 "l"(m), "r"(bar), "r"(c0), "r"(c1), "h"((unsigned short)3) : "memory");
}
__device__ __forceinline__ void tma_5d_mc(uint32_t dst, const CUtensorMap* m, int c0, int c1, int c2, int c3, int c4, uint32_t bar) {
    asm volatile("cp.async.bulk.tensor.5d.shared::cluster.global.mbarrier::complete_tx::bytes.multicast::cluster [%0], [%1, {%3,%4,%5,%6,%7}], [%2], %8;" ::"r"(dst),
                 "l"(m), "r"(bar), "r"(c0), "r"(c1), "r"(c2), "r"(c3), "r"(c4), "h"((unsigned short)3) : "memory");
}
__device__ __forceinline__ void bulk_g2s_mc(uint32_t dst, const void* src, uint32_t bytes, uint32_t bar) {
    asm volatile("cp.async.bulk.shared::cluster.global.mbarrier::complete_tx::bytes.multicast::cluster [%0], [%1], %2, [%3], %4;" ::"r"(dst),
                 "l"(src), "r"(bytes), "r"(bar), "h"((unsigned short)3) : "memory");
}
__device__ __forceinline__ void tma_store_5d(const CUtensorMap* m, int c0, int c1, int c2, int c3, int c4, uint32_t src) {
    asm volatile("cp.async.bulk.tensor.5d.global.shared::cta.bulk_group [%0, {%2,%3,%4,%5,%6}], [%1];" ::"l"(m), "r"(src),
                 "r"(c0), "r"(c1), "r"(c2), "r"(c3), "r"(c4) : "memory");
}
__device__ __forceinline__ uint32_t lds32(uint32_t a) { uint32_t v; asm volatile("ld.shared.u32 %0, [%1];" : "=r"(v) : "r"(a) : "memory"); return v; }
__device__ __forceinline__ uint4 ld_relaxed_u4(const uint4* p) {
    uint4 v;
    asm volatile("ld.relaxed.gpu.global.v4.u32 {%0,%1,%2,%3}, [%4];" : "=r"(v.x), "=r"(v.y), "=r"(v.z), "=r"(v.w) : "l"(p) : "memory");
    return v;
}
__device__ __forceinline__ void fence_async() { asm volatile("fence.proxy.async.global;" ::: "memory"); }
__device__ __forceinline__ void red_relaxed(unsigned* p, unsigned v) {
    asm volatile("red.relaxed.gpu.global.add.u32 [%0], %1;" ::"l"(p), "r"(v) : "memory");
}
__device__ __forceinline__ uint32_t mapa(uint32_t a, uint32_t rank) {
    uint32_t d;
    asm("mapa.shared::cluster.u32 %0, %1, %2;" : "=r"(d) : "r"(a), "r"(rank));
    return d;
}
__device__ __forceinline__ void mbar_arrive_remote(uint32_t ra) {
    asm volatile("mbarrier.arrive.relaxed.cluster.shared::cluster.b64 _, [%0];" ::"r"(ra) : "memory");
}
__device__ __forceinline__ void mbar_wait_cluster(uint32_t a, uint32_t parity) {
    asm volatile("{\n.reg .pred p, q;\n.reg .u32 n;\nmov.u32 n, 0;\n"
                 "W_%=:\nmbarrier.try_wait.parity.acquire.cluster.shared::cta.b64 p, [%0], %1;\n@p bra D_%=;\n"
                 "add.u32 n, n, 1;\nsetp.lt.u32 q, n, 4194304;\n@q bra W_%=;\nD_%=:\n}" ::"r"(a), "r"(parity) : "memory");
}
__device__ __forceinline__ void bulk_s2peer(uint32_t rdst, uint32_t src, uint32_t bytes, uint32_t rbar) {
    asm volatile("cp.async.bulk.shared::cluster.shared::cta.mbarrier::complete_tx::bytes [%0], [%1], %2, [%3];" ::"r"(rdst),
                 "r"(src), "r"(bytes), "r"(rbar) : "memory");
}
__device__ __forceinline__ void fence_async_smem() { asm volatile("fence.proxy.async.shared::cta;" ::: "memory"); }
__device__ __forceinline__ void wg_fence() { asm volatile("wgmma.fence.sync.aligned;" ::: "memory"); }
__device__ __forceinline__ void wg_commit() { asm volatile("wgmma.commit_group.sync.aligned;" ::: "memory"); }
template <int N> __device__ __forceinline__ void wg_wait() { asm volatile("wgmma.wait_group.sync.aligned %0;" ::"n"(N) : "memory"); }
__device__ __forceinline__ void bar_sync(int id, int n) { asm volatile("bar.sync %0, %1;" ::"r"(id), "r"(n) : "memory"); }
__device__ __forceinline__ void bar_arrive(int id, int n) { asm volatile("bar.arrive %0, %1;" ::"r"(id), "r"(n) : "memory"); }
__device__ __forceinline__ unsigned ld_acquire(const unsigned* p) {
    unsigned v;
    asm volatile("ld.acquire.gpu.global.u32 %0, [%1];" : "=r"(v) : "l"(p) : "memory");
    return v;
}
__device__ __forceinline__ void red_release(unsigned* p, unsigned v) {
    asm volatile("red.release.gpu.global.add.u32 [%0], %1;" ::"l"(p), "r"(v) : "memory");
}
__device__ __forceinline__ void wait_count(const unsigned* p, unsigned target) {
    unsigned n = 0;
#pragma unroll 1
    while ((int)(ld_acquire(p) - target) < 0 && ++n < SPIN_LIMIT) {}
}
__device__ __forceinline__ float4 ld_relaxed_f4(const float4* p) {
    float4 v;
    asm volatile("ld.relaxed.gpu.global.v4.f32 {%0,%1,%2,%3}, [%4];" : "=f"(v.x), "=f"(v.y), "=f"(v.z), "=f"(v.w) : "l"(p) : "memory");
    return v;
}
__device__ __forceinline__ void st_relaxed_f4(float4* p, float4 v) {
    asm volatile("st.relaxed.gpu.global.v4.f32 [%0], {%1,%2,%3,%4};" ::"l"(p), "f"(v.x), "f"(v.y), "f"(v.z), "f"(v.w) : "memory");
}
__device__ __forceinline__ uint32_t pack_bf16(float lo, float hi) {
    uint32_t r;
    asm("cvt.rn.bf16x2.f32 %0, %1, %2;" : "=r"(r) : "f"(hi), "f"(lo));
    return r;
}
__device__ __forceinline__ uint32_t hmul2(uint32_t a, uint32_t b) {
    uint32_t r;
    asm("mul.rn.bf16x2 %0, %1, %2;" : "=r"(r) : "r"(a), "r"(b));
    return r;
}
__device__ __forceinline__ uint32_t hfma2(uint32_t a, uint32_t b, uint32_t c) {
    uint32_t r;
    asm("fma.rn.bf16x2 %0, %1, %2, %3;" : "=r"(r) : "r"(a), "r"(b), "r"(c));
    return r;
}
__device__ __forceinline__ float bf_lo(uint32_t v) { return __uint_as_float(v << 16); }
__device__ __forceinline__ float bf_hi(uint32_t v) { return __uint_as_float(v & 0xffff0000u); }
__device__ __forceinline__ void sts32(uint32_t a, uint32_t v) { asm volatile("st.shared.u32 [%0], %1;" ::"r"(a), "r"(v) : "memory"); }
__device__ __forceinline__ void sts128(uint32_t a, uint4 v) {
    asm volatile("st.shared.v4.u32 [%0], {%1,%2,%3,%4};" ::"r"(a), "r"(v.x), "r"(v.y), "r"(v.z), "r"(v.w) : "memory");
}

__device__ __forceinline__ uint64_t desc_ni(uint32_t addr, uint32_t lbo, uint32_t sbo) {
    return (uint64_t)((addr & 0x3FFFF) >> 4) | ((uint64_t)(lbo >> 4) << 16) | ((uint64_t)(sbo >> 4) << 32);
}
__device__ __forceinline__ uint64_t desc_a(uint32_t addr) { return desc_ni(addr, 128, 1024); }
template <int N> __device__ __forceinline__ uint64_t desc_b(uint32_t addr) { return desc_ni(addr, 16 * N, 128); }
__device__ __forceinline__ uint64_t desc_k(uint32_t addr) {
    return (uint64_t)((addr & 0x3FFFF) >> 4) | (1ull << 16) | (64ull << 32) | (1ull << 62);
}
__device__ __forceinline__ uint64_t desc_mn(uint32_t addr, uint32_t lbo) {
    return (uint64_t)((addr & 0x3FFFF) >> 4) | ((uint64_t)(lbo >> 4) << 16) | (64ull << 32) | (1ull << 62);
}

#define ACC8(d, o) "+f"(d[o + 0]), "+f"(d[o + 1]), "+f"(d[o + 2]), "+f"(d[o + 3]), "+f"(d[o + 4]), "+f"(d[o + 5]), "+f"(d[o + 6]), "+f"(d[o + 7])
template <int TB, int SA = 1>
__device__ __forceinline__ void wgmma_n128(float (&d)[64], uint64_t da, uint64_t db, int sd) {
    asm volatile(
        "{\n.reg .pred p;\nsetp.ne.b32 p, %66, 0;\n"
        "wgmma.mma_async.sync.aligned.m64n128k16.f32.bf16.bf16 "
        "{%0,%1,%2,%3,%4,%5,%6,%7,%8,%9,%10,%11,%12,%13,%14,%15,%16,%17,%18,%19,%20,%21,%22,%23,%24,%25,%26,%27,%28,%29,%30,%31,"
        "%32,%33,%34,%35,%36,%37,%38,%39,%40,%41,%42,%43,%44,%45,%46,%47,%48,%49,%50,%51,%52,%53,%54,%55,%56,%57,%58,%59,%60,%61,%62,%63},"
        " %64, %65, p, %68, 1, 0, %67;\n}"
        : ACC8(d, 0), ACC8(d, 8), ACC8(d, 16), ACC8(d, 24), ACC8(d, 32), ACC8(d, 40), ACC8(d, 48), ACC8(d, 56)
        : "l"(da), "l"(db), "r"(sd), "n"(TB), "n"(SA));
}
template <int N> __device__ __forceinline__ void acc_def(float (&d)[N]) {
#pragma unroll
    for (int i = 0; i < N; i++) d[i] = 0.f;
}
template <int TB>
__device__ __forceinline__ void wgmma_n64(float (&d)[32], uint64_t da, uint64_t db, int sd) {
    asm volatile(
        "{\n.reg .pred p;\nsetp.ne.b32 p, %34, 0;\n"
        "wgmma.mma_async.sync.aligned.m64n64k16.f32.bf16.bf16 "
        "{%0,%1,%2,%3,%4,%5,%6,%7,%8,%9,%10,%11,%12,%13,%14,%15,%16,%17,%18,%19,%20,%21,%22,%23,%24,%25,%26,%27,%28,%29,%30,%31},"
        " %32, %33, p, 1, 1, 0, %35;\n}"
        : ACC8(d, 0), ACC8(d, 8), ACC8(d, 16), ACC8(d, 24)
        : "l"(da), "l"(db), "r"(sd), "n"(TB));
}
template <int SA>
__device__ __forceinline__ void wgmma_n64s(float (&d)[32], uint64_t da, uint64_t db, int sd) {
    asm volatile(
        "{\n.reg .pred p;\nsetp.ne.b32 p, %34, 0;\n"
        "wgmma.mma_async.sync.aligned.m64n64k16.f32.bf16.bf16 "
        "{%0,%1,%2,%3,%4,%5,%6,%7,%8,%9,%10,%11,%12,%13,%14,%15,%16,%17,%18,%19,%20,%21,%22,%23,%24,%25,%26,%27,%28,%29,%30,%31},"
        " %32, %33, p, %35, 1, 0, 1;\n}"
        : ACC8(d, 0), ACC8(d, 8), ACC8(d, 16), ACC8(d, 24)
        : "l"(da), "l"(db), "r"(sd), "n"(SA));
}
__device__ __forceinline__ void wgmma_n64_rs(float (&d)[32], uint32_t a0, uint32_t a1, uint32_t a2, uint32_t a3, uint64_t db, int sd) {
    asm volatile(
        "{\n.reg .pred p;\nsetp.ne.b32 p, %37, 0;\n"
        "wgmma.mma_async.sync.aligned.m64n64k16.f32.bf16.bf16 "
        "{%0,%1,%2,%3,%4,%5,%6,%7,%8,%9,%10,%11,%12,%13,%14,%15,%16,%17,%18,%19,%20,%21,%22,%23,%24,%25,%26,%27,%28,%29,%30,%31},"
        " {%32,%33,%34,%35}, %36, p, 1, 1, 1;\n}"
        : ACC8(d, 0), ACC8(d, 8), ACC8(d, 16), ACC8(d, 24)
        : "r"(a0), "r"(a1), "r"(a2), "r"(a3), "l"(db), "r"(sd));
}

struct Params {
    const __nv_bfloat16* x0;
    const __nv_bfloat16* w_r;
    const __nv_bfloat16* w_i;
    const __nv_bfloat16* lam_re;
    const __nv_bfloat16* lam_im;
    const __nv_bfloat16* log_dt;
    const __nv_bfloat16* dskip;
    float* out;
    int stop;
};

__device__ __forceinline__ float ldbf(const __nv_bfloat16* p) { return __bfloat162float(*p); }

__device__ __forceinline__ void dft_fp(int j, int& f, int& ph) {
    int cs = j >> 1;
    if (j == 1) { f = 256; ph = 0; }
    else { f = cs; ph = (j & 1) ? 128 : 0; }
}

__device__ __forceinline__ void gen_col_consts(uint32_t sb, int tid) {
#pragma unroll 1
    for (int task = tid; task < 640; task += 256) {
        int f, c8;
        uint32_t a_cc, d_pi, d_po;
        if (task < 512) {
            f = task & 63; c8 = task >> 6;
            a_cc = sb + SM_X + (f >> 5) * 16384 + ((f >> 3) & 3) * 2048 + c8 * 128 + (f & 7) * 16;
            d_pi = 8192; d_po = 1024;
        } else {
            int n2 = task & 31;
            f = 2 * n2; c8 = (task >> 5) & 3;
            a_cc = sb + SM_X + 32768 + (n2 >> 3) * 1024 + c8 * 128 + (n2 & 7) * 16;
            d_pi = 4096; d_po = 512;
        }
        float cd, sd, cs, sn;
        __sincosf((float)(f >= 32 ? f - 64 : f) * (6.283185307179586f / 64.f), &sd, &cd);
        int a = (8 * c8 * f) & 63;
        __sincosf((float)(a >= 32 ? a - 64 : a) * (6.283185307179586f / 64.f), &sn, &cs);
        float cv[8], sv[8];
#pragma unroll
        for (int e = 0; e < 8; e++) {
            cv[e] = cs; sv[e] = sn;
            float t = cs * cd - sn * sd;
            sn = sn * cd + cs * sd;
            cs = t;
        }
        uint4 oc = make_uint4(pack_bf16(cv[0], cv[1]), pack_bf16(cv[2], cv[3]), pack_bf16(cv[4], cv[5]), pack_bf16(cv[6], cv[7]));
        uint4 os = make_uint4(pack_bf16(sv[0], sv[1]), pack_bf16(sv[2], sv[3]), pack_bf16(sv[4], sv[5]), pack_bf16(sv[6], sv[7]));
        sts128(a_cc, oc);
        sts128(a_cc + d_pi, os);
        sts128(a_cc + d_po, make_uint4(os.x ^ 0x80008000u, os.y ^ 0x80008000u, os.z ^ 0x80008000u, os.w ^ 0x80008000u));
        sts128(a_cc + d_pi + d_po, oc);
    }
}

__global__ void __launch_bounds__(NTHREADS, 1)
fused_kernel(const __grid_constant__ CUtensorMap tm_x, const __grid_constant__ CUtensorMap tm_bre,
             const __grid_constant__ CUtensorMap tm_bim, const __grid_constant__ CUtensorMap tm_cre,
             const __grid_constant__ CUtensorMap tm_cim, const __grid_constant__ CUtensorMap tm_col, const Params p) {
    extern __shared__ __align__(1024) uint8_t sm[];
    const uint32_t sb = s2u(sm);
    const int tid = threadIdx.x, b = blockIdx.x;
    const int c = b >> 3, r = b & 7;
    const int par = r & 1, pi_ = r >> 1, own = 4 * par + pi_;
    const int wg = __shfl_sync(~0u, tid >> 7, 0), w = __shfl_sync(~0u, (tid >> 5) & 3, 0), lane = tid & 31, g = lane >> 2, q = lane & 3;
    auto BAR = [&](int i) { return sb + SM_BAR + 8 * i; };
    unsigned* s_tgt = (unsigned*)(sm + SM_TGT);

    if (tid < NBARS) {
        int cnt = 1;
        if (tid >= B_EMPTY0 && tid < B_EMPTY0 + 4) cnt = 16;
        if (tid >= B_XEMPTY && tid < B_XEMPTY + 4) cnt = 24;
        if (tid == B_RFREE) cnt = 12;
        if (tid == B_HDONE) cnt = 2;
        if (tid == B_SETUP) cnt = 3;
        if ((tid >= B_AEMPTY && tid < B_AEMPTY + 8) || tid == B_BFREE) cnt = 8;
        if (tid == B_AFREE) cnt = 4;
        mbar_init(BAR(tid), cnt);
        asm volatile("fence.mbarrier_init.release.cluster;" ::: "memory");
    }
    asm volatile("barrier.cluster.arrive.release.aligned;" ::: "memory");

    if (wg == 3) {
        asm volatile("setmaxnreg.dec.sync.aligned.u32 56;");
        if (w == 0 && lane < 6) {
            const CUtensorMap* tm = lane == 0 ? &tm_x : lane == 1 ? &tm_bre : lane == 2 ? &tm_bim : lane == 3 ? &tm_cre : lane == 4 ? &tm_cim : &tm_col;
            asm volatile("prefetch.tensormap [%0];" ::"l"(tm) : "memory");
        }
        __syncwarp();
        asm volatile("barrier.cluster.wait.acquire.aligned;" ::: "memory");
        if (w > 0) {
            {
                int i = tid - 416;
                int ps = i < 64 ? 64 * r + i : 32 * c + i - 64;
                float lr = ldbf(p.lam_re + ps), li = ldbf(p.lam_im + ps);
                float dt = __bfloat162float(__float2bfloat16(expf(ldbf(p.log_dt + ps))));
                if (i < 6) s_tgt[i] = ((ld_acquire(&g_bar[i]) >> 7) + 1u) << 7;
                float mag = expf(lr * dt), t = li * dt * 0.15915494309189535f, sn, cs;
                t -= rintf(t);
                sincospif(2.f * t, &sn, &cs);
                float er = mag * cs, ei = mag * sn;
                if (i < 64) {
                    *(float2*)(sm + SM_LAM + i * 8) = make_float2(er, ei);
                } else {
                    er -= 1.f;
                    float inv = 1.f / (lr * lr + li * li);
                    *(float2*)(sm + SM_TAB + (i - 64) * 8) = make_float2((er * lr + ei * li) * inv, (ei * lr - er * li) * inv);
                }
            }
            __syncwarp();
            bar_arrive(15, 224);
            if (lane == 0) mbar_arrive(BAR(B_SETUP), 1);
            if (w == 2) {
                const int kq = 2 * b + (lane >> 4), row = (kq >> 2) + 128 * (kq & 3) + 512 * ((lane >> 1) & 3) + 64 * (lane & 1);
                const char* src = (const char*)(((lane >> 3) & 1) ? p.w_i : p.w_r) + (size_t)row * 514;
                size_t a0 = (size_t)src & ~(size_t)15;
                int bytes = row == 2047 ? 512 : 544;
                asm volatile("cp.async.bulk.prefetch.L2.global [%0], %1;" ::"l"(a0), "r"(bytes) : "memory");
            }
            if (w > 1) bar_sync(0, 224);
#pragma unroll 1
            for (int i = tid - 448; i < 1536 + 128 && w > 1; i += 64) {
                if (i < 1536) g_P[(uint32_t)(b * 4 + i / 384) * 1024 + 640 + i % 384] = make_uint4(0, 0, 0, 0);
                else g_Ebuf[b * 128 + i - 1536] = make_float4(0.f, 0.f, 0.f, 0.f);
            }
            __syncwarp();
            if (w == 3) bar_arrive(11, 192);
            if (w == 2) {
                bar_sync(11, 192);
                if (lane == 0) red_release(&g_bar[4], 1);
            }
            if (w == 3) {
#pragma unroll 1
                for (int it = 0; it < 8; it++) {
                    const int m = 4 * c + (it >> 1), d = 64 * r + m, ch = lane + 32 * (it & 1);
                    float v[8];
#pragma unroll
                    for (int e = 0; e < 8; e++) {
                        int j = 8 * ch + e, f, ph;
                        dft_fp(j, f, ph);
                        int a = (d * f + ph) & 511;
                        a = a >= 256 ? a - 512 : a;
                        float wj = j == 0 ? 0.f : (j == 1 ? 1.f / 512.f : 2.f / 512.f);
                        v[e] = wj * __cosf((float)a * (6.283185307179586f / 512.f));
                    }
                    uint32_t off = (uint32_t)(64 + r * 8 + (ch >> 3)) * 8192 + (m >> 3) * 1024 + (ch & 7) * 128 + (m & 7) * 16;
                    *(uint4*)(g_E + off) = make_uint4(pack_bf16(v[0], v[1]), pack_bf16(v[2], v[3]), pack_bf16(v[4], v[5]), pack_bf16(v[6], v[7]));
                }
                __syncwarp();
                if (lane == 0) { fence_async(); red_release(&g_bar[6], 1); }
                return;
            }
            if (w == 2) {
#pragma unroll 1
                for (int it = 0; it < 4; it++) {
                    const int hf = it & 1;
                    __syncwarp();
                    if (hf == 0) bar_sync(13, 288); else bar_sync(6, 416);
                    if (lane == 0) {
                        const uint32_t src = sb + SM_HH + par * 32768 + hf * 16384;
                        bulk_s2peer(mapa(src, par ^ 1), src, 16384, mapa(BAR(hf ? B_HPEER1 : B_HPEER), par ^ 1));
                    }
                }
                return;
            }
            bar_sync(2, 288);
            if (lane == 0) {
                TX(5);
                fence_async();
                red_release(&g_bar[0], 1);
                TX(6);
            }
            __syncwarp();
            bar_arrive(0, 224);
            bar_sync(12, 160);
            if (lane == 0) {
                asm volatile("cp.async.bulk.global.shared::cta.bulk_group [%0], [%1], 8192;" ::"l"(g_A1 + (uint32_t)(((c >> 1) * 8 + r) * 16384 + (c & 1) * 8192)),
                             "r"(sb + SM_B1ST) : "memory");
                asm volatile("cp.async.bulk.commit_group;" ::: "memory");
                asm volatile("cp.async.bulk.wait_group 0;" ::: "memory");
                mbar_arrive(BAR(B_B1DONE), 1);
                fence_async();
                red_release(&g_bar[7], 1);
            }
#pragma unroll 1
            for (int layer = 0; layer < 2; layer++) {
                __syncwarp();
                bar_sync(5, 416);
                if (lane == 0) {
                    TX(0 + 8 * layer);
                    tma_store_5d(&tm_col, 32 * (b & 1), 0, b >> 1, 0, layer, sb + SM_RAW);
                    asm volatile("cp.reduce.async.bulk.global.shared::cta.bulk_group.add.f32 [%0], [%1], 8192;" ::"l"(g_ssqc + (layer * 16 + (b & 15)) * 2048),
                                 "r"(sb + SM_SSQ) : "memory");
                    asm volatile("cp.async.bulk.commit_group;" ::: "memory");
                    asm volatile("cp.async.bulk.wait_group 0;" ::: "memory");
                    TX(1 + 8 * layer);
                    fence_async();
                    red_release(&g_bar[1 + 2 * layer], 1);
                    TX(2 + 8 * layer);
                }
            }
        } else if (tid == 384) {
#pragma unroll 1
            for (int kb = 0; kb < 8; kb++) {
                uint32_t fb = BAR(B_FULL0 + kb);
                mbar_expect(fb, 16384);
                tma_5d_mc(sb + SM_A + 65536 + kb * 16384 + par * 8192, &tm_x, kb * 64, 0, 0, 8 * par, c, fb);
            }
#pragma unroll 1
            for (int k2 = 0; k2 < 8; k2++) {
                asm volatile("cp.async.bulk.prefetch.tensor.2d.L2.global [%0, {%1,%2}];" ::"l"(par ? &tm_bim : &tm_bre), "r"(k2 * 64), "r"(32 * c) : "memory");
                if ((k2 & 1) == par)
                    asm volatile("cp.async.bulk.prefetch.tensor.2d.L2.global [%0, {%1,%2}];" ::"l"((c & 1) ? &tm_cim : &tm_cre), "r"(64 * (c >> 1)), "r"(k2 * 64) : "memory");
            }
            mbar_wait(BAR(B_SETUP), 0);
#pragma unroll 1
            for (int layer = 0; layer < 2; layer++) {
                wait_count(&g_bar[2 * layer], s_tgt[2 * layer]);
                TX(4 + 8 * layer);
                fence_async();
                mbar_expect(BAR(B_COL), 16384 + 8192);
                tma_5d(sb + SM_RAW, &tm_col, 32 * (b & 1), 0, b >> 1, 0, layer, BAR(B_COL));
                bulk_g2s(sb + SM_SSQ, g_ssq + layer * 2048, 8192, BAR(B_COL));
                if (layer == 0) {
                    wait_count(&g_bar[4], s_tgt[4]);
                    mbar_arrive(BAR(B_WRDY), 1);
                    wait_count(&g_bar[7], s_tgt[4]);
                    fence_async();
                }
                if (layer == 0) mbar_wait(BAR(B_AFREE), 0);
                mbar_wait(BAR(B_COL), layer);
#pragma unroll 1
                for (int s = 0; s < 8; s++) {
                    if (layer == 1) mbar_wait(BAR(B_AEMPTY + s), 1);
                    if (s >= 2) mbar_wait(BAR(B_AFULL + s - 2), 0);
                    mbar_expect(BAR(B_AFULL + s), 16384);
                    bulk_g2s(sb + SM_A + s * 16384, g_A1 + (uint32_t)(r * 8 + s) * 16384, 16384, BAR(B_AFULL + s));
                }
                if (layer == 1) wait_count(&g_bar[6], s_tgt[4]);
                wait_count(&g_bar[1 + 2 * layer], s_tgt[1 + 2 * layer]);
                TX(3 + 8 * layer);
                fence_async();
                const uint8_t* xsrc = g_X + (uint32_t)(layer * 16 + c) * 8 * 16384;
                const uint8_t* esrc = g_E + (uint32_t)(layer * 8 + own) * 8 * 8192;
                mbar_arrive(BAR(B_SSQ), 1);
                mbar_expect(BAR(B_HPEER), 16384);
                mbar_expect(BAR(B_HPEER1), 16384);
#pragma unroll 1
                for (int it = 0; it < 16; it++) {
                    if (it < 8) {
                        int st = it & 3, f = layer * 2 + (it >> 2);
                        if (f > 0) mbar_wait_cluster(BAR(B_XEMPTY + st), (f - 1) & 1);
                        mbar_expect(BAR(B_XFULL + st), 24576);
                        bulk_g2s_mc(sb + SM_X + st * 24576 + par * 8192, xsrc + (uint32_t)it * 16384 + par * 8192, 8192, BAR(B_XFULL + st));
                        bulk_g2s(sb + SM_X + st * 24576 + 16384, esrc + (uint32_t)it * 8192, 8192, BAR(B_XFULL + st));
                    }
                    if (it >= 8) {
                        if (it == 8) mbar_wait(BAR(B_AEMPTY + 5), 0);
                        int s = it - 8, tile = 4 * par + ((pi_ + 1 + (s >> 1)) & 3), sl = r ^ (s & 1);
                        mbar_wait(BAR(B_AEMPTY + s), 0);
                        uint32_t fb = BAR(B_AFULL + s), dst = sb + SM_A + s * 16384;
                        mbar_expect(fb, 16384);
                        if (layer == 1) {
                            tma_2d(dst, &tm_cre, 64 * sl, 64 * tile, fb);
                            tma_2d(dst + 8192, &tm_cim, 64 * sl, 64 * tile, fb);
                        } else {
                            bulk_g2s(dst, g_A2 + (uint32_t)(sl * 8 + tile) * 16384, 16384, fb);
                        }
                    }
                }
            }
        }
        return;
    }

    asm volatile("setmaxnreg.inc.sync.aligned.u32 152;");
    if (tid >= 96 && tid < 112) g_ssq[2048 + 16 * b + tid - 96] = 0.f;
    if (tid >= 128 && tid < 256) ((float4*)g_ssqc)[b * 128 + tid - 128] = make_float4(0.f, 0.f, 0.f, 0.f);
    TS(0);
    if (wg == 0) TC(30);
    {
        const int f = 32 * r + lane;
        float cd, sd;
        __sincosf((float)f * (6.283185307179586f / 512.f), &sd, &cd);
        const uint32_t dst = sb + SM_A + (lane >> 2) * 1024 + (lane & 3) * 32;
#pragma unroll 1
        for (int ch = tid >> 5; ch < 64; ch += 12) {
            int a = (8 * ch * f) & 511;
            a = a >= 256 ? a - 512 : a;
            float cs, sn;
            __sincosf((float)a * (6.283185307179586f / 512.f), &sn, &cs);
            float cv[8], sv[8];
#pragma unroll
            for (int e = 0; e < 8; e++) {
                cv[e] = cs; sv[e] = -sn;
                float t = cs * cd - sn * sd;
                sn = sn * cd + cs * sd;
                cs = t;
            }
            uint4 o1 = make_uint4(pack_bf16(sv[0], sv[1]), pack_bf16(sv[2], sv[3]), pack_bf16(sv[4], sv[5]), pack_bf16(sv[6], sv[7]));
            if (f == 0) o1 = make_uint4(0xbf803f80u, 0xbf803f80u, 0xbf803f80u, 0xbf803f80u);
            uint32_t a0 = dst + (ch >> 3) * 8192 + (ch & 7) * 128;
            sts128(a0, make_uint4(pack_bf16(cv[0], cv[1]), pack_bf16(cv[2], cv[3]), pack_bf16(cv[4], cv[5]), pack_bf16(cv[6], cv[7])));
            sts128(a0 + 16, o1);
        }
    }
    fence_async_smem();
    asm volatile("barrier.cluster.wait.acquire.aligned;" ::: "memory");
    bar_sync(10, 384);
    TS(1);
    if (wg < 2) {
        float acc[32];
        acc_def(acc);
        const int npos = 16 * r + 8 * wg + 2 * w;
        float sh0 = 0.f, sh1 = 0.f, s0 = 0.f, s1 = 0.f, q0 = 0.f, q1 = 0.f;
#pragma unroll 1
        for (int kb = 0; kb < 8; kb++) {
            uint32_t slot = sb + SM_A + 65536 + kb * 16384;
            mbar_wait(BAR(B_FULL0 + kb), 0);
            wg_fence();
#pragma unroll
            for (int ks = 0; ks < 4; ks++)
                wgmma_n64<0>(acc, desc_a(sb + SM_A + kb * 8192 + ks * 256), desc_k(slot + wg * 8192 + ks * 32), 1);
            wg_commit();
            {
                uint32_t v0 = lds32(slot + npos * 128 + lane * 4), v1 = lds32(slot + npos * 128 + 128 + lane * 4);
                if (kb == 0) { sh0 = __shfl_sync(~0u, bf_lo(v0), 0); sh1 = __shfl_sync(~0u, bf_lo(v1), 0); }
                float a = bf_lo(v0) - sh0, bq = bf_hi(v0) - sh0, cq = bf_lo(v1) - sh1, d = bf_hi(v1) - sh1;
                s0 += a + bq; q0 += a * a + bq * bq; s1 += cq + d; q1 += cq * cq + d * d;
            }
            wg_wait<1>();
            if (kb > 0 && kb <= 4 && lane == 0) { mbar_arrive(BAR(B_EMPTY0 + kb - 1), 1); mbar_arrive_remote(mapa(BAR(B_EMPTY0 + kb - 1), par ^ 1)); }
        }
#pragma unroll
        for (int o = 16; o; o >>= 1) {
            s0 += __shfl_xor_sync(~0u, s0, o); q0 += __shfl_xor_sync(~0u, q0, o);
            s1 += __shfl_xor_sync(~0u, s1, o); q1 += __shfl_xor_sync(~0u, q1, o);
        }
        if (lane == 0) *(float2*)(g_ssq + 128 * c + npos) = make_float2(fmaxf(q0 - s0 * s0 * (1.f / 512.f), 0.f), fmaxf(q1 - s1 * s1 * (1.f / 512.f), 0.f));
        wg_wait<0>();
        TS(2);
        uint8_t* dst = g_X + (uint32_t)((c * 8 + r) * 16384 + w * 4096 + wg * 1024 + g * 16 + 4 * q);
#pragma unroll
        for (int i = 0; i < 8; i++) {
            *(uint32_t*)(dst + i * 128) = pack_bf16(acc[4 * i], acc[4 * i + 1]);
            *(uint32_t*)(dst + 2048 + i * 128) = pack_bf16(acc[4 * i + 2], acc[4 * i + 3]);
        }
        bar_sync(2, 288);
        mbar_wait(BAR(B_SETUP), 0);
        TS(3);
    }

    if (wg == 2) {
        bar_sync(0, 224);
        {
            const int cb = tid & 127;
            const int c0 = cb == 0 ? 256 : 2 * cb, c1 = 2 * cb + 1;
            uint32_t wf[2][16];
#pragma unroll
            for (int h = 0; h < 2; h++) {
                const int kq = 2 * b + h, k1 = kq >> 2, qq = kq & 3;
                const unsigned short* wr_ = (const unsigned short*)p.w_r + (k1 + 128 * qq) * 257;
                const unsigned short* wi_ = (const unsigned short*)p.w_i + (k1 + 128 * qq) * 257;
#pragma unroll
                for (int i = 0; i < 4; i++) {
                    int o = 512 * i * 257;
                    wf[h][2 * i] = (uint32_t)__ldg(wr_ + o + c0) | ((uint32_t)__ldg(wr_ + o + 64 * 257 + c0) << 16);
                    wf[h][2 * i + 1] = ((uint32_t)__ldg(wi_ + o + c0) | ((uint32_t)__ldg(wi_ + o + 64 * 257 + c0) << 16)) ^ 0x80008000u;
                    wf[h][8 + 2 * i] = (uint32_t)__ldg(wr_ + o + c1) | ((uint32_t)__ldg(wr_ + o + 64 * 257 + c1) << 16);
                    wf[h][8 + 2 * i + 1] = ((uint32_t)__ldg(wi_ + o + c1) | ((uint32_t)__ldg(wi_ + o + 64 * 257 + c1) << 16)) ^ 0x80008000u;
                }
            }
            uint4 p0 = __ldg((const uint4*)p.dskip + 2 * lane), p1 = __ldg((const uint4*)p.dskip + 2 * lane + 1);
            uint32_t u[8] = {p0.x, p0.y, p0.z, p0.w, p1.x, p1.y, p1.z, p1.w};
            int j = 64 * r + 4 * c + w, f, ph;
            dft_fp(j, f, ph);
            float s = 0.f;
            int idx = 16 * lane * f + ph;
#pragma unroll
            for (int i = 0; i < 16; i++) {
                int a = idx & 511;
                idx += f;
                a = a >= 256 ? a - 512 : a;
                s += ((i & 1) ? bf_hi(u[i >> 1]) : bf_lo(u[i >> 1])) * __cosf((float)a * (6.283185307179586f / 512.f));
            }
#pragma unroll
            for (int o = 16; o; o >>= 1) s += __shfl_xor_sync(~0u, s, o);
            if (lane == 0) g_Dh[j] = s;
            uint4* wd = g_Wfrag + (uint32_t)(cb * 1024 + 2 * b);
#pragma unroll
            for (int i = 0; i < 4; i++) {
                wd[i * 256] = make_uint4(wf[0][4 * i], wf[0][4 * i + 1], wf[0][4 * i + 2], wf[0][4 * i + 3]);
                wd[i * 256 + 1] = make_uint4(wf[1][4 * i], wf[1][4 * i + 1], wf[1][4 * i + 2], wf[1][4 * i + 3]);
            }
            bar_arrive(11, 192);
        }
        bar_sync(15, 224);
        float acc[32];
        acc_def(acc);
        if (tid == 256) {
#pragma unroll 1
            for (int s = 0; s < 4; s++) mbar_wait_cluster(BAR(B_EMPTY0 + s), 0);
            mbar_expect(BAR(B_FULLB), 65536);
#pragma unroll 1
            for (int k2 = 0; k2 < 8; k2++)
                tma_2d_mc(sb + SM_A + 65536 + k2 * 8192 + par * 4096, par ? &tm_bim : &tm_bre, k2 * 64, 32 * c, BAR(B_FULLB));
        }
        __syncwarp();
        mbar_wait(BAR(B_FULLB), 0);
        wg_fence();
#pragma unroll 1
        for (int kb = 0; kb < 8; kb++) {
#pragma unroll
            for (int ks = 0; ks < 4; ks++)
                wgmma_n64<0>(acc, desc_a(sb + SM_A + kb * 8192 + ks * 256), desc_k(sb + SM_A + 65536 + kb * 8192 + ks * 32), 1);
            wg_commit();
        }
        wg_wait<0>();
        if (lane == 0) { mbar_arrive(BAR(B_BFREE), 1); mbar_arrive_remote(mapa(BAR(B_BFREE), par ^ 1)); }
        if (tid == 256) {
            mbar_wait_cluster(BAR(B_BFREE), 0);
            mbar_expect(BAR(B_FULLC), 65536);
#pragma unroll 1
            for (int k2 = par; k2 < 8; k2 += 2)
                tma_2d_mc(sb + SM_A + 65536 + k2 * 8192, (c & 1) ? &tm_cim : &tm_cre, 64 * (c >> 1), k2 * 64, BAR(B_FULLC));
        }
        __syncwarp();
        {
            uint8_t* dst = sm + SM_B1ST + w * 256 + q * 32 + g * 2;
            const float wj0 = (r == 0 && w == 0 && g < 2) ? (g == 0 ? 0.f : 1.f / 512.f) : 2.f / 512.f;
#pragma unroll
            for (int i = 0; i < 4; i++) {
#pragma unroll
                for (int e = 0; e < 2; e++) {
                    float2 cf = *(const float2*)(sm + SM_TAB + (8 * i + 2 * q + e) * 8);
#pragma unroll
                    for (int h = 0; h < 2; h++) {
                        float wj = h == 0 ? wj0 : 2.f / 512.f;
                        float pr = acc[4 * i + 2 * h + e] * wj, pi = acc[16 + 4 * i + 2 * h + e] * wj;
                        uint8_t* d2 = dst + i * 2048 + h * 128 + e * 16;
                        *(__nv_bfloat16*)(d2) = __float2bfloat16(cf.x * pr - cf.y * pi);
                        *(__nv_bfloat16*)(d2 + 1024) = __float2bfloat16(cf.x * pi + cf.y * pr);
                    }
                }
            }
            fence_async_smem();
            bar_arrive(12, 160);
        }
        acc_def(acc);
        mbar_wait(BAR(B_FULLC), 0);
        wg_fence();
#pragma unroll 1
        for (int kb = 0; kb < 8; kb++) {
#pragma unroll
            for (int ks = 0; ks < 4; ks++)
                wgmma_n64<1>(acc, desc_a(sb + SM_A + kb * 8192 + ks * 256), desc_mn(sb + SM_A + 65536 + kb * 8192 + ks * 2048, 8192), 1);
            wg_commit();
        }
        wg_wait<0>();
        fence_async_smem();
        if (lane == 0) mbar_arrive(BAR(B_AFREE), 1);
        uint8_t* dst = g_A2 + (uint32_t)(((c >> 1) * 8 + r) * 16384 + (c & 1) * 8192 + w * 2048 + g * 16 + 4 * q);
#pragma unroll
        for (int i = 0; i < 8; i++) {
            *(uint32_t*)(dst + i * 128) = pack_bf16(acc[4 * i], acc[4 * i + 1]);
            *(uint32_t*)(dst + 1024 + i * 128) = pack_bf16(acc[4 * i + 2], acc[4 * i + 3]);
        }
        {
            const int m = 4 * c + w, jp = 64 * r + m;
            int fp, php;
            dft_fp(jp, fp, php);
            const __nv_bfloat16* dh = (const __nv_bfloat16*)(sm + SM_RSTD);
            if (tid == 256) wait_count(&g_bar[4], s_tgt[4]);
            bar_sync(3, 128);
            float4 d4 = __ldcg((const float4*)g_Dh + (tid - 256));
            *(uint2*)(sm + SM_RSTD + (tid - 256) * 8) = make_uint2(pack_bf16(d4.x, d4.y), pack_bf16(d4.z, d4.w));
            bar_sync(3, 128);
#pragma unroll 1
            for (int it = 0; it < 2; it++) {
                const int ch = lane + 32 * it;
                float v[8];
#pragma unroll
                for (int e = 0; e < 8; e++) {
                    int j = 8 * ch + e, f, ph;
                    dft_fp(j, f, ph);
                    float wj = j == 0 ? 0.f : (j == 1 ? 1.f / 512.f : 2.f / 512.f);
                    float gsum = 0.f;
#pragma unroll
                    for (int sgn = 0; sgn < 2; sgn++) {
                        int mm = (sgn ? f - fp : f + fp) & 511, pp = (sgn ? ph - php : ph + php) & 511;
                        if (mm > 256) { mm = 512 - mm; pp = (512 - pp) & 511; }
                        int odd = (pp >> 7) & 1;
                        float t = __bfloat162float(dh[mm == 256 ? 1 : 2 * mm + odd]);
                        if (odd && (mm & 255) == 0) t = 0.f;
                        gsum += (pp & 256) ? -t : t;
                    }
                    v[e] = 0.5f * wj * gsum;
                }
                uint32_t off = (uint32_t)(r * 8 + (ch >> 3)) * 8192 + (m >> 3) * 1024 + (ch & 7) * 128 + (m & 7) * 16;
                *(uint4*)(g_E + off) = make_uint4(pack_bf16(v[0], v[1]), pack_bf16(v[2], v[3]), pack_bf16(v[4], v[5]), pack_bf16(v[6], v[7]));
            }
        }
    }

#pragma unroll 1
    for (int layer = 0; layer < 2; layer++) {
        if (wg < 2) {
            const int n1 = 32 * wg + 8 * w + g;
            const int ct = n1 >> 2;
            gen_col_consts(sb, tid);
            uint32_t tr2[4], ti2[4], tn2[4];
#pragma unroll
            for (int i = 0; i < 4; i++) {
                float cr[2], ci[2];
#pragma unroll
                for (int e = 0; e < 2; e++) {
                    int a = (n1 * (8 * i + 2 * q + e)) & 2047;
                    a = a >= 1024 ? a - 2048 : a;
                    float ang = (float)a * (-6.283185307179586f / 2048.f);
                    cr[e] = __cosf(ang); ci[e] = __sinf(ang);
                }
                tr2[i] = pack_bf16(cr[0], cr[1]); ti2[i] = pack_bf16(ci[0], ci[1]); tn2[i] = ti2[i] ^ 0x80008000u;
            }
            uint32_t wf[16];
            const uint4* ws = g_Wfrag + (uint32_t)(b * 1024 + n1 * 4 + q);
#pragma unroll
            for (int i = 0; i < 4; i++) {
                uint4 v = make_uint4(0, 0, 0, 0);
                if (layer == 1) v = __ldcg(ws + i * 256);
                wf[4 * i] = v.x; wf[4 * i + 1] = v.y; wf[4 * i + 2] = v.z; wf[4 * i + 3] = v.w;
            }
            mbar_wait(BAR(B_COL), layer);
            TS(4 + 12 * layer);
            if (wg == 0) TC(0 + 10 * layer);
            const uint32_t rw0 = sb + SM_RAW + ct * 1024 + q * 64 + ((q >> 1) << 4) + (g & 3) * 4, rw1 = rw0 ^ 16;
            const int pos0 = 128 * ct + 8 * q + 2 * (g & 3);
            const int sw = b == 0 ? 1 : 0;
            uint32_t xr[4][4];
            const uint32_t st0 = sb + SM_H + (n1 >> 3) * 1024 + g * 16 + 4 * q;
#pragma unroll
            for (int i = 0; i < 4; i++) {
                float2 sq = *(const float2*)(sm + SM_SSQ + (pos0 + 32 * i) * 4);
                const uint32_t rs2 = pack_bf16(rsqrtf(sq.x * (1.f / 512.f) + 1e-5f), rsqrtf(sq.y * (1.f / 512.f) + 1e-5f));
#pragma unroll
                for (int jj = 0; jj < 4; jj++) {
                    const int K = jj ^ (2 * (i & 1));
                    uint32_t a = ((K & 1) ? rw1 : rw0) + i * 256 + (K & 2) * 16;
                    if (jj < 2) a ^= sw << 4;
                    uint32_t v = lds32(a);
                    xr[jj][i] = v;
                    uint32_t o = hmul2(v, rs2);
                    if (jj == 1 && sw) o = 0u;
                    sts32(st0 + (jj & 1) * 8192 + (4 * (jj >> 1) + i) * 128, o);
                }
            }
            if (wg == 0) TC(1 + 10 * layer);
            fence_async_smem();
            bar_sync(1, 256);
            float acc[32];
            const uint32_t s1a = sb + SM_X + wg * 16384, s2b = sb + SM_X + 32768;
            wg_fence();
#pragma unroll
            for (int ks = 0; ks < 8; ks++)
                wgmma_n64<1>(acc, desc_a(s1a + (ks >> 2) * 8192 + (ks & 3) * 256), desc_b<64>(sb + SM_H + ks * 2048), ks != 0);
            wg_commit();
            if (layer == 0) {
                mbar_wait(BAR(B_WRDY), 0);
#pragma unroll
                for (int i = 0; i < 4; i++) {
                    uint4 v = __ldcg(ws + i * 256);
                    wf[4 * i] = v.x; wf[4 * i + 1] = v.y; wf[4 * i + 2] = v.z; wf[4 * i + 3] = v.w;
                }
            }
            wg_wait<0>();
            if (wg == 0) TC(2 + 10 * layer);
            uint32_t are[2][4], aim[2][4];
#pragma unroll
            for (int col = 0; col < 2; col++) {
#pragma unroll
                for (int i = 0; i < 4; i++) {
                    int o = 4 * (4 * col + i);
                    uint32_t zr = pack_bf16(acc[o], acc[o + 1]), zi = pack_bf16(acc[o + 2], acc[o + 3]);
                    are[col][i] = hfma2(zr, tr2[i], hmul2(zi, tn2[i]));
                    aim[col][i] = hfma2(zr, ti2[i], hmul2(zi, tr2[i]));
                }
            }
            wg_fence();
#pragma unroll
            for (int ks = 0; ks < 2; ks++)
                wgmma_n64_rs(acc, are[0][2 * ks], are[1][2 * ks], are[0][2 * ks + 1], are[1][2 * ks + 1], desc_b<64>(s2b + ks * 2048), ks != 0);
#pragma unroll
            for (int ks = 0; ks < 2; ks++)
                wgmma_n64_rs(acc, aim[0][2 * ks], aim[1][2 * ks], aim[0][2 * ks + 1], aim[1][2 * ks + 1], desc_b<64>(s2b + 4096 + ks * 2048), 1);
            wg_commit();
            wg_wait<0>();
            if (wg == 0) TC(3 + 10 * layer);
#pragma unroll
            for (int col = 0; col < 2; col++) {
#pragma unroll
                for (int i = 0; i < 4; i++) {
                    uint32_t wr = wf[col * 8 + 2 * i], wn = wf[col * 8 + 2 * i + 1];
                    uint32_t zr = pack_bf16(acc[4 * i + 2 * col], acc[4 * i + 2 * col + 1]);
                    uint32_t zi = pack_bf16(acc[16 + 4 * i + 2 * col], acc[16 + 4 * i + 2 * col + 1]);
                    are[col][i] = hfma2(zr, wr, hmul2(zi, wn));
                    aim[col][i] = hfma2(zr, wn, hmul2(zi ^ 0x80008000u, wr));
                }
            }
            wg_fence();
#pragma unroll
            for (int ks = 0; ks < 2; ks++)
                wgmma_n64_rs(acc, are[0][2 * ks], are[1][2 * ks], are[0][2 * ks + 1], are[1][2 * ks + 1], desc_b<64>(s2b + ks * 2048), ks != 0);
#pragma unroll
            for (int ks = 0; ks < 2; ks++)
                wgmma_n64_rs(acc, aim[0][2 * ks], aim[1][2 * ks], aim[0][2 * ks + 1], aim[1][2 * ks + 1], desc_b<64>(s2b + 4096 + ks * 2048), 1);
            wg_commit();
            wg_wait<0>();
            if (wg == 0) TC(4 + 10 * layer);
            mbar_wait(BAR(B_B1DONE), 0);
#pragma unroll
            for (int col = 0; col < 2; col++) {
#pragma unroll
                for (int i = 0; i < 4; i++) {
                    uint32_t zr = pack_bf16(acc[4 * i + 2 * col], acc[4 * i + 2 * col + 1]);
                    uint32_t zi = pack_bf16(acc[16 + 4 * i + 2 * col], acc[16 + 4 * i + 2 * col + 1]);
                    sts32(st0 + 16384 + (4 * col + i) * 128, hfma2(zr, tr2[i], hmul2(zi, tn2[i])));
                    sts32(st0 + 16384 + 8192 + (4 * col + i) * 128, hfma2(zr, ti2[i], hmul2(zi, tr2[i])));
                }
            }
            if (wg == 0) TC(5 + 10 * layer);
            fence_async_smem();
            bar_sync(1, 256);
            wg_fence();
#pragma unroll
            for (int ks = 0; ks < 8; ks++)
                wgmma_n64<1>(acc, desc_a(s1a + (ks >> 2) * 8192 + (ks & 3) * 256), desc_b<64>(sb + SM_H + 16384 + ks * 2048), ks != 0);
            wg_commit();
            wg_wait<0>();
            if (wg == 0) TC(6 + 10 * layer);
            const float sc = 1.f / 2048.f;
            const float sci0 = sw ? 0.f : -sc;
            const float wr0 = sw ? 0.5f : 1.f, wi0 = sw ? 0.f : 1.f;
#pragma unroll
            for (int i = 0; i < 4; i++) {
                float ss0, ss1;
#pragma unroll
                for (int col = 0; col < 2; col++) {
                    int o = 4 * (4 * col + i);
                    uint32_t vr = xr[2 * col][i], vi = xr[2 * col + 1][i];
                    float si = col == 0 ? sci0 : -sc;
                    uint32_t nr = pack_bf16(fmaf(acc[o], sc, bf_lo(vr)), fmaf(acc[o + 1], sc, bf_hi(vr)));
                    uint32_t ni = pack_bf16(fmaf(acc[o + 2], si, bf_lo(vi)), fmaf(acc[o + 3], si, bf_hi(vi)));
                    float a0 = bf_lo(nr), a1 = bf_hi(nr), b0 = bf_lo(ni), b1 = bf_hi(ni);
                    if (col == 0) {
                        ss0 = wr0 * a0 * a0 + wi0 * b0 * b0;
                        ss1 = wr0 * a1 * a1 + wi0 * b1 * b1;
                    } else {
                        ss0 += a0 * a0 + b0 * b0;
                        ss1 += a1 * a1 + b1 * b1;
                    }
                    const int K = (2 * col) ^ (2 * (i & 1));
                    uint32_t a = rw0 + i * 256 + K * 16;
                    if (col == 0) a ^= sw << 4;
                    sts32(a, nr);
                    sts32(a ^ 16, ni);
                }
                *(float2*)(sm + SM_SSQ + (pos0 + 32 * i) * 4) = make_float2(ss0 * (2.f / 512.f), ss1 * (2.f / 512.f));
            }
            fence_async_smem();
        }
        TS(5 + 12 * layer);
        if (wg == 0) TC(7 + 10 * layer);
        bar_arrive(5, 416);

        float acc[64];
        float* s_rstd = (float*)(sm + SM_RSTD);
        float* s_mean = (float*)(sm + SM_MEAN);
        const unsigned epoch = s_tgt[0] >> 7;
        const uint32_t pt3 = 1u + (2u * epoch + layer) % 3u;
        const uint32_t ptag = (pt3 & 1u) | ((pt3 & 2u) << 15);
        const uint64_t dstep = layer == 0 ? 16 : 2;
        auto c_desc = [&](int s) { return layer == 0 ? desc_a(sb + SM_A + s * 16384) : desc_k(sb + SM_A + s * 16384); };
        if (wg < 2) {
            const int prow = 32 * wg + 8 * w + g;
            const float2 l1 = *(const float2*)(sm + SM_LAM + prow * 8);
            float lr32 = l1.x, li32 = l1.y;
#pragma unroll
            for (int i = 0; i < 5; i++) { float t = lr32 * lr32 - li32 * li32; li32 = 2.f * lr32 * li32; lr32 = t; }
            float lr128 = lr32, li128 = li32;
#pragma unroll
            for (int i = 0; i < 2; i++) { float t = lr128 * lr128 - li128 * li128; li128 = 2.f * lr128 * li128; lr128 = t; }
            const float lr1 = l1.x, li1 = l1.y;
            acc_def(acc);
#pragma unroll 1
            for (int kb = 0; kb < 8; kb++) {
                mbar_wait(BAR(B_AFULL + kb), 0);
                mbar_wait(BAR(B_XFULL + (kb & 3)), (kb >> 2) & 1);
                wg_fence();
#pragma unroll
                for (int ks = 0; ks < 4; ks++)
                    wgmma_n128<1>(acc, desc_a(sb + SM_A + kb * 16384 + wg * 8192 + ks * 256),
                                  desc_b<128>(sb + SM_X + (kb & 3) * 24576 + ks * 4096), 1);
                wg_commit();
                wg_wait<1>();
                if (kb > 0 && lane == 0) {
                    mbar_arrive(BAR(B_AEMPTY + kb - 1), 1); mbar_arrive(BAR(B_XEMPTY + ((kb - 1) & 3)), 1);
                    mbar_arrive_remote(mapa(BAR(B_XEMPTY + ((kb - 1) & 3)), par ^ 1));
                }
            }
            wg_wait<0>();
            if (lane == 0) {
                mbar_arrive(BAR(B_AEMPTY + 7), 1); mbar_arrive(BAR(B_XEMPTY + 3), 1);
                mbar_arrive_remote(mapa(BAR(B_XEMPTY + 3), par ^ 1)); mbar_arrive_remote(mapa(BAR(B_RFREE), par ^ 1));
            }
            bar_arrive(14, 384);
            TS(6 + 12 * layer);
            bar_sync(4, 384);
            TS(7 + 12 * layer);
            float er = 0.f, ei = 0.f;
#pragma unroll
            for (int i = 0; i < 16; i++) {
                float2 rs = *(const float2*)(s_rstd + 128 + 8 * i + 2 * q);
                acc[4 * i] *= rs.x; acc[4 * i + 1] *= rs.y; acc[4 * i + 2] *= rs.x; acc[4 * i + 3] *= rs.y;
                float nr = lr1 * er - li1 * ei + acc[4 * i], ni = lr1 * ei + li1 * er + acc[4 * i + 2];
                er = lr1 * nr - li1 * ni + acc[4 * i + 1];
                ei = lr1 * ni + li1 * nr + acc[4 * i + 3];
            }
            float cr = 0.f, ci = 0.f, tr = 0.f, ti = 0.f;
#pragma unroll
            for (int qq = 0; qq < 4; qq++) {
                float xr_ = __shfl_sync(~0u, er, (lane & ~3) | qq), xi_ = __shfl_sync(~0u, ei, (lane & ~3) | qq);
                if (qq == q) { cr = tr; ci = ti; }
                float nr = lr32 * tr - li32 * ti + xr_, ni = lr32 * ti + li32 * tr + xi_;
                tr = nr; ti = ni;
            }
            float4* eb = g_Ebuf + (uint32_t)(layer * 16 * 512 + 64 * r + prow);
            if (q == 0 && c < 15) st_relaxed_f4(eb + c * 512, make_float4(tr, ti, __uint_as_float(epoch), 0.f));
            TS(8 + 12 * layer);
            float pr[4], pi[4];
            {
                unsigned n = 0;
                bool ok;
#pragma unroll 1
                do {
                    ok = true;
#pragma unroll
                    for (int k = 0; k < 4; k++) {
                        float4 v = make_float4(0.f, 0.f, __uint_as_float(epoch), 0.f);
                        if (4 * k + q < c) v = ld_relaxed_f4(eb + (4 * k + q) * 512);
                        pr[k] = v.x; pi[k] = v.y;
                        ok = ok && __float_as_uint(v.z) == epoch;
                    }
                } while (!ok && ++n < SPIN_LIMIT);
            }
            __syncwarp();
            TS(9 + 12 * layer);
            float hr = 0.f, hi = 0.f;
#pragma unroll
            for (int cc = 0; cc < 15; cc++) {
                float xr_ = __shfl_sync(~0u, pr[cc >> 2], (lane & ~3) | (cc & 3)), xi_ = __shfl_sync(~0u, pi[cc >> 2], (lane & ~3) | (cc & 3));
                if (cc < c) {
                    float nr = lr128 * hr - li128 * hi + xr_, ni = lr128 * hi + li128 * hr + xi_;
                    hr = nr; hi = ni;
                }
            }
#pragma unroll
            for (int qq = 0; qq < 3; qq++) {
                if (qq < q) { float nr = lr32 * hr - li32 * hi, ni = lr32 * hi + li32 * hr; hr = nr; hi = ni; }
            }
            er = cr + hr; ei = ci + hi;
            bar_sync(7, 384);
            mbar_wait_cluster(BAR(B_RFREE), layer);
            const uint32_t ha = sb + SM_HH + par * 32768 + (prow >> 3) * 1024 + g * 16 + 4 * q;
#pragma unroll
            for (int i = 0; i < 16; i++) {
                float nr = lr1 * er - li1 * ei + acc[4 * i], ni = lr1 * ei + li1 * er + acc[4 * i + 2];
                er = lr1 * nr - li1 * ni + acc[4 * i + 1];
                ei = lr1 * ni + li1 * nr + acc[4 * i + 3];
                sts32(ha + (i >> 3) * 16384 + (i & 7) * 128, pack_bf16(nr, er));
                sts32(ha + (i >> 3) * 16384 + 8192 + (i & 7) * 128, pack_bf16(ni, ei));
                if (i == 7) { fence_async_smem(); bar_arrive(13, 288); }
            }
            fence_async_smem();
            acc_def(acc);
            float acc2[32];
            acc_def(acc2);
            TS(10 + 12 * layer);
            bar_sync(6, 416);
            TS(11 + 12 * layer);
            float (&a0)[32] = *reinterpret_cast<float (*)[32]>(&acc[0]);
            float (&a1)[32] = *reinterpret_cast<float (*)[32]>(&acc[32]);
            auto tile_mma = [&](float (&d)[32], int u) {
#pragma unroll 1
                for (int k = 0; k < 2; k++) {
                    const uint32_t hb = sb + SM_HH + (par ^ k) * 32768 + wg * 16384;
                    if (k == 1) mbar_wait(BAR(wg ? B_HPEER1 : B_HPEER), layer);
                    mbar_wait(BAR(B_AFULL + 2 * u + k), 1);
                    const uint64_t da = c_desc(2 * u + k);
                    wg_fence();
#pragma unroll
                    for (int ks = 0; ks < 4; ks++) wgmma_n64s<1>(d, da + ks * dstep, desc_b<64>(hb + ks * 2048), 1);
#pragma unroll
                    for (int ks = 0; ks < 4; ks++) wgmma_n64s<-1>(d, da + 512 + ks * dstep, desc_b<64>(hb + 8192 + ks * 2048), 1);
                }
                wg_commit();
            };
            auto tile_ship = [&](float (&d)[32], int u) {
                uint4* dst = g_P + (uint32_t)(((c * 8 + 2 * ((pi_ + 1 + u) & 3) + par) * 4 + pi_) * 1024 + wg * 512 + (tid & 127));
#pragma unroll
                for (int i = 0; i < 4; i++)
                    dst[i * 128] = make_uint4((pack_bf16(d[8 * i], d[8 * i + 1]) & 0xfffefffeu) | ptag, pack_bf16(d[8 * i + 2], d[8 * i + 3]),
                                              pack_bf16(d[8 * i + 4], d[8 * i + 5]), pack_bf16(d[8 * i + 6], d[8 * i + 7]));
            };
            tile_mma(a0, 0);
            if ((tid & 127) == 0) mbar_arrive_remote(mapa(BAR(B_HDONE), par ^ 1));
            __syncwarp();
            tile_mma(a1, 1);
            wg_wait<1>();
            tile_ship(a0, 0);
            tile_mma(acc2, 2);
            bar_arrive(12, 384);
            wg_wait<1>();
            tile_ship(a1, 1);
            wg_wait<0>();
            tile_ship(acc2, 2);
            if (lane < 6) mbar_arrive(BAR(B_AEMPTY + lane), 1);
            TS(12 + 12 * layer);
        } else {
            const int t2 = tid - 256;
            const uint8_t* ximg = g_X + (uint32_t)layer * 16 * 8 * 16384;
            mbar_wait(BAR(B_SSQ), layer);
            TS(6 + 12 * layer);
            float sqv[16];
#pragma unroll
            for (int i = 0; i < 16; i++) sqv[i] = __ldcg(g_ssqc + (layer * 16 + i) * 2048 + 128 * c + t2);
            const unsigned short xm = __ldcg((const unsigned short*)(ximg + (uint32_t)(c * 8 * 16384 + (t2 >> 3) * 128 + (t2 & 7) * 2)));
            acc_def(acc);
#pragma unroll 1
            for (int kb = 0; kb < 8; kb++) {
                if (kb == 4) {
                    wg_wait<0>();
                    if (lane == 0) { mbar_arrive(BAR(B_XEMPTY + 3), 1); mbar_arrive_remote(mapa(BAR(B_XEMPTY + 3), par ^ 1)); }
                    float tot = 0.f;
#pragma unroll
                    for (int i = 0; i < 16; i++) tot += sqv[i];
                    float rs = rsqrtf(tot * (1.f / 512.f) + 1e-5f);
                    s_rstd[t2] = rs;
                    s_rstd[128 + t2] = 2.f * rs;
                    s_mean[t2] = layer == 0 ? 0.f : __uint_as_float((uint32_t)xm << 16) * (1.f / 512.f);
                    TS(7 + 12 * layer);
                    bar_arrive(4, 384);
                    bar_sync(14, 384);
                }
                mbar_wait(BAR(B_XFULL + (kb & 3)), (kb >> 2) & 1);
                wg_fence();
#pragma unroll
                for (int ks = 0; ks < 4; ks++)
                    wgmma_n128<1>(acc, desc_a(sb + SM_X + (kb & 3) * 24576 + 16384 + ks * 256), desc_b<128>(sb + SM_X + (kb & 3) * 24576 + ks * 4096), 1);
                wg_commit();
                wg_wait<1>();
                if ((kb & 3) != 0 && lane == 0) { mbar_arrive(BAR(B_XEMPTY + ((kb - 1) & 3)), 1); mbar_arrive_remote(mapa(BAR(B_XEMPTY + ((kb - 1) & 3)), par ^ 1)); }
            }
            wg_wait<0>();
            if (lane == 0) { mbar_arrive(BAR(B_XEMPTY + 3), 1); mbar_arrive_remote(mapa(BAR(B_XEMPTY + 3), par ^ 1)); mbar_arrive_remote(mapa(BAR(B_RFREE), par ^ 1)); }
            bar_arrive(7, 384);
            bar_sync(3, 128);
            TS(9 + 12 * layer);
            const int m0 = 16 * w + g;
            const uint32_t xoff = (uint32_t)((c * 8 + own) * 16384 + w * 4096 + g * 16 + 4 * q);
            if (layer == 0) {
                const uint8_t* xs = g_X + xoff;
#pragma unroll
                for (int i = 0; i < 16; i++) {
                    float2 rs = *(const float2*)(s_rstd + 8 * i + 2 * q);
                    uint32_t x0v = __ldcg((const uint32_t*)(xs + i * 128)), x1v = __ldcg((const uint32_t*)(xs + 2048 + i * 128));
                    acc[4 * i] = acc[4 * i] * rs.x + bf_lo(x0v);
                    acc[4 * i + 1] = acc[4 * i + 1] * rs.y + bf_hi(x0v);
                    acc[4 * i + 2] = acc[4 * i + 2] * rs.x + bf_lo(x1v);
                    acc[4 * i + 3] = acc[4 * i + 3] * rs.y + bf_hi(x1v);
                }
            } else {
                float d0 = ldbf(p.dskip + 64 * own + m0), d1 = ldbf(p.dskip + 64 * own + m0 + 8);
#pragma unroll
                for (int i = 0; i < 16; i++) {
                    float2 rs = *(const float2*)(s_rstd + 8 * i + 2 * q);
                    float2 mn = *(const float2*)(s_mean + 8 * i + 2 * q);
                    acc[4 * i] = acc[4 * i] * (1.f + rs.x * d0) + mn.x;
                    acc[4 * i + 1] = acc[4 * i + 1] * (1.f + rs.y * d0) + mn.y;
                    acc[4 * i + 2] = acc[4 * i + 2] * (1.f + rs.x * d1) + mn.x;
                    acc[4 * i + 3] = acc[4 * i + 3] * (1.f + rs.y * d1) + mn.y;
                }
            }
            TS(10 + 12 * layer);
            bar_sync(6, 416);
            TS(11 + 12 * layer);
            {
                float (&a0)[32] = *reinterpret_cast<float (*)[32]>(&acc[0]);
                float (&a1)[32] = *reinterpret_cast<float (*)[32]>(&acc[32]);
#pragma unroll 1
                for (int k = 0; k < 2; k++) {
                    const uint32_t hb = sb + SM_HH + (par ^ k) * 32768;
                    if (k == 1) {
                        mbar_wait(BAR(B_HPEER), layer);
                        mbar_wait(BAR(B_HPEER1), layer);
                        bar_sync(12, 384);
                    }
                    mbar_wait(BAR(B_AFULL + 6 + k), 1);
                    const uint64_t da = c_desc(6 + k);
                    wg_fence();
#pragma unroll
                    for (int ks = 0; ks < 4; ks++) {
                        wgmma_n64s<1>(a0, da + ks * dstep, desc_b<64>(hb + ks * 2048), 1);
                        wgmma_n64s<1>(a1, da + ks * dstep, desc_b<64>(hb + 16384 + ks * 2048), 1);
                    }
#pragma unroll
                    for (int ks = 0; ks < 4; ks++) {
                        wgmma_n64s<-1>(a0, da + 512 + ks * dstep, desc_b<64>(hb + 8192 + ks * 2048), 1);
                        wgmma_n64s<-1>(a1, da + 512 + ks * dstep, desc_b<64>(hb + 16384 + 8192 + ks * 2048), 1);
                    }
                    wg_commit();
                }
                wg_wait<0>();
            }
#pragma unroll
            for (int i = 0; i < 16; i++)
                *(float4*)(sm + SM_A + 6 * 16384 + i * 2048 + t2 * 16) = make_float4(acc[4 * i], acc[4 * i + 1], acc[4 * i + 2], acc[4 * i + 3]);
            TS(12 + 12 * layer);
        }
        {
            const int t = tid & 127;
            const int nch = wg == 2 ? 2 : 3;
            const uint4* pb = g_P + (uint32_t)((c * 8 + r) * 4 * 1024 + wg * 128 + t);
            uint4 v[3][3];
            unsigned n = 0;
#pragma unroll 1
            while (true) {
                if (lane == 31) {
#pragma unroll 1
                    while (true) {
                        uint32_t bad = 0;
#pragma unroll
                        for (int sx = 0; sx < 3; sx++) {
                            uint32_t t0;
                            asm volatile("ld.relaxed.gpu.global.u32 %0, [%1];" : "=r"(t0) : "l"(pb + ((pi_ + 1 + sx) & 3) * 1024 + (nch - 1) * 384) : "memory");
                            bad |= t0 ^ ptag;
                        }
                        if (!(bad & 0x00010001u) || ++n >= SPIN_LIMIT) break;
                    }
                }
                __syncwarp();
                uint32_t bad = 0;
#pragma unroll
                for (int k = 0; k < 3; k++)
#pragma unroll
                    for (int sx = 0; sx < 3; sx++) {
                        v[k][sx] = make_uint4(ptag, 0, 0, 0);
                        if (k < nch) v[k][sx] = ld_relaxed_u4(pb + ((pi_ + 1 + sx) & 3) * 1024 + k * 384);
                        bad |= v[k][sx].x ^ ptag;
                    }
                if (!__any_sync(~0u, bad & 0x00010001u) || ++n >= SPIN_LIMIT) break;
            }
            bar_sync(8, 384);
            TS(13 + 12 * layer);
            const int m0 = 16 * w + g;
            const float w0 = (own == 0 && m0 < 2) ? (m0 == 0 ? 0.f : 0.5f) : 1.f;
#pragma unroll
            for (int k = 0; k < 3; k++) {
                if (k < nch) {
                    const int i = wg + 3 * k;
                    float4 a = *(const float4*)(sm + SM_A + 6 * 16384 + (2 * i) * 2048 + t * 16);
                    float4 bq = *(const float4*)(sm + SM_A + 6 * 16384 + (2 * i + 1) * 2048 + t * 16);
#pragma unroll
                    for (int sx = 0; sx < 3; sx++) {
                        a.x += bf_lo(v[k][sx].x); a.y += bf_hi(v[k][sx].x); a.z += bf_lo(v[k][sx].y); a.w += bf_hi(v[k][sx].y);
                        bq.x += bf_lo(v[k][sx].z); bq.y += bf_hi(v[k][sx].z); bq.z += bf_lo(v[k][sx].w); bq.w += bf_hi(v[k][sx].w);
                    }
                    if (layer == 0) {
                        uint8_t* xd = g_X + (uint32_t)((16 * 8 + c * 8 + own) * 16384 + w * 4096 + g * 16 + 4 * q + i * 256);
                        uint32_t v0 = pack_bf16(a.x, a.y), v1 = pack_bf16(a.z, a.w), v2 = pack_bf16(bq.x, bq.y), v3 = pack_bf16(bq.z, bq.w);
                        *(uint32_t*)(xd) = v0; *(uint32_t*)(xd + 2048) = v1; *(uint32_t*)(xd + 128) = v2; *(uint32_t*)(xd + 2048 + 128) = v3;
                        float sq[4];
                        sq[0] = w0 * bf_lo(v0) * bf_lo(v0) + bf_lo(v1) * bf_lo(v1);
                        sq[1] = w0 * bf_hi(v0) * bf_hi(v0) + bf_hi(v1) * bf_hi(v1);
                        sq[2] = w0 * bf_lo(v2) * bf_lo(v2) + bf_lo(v3) * bf_lo(v3);
                        sq[3] = w0 * bf_hi(v2) * bf_hi(v2) + bf_hi(v3) * bf_hi(v3);
                        float u0 = (g & 1) ? sq[2] : sq[0], u1 = (g & 1) ? sq[3] : sq[1];
                        u0 += __shfl_xor_sync(~0u, (g & 1) ? sq[0] : sq[2], 4);
                        u1 += __shfl_xor_sync(~0u, (g & 1) ? sq[1] : sq[3], 4);
                        float z = (g & 2) ? u1 : u0;
                        z += __shfl_xor_sync(~0u, (g & 2) ? u0 : u1, 8);
                        z += __shfl_xor_sync(~0u, z, 16);
                        if (g < 4) atomicAdd(s_mean + 16 * i + 8 * (g & 1) + 2 * q + (g >> 1), z);
                    } else {
                        float* o = p.out + (uint32_t)((128 * c + 32 * q + 4 * i) * 512 + 64 * own + m0);
                        o[0] = a.x; o[512] = a.y; o[8] = a.z; o[512 + 8] = a.w;
                        o[1024] = bq.x; o[1536] = bq.y; o[1024 + 8] = bq.z; o[1536 + 8] = bq.w;
                    }
                }
            }
            if (wg < 2) mbar_wait_cluster(BAR(B_HDONE), layer);
            if (layer == 0) {
                fence_async_smem();
                bar_sync(9, 384);
                TS(14 + 12 * layer);
                if (wg == 2) {
                    atomicAdd(g_ssq + 2048 + 128 * c + t, s_mean[t] * (2.f / 512.f));
                    bar_sync(3, 128);
                    if (lane == 0) { mbar_arrive(BAR(B_AEMPTY + 6), 2); mbar_arrive(BAR(B_AEMPTY + 7), 2); }
                    if (t == 0) { fence_async(); red_release(&g_bar[2], 1); }
                }
            }
        }
        TS(15 + 12 * layer);
        if (wg == 0) TC(31);
    }
}

typedef CUresult (*EncFn)(CUtensorMap*, CUtensorMapDataType, cuuint32_t, void*, const cuuint64_t*, const cuuint64_t*,
                          const cuuint32_t*, const cuuint32_t*, CUtensorMapInterleave, CUtensorMapSwizzle,
                          CUtensorMapL2promotion, CUtensorMapFloatOOBfill);

void launch_impl(void* const* d_in, void* d_out, int stop) {
    static EncFn enc = nullptr;
    if (!enc) {
        void* fn = nullptr;
        cudaDriverEntryPointQueryResult qr;
        cudaGetDriverEntryPoint("cuTensorMapEncodeTiled", &fn, cudaEnableDefault, &qr);
        enc = (EncFn)fn;
        cudaFuncSetAttribute(fused_kernel, cudaFuncAttributeMaxDynamicSharedMemorySize, SM_TOTAL);
    }
    CUtensorMap tx, tbr, tbi, tcr, tci, tcol;
    {
        void* gx = nullptr;
        cudaGetSymbolAddress(&gx, g_X);
        cuuint64_t gd[5] = {64, 16, 64, 16, 2};
        cuuint64_t gs[4] = {128, 2048, 128 * 1024, 2048 * 1024};
        cuuint32_t bx[5] = {32, 16, 1, 16, 1};
        cuuint32_t es[5] = {1, 1, 1, 1, 1};
        enc(&tcol, CU_TENSOR_MAP_DATA_TYPE_BFLOAT16, 5, gx, gd, gs, bx, es, CU_TENSOR_MAP_INTERLEAVE_NONE,
            CU_TENSOR_MAP_SWIZZLE_64B, CU_TENSOR_MAP_L2_PROMOTION_NONE, CU_TENSOR_MAP_FLOAT_OOB_FILL_NONE);
    }
    {
        cuuint64_t gd[5] = {512, 2, 4, 16, 16};
        cuuint64_t gs[4] = {1024, 32 * 1024, 2 * 1024, 128 * 1024};
        cuuint32_t bx[5] = {64, 2, 4, 8, 1};
        cuuint32_t es[5] = {1, 1, 1, 1, 1};
        enc(&tx, CU_TENSOR_MAP_DATA_TYPE_BFLOAT16, 5, d_in[0], gd, gs, bx, es, CU_TENSOR_MAP_INTERLEAVE_NONE,
            CU_TENSOR_MAP_SWIZZLE_128B, CU_TENSOR_MAP_L2_PROMOTION_L2_128B, CU_TENSOR_MAP_FLOAT_OOB_FILL_NONE);
    }
    auto mk2 = [&](CUtensorMap* m, void* ptr, cuuint32_t rows) {
        cuuint64_t gd[2] = {512, 512};
        cuuint64_t gs[1] = {1024};
        cuuint32_t bx[2] = {64, rows};
        cuuint32_t es[2] = {1, 1};
        enc(m, CU_TENSOR_MAP_DATA_TYPE_BFLOAT16, 2, ptr, gd, gs, bx, es, CU_TENSOR_MAP_INTERLEAVE_NONE,
            CU_TENSOR_MAP_SWIZZLE_128B, CU_TENSOR_MAP_L2_PROMOTION_L2_128B, CU_TENSOR_MAP_FLOAT_OOB_FILL_NONE);
    };
    mk2(&tbr, d_in[6], 32);
    mk2(&tbi, d_in[7], 32);
    mk2(&tcr, d_in[8], 64);
    mk2(&tci, d_in[9], 64);
    Params p;
    p.x0 = (const __nv_bfloat16*)d_in[0];
    p.w_r = (const __nv_bfloat16*)d_in[1];
    p.w_i = (const __nv_bfloat16*)d_in[2];
    p.lam_re = (const __nv_bfloat16*)d_in[4];
    p.lam_im = (const __nv_bfloat16*)d_in[5];
    p.log_dt = (const __nv_bfloat16*)d_in[10];
    p.dskip = (const __nv_bfloat16*)d_in[11];
    p.out = (float*)d_out;
    p.stop = stop;
    cudaLaunchConfig_t cfg = {};
    cfg.gridDim = dim3(NCTA); cfg.blockDim = dim3(NTHREADS); cfg.dynamicSmemBytes = SM_TOTAL; cfg.stream = cudaStreamPerThread;
    cudaLaunchAttribute at[1];
    at[0].id = cudaLaunchAttributeClusterDimension;
    at[0].val.clusterDim.x = 2; at[0].val.clusterDim.y = 1; at[0].val.clusterDim.z = 1;
    cfg.attrs = at; cfg.numAttrs = 1;
    cudaLaunchKernelEx(&cfg, fused_kernel, tx, tbr, tbi, tcr, tci, tcol, p);
}

}

extern "C" void kernel_launch(void* const* d_in, const int* in_sizes, int n_in, void* d_out, int out_size) {
    (void)in_sizes; (void)n_in; (void)out_size;
    launch_impl(d_in, d_out, 100);
}
```

```cpp
#include <cuda_runtime.h>
#include <cuda_bf16.h>
#include <cuda.h>
#include <stdint.h>

namespace {

constexpr int NCTA = 128;
constexpr int NTHREADS = 512;
constexpr int SM_A = 0;
constexpr int SM_X = 131072;
constexpr int SM_H = 196608;
constexpr int SM_HH = SM_X + 32768;
constexpr int SM_M = 229376;
constexpr int SM_TOTAL = 232448;
constexpr int SM_BAR = SM_M;
constexpr int SM_TGT = SM_M + 392;
constexpr int SM_LAM = SM_M + 416;
constexpr int SM_TAB = SM_M + 928;
constexpr int SM_RSTD = SM_M + 1920;
constexpr int SM_MEAN = SM_TAB;
constexpr int SM_T64 = SM_M + 2944;
constexpr int SM_B1ST = SM_H + 24576;
constexpr int SM_RAW = SM_X + 40960;
constexpr int SM_SSQ = SM_X + 57344;
constexpr int B_FULL0 = 0;
constexpr int B_EMPTY0 = 8;
constexpr int B_FULLC = 12;
constexpr int B_AFULL = 13;
constexpr int B_AEMPTY = 21;
constexpr int B_XFULL = 29;
constexpr int B_XEMPTY = 33;
constexpr int B_AFREE = 37;
constexpr int B_COL = 38;
constexpr int B_SSQ = 39;
constexpr int B_HPEER = 40;
constexpr int B_RFREE = 41;
constexpr int B_HDONE = 42;
constexpr int B_WRDY = 43;
constexpr int B_HPEER1 = 44;
constexpr int B_FULLB = 45;
constexpr int B_BFREE = 46;
constexpr int B_SETUP = 47;
constexpr int B_B1DONE = 48;
constexpr int NBARS = 49;

__device__ __align__(1024) uint8_t g_X[2 * 16 * 8 * 16384];
__device__ __align__(1024) uint8_t g_A1[8 * 8 * 16384];
__device__ __align__(1024) uint8_t g_A2[8 * 8 * 16384];
__device__ __align__(1024) uint8_t g_E[2 * 8 * 8 * 8192];
__device__ __align__(16) float g_ssq[2 * 2048];
__device__ __align__(16) float g_ssqc[2 * 16 * 2048];
__device__ __align__(16) float g_Dh[512];
__device__ __align__(16) uint4 g_Wfrag[128 * 4 * 256];
__device__ __align__(16) float4 g_Ebuf[2 * 16 * 512];
__device__ __align__(16) uint4 g_P[16 * 8 * 4 * 1024];
__device__ unsigned g_bar[8];
__device__ unsigned g_err;
#define TX(i)
#define TQ(i)
#define TS(i)
#define TC(i)

constexpr unsigned SPIN_LIMIT = 1u << 22;

__device__ __forceinline__ uint32_t s2u(const void* p) { return (uint32_t)__cvta_generic_to_shared(p); }
__device__ __forceinline__ void mbar_init(uint32_t a, uint32_t c) {
    asm volatile("mbarrier.init.shared::cta.b64 [%0], %1;" ::"r"(a), "r"(c) : "memory");
}
__device__ __forceinline__ void mbar_expect(uint32_t a, uint32_t bytes) {
    asm volatile("mbarrier.arrive.expect_tx.shared::cta.b64 _, [%0], %1;" ::"r"(a), "r"(bytes) : "memory");
}
__device__ __forceinline__ void mbar_arrive(uint32_t a, uint32_t cnt) {
    asm volatile("mbarrier.arrive.shared::cta.b64 _, [%0], %1;" ::"r"(a), "r"(cnt) : "memory");
}
__device__ __forceinline__ bool mbar_try(uint32_t a, uint32_t parity) {
    uint32_t ok;
    asm volatile("{\n.reg .pred p;\nmbarrier.try_wait.parity.shared::cta.b64 p, [%1], %2;\nselp.u32 %0, 1, 0, p;\n}"
                 : "=r"(ok) : "r"(a), "r"(parity) : "memory");
    return ok != 0;
}
__device__ __forceinline__ void mbar_wait(uint32_t a, uint32_t parity) {
    asm volatile("{\n.reg .pred p, q;\n.reg .u32 n;\nmov.u32 n, 0;\n"
                 "W_%=:\nmbarrier.try_wait.parity.shared::cta.b64 p, [%0], %1;\n@p bra D_%=;\n"
                 "add.u32 n, n, 1;\nsetp.lt.u32 q, n, 4194304;\n@q bra W_%=;\nD_%=:\n}" ::"r"(a), "r"(parity) : "memory");
}
__device__ __forceinline__ void bulk_g2s(uint32_t dst, const void* src, uint32_t bytes, uint32_t bar) {
    asm volatile("cp.async.bulk.shared::cluster.global.mbarrier::complete_tx::bytes [%0], [%1], %2, [%3];" ::"r"(dst),
                 "l"(src), "r"(bytes), "r"(bar) : "memory");
}
__device__ __forceinline__ void tma_2d(uint32_t dst, const CUtensorMap* m, int c0, int c1, uint32_t bar) {
    asm volatile("cp.async.bulk.tensor.2d.shared::cluster.global.mbarrier::complete_tx::bytes [%0], [%1, {%3,%4}], [%2];" ::"r"(dst),
                 "l"(m), "r"(bar), "r"(c0), "r"(c1) : "memory");
}
__device__ __forceinline__ void tma_5d(uint32_t dst, const CUtensorMap* m, int c0, int c1, int c2, int c3, int c4, uint32_t bar) {
    asm volatile("cp.async.bulk.tensor.5d.shared::cluster.global.mbarrier::complete_tx::bytes [%0], [%1, {%3,%4,%5,%6,%7}], [%2];" ::"r"(dst),
                 "l"(m), "r"(bar), "r"(c0), "r"(c1), "r"(c2), "r"(c3), "r"(c4) : "memory");
}
__device__ __forceinline__ void tma_2d_mc(uint32_t dst, const CUtensorMap* m, int c0, int c1, uint32_t bar) {
    asm volatile("cp.async.bulk.tensor.2d.shared::cluster.global.mbarrier::complete_tx::bytes.multicast::cluster [%0], [%1, {%3,%4}], [%2], %5;" ::"r"(dst),
                 "l"(m), "r"(bar), "r"(c0), "r"(c1), "h"((unsigned short)3) : "memory");
}
__device__ __forceinline__ void tma_5d_mc(uint32_t dst, const CUtensorMap* m, int c0, int c1, int c2, int c3, int c4, uint32_t bar) {
    asm volatile("cp.async.bulk.tensor.5d.shared::cluster.global.mbarrier::complete_tx::bytes.multicast::cluster [%0], [%1, {%3,%4,%5,%6,%7}], [%2], %8;" ::"r"(dst),
                 "l"(m), "r"(bar), "r"(c0), "r"(c1), "r"(c2), "r"(c3), "r"(c4), "h"((unsigned short)3) : "memory");
}
__device__ __forceinline__ void bulk_g2s_mc(uint32_t dst, const void* src, uint32_t bytes, uint32_t bar) {
    asm volatile("cp.async.bulk.shared::cluster.global.mbarrier::complete_tx::bytes.multicast::cluster [%0], [%1], %2, [%3], %4;" ::"r"(dst),
                 "l"(src), "r"(bytes), "r"(bar), "h"((unsigned short)3) : "memory");
}
__device__ __forceinline__ void tma_store_5d(const CUtensorMap* m, int c0, int c1, int c2, int c3, int c4, uint32_t src) {
    asm volatile("cp.async.bulk.tensor.5d.global.shared::cta.bulk_group [%0, {%2,%3,%4,%5,%6}], [%1];" ::"l"(m), "r"(src),
                 "r"(c0), "r"(c1), "r"(c2), "r"(c3), "r"(c4) : "memory");
}
__device__ __forceinline__ uint32_t lds32(uint32_t a) { uint32_t v; asm volatile("ld.shared.u32 %0, [%1];" : "=r"(v) : "r"(a) : "memory"); return v; }
__device__ __forceinline__ uint4 ld_relaxed_u4(const uint4* p) {
    uint4 v;
    asm volatile("ld.relaxed.gpu.global.v4.u32 {%0,%1,%2,%3}, [%4];" : "=r"(v.x), "=r"(v.y), "=r"(v.z), "=r"(v.w) : "l"(p) : "memory");
    return v;
}
__device__ __forceinline__ void fence_async() { asm volatile("fence.proxy.async.global;" ::: "memory"); }
__device__ __forceinline__ void red_relaxed(unsigned* p, unsigned v) {
    asm volatile("red.relaxed.gpu.global.add.u32 [%0], %1;" ::"l"(p), "r"(v) : "memory");
}
__device__ __forceinline__ uint32_t mapa(uint32_t a, uint32_t rank) {
    uint32_t d;
    asm("mapa.shared::cluster.u32 %0, %1, %2;" : "=r"(d) : "r"(a), "r"(rank));
    return d;
}
__device__ __forceinline__ void mbar_arrive_remote(uint32_t ra) {
    asm volatile("mbarrier.arrive.relaxed.cluster.shared::cluster.b64 _, [%0];" ::"r"(ra) : "memory");
}
__device__ __forceinline__ void mbar_wait_cluster(uint32_t a, uint32_t parity) {
    asm volatile("{\n.reg .pred p, q;\n.reg .u32 n;\nmov.u32 n, 0;\n"
                 "W_%=:\nmbarrier.try_wait.parity.acquire.cluster.shared::cta.b64 p, [%0], %1;\n@p bra D_%=;\n"
                 "add.u32 n, n, 1;\nsetp.lt.u32 q, n, 4194304;\n@q bra W_%=;\nD_%=:\n}" ::"r"(a), "r"(parity) : "memory");
}
__device__ __forceinline__ void bulk_s2peer(uint32_t rdst, uint32_t src, uint32_t bytes, uint32_t rbar) {
    asm volatile("cp.async.bulk.shared::cluster.shared::cta.mbarrier::complete_tx::bytes [%0], [%1], %2, [%3];" ::"r"(rdst),
                 "r"(src), "r"(bytes), "r"(rbar) : "memory");
}
__device__ __forceinline__ void fence_async_smem() { asm volatile("fence.proxy.async.shared::cta;" ::: "memory"); }
__device__ __forceinline__ void wg_fence() { asm volatile("wgmma.fence.sync.aligned;" ::: "memory"); }
__device__ __forceinline__ void wg_commit() { asm volatile("wgmma.commit_group.sync.aligned;" ::: "memory"); }
template <int N> __device__ __forceinline__ void wg_wait() { asm volatile("wgmma.wait_group.sync.aligned %0;" ::"n"(N) : "memory"); }
__device__ __forceinline__ void bar_sync(int id, int n) { asm volatile("bar.sync %0, %1;" ::"r"(id), "r"(n) : "memory"); }
__device__ __forceinline__ void bar_arrive(int id, int n) { asm volatile("bar.arrive %0, %1;" ::"r"(id), "r"(n) : "memory"); }
__device__ __forceinline__ unsigned ld_acquire(const unsigned* p) {
    unsigned v;
    asm volatile("ld.acquire.gpu.global.u32 %0, [%1];" : "=r"(v) : "l"(p) : "memory");
    return v;
}
__device__ __forceinline__ void red_release(unsigned* p, unsigned v) {
    asm volatile("red.release.gpu.global.add.u32 [%0], %1;" ::"l"(p), "r"(v) : "memory");
}
__device__ __forceinline__ void wait_count(const unsigned* p, unsigned target) {
    unsigned n = 0;
#pragma unroll 1
    while ((int)(ld_acquire(p) - target) < 0 && ++n < SPIN_LIMIT) {}
}
__device__ __forceinline__ float4 ld_relaxed_f4(const float4* p) {
    float4 v;
    asm volatile("ld.relaxed.gpu.global.v4.f32 {%0,%1,%2,%3}, [%4];" : "=f"(v.x), "=f"(v.y), "=f"(v.z), "=f"(v.w) : "l"(p) : "memory");
    return v;
}
__device__ __forceinline__ void st_relaxed_f4(float4* p, float4 v) {
    asm volatile("st.relaxed.gpu.global.v4.f32 [%0], {%1,%2,%3,%4};" ::"l"(p), "f"(v.x), "f"(v.y), "f"(v.z), "f"(v.w) : "memory");
}
__device__ __forceinline__ uint32_t pack_bf16(float lo, float hi) {
    uint32_t r;
    asm("cvt.rn.bf16x2.f32 %0, %1, %2;" : "=r"(r) : "f"(hi), "f"(lo));
    return r;
}
__device__ __forceinline__ uint32_t hmul2(uint32_t a, uint32_t b) {
    uint32_t r;
    asm("mul.rn.bf16x2 %0, %1, %2;" : "=r"(r) : "r"(a), "r"(b));
    return r;
}
__device__ __forceinline__ uint32_t hfma2(uint32_t a, uint32_t b, uint32_t c) {
    uint32_t r;
    asm("fma.rn.bf16x2 %0, %1, %2, %3;" : "=r"(r) : "r"(a), "r"(b), "r"(c));
    return r;
}
__device__ __forceinline__ float bf_lo(uint32_t v) { return __uint_as_float(v << 16); }
__device__ __forceinline__ float bf_hi(uint32_t v) { return __uint_as_float(v & 0xffff0000u); }
__device__ __forceinline__ void sts32(uint32_t a, uint32_t v) { asm volatile("st.shared.u32 [%0], %1;" ::"r"(a), "r"(v) : "memory"); }
__device__ __forceinline__ void sts128(uint32_t a, uint4 v) {
    asm volatile("st.shared.v4.u32 [%0], {%1,%2,%3,%4};" ::"r"(a), "r"(v.x), "r"(v.y), "r"(v.z), "r"(v.w) : "memory");
}

__device__ __forceinline__ uint64_t desc_ni(uint32_t addr, uint32_t lbo, uint32_t sbo) {
    return (uint64_t)((addr & 0x3FFFF) >> 4) | ((uint64_t)(lbo >> 4) << 16) | ((uint64_t)(sbo >> 4) << 32);
}
__device__ __forceinline__ uint64_t desc_a(uint32_t addr) { return desc_ni(addr, 128, 1024); }
template <int N> __device__ __forceinline__ uint64_t desc_b(uint32_t addr) { return desc_ni(addr, 16 * N, 128); }
__device__ __forceinline__ uint64_t desc_k(uint32_t addr) {
    return (uint64_t)((addr & 0x3FFFF) >> 4) | (1ull << 16) | (64ull << 32) | (1ull << 62);
}
__device__ __forceinline__ uint64_t desc_mn(uint32_t addr, uint32_t lbo) {
    return (uint64_t)((addr & 0x3FFFF) >> 4) | ((uint64_t)(lbo >> 4) << 16) | (64ull << 32) | (1ull << 62);
}

#define ACC8(d, o) "+f"(d[o + 0]), "+f"(d[o + 1]), "+f"(d[o + 2]), "+f"(d[o + 3]), "+f"(d[o + 4]), "+f"(d[o + 5]), "+f"(d[o + 6]), "+f"(d[o + 7])
template <int TB, int SA = 1>
__device__ __forceinline__ void wgmma_n128(float (&d)[64], uint64_t da, uint64_t db, int sd) {
    asm volatile(
        "{\n.reg .pred p;\nsetp.ne.b32 p, %66, 0;\n"
        "wgmma.mma_async.sync.aligned.m64n128k16.f32.bf16.bf16 "
        "{%0,%1,%2,%3,%4,%5,%6,%7,%8,%9,%10,%11,%12,%13,%14,%15,%16,%17,%18,%19,%20,%21,%22,%23,%24,%25,%26,%27,%28,%29,%30,%31,"
        "%32,%33,%34,%35,%36,%37,%38,%39,%40,%41,%42,%43,%44,%45,%46,%47,%48,%49,%50,%51,%52,%53,%54,%55,%56,%57,%58,%59,%60,%61,%62,%63},"
        " %64, %65, p, %68, 1, 0, %67;\n}"
        : ACC8(d, 0), ACC8(d, 8), ACC8(d, 16), ACC8(d, 24), ACC8(d, 32), ACC8(d, 40), ACC8(d, 48), ACC8(d, 56)
        : "l"(da), "l"(db), "r"(sd), "n"(TB), "n"(SA));
}
template <int N> __device__ __forceinline__ void acc_def(float (&d)[N]) {
#pragma unroll
    for (int i = 0; i < N; i++) d[i] = 0.f;
}
template <int TB>
__device__ __forceinline__ void wgmma_n64(float (&d)[32], uint64_t da, uint64_t db, int sd) {
    asm volatile(
        "{\n.reg .pred p;\nsetp.ne.b32 p, %34, 0;\n"
        "wgmma.mma_async.sync.aligned.m64n64k16.f32.bf16.bf16 "
        "{%0,%1,%2,%3,%4,%5,%6,%7,%8,%9,%10,%11,%12,%13,%14,%15,%16,%17,%18,%19,%20,%21,%22,%23,%24,%25,%26,%27,%28,%29,%30,%31},"
        " %32, %33, p, 1, 1, 0, %35;\n}"
        : ACC8(d, 0), ACC8(d, 8), ACC8(d, 16), ACC8(d, 24)
        : "l"(da), "l"(db), "r"(sd), "n"(TB));
}
template <int SA>
__device__ __forceinline__ void wgmma_n64s(float (&d)[32], uint64_t da, uint64_t db, int sd) {
    asm volatile(
        "{\n.reg .pred p;\nsetp.ne.b32 p, %34, 0;\n"
        "wgmma.mma_async.sync.aligned.m64n64k16.f32.bf16.bf16 "
        "{%0,%1,%2,%3,%4,%5,%6,%7,%8,%9,%10,%11,%12,%13,%14,%15,%16,%17,%18,%19,%20,%21,%22,%23,%24,%25,%26,%27,%28,%29,%30,%31},"
        " %32, %33, p, %35, 1, 0, 1;\n}"
        : ACC8(d, 0), ACC8(d, 8), ACC8(d, 16), ACC8(d, 24)
        : "l"(da), "l"(db), "r"(sd), "n"(SA));
}
__device__ __forceinline__ void wgmma_n64_rs(float (&d)[32], uint32_t a0, uint32_t a1, uint32_t a2, uint32_t a3, uint64_t db, int sd) {
    asm volatile(
        "{\n.reg .pred p;\nsetp.ne.b32 p, %37, 0;\n"
        "wgmma.mma_async.sync.aligned.m64n64k16.f32.bf16.bf16 "
        "{%0,%1,%2,%3,%4,%5,%6,%7,%8,%9,%10,%11,%12,%13,%14,%15,%16,%17,%18,%19,%20,%21,%22,%23,%24,%25,%26,%27,%28,%29,%30,%31},"
        " {%32,%33,%34,%35}, %36, p, 1, 1, 1;\n}"
        : ACC8(d, 0), ACC8(d, 8), ACC8(d, 16), ACC8(d, 24)
        : "r"(a0), "r"(a1), "r"(a2), "r"(a3), "l"(db), "r"(sd));
}

struct Params {
    const __nv_bfloat16* x0;
    const __nv_bfloat16* w_r;
    const __nv_bfloat16* w_i;
    const __nv_bfloat16* lam_re;
    const __nv_bfloat16* lam_im;
    const __nv_bfloat16* log_dt;
    const __nv_bfloat16* dskip;
    float* out;
    int stop;
};

__device__ __forceinline__ float ldbf(const __nv_bfloat16* p) { return __bfloat162float(*p); }

__device__ __forceinline__ void dft_fp(int j, int& f, int& ph) {
    int cs = j >> 1;
    if (j == 1) { f = 256; ph = 0; }
    else { f = cs; ph = (j & 1) ? 128 : 0; }
}

__device__ __forceinline__ void gen_col_consts(uint32_t sb, int tid) {
#pragma unroll 1
    for (int task = tid; task < 640; task += 256) {
        int f, c8;
        uint32_t a_cc, d_pi, d_po;
        if (task < 512) {
            f = task & 63; c8 = task >> 6;
            a_cc = sb + SM_X + (f >> 5) * 16384 + ((f >> 3) & 3) * 2048 + c8 * 128 + (f & 7) * 16;
            d_pi = 8192; d_po = 1024;
        } else {
            int n2 = task & 31;
            f = 2 * n2; c8 = (task >> 5) & 3;
            a_cc = sb + SM_X + 32768 + (n2 >> 3) * 1024 + c8 * 128 + (n2 & 7) * 16;
            d_pi = 4096; d_po = 512;
        }
        float cd, sd, cs, sn;
        __sincosf((float)(f >= 32 ? f - 64 : f) * (6.283185307179586f / 64.f), &sd, &cd);
        int a = (8 * c8 * f) & 63;
        __sincosf((float)(a >= 32 ? a - 64 : a) * (6.283185307179586f / 64.f), &sn, &cs);
        float cv[8], sv[8];
#pragma unroll
        for (int e = 0; e < 8; e++) {
            cv[e] = cs; sv[e] = sn;
            float t = cs * cd - sn * sd;
            sn = sn * cd + cs * sd;
            cs = t;
        }
        uint4 oc = make_uint4(pack_bf16(cv[0], cv[1]), pack_bf16(cv[2], cv[3]), pack_bf16(cv[4], cv[5]), pack_bf16(cv[6], cv[7]));
        uint4 os = make_uint4(pack_bf16(sv[0], sv[1]), pack_bf16(sv[2], sv[3]), pack_bf16(sv[4], sv[5]), pack_bf16(sv[6], sv[7]));
        sts128(a_cc, oc);
        sts128(a_cc + d_pi, os);
        sts128(a_cc + d_po, make_uint4(os.x ^ 0x80008000u, os.y ^ 0x80008000u, os.z ^ 0x80008000u, os.w ^ 0x80008000u));
        sts128(a_cc + d_pi + d_po, oc);
    }
}

__global__ void __launch_bounds__(NTHREADS, 1)
fused_kernel(const __grid_constant__ CUtensorMap tm_x, const __grid_constant__ CUtensorMap tm_bre,
             const __grid_constant__ CUtensorMap tm_bim, const __grid_constant__ CUtensorMap tm_cre,
             const __grid_constant__ CUtensorMap tm_cim, const __grid_constant__ CUtensorMap tm_col, const Params p) {
    extern __shared__ __align__(1024) uint8_t sm[];
    const uint32_t sb = s2u(sm);
    const int tid = threadIdx.x, b = blockIdx.x;
    const int c = b >> 3, r = b & 7;
    const int par = r & 1, pi_ = r >> 1, own = 4 * par + pi_;
    const int wg = __shfl_sync(~0u, tid >> 7, 0), w = __shfl_sync(~0u, (tid >> 5) & 3, 0), lane = tid & 31, g = lane >> 2, q = lane & 3;
    auto BAR = [&](int i) { return sb + SM_BAR + 8 * i; };
    unsigned* s_tgt = (unsigned*)(sm + SM_TGT);

    if (tid < NBARS) {
        int cnt = 1;
        if (tid >= B_EMPTY0 && tid < B_EMPTY0 + 4) cnt = 16;
        if (tid >= B_XEMPTY && tid < B_XEMPTY + 4) cnt = 24;
        if (tid == B_RFREE) cnt = 12;
        if (tid == B_HDONE) cnt = 2;
        if (tid == B_SETUP) cnt = 3;
        if ((tid >= B_AEMPTY && tid < B_AEMPTY + 8) || tid == B_BFREE) cnt = 8;
        if (tid == B_AFREE) cnt = 4;
        mbar_init(BAR(tid), cnt);
        asm volatile("fence.mbarrier_init.release.cluster;" ::: "memory");
    }
    asm volatile("barrier.cluster.arrive.release.aligned;" ::: "memory");

    if (wg == 3) {
        asm volatile("setmaxnreg.dec.sync.aligned.u32 56;");
        if (w == 0 && lane < 6) {
            const CUtensorMap* tm = lane == 0 ? &tm_x : lane == 1 ? &tm_bre : lane == 2 ? &tm_bim : lane == 3 ? &tm_cre : lane == 4 ? &tm_cim : &tm_col;
            asm volatile("prefetch.tensormap [%0];" ::"l"(tm) : "memory");
        }
        __syncwarp();
        asm volatile("barrier.cluster.wait.acquire.aligned;" ::: "memory");
        if (w > 0) {
            {
                int i = tid - 416;
                int ps = i < 64 ? 64 * r + i : 32 * c + i - 64;
                float lr = ldbf(p.lam_re + ps), li = ldbf(p.lam_im + ps);
                float dt = __bfloat162float(__float2bfloat16(expf(ldbf(p.log_dt + ps))));
                if (i < 6) s_tgt[i] = ((ld_acquire(&g_bar[i]) >> 7) + 1u) << 7;
                float mag = expf(lr * dt), t = li * dt * 0.15915494309189535f, sn, cs;
                t -= rintf(t);
                sincospif(2.f * t, &sn, &cs);
                float er = mag * cs, ei = mag * sn;
                if (i < 64) {
                    *(float2*)(sm + SM_LAM + i * 8) = make_float2(er, ei);
                } else {
                    er -= 1.f;
                    float inv = 1.f / (lr * lr + li * li);
                    *(float2*)(sm + SM_TAB + (i - 64) * 8) = make_float2((er * lr + ei * li) * inv, (ei * lr - er * li) * inv);
                }
            }
            __syncwarp();
            bar_arrive(15, 224);
            if (lane == 0) mbar_arrive(BAR(B_SETUP), 1);
            if (w > 1) bar_sync(0, 224);
#pragma unroll 1
            for (int i = tid - 448; i < 96 + 128 && w > 1; i += 64) {
                if (i < 96) g_P[(uint32_t)(b * 4 + i / 24) * 1024 + 640 + ((i % 24) >> 1) * 32 + 30 + (i & 1)] = make_uint4(0, 0, 0, 0);
                else g_Ebuf[b * 128 + i - 96] = make_float4(0.f, 0.f, 0.f, 0.f);
            }
            __syncwarp();
            if (w == 3) bar_arrive(11, 192);
            if (w == 2) {
                bar_sync(11, 192);
                if (lane == 0) red_release(&g_bar[4], 1);
            }
            if (w == 3) {
#pragma unroll 1
                for (int it = 0; it < 8; it++) {
                    const int m = 4 * c + (it >> 1), d = 64 * r + m, ch = lane + 32 * (it & 1);
                    float v[8];
#pragma unroll
                    for (int e = 0; e < 8; e++) {
                        int j = 8 * ch + e, f, ph;
                        dft_fp(j, f, ph);
                        int a = (d * f + ph) & 511;
                        a = a >= 256 ? a - 512 : a;
                        float wj = j == 0 ? 0.f : (j == 1 ? 1.f / 512.f : 2.f / 512.f);
                        v[e] = wj * __cosf((float)a * (6.283185307179586f / 512.f));
                    }
                    uint32_t off = (uint32_t)(64 + r * 8 + (ch >> 3)) * 8192 + (m >> 3) * 1024 + (ch & 7) * 128 + (m & 7) * 16;
                    *(uint4*)(g_E + off) = make_uint4(pack_bf16(v[0], v[1]), pack_bf16(v[2], v[3]), pack_bf16(v[4], v[5]), pack_bf16(v[6], v[7]));
                }
                __syncwarp();
                if (lane == 0) { fence_async(); red_release(&g_bar[6], 1); }
                return;
            }
            if (w == 2) {
#pragma unroll 1
                for (int it = 0; it < 4; it++) {
                    const int hf = it & 1;
                    __syncwarp();
                    if (hf == 0) bar_sync(13, 288); else bar_sync(6, 416);
                    if (lane == 0) {
                        const uint32_t src = sb + SM_HH + par * 32768 + hf * 16384;
                        bulk_s2peer(mapa(src, par ^ 1), src, 16384, mapa(BAR(hf ? B_HPEER1 : B_HPEER), par ^ 1));
                    }
                }
                return;
            }
            bar_sync(2, 288);
            if (lane == 0) {
                TX(5);
                fence_async();
                red_release(&g_bar[0], 1);
                TX(6);
            }
            __syncwarp();
            bar_arrive(0, 224);
            bar_sync(12, 160);
            if (lane == 0) {
                asm volatile("cp.async.bulk.global.shared::cta.bulk_group [%0], [%1], 8192;" ::"l"(g_A1 + (uint32_t)(((c >> 1) * 8 + r) * 16384 + (c & 1) * 8192)),
                             "r"(sb + SM_B1ST) : "memory");
                asm volatile("cp.async.bulk.commit_group;" ::: "memory");
                asm volatile("cp.async.bulk.wait_group 0;" ::: "memory");
                mbar_arrive(BAR(B_B1DONE), 1);
                fence_async();
                red_release(&g_bar[7], 1);
            }
#pragma unroll 1
            for (int layer = 0; layer < 2; layer++) {
                __syncwarp();
                bar_sync(5, 416);
                if (lane == 0) {
                    TX(0 + 8 * layer);
                    tma_store_5d(&tm_col, 32 * (b & 1), 0, b >> 1, 0, layer, sb + SM_RAW);
                    asm volatile("cp.reduce.async.bulk.global.shared::cta.bulk_group.add.f32 [%0], [%1], 8192;" ::"l"(g_ssqc + (layer * 16 + (b & 15)) * 2048),
                                 "r"(sb + SM_SSQ) : "memory");
                    asm volatile("cp.async.bulk.commit_group;" ::: "memory");
                    asm volatile("cp.async.bulk.wait_group 0;" ::: "memory");
                    TX(1 + 8 * layer);
                    fence_async();
                    red_release(&g_bar[1 + 2 * layer], 1);
                    TX(2 + 8 * layer);
                }
            }
        } else if (tid == 384) {
#pragma unroll 1
            for (int kb = 0; kb < 8; kb++) {
                uint32_t fb = BAR(B_FULL0 + kb);
                mbar_expect(fb, 16384);
                tma_5d_mc(sb + SM_A + 65536 + kb * 16384 + par * 8192, &tm_x, kb * 64, 0, 0, 8 * par, c, fb);
            }
#pragma unroll 1
            for (int k2 = 0; k2 < 8; k2++) {
                asm volatile("cp.async.bulk.prefetch.tensor.2d.L2.global [%0, {%1,%2}];" ::"l"(par ? &tm_bim : &tm_bre), "r"(k2 * 64), "r"(32 * c) : "memory");
                if ((k2 & 1) == par)
                    asm volatile("cp.async.bulk.prefetch.tensor.2d.L2.global [%0, {%1,%2}];" ::"l"((c & 1) ? &tm_cim : &tm_cre), "r"(64 * (c >> 1)), "r"(k2 * 64) : "memory");
            }
            mbar_wait(BAR(B_SETUP), 0);
#pragma unroll 1
            for (int layer = 0; layer < 2; layer++) {
                wait_count(&g_bar[2 * layer], s_tgt[2 * layer]);
                TX(4 + 8 * layer);
                fence_async();
                mbar_expect(BAR(B_COL), 16384 + 8192);
                tma_5d(sb + SM_RAW, &tm_col, 32 * (b & 1), 0, b >> 1, 0, layer, BAR(B_COL));
                bulk_g2s(sb + SM_SSQ, g_ssq + layer * 2048, 8192, BAR(B_COL));
                if (layer == 0) {
                    wait_count(&g_bar[4], s_tgt[4]);
                    mbar_arrive(BAR(B_WRDY), 1);
                    wait_count(&g_bar[7], s_tgt[4]);
                    fence_async();
                }
                if (layer == 0) mbar_wait(BAR(B_AFREE), 0);
                mbar_wait(BAR(B_COL), layer);
#pragma unroll 1
                for (int s = 0; s < 8; s++) {
                    if (layer == 1) mbar_wait(BAR(B_AEMPTY + s), 1);
                    if (s >= 2) mbar_wait(BAR(B_AFULL + s - 2), 0);
                    mbar_expect(BAR(B_AFULL + s), 16384);
                    bulk_g2s(sb + SM_A + s * 16384, g_A1 + (uint32_t)(r * 8 + s) * 16384, 16384, BAR(B_AFULL + s));
                }
                if (layer == 1) wait_count(&g_bar[6], s_tgt[4]);
                wait_count(&g_bar[1 + 2 * layer], s_tgt[1 + 2 * layer]);
                TX(3 + 8 * layer);
                fence_async();
                const uint8_t* xsrc = g_X + (uint32_t)(layer * 16 + c) * 8 * 16384;
                const uint8_t* esrc = g_E + (uint32_t)(layer * 8 + own) * 8 * 8192;
                mbar_arrive(BAR(B_SSQ), 1);
                mbar_expect(BAR(B_HPEER), 16384);
                mbar_expect(BAR(B_HPEER1), 16384);
#pragma unroll 1
                for (int it = 0; it < 16; it++) {
                    if (it < 8) {
                        int st = it & 3, f = layer * 2 + (it >> 2);
                        if (f > 0) mbar_wait_cluster(BAR(B_XEMPTY + st), (f - 1) & 1);
                        mbar_expect(BAR(B_XFULL + st), 24576);
                        bulk_g2s_mc(sb + SM_X + st * 24576 + par * 8192, xsrc + (uint32_t)it * 16384 + par * 8192, 8192, BAR(B_XFULL + st));
                        bulk_g2s(sb + SM_X + st * 24576 + 16384, esrc + (uint32_t)it * 8192, 8192, BAR(B_XFULL + st));
                    }
                    if (it >= 8) {
                        if (it == 8) mbar_wait(BAR(B_AEMPTY + 5), 0);
                        int s = it - 8, tile = 4 * par + ((pi_ + 1 + (s >> 1)) & 3), sl = r ^ (s & 1);
                        mbar_wait(BAR(B_AEMPTY + s), 0);
                        uint32_t fb = BAR(B_AFULL + s), dst = sb + SM_A + s * 16384;
                        mbar_expect(fb, 16384);
                        if (layer == 1) {
                            tma_2d(dst, &tm_cre, 64 * sl, 64 * tile, fb);
                            tma_2d(dst + 8192, &tm_cim, 64 * sl, 64 * tile, fb);
                        } else {
                            bulk_g2s(dst, g_A2 + (uint32_t)(sl * 8 + tile) * 16384, 16384, fb);
                        }
                    }
                }
            }
        }
        return;
    }

    asm volatile("setmaxnreg.inc.sync.aligned.u32 152;");
    if (tid >= 96 && tid < 112) g_ssq[2048 + 16 * b + tid - 96] = 0.f;
    if (tid >= 128 && tid < 256) ((float4*)g_ssqc)[b * 128 + tid - 128] = make_float4(0.f, 0.f, 0.f, 0.f);
    TS(0);
    if (wg == 0) TC(30);
    {
        const int f = 32 * r + lane;
        float cd, sd;
        __sincosf((float)f * (6.283185307179586f / 512.f), &sd, &cd);
        const uint32_t dst = sb + SM_A + (lane >> 2) * 1024 + (lane & 3) * 32;
#pragma unroll 1
        for (int ch = tid >> 5; ch < 64; ch += 12) {
            int a = (8 * ch * f) & 511;
            a = a >= 256 ? a - 512 : a;
            float cs, sn;
            __sincosf((float)a * (6.283185307179586f / 512.f), &sn, &cs);
            float cv[8], sv[8];
#pragma unroll
            for (int e = 0; e < 8; e++) {
                cv[e] = cs; sv[e] = -sn;
                float t = cs * cd - sn * sd;
                sn = sn * cd + cs * sd;
                cs = t;
            }
            uint4 o1 = make_uint4(pack_bf16(sv[0], sv[1]), pack_bf16(sv[2], sv[3]), pack_bf16(sv[4], sv[5]), pack_bf16(sv[6], sv[7]));
            if (f == 0) o1 = make_uint4(0xbf803f80u, 0xbf803f80u, 0xbf803f80u, 0xbf803f80u);
            uint32_t a0 = dst + (ch >> 3) * 8192 + (ch & 7) * 128;
            sts128(a0, make_uint4(pack_bf16(cv[0], cv[1]), pack_bf16(cv[2], cv[3]), pack_bf16(cv[4], cv[5]), pack_bf16(cv[6], cv[7])));
            sts128(a0 + 16, o1);
        }
    }
    fence_async_smem();
    asm volatile("barrier.cluster.wait.acquire.aligned;" ::: "memory");
    bar_sync(10, 384);
    TS(1);
    if (wg < 2) {
        float acc[32];
        acc_def(acc);
        const int npos = 16 * r + 8 * wg + 2 * w;
        float sh0 = 0.f, sh1 = 0.f, s0 = 0.f, s1 = 0.f, q0 = 0.f, q1 = 0.f;
#pragma unroll 1
        for (int kb = 0; kb < 8; kb++) {
            uint32_t slot = sb + SM_A + 65536 + kb * 16384;
            mbar_wait(BAR(B_FULL0 + kb), 0);
            wg_fence();
#pragma unroll
            for (int ks = 0; ks < 4; ks++)
                wgmma_n64<0>(acc, desc_a(sb + SM_A + kb * 8192 + ks * 256), desc_k(slot + wg * 8192 + ks * 32), 1);
            wg_commit();
            {
                uint32_t v0 = lds32(slot + npos * 128 + lane * 4), v1 = lds32(slot + npos * 128 + 128 + lane * 4);
                if (kb == 0) { sh0 = __shfl_sync(~0u, bf_lo(v0), 0); sh1 = __shfl_sync(~0u, bf_lo(v1), 0); }
                float a = bf_lo(v0) - sh0, bq = bf_hi(v0) - sh0, cq = bf_lo(v1) - sh1, d = bf_hi(v1) - sh1;
                s0 += a + bq; q0 += a * a + bq * bq; s1 += cq + d; q1 += cq * cq + d * d;
            }
            wg_wait<1>();
            if (kb > 0 && kb <= 4 && lane == 0) { mbar_arrive(BAR(B_EMPTY0 + kb - 1), 1); mbar_arrive_remote(mapa(BAR(B_EMPTY0 + kb - 1), par ^ 1)); }
        }
#pragma unroll
        for (int o = 16; o; o >>= 1) {
            s0 += __shfl_xor_sync(~0u, s0, o); q0 += __shfl_xor_sync(~0u, q0, o);
            s1 += __shfl_xor_sync(~0u, s1, o); q1 += __shfl_xor_sync(~0u, q1, o);
        }
        if (lane == 0) *(float2*)(g_ssq + 128 * c + npos) = make_float2(fmaxf(q0 - s0 * s0 * (1.f / 512.f), 0.f), fmaxf(q1 - s1 * s1 * (1.f / 512.f), 0.f));
        wg_wait<0>();
        TS(2);
        uint8_t* dst = g_X + (uint32_t)((c * 8 + r) * 16384 + w * 4096 + wg * 1024 + g * 16 + 4 * q);
#pragma unroll
        for (int i = 0; i < 8; i++) {
            *(uint32_t*)(dst + i * 128) = pack_bf16(acc[4 * i], acc[4 * i + 1]);
            *(uint32_t*)(dst + 2048 + i * 128) = pack_bf16(acc[4 * i + 2], acc[4 * i + 3]);
        }
        bar_sync(2, 288);
        mbar_wait(BAR(B_SETUP), 0);
        TS(3);
    }

    if (wg == 2) {
        uint32_t wf[2][16];
        {
            const int cb = tid & 127;
            const int c0 = cb == 0 ? 256 : 2 * cb, c1 = 2 * cb + 1;
#pragma unroll
            for (int h = 0; h < 2; h++) {
                const int kq = 2 * b + h, k1 = kq >> 2, qq = kq & 3;
                const unsigned short* wr_ = (const unsigned short*)p.w_r + (k1 + 128 * qq) * 257;
                const unsigned short* wi_ = (const unsigned short*)p.w_i + (k1 + 128 * qq) * 257;
#pragma unroll
                for (int i = 0; i < 4; i++) {
                    int o = 512 * i * 257;
                    wf[h][2 * i] = (uint32_t)__ldg(wr_ + o + c0) | ((uint32_t)__ldg(wr_ + o + 64 * 257 + c0) << 16);
                    wf[h][2 * i + 1] = ((uint32_t)__ldg(wi_ + o + c0) | ((uint32_t)__ldg(wi_ + o + 64 * 257 + c0) << 16)) ^ 0x80008000u;
                    wf[h][8 + 2 * i] = (uint32_t)__ldg(wr_ + o + c1) | ((uint32_t)__ldg(wr_ + o + 64 * 257 + c1) << 16);
                    wf[h][8 + 2 * i + 1] = ((uint32_t)__ldg(wi_ + o + c1) | ((uint32_t)__ldg(wi_ + o + 64 * 257 + c1) << 16)) ^ 0x80008000u;
                }
            }
            uint4 p0 = __ldg((const uint4*)p.dskip + 2 * lane), p1 = __ldg((const uint4*)p.dskip + 2 * lane + 1);
            uint32_t u[8] = {p0.x, p0.y, p0.z, p0.w, p1.x, p1.y, p1.z, p1.w};
            int j = 64 * r + 4 * c + w, f, ph;
            dft_fp(j, f, ph);
            float s = 0.f;
            int idx = 16 * lane * f + ph;
#pragma unroll
            for (int i = 0; i < 16; i++) {
                int a = idx & 511;
                idx += f;
                a = a >= 256 ? a - 512 : a;
                s += ((i & 1) ? bf_hi(u[i >> 1]) : bf_lo(u[i >> 1])) * __cosf((float)a * (6.283185307179586f / 512.f));
            }
#pragma unroll
            for (int o = 16; o; o >>= 1) s += __shfl_xor_sync(~0u, s, o);
            if (lane == 0) g_Dh[j] = s;
        }
        bar_sync(15, 224);
        float acc[32];
        acc_def(acc);
        if (tid == 256) {
#pragma unroll 1
            for (int s = 0; s < 4; s++) mbar_wait_cluster(BAR(B_EMPTY0 + s), 0);
            mbar_expect(BAR(B_FULLB), 65536);
#pragma unroll 1
            for (int k2 = 0; k2 < 8; k2++)
                tma_2d_mc(sb + SM_A + 65536 + k2 * 8192 + par * 4096, par ? &tm_bim : &tm_bre, k2 * 64, 32 * c, BAR(B_FULLB));
        }
        __syncwarp();
        mbar_wait(BAR(B_FULLB), 0);
        wg_fence();
#pragma unroll 1
        for (int kb = 0; kb < 8; kb++) {
#pragma unroll
            for (int ks = 0; ks < 4; ks++)
                wgmma_n64<0>(acc, desc_a(sb + SM_A + kb * 8192 + ks * 256), desc_k(sb + SM_A + 65536 + kb * 8192 + ks * 32), 1);
            wg_commit();
        }
        wg_wait<0>();
        if (lane == 0) { mbar_arrive(BAR(B_BFREE), 1); mbar_arrive_remote(mapa(BAR(B_BFREE), par ^ 1)); }
        if (tid == 256) {
            mbar_wait_cluster(BAR(B_BFREE), 0);
            mbar_expect(BAR(B_FULLC), 65536);
#pragma unroll 1
            for (int k2 = par; k2 < 8; k2 += 2)
                tma_2d_mc(sb + SM_A + 65536 + k2 * 8192, (c & 1) ? &tm_cim : &tm_cre, 64 * (c >> 1), k2 * 64, BAR(B_FULLC));
        }
        __syncwarp();
        {
            uint8_t* dst = sm + SM_B1ST + w * 256 + q * 32 + g * 2;
            const float wj0 = (r == 0 && w == 0 && g < 2) ? (g == 0 ? 0.f : 1.f / 512.f) : 2.f / 512.f;
#pragma unroll
            for (int i = 0; i < 4; i++) {
#pragma unroll
                for (int e = 0; e < 2; e++) {
                    float2 cf = *(const float2*)(sm + SM_TAB + (8 * i + 2 * q + e) * 8);
#pragma unroll
                    for (int h = 0; h < 2; h++) {
                        float wj = h == 0 ? wj0 : 2.f / 512.f;
                        float pr = acc[4 * i + 2 * h + e] * wj, pi = acc[16 + 4 * i + 2 * h + e] * wj;
                        uint8_t* d2 = dst + i * 2048 + h * 128 + e * 16;
                        *(__nv_bfloat16*)(d2) = __float2bfloat16(cf.x * pr - cf.y * pi);
                        *(__nv_bfloat16*)(d2 + 1024) = __float2bfloat16(cf.x * pi + cf.y * pr);
                    }
                }
            }
            fence_async_smem();
            bar_arrive(12, 160);
        }
        bar_sync(0, 224);
        {
            uint4* wd = g_Wfrag + (uint32_t)((tid & 127) * 1024 + 2 * b);
#pragma unroll
            for (int i = 0; i < 4; i++) {
                wd[i * 256] = make_uint4(wf[0][4 * i], wf[0][4 * i + 1], wf[0][4 * i + 2], wf[0][4 * i + 3]);
                wd[i * 256 + 1] = make_uint4(wf[1][4 * i], wf[1][4 * i + 1], wf[1][4 * i + 2], wf[1][4 * i + 3]);
            }
            bar_arrive(11, 192);
        }
        acc_def(acc);
        mbar_wait(BAR(B_FULLC), 0);
        wg_fence();
#pragma unroll 1
        for (int kb = 0; kb < 8; kb++) {
#pragma unroll
            for (int ks = 0; ks < 4; ks++)
                wgmma_n64<1>(acc, desc_a(sb + SM_A + kb * 8192 + ks * 256), desc_mn(sb + SM_A + 65536 + kb * 8192 + ks * 2048, 8192), 1);
            wg_commit();
        }
        wg_wait<0>();
        fence_async_smem();
        if (lane == 0) mbar_arrive(BAR(B_AFREE), 1);
        uint8_t* dst = g_A2 + (uint32_t)(((c >> 1) * 8 + r) * 16384 + (c & 1) * 8192 + w * 2048 + g * 16 + 4 * q);
#pragma unroll
        for (int i = 0; i < 8; i++) {
            *(uint32_t*)(dst + i * 128) = pack_bf16(acc[4 * i], acc[4 * i + 1]);
            *(uint32_t*)(dst + 1024 + i * 128) = pack_bf16(acc[4 * i + 2], acc[4 * i + 3]);
        }
        {
            const int m = 4 * c + w, jp = 64 * r + m;
            int fp, php;
            dft_fp(jp, fp, php);
            const __nv_bfloat16* dh = (const __nv_bfloat16*)(sm + SM_RSTD);
            if (tid == 256) wait_count(&g_bar[4], s_tgt[4]);
            bar_sync(3, 128);
            float4 d4 = __ldcg((const float4*)g_Dh + (tid - 256));
            *(uint2*)(sm + SM_RSTD + (tid - 256) * 8) = make_uint2(pack_bf16(d4.x, d4.y), pack_bf16(d4.z, d4.w));
            bar_sync(3, 128);
#pragma unroll 1
            for (int it = 0; it < 2; it++) {
                const int ch = lane + 32 * it;
                float v[8];
#pragma unroll
                for (int e = 0; e < 8; e++) {
                    int j = 8 * ch + e, f, ph;
                    dft_fp(j, f, ph);
                    float wj = j == 0 ? 0.f : (j == 1 ? 1.f / 512.f : 2.f / 512.f);
                    float gsum = 0.f;
#pragma unroll
                    for (int sgn = 0; sgn < 2; sgn++) {
                        int mm = (sgn ? f - fp : f + fp) & 511, pp = (sgn ? ph - php : ph + php) & 511;
                        if (mm > 256) { mm = 512 - mm; pp = (512 - pp) & 511; }
                        int odd = (pp >> 7) & 1;
                        float t = __bfloat162float(dh[mm == 256 ? 1 : 2 * mm + odd]);
                        if (odd && (mm & 255) == 0) t = 0.f;
                        gsum += (pp & 256) ? -t : t;
                    }
                    v[e] = 0.5f * wj * gsum;
                }
                uint32_t off = (uint32_t)(r * 8 + (ch >> 3)) * 8192 + (m >> 3) * 1024 + (ch & 7) * 128 + (m & 7) * 16;
                *(uint4*)(g_E + off) = make_uint4(pack_bf16(v[0], v[1]), pack_bf16(v[2], v[3]), pack_bf16(v[4], v[5]), pack_bf16(v[6], v[7]));
            }
        }
    }

#pragma unroll 1
    for (int layer = 0; layer < 2; layer++) {
        if (wg < 2) {
            const int n1 = 32 * wg + 8 * w + g;
            const int ct = n1 >> 2;
            gen_col_consts(sb, tid);
            uint32_t tr2[4], ti2[4], tn2[4];
#pragma unroll
            for (int i = 0; i < 4; i++) {
                float cr[2], ci[2];
#pragma unroll
                for (int e = 0; e < 2; e++) {
                    int a = (n1 * (8 * i + 2 * q + e)) & 2047;
                    a = a >= 1024 ? a - 2048 : a;
                    float ang = (float)a * (-6.283185307179586f / 2048.f);
                    cr[e] = __cosf(ang); ci[e] = __sinf(ang);
                }
                tr2[i] = pack_bf16(cr[0], cr[1]); ti2[i] = pack_bf16(ci[0], ci[1]); tn2[i] = ti2[i] ^ 0x80008000u;
            }
            uint32_t wf[16];
            const uint4* ws = g_Wfrag + (uint32_t)(b * 1024 + n1 * 4 + q);
#pragma unroll
            for (int i = 0; i < 4; i++) {
                uint4 v = make_uint4(0, 0, 0, 0);
                if (layer == 1) v = __ldcg(ws + i * 256);
                wf[4 * i] = v.x; wf[4 * i + 1] = v.y; wf[4 * i + 2] = v.z; wf[4 * i + 3] = v.w;
            }
            mbar_wait(BAR(B_COL), layer);
            TS(4 + 12 * layer);
            if (wg == 0) TC(0 + 10 * layer);
            const uint32_t rw0 = sb + SM_RAW + ct * 1024 + q * 64 + ((q >> 1) << 4) + (g & 3) * 4, rw1 = rw0 ^ 16;
            const int pos0 = 128 * ct + 8 * q + 2 * (g & 3);
            const int sw = b == 0 ? 1 : 0;
            uint32_t xr[4][4];
            const uint32_t st0 = sb + SM_H + (n1 >> 3) * 1024 + g * 16 + 4 * q;
#pragma unroll
            for (int i = 0; i < 4; i++) {
                float2 sq = *(const float2*)(sm + SM_SSQ + (pos0 + 32 * i) * 4);
                const uint32_t rs2 = pack_bf16(rsqrtf(sq.x * (1.f / 512.f) + 1e-5f), rsqrtf(sq.y * (1.f / 512.f) + 1e-5f));
#pragma unroll
                for (int jj = 0; jj < 4; jj++) {
                    const int K = jj ^ (2 * (i & 1));
                    uint32_t a = ((K & 1) ? rw1 : rw0) + i * 256 + (K & 2) * 16;
                    if (jj < 2) a ^= sw << 4;
                    uint32_t v = lds32(a);
                    xr[jj][i] = v;
                    uint32_t o = hmul2(v, rs2);
                    if (jj == 1 && sw) o = 0u;
                    sts32(st0 + (jj & 1) * 8192 + (4 * (jj >> 1) + i) * 128, o);
                }
            }
            if (wg == 0) TC(1 + 10 * layer);
            fence_async_smem();
            bar_sync(1, 256);
            float acc[32];
            const uint32_t s1a = sb + SM_X + wg * 16384, s2b = sb + SM_X + 32768;
            wg_fence();
#pragma unroll
            for (int ks = 0; ks < 8; ks++)
                wgmma_n64<1>(acc, desc_a(s1a + (ks >> 2) * 8192 + (ks & 3) * 256), desc_b<64>(sb + SM_H + ks * 2048), ks != 0);
            wg_commit();
            if (layer == 0) {
                mbar_wait(BAR(B_WRDY), 0);
#pragma unroll
                for (int i = 0; i < 4; i++) {
                    uint4 v = __ldcg(ws + i * 256);
                    wf[4 * i] = v.x; wf[4 * i + 1] = v.y; wf[4 * i + 2] = v.z; wf[4 * i + 3] = v.w;
                }
            }
            wg_wait<0>();
            if (wg == 0) TC(2 + 10 * layer);
            uint32_t are[2][4], aim[2][4];
#pragma unroll
            for (int col = 0; col < 2; col++) {
#pragma unroll
                for (int i = 0; i < 4; i++) {
                    int o = 4 * (4 * col + i);
                    uint32_t zr = pack_bf16(acc[o], acc[o + 1]), zi = pack_bf16(acc[o + 2], acc[o + 3]);
                    are[col][i] = hfma2(zr, tr2[i], hmul2(zi, tn2[i]));
                    aim[col][i] = hfma2(zr, ti2[i], hmul2(zi, tr2[i]));
                }
            }
            wg_fence();
#pragma unroll
            for (int ks = 0; ks < 2; ks++)
                wgmma_n64_rs(acc, are[0][2 * ks], are[1][2 * ks], are[0][2 * ks + 1], are[1][2 * ks + 1], desc_b<64>(s2b + ks * 2048), ks != 0);
#pragma unroll
            for (int ks = 0; ks < 2; ks++)
                wgmma_n64_rs(acc, aim[0][2 * ks], aim[1][2 * ks], aim[0][2 * ks + 1], aim[1][2 * ks + 1], desc_b<64>(s2b + 4096 + ks * 2048), 1);
            wg_commit();
            wg_wait<0>();
            if (wg == 0) TC(3 + 10 * layer);
#pragma unroll
            for (int col = 0; col < 2; col++) {
#pragma unroll
                for (int i = 0; i < 4; i++) {
                    uint32_t wr = wf[col * 8 + 2 * i], wn = wf[col * 8 + 2 * i + 1];
                    uint32_t zr = pack_bf16(acc[4 * i + 2 * col], acc[4 * i + 2 * col + 1]);
                    uint32_t zi = pack_bf16(acc[16 + 4 * i + 2 * col], acc[16 + 4 * i + 2 * col + 1]);
                    are[col][i] = hfma2(zr, wr, hmul2(zi, wn));
                    aim[col][i] = hfma2(zr, wn, hmul2(zi ^ 0x80008000u, wr));
                }
            }
            wg_fence();
#pragma unroll
            for (int ks = 0; ks < 2; ks++)
                wgmma_n64_rs(acc, are[0][2 * ks], are[1][2 * ks], are[0][2 * ks + 1], are[1][2 * ks + 1], desc_b<64>(s2b + ks * 2048), ks != 0);
#pragma unroll
            for (int ks = 0; ks < 2; ks++)
                wgmma_n64_rs(acc, aim[0][2 * ks], aim[1][2 * ks], aim[0][2 * ks + 1], aim[1][2 * ks + 1], desc_b<64>(s2b + 4096 + ks * 2048), 1);
            wg_commit();
            wg_wait<0>();
            if (wg == 0) TC(4 + 10 * layer);
            mbar_wait(BAR(B_B1DONE), 0);
#pragma unroll
            for (int col = 0; col < 2; col++) {
#pragma unroll
                for (int i = 0; i < 4; i++) {
                    uint32_t zr = pack_bf16(acc[4 * i + 2 * col], acc[4 * i + 2 * col + 1]);
                    uint32_t zi = pack_bf16(acc[16 + 4 * i + 2 * col], acc[16 + 4 * i + 2 * col + 1]);
                    sts32(st0 + 16384 + (4 * col + i) * 128, hfma2(zr, tr2[i], hmul2(zi, tn2[i])));
                    sts32(st0 + 16384 + 8192 + (4 * col + i) * 128, hfma2(zr, ti2[i], hmul2(zi, tr2[i])));
                }
            }
            if (wg == 0) TC(5 + 10 * layer);
            fence_async_smem();
            bar_sync(1, 256);
            wg_fence();
#pragma unroll
            for (int ks = 0; ks < 8; ks++)
                wgmma_n64<1>(acc, desc_a(s1a + (ks >> 2) * 8192 + (ks & 3) * 256), desc_b<64>(sb + SM_H + 16384 + ks * 2048), ks != 0);
            wg_commit();
            wg_wait<0>();
            if (wg == 0) TC(6 + 10 * layer);
            const float sc = 1.f / 2048.f;
            const float sci0 = sw ? 0.f : -sc;
            const float wr0 = sw ? 0.5f : 1.f, wi0 = sw ? 0.f : 1.f;
#pragma unroll
            for (int i = 0; i < 4; i++) {
                float ss0, ss1;
#pragma unroll
                for (int col = 0; col < 2; col++) {
                    int o = 4 * (4 * col + i);
                    uint32_t vr = xr[2 * col][i], vi = xr[2 * col + 1][i];
                    float si = col == 0 ? sci0 : -sc;
                    uint32_t nr = pack_bf16(fmaf(acc[o], sc, bf_lo(vr)), fmaf(acc[o + 1], sc, bf_hi(vr)));
                    uint32_t ni = pack_bf16(fmaf(acc[o + 2], si, bf_lo(vi)), fmaf(acc[o + 3], si, bf_hi(vi)));
                    float a0 = bf_lo(nr), a1 = bf_hi(nr), b0 = bf_lo(ni), b1 = bf_hi(ni);
                    if (col == 0) {
                        ss0 = wr0 * a0 * a0 + wi0 * b0 * b0;
                        ss1 = wr0 * a1 * a1 + wi0 * b1 * b1;
                    } else {
                        ss0 += a0 * a0 + b0 * b0;
                        ss1 += a1 * a1 + b1 * b1;
                    }
                    const int K = (2 * col) ^ (2 * (i & 1));
                    uint32_t a = rw0 + i * 256 + K * 16;
                    if (col == 0) a ^= sw << 4;
                    sts32(a, nr);
                    sts32(a ^ 16, ni);
                }
                *(float2*)(sm + SM_SSQ + (pos0 + 32 * i) * 4) = make_float2(ss0 * (2.f / 512.f), ss1 * (2.f / 512.f));
            }
            fence_async_smem();
        }
        TS(5 + 12 * layer);
        if (wg == 0) TC(7 + 10 * layer);
        bar_arrive(5, 416);

        float acc[64];
        float* s_rstd = (float*)(sm + SM_RSTD);
        float* s_mean = (float*)(sm + SM_MEAN);
        const unsigned epoch = s_tgt[0] >> 7;
        const uint32_t pt3 = 1u + (2u * epoch + layer) % 3u;
        const uint32_t ptag = (pt3 & 1u) | ((pt3 & 2u) << 15);
        const uint64_t dstep = layer == 0 ? 16 : 2;
        auto c_desc = [&](int s) { return layer == 0 ? desc_a(sb + SM_A + s * 16384) : desc_k(sb + SM_A + s * 16384); };
        if (wg < 2) {
            const int prow = 32 * wg + 8 * w + g;
            const float2 l1 = *(const float2*)(sm + SM_LAM + prow * 8);
            float lr32 = l1.x, li32 = l1.y;
#pragma unroll
            for (int i = 0; i < 5; i++) { float t = lr32 * lr32 - li32 * li32; li32 = 2.f * lr32 * li32; lr32 = t; }
            float lr128 = lr32, li128 = li32;
#pragma unroll
            for (int i = 0; i < 2; i++) { float t = lr128 * lr128 - li128 * li128; li128 = 2.f * lr128 * li128; lr128 = t; }
            const float lr1 = l1.x, li1 = l1.y;
            acc_def(acc);
#pragma unroll 1
            for (int kb = 0; kb < 8; kb++) {
                mbar_wait(BAR(B_AFULL + kb), 0);
                mbar_wait(BAR(B_XFULL + (kb & 3)), (kb >> 2) & 1);
                wg_fence();
#pragma unroll
                for (int ks = 0; ks < 4; ks++)
                    wgmma_n128<1>(acc, desc_a(sb + SM_A + kb * 16384 + wg * 8192 + ks * 256),
                                  desc_b<128>(sb + SM_X + (kb & 3) * 24576 + ks * 4096), 1);
                wg_commit();
                wg_wait<1>();
                if (kb > 0 && lane == 0) {
                    mbar_arrive(BAR(B_AEMPTY + kb - 1), 1); mbar_arrive(BAR(B_XEMPTY + ((kb - 1) & 3)), 1);
                    mbar_arrive_remote(mapa(BAR(B_XEMPTY + ((kb - 1) & 3)), par ^ 1));
                }
            }
            wg_wait<0>();
            if (lane == 0) {
                mbar_arrive(BAR(B_AEMPTY + 7), 1); mbar_arrive(BAR(B_XEMPTY + 3), 1);
                mbar_arrive_remote(mapa(BAR(B_XEMPTY + 3), par ^ 1)); mbar_arrive_remote(mapa(BAR(B_RFREE), par ^ 1));
            }
            bar_arrive(14, 384);
            TS(6 + 12 * layer);
            bar_sync(4, 384);
            TS(7 + 12 * layer);
            float er = 0.f, ei = 0.f;
#pragma unroll
            for (int i = 0; i < 16; i++) {
                float2 rs = *(const float2*)(s_rstd + 128 + 8 * i + 2 * q);
                acc[4 * i] *= rs.x; acc[4 * i + 1] *= rs.y; acc[4 * i + 2] *= rs.x; acc[4 * i + 3] *= rs.y;
                float nr = lr1 * er - li1 * ei + acc[4 * i], ni = lr1 * ei + li1 * er + acc[4 * i + 2];
                er = lr1 * nr - li1 * ni + acc[4 * i + 1];
                ei = lr1 * ni + li1 * nr + acc[4 * i + 3];
            }
            float cr = 0.f, ci = 0.f, tr = 0.f, ti = 0.f;
#pragma unroll
            for (int qq = 0; qq < 4; qq++) {
                float xr_ = __shfl_sync(~0u, er, (lane & ~3) | qq), xi_ = __shfl_sync(~0u, ei, (lane & ~3) | qq);
                if (qq == q) { cr = tr; ci = ti; }
                float nr = lr32 * tr - li32 * ti + xr_, ni = lr32 * ti + li32 * tr + xi_;
                tr = nr; ti = ni;
            }
            float4* eb = g_Ebuf + (uint32_t)(layer * 16 * 512 + 64 * r + prow);
            if (q == 0 && c < 15) st_relaxed_f4(eb + c * 512, make_float4(tr, ti, __uint_as_float(epoch), 0.f));
            TS(8 + 12 * layer);
            float pr[4], pi[4];
            {
                unsigned n = 0;
                bool ok;
#pragma unroll 1
                do {
                    ok = true;
#pragma unroll
                    for (int k = 0; k < 4; k++) {
                        float4 v = make_float4(0.f, 0.f, __uint_as_float(epoch), 0.f);
                        if (4 * k + q < c) v = ld_relaxed_f4(eb + (4 * k + q) * 512);
                        pr[k] = v.x; pi[k] = v.y;
                        ok = ok && __float_as_uint(v.z) == epoch;
                    }
                } while (!ok && ++n < SPIN_LIMIT);
            }
            __syncwarp();
            TS(9 + 12 * layer);
            float hr = 0.f, hi = 0.f;
#pragma unroll
            for (int cc = 0; cc < 15; cc++) {
                float xr_ = __shfl_sync(~0u, pr[cc >> 2], (lane & ~3) | (cc & 3)), xi_ = __shfl_sync(~0u, pi[cc >> 2], (lane & ~3) | (cc & 3));
                if (cc < c) {
                    float nr = lr128 * hr - li128 * hi + xr_, ni = lr128 * hi + li128 * hr + xi_;
                    hr = nr; hi = ni;
                }
            }
#pragma unroll
            for (int qq = 0; qq < 3; qq++) {
                if (qq < q) { float nr = lr32 * hr - li32 * hi, ni = lr32 * hi + li32 * hr; hr = nr; hi = ni; }
            }
            er = cr + hr; ei = ci + hi;
            bar_sync(7, 384);
            mbar_wait_cluster(BAR(B_RFREE), layer);
            const uint32_t ha = sb + SM_HH + par * 32768 + (prow >> 3) * 1024 + g * 16 + 4 * q;
#pragma unroll
            for (int i = 0; i < 16; i++) {
                float nr = lr1 * er - li1 * ei + acc[4 * i], ni = lr1 * ei + li1 * er + acc[4 * i + 2];
                er = lr1 * nr - li1 * ni + acc[4 * i + 1];
                ei = lr1 * ni + li1 * nr + acc[4 * i + 3];
                sts32(ha + (i >> 3) * 16384 + (i & 7) * 128, pack_bf16(nr, er));
                sts32(ha + (i >> 3) * 16384 + 8192 + (i & 7) * 128, pack_bf16(ni, ei));
                if (i == 7) { fence_async_smem(); bar_arrive(13, 288); }
            }
            fence_async_smem();
            acc_def(acc);
            float acc2[32];
            acc_def(acc2);
            TS(10 + 12 * layer);
            bar_sync(6, 416);
            TS(11 + 12 * layer);
            float (&a0)[32] = *reinterpret_cast<float (*)[32]>(&acc[0]);
            float (&a1)[32] = *reinterpret_cast<float (*)[32]>(&acc[32]);
            auto tile_mma = [&](float (&d)[32], int u) {
#pragma unroll 1
                for (int k = 0; k < 2; k++) {
                    const uint32_t hb = sb + SM_HH + (par ^ k) * 32768 + wg * 16384;
                    if (k == 1) mbar_wait(BAR(wg ? B_HPEER1 : B_HPEER), layer);
                    mbar_wait(BAR(B_AFULL + 2 * u + k), 1);
                    const uint64_t da = c_desc(2 * u + k);
                    wg_fence();
#pragma unroll
                    for (int ks = 0; ks < 4; ks++) wgmma_n64s<1>(d, da + ks * dstep, desc_b<64>(hb + ks * 2048), 1);
#pragma unroll
                    for (int ks = 0; ks < 4; ks++) wgmma_n64s<-1>(d, da + 512 + ks * dstep, desc_b<64>(hb + 8192 + ks * 2048), 1);
                }
                wg_commit();
            };
            auto tile_ship = [&](float (&d)[32], int u) {
                uint4* dst = g_P + (uint32_t)(((c * 8 + 2 * ((pi_ + 1 + u) & 3) + par) * 4 + pi_) * 1024 + wg * 512 + (tid & 127));
#pragma unroll
                for (int i = 0; i < 4; i++)
                    dst[i * 128] = make_uint4((pack_bf16(d[8 * i], d[8 * i + 1]) & 0xfffefffeu) | ptag, pack_bf16(d[8 * i + 2], d[8 * i + 3]),
                                              pack_bf16(d[8 * i + 4], d[8 * i + 5]), pack_bf16(d[8 * i + 6], d[8 * i + 7]));
            };
            tile_mma(a0, 0);
            if ((tid & 127) == 0) mbar_arrive_remote(mapa(BAR(B_HDONE), par ^ 1));
            __syncwarp();
            tile_mma(a1, 1);
            wg_wait<1>();
            tile_ship(a0, 0);
            tile_mma(acc2, 2);
            bar_arrive(12, 384);
            wg_wait<1>();
            tile_ship(a1, 1);
            wg_wait<0>();
            tile_ship(acc2, 2);
            if (lane < 6) mbar_arrive(BAR(B_AEMPTY + lane), 1);
            TS(12 + 12 * layer);
        } else {
            const int t2 = tid - 256;
            const uint8_t* ximg = g_X + (uint32_t)layer * 16 * 8 * 16384;
            mbar_wait(BAR(B_SSQ), layer);
            TS(6 + 12 * layer);
            float sqv[16];
#pragma unroll
            for (int i = 0; i < 16; i++) sqv[i] = __ldcg(g_ssqc + (layer * 16 + i) * 2048 + 128 * c + t2);
            const unsigned short xm = __ldcg((const unsigned short*)(ximg + (uint32_t)(c * 8 * 16384 + (t2 >> 3) * 128 + (t2 & 7) * 2)));
            acc_def(acc);
#pragma unroll 1
            for (int kb = 0; kb < 8; kb++) {
                if (kb == 4) {
                    wg_wait<0>();
                    if (lane == 0) { mbar_arrive(BAR(B_XEMPTY + 3), 1); mbar_arrive_remote(mapa(BAR(B_XEMPTY + 3), par ^ 1)); }
                    float tot = 0.f;
#pragma unroll
                    for (int i = 0; i < 16; i++) tot += sqv[i];
                    float rs = rsqrtf(tot * (1.f / 512.f) + 1e-5f);
                    s_rstd[t2] = rs;
                    s_rstd[128 + t2] = 2.f * rs;
                    s_mean[t2] = layer == 0 ? 0.f : __uint_as_float((uint32_t)xm << 16) * (1.f / 512.f);
                    TS(7 + 12 * layer);
                    bar_arrive(4, 384);
                    bar_sync(14, 384);
                }
                mbar_wait(BAR(B_XFULL + (kb & 3)), (kb >> 2) & 1);
                wg_fence();
#pragma unroll
                for (int ks = 0; ks < 4; ks++)
                    wgmma_n128<1>(acc, desc_a(sb + SM_X + (kb & 3) * 24576 + 16384 + ks * 256), desc_b<128>(sb + SM_X + (kb & 3) * 24576 + ks * 4096), 1);
                wg_commit();
                wg_wait<1>();
                if ((kb & 3) != 0 && lane == 0) { mbar_arrive(BAR(B_XEMPTY + ((kb - 1) & 3)), 1); mbar_arrive_remote(mapa(BAR(B_XEMPTY + ((kb - 1) & 3)), par ^ 1)); }
            }
            wg_wait<0>();
            if (lane == 0) { mbar_arrive(BAR(B_XEMPTY + 3), 1); mbar_arrive_remote(mapa(BAR(B_XEMPTY + 3), par ^ 1)); mbar_arrive_remote(mapa(BAR(B_RFREE), par ^ 1)); }
            bar_arrive(7, 384);
            bar_sync(3, 128);
            TS(9 + 12 * layer);
            const int m0 = 16 * w + g;
            const uint32_t xoff = (uint32_t)((c * 8 + own) * 16384 + w * 4096 + g * 16 + 4 * q);
            if (layer == 0) {
                const uint8_t* xs = g_X + xoff;
#pragma unroll
                for (int i = 0; i < 16; i++) {
                    float2 rs = *(const float2*)(s_rstd + 8 * i + 2 * q);
                    uint32_t x0v = __ldcg((const uint32_t*)(xs + i * 128)), x1v = __ldcg((const uint32_t*)(xs + 2048 + i * 128));
                    acc[4 * i] = acc[4 * i] * rs.x + bf_lo(x0v);
                    acc[4 * i + 1] = acc[4 * i + 1] * rs.y + bf_hi(x0v);
                    acc[4 * i + 2] = acc[4 * i + 2] * rs.x + bf_lo(x1v);
                    acc[4 * i + 3] = acc[4 * i + 3] * rs.y + bf_hi(x1v);
                }
            } else {
                float d0 = ldbf(p.dskip + 64 * own + m0), d1 = ldbf(p.dskip + 64 * own + m0 + 8);
#pragma unroll
                for (int i = 0; i < 16; i++) {
                    float2 rs = *(const float2*)(s_rstd + 8 * i + 2 * q);
                    float2 mn = *(const float2*)(s_mean + 8 * i + 2 * q);
                    acc[4 * i] = acc[4 * i] * (1.f + rs.x * d0) + mn.x;
                    acc[4 * i + 1] = acc[4 * i + 1] * (1.f + rs.y * d0) + mn.y;
                    acc[4 * i + 2] = acc[4 * i + 2] * (1.f + rs.x * d1) + mn.x;
                    acc[4 * i + 3] = acc[4 * i + 3] * (1.f + rs.y * d1) + mn.y;
                }
            }
            TS(10 + 12 * layer);
            bar_sync(6, 416);
            TS(11 + 12 * layer);
            {
                float (&a0)[32] = *reinterpret_cast<float (*)[32]>(&acc[0]);
                float (&a1)[32] = *reinterpret_cast<float (*)[32]>(&acc[32]);
#pragma unroll 1
                for (int k = 0; k < 2; k++) {
                    const uint32_t hb = sb + SM_HH + (par ^ k) * 32768;
                    if (k == 1) {
                        mbar_wait(BAR(B_HPEER), layer);
                        mbar_wait(BAR(B_HPEER1), layer);
                        bar_sync(12, 384);
                    }
                    mbar_wait(BAR(B_AFULL + 6 + k), 1);
                    const uint64_t da = c_desc(6 + k);
                    wg_fence();
#pragma unroll
                    for (int ks = 0; ks < 4; ks++) {
                        wgmma_n64s<1>(a0, da + ks * dstep, desc_b<64>(hb + ks * 2048), 1);
                        wgmma_n64s<1>(a1, da + ks * dstep, desc_b<64>(hb + 16384 + ks * 2048), 1);
                    }
#pragma unroll
                    for (int ks = 0; ks < 4; ks++) {
                        wgmma_n64s<-1>(a0, da + 512 + ks * dstep, desc_b<64>(hb + 8192 + ks * 2048), 1);
                        wgmma_n64s<-1>(a1, da + 512 + ks * dstep, desc_b<64>(hb + 16384 + 8192 + ks * 2048), 1);
                    }
                    wg_commit();
                }
                wg_wait<0>();
            }
#pragma unroll
            for (int i = 0; i < 16; i++)
                *(float4*)(sm + SM_A + 6 * 16384 + i * 2048 + t2 * 16) = make_float4(acc[4 * i], acc[4 * i + 1], acc[4 * i + 2], acc[4 * i + 3]);
            TS(12 + 12 * layer);
        }
        {
            const int t = tid & 127;
            const int nch = wg == 2 ? 2 : 3;
            const uint4* pb = g_P + (uint32_t)((c * 8 + r) * 4 * 1024 + wg * 128 + t);
            uint4 v[3][3];
            unsigned n = 0;
#pragma unroll 1
            while (true) {
                if (lane == 31) {
#pragma unroll 1
                    while (true) {
                        uint32_t bad = 0;
#pragma unroll
                        for (int sx = 0; sx < 3; sx++) {
                            uint32_t t0;
                            asm volatile("ld.relaxed.gpu.global.u32 %0, [%1];" : "=r"(t0) : "l"(pb + ((pi_ + 1 + sx) & 3) * 1024 + (nch - 1) * 384) : "memory");
                            bad |= t0 ^ ptag;
                        }
                        if (!(bad & 0x00010001u) || ++n >= SPIN_LIMIT) break;
                    }
                }
                __syncwarp();
                uint32_t bad = 0;
#pragma unroll
                for (int k = 0; k < 3; k++)
#pragma unroll
                    for (int sx = 0; sx < 3; sx++) {
                        v[k][sx] = make_uint4(ptag, 0, 0, 0);
                        if (k < nch) v[k][sx] = ld_relaxed_u4(pb + ((pi_ + 1 + sx) & 3) * 1024 + k * 384);
                        bad |= v[k][sx].x ^ ptag;
                    }
                if (!__any_sync(~0u, bad & 0x00010001u) || ++n >= SPIN_LIMIT) break;
            }
            bar_sync(8, 384);
            TS(13 + 12 * layer);
            const int m0 = 16 * w + g;
            const float w0 = (own == 0 && m0 < 2) ? (m0 == 0 ? 0.f : 0.5f) : 1.f;
#pragma unroll
            for (int k = 0; k < 3; k++) {
                if (k < nch) {
                    const int i = wg + 3 * k;
                    float4 a = *(const float4*)(sm + SM_A + 6 * 16384 + (2 * i) * 2048 + t * 16);
                    float4 bq = *(const float4*)(sm + SM_A + 6 * 16384 + (2 * i + 1) * 2048 + t * 16);
#pragma unroll
                    for (int sx = 0; sx < 3; sx++) {
                        a.x += bf_lo(v[k][sx].x); a.y += bf_hi(v[k][sx].x); a.z += bf_lo(v[k][sx].y); a.w += bf_hi(v[k][sx].y);
                        bq.x += bf_lo(v[k][sx].z); bq.y += bf_hi(v[k][sx].z); bq.z += bf_lo(v[k][sx].w); bq.w += bf_hi(v[k][sx].w);
                    }
                    if (layer == 0) {
                        uint8_t* xd = g_X + (uint32_t)((16 * 8 + c * 8 + own) * 16384 + w * 4096 + g * 16 + 4 * q + i * 256);
                        uint32_t v0 = pack_bf16(a.x, a.y), v1 = pack_bf16(a.z, a.w), v2 = pack_bf16(bq.x, bq.y), v3 = pack_bf16(bq.z, bq.w);
                        *(uint32_t*)(xd) = v0; *(uint32_t*)(xd + 2048) = v1; *(uint32_t*)(xd + 128) = v2; *(uint32_t*)(xd + 2048 + 128) = v3;
                        float sq[4];
                        sq[0] = w0 * bf_lo(v0) * bf_lo(v0) + bf_lo(v1) * bf_lo(v1);
                        sq[1] = w0 * bf_hi(v0) * bf_hi(v0) + bf_hi(v1) * bf_hi(v1);
                        sq[2] = w0 * bf_lo(v2) * bf_lo(v2) + bf_lo(v3) * bf_lo(v3);
                        sq[3] = w0 * bf_hi(v2) * bf_hi(v2) + bf_hi(v3) * bf_hi(v3);
                        float u0 = (g & 1) ? sq[2] : sq[0], u1 = (g & 1) ? sq[3] : sq[1];
                        u0 += __shfl_xor_sync(~0u, (g & 1) ? sq[0] : sq[2], 4);
                        u1 += __shfl_xor_sync(~0u, (g & 1) ? sq[1] : sq[3], 4);
                        float z = (g & 2) ? u1 : u0;
                        z += __shfl_xor_sync(~0u, (g & 2) ? u0 : u1, 8);
                        z += __shfl_xor_sync(~0u, z, 16);
                        if (g < 4) atomicAdd(s_mean + 16 * i + 8 * (g & 1) + 2 * q + (g >> 1), z);
                    } else {
                        float* o = p.out + (uint32_t)((128 * c + 32 * q + 4 * i) * 512 + 64 * own + m0);
                        o[0] = a.x; o[512] = a.y; o[8] = a.z; o[512 + 8] = a.w;
                        o[1024] = bq.x; o[1536] = bq.y; o[1024 + 8] = bq.z; o[1536 + 8] = bq.w;
                    }
                }
            }
            if (wg < 2) mbar_wait_cluster(BAR(B_HDONE), layer);
            if (layer == 0) {
                fence_async_smem();
                bar_sync(9, 384);
                TS(14 + 12 * layer);
                if (wg == 2) {
                    atomicAdd(g_ssq + 2048 + 128 * c + t, s_mean[t] * (2.f / 512.f));
                    bar_sync(3, 128);
                    if (lane == 0) { mbar_arrive(BAR(B_AEMPTY + 6), 2); mbar_arrive(BAR(B_AEMPTY + 7), 2); }
                    if (t == 0) { fence_async(); red_release(&g_bar[2], 1); }
                }
            }
        }
        TS(15 + 12 * layer);
        if (wg == 0) TC(31);
    }
}

typedef CUresult (*EncFn)(CUtensorMap*, CUtensorMapDataType, cuuint32_t, void*, const cuuint64_t*, const cuuint64_t*,
                          const cuuint32_t*, const cuuint32_t*, CUtensorMapInterleave, CUtensorMapSwizzle,
                          CUtensorMapL2promotion, CUtensorMapFloatOOBfill);

void launch_impl(void* const* d_in, void* d_out, int stop) {
    static EncFn enc = nullptr;
    if (!enc) {
        void* fn = nullptr;
        cudaDriverEntryPointQueryResult qr;
        cudaGetDriverEntryPoint("cuTensorMapEncodeTiled", &fn, cudaEnableDefault, &qr);
        enc = (EncFn)fn;
        cudaFuncSetAttribute(fused_kernel, cudaFuncAttributeMaxDynamicSharedMemorySize, SM_TOTAL);
    }
    CUtensorMap tx, tbr, tbi, tcr, tci, tcol;
    {
        void* gx = nullptr;
        cudaGetSymbolAddress(&gx, g_X);
        cuuint64_t gd[5] = {64, 16, 64, 16, 2};
        cuuint64_t gs[4] = {128, 2048, 128 * 1024, 2048 * 1024};
        cuuint32_t bx[5] = {32, 16, 1, 16, 1};
        cuuint32_t es[5] = {1, 1, 1, 1, 1};
        enc(&tcol, CU_TENSOR_MAP_DATA_TYPE_BFLOAT16, 5, gx, gd, gs, bx, es, CU_TENSOR_MAP_INTERLEAVE_NONE,
            CU_TENSOR_MAP_SWIZZLE_64B, CU_TENSOR_MAP_L2_PROMOTION_NONE, CU_TENSOR_MAP_FLOAT_OOB_FILL_NONE);
    }
    {
        cuuint64_t gd[5] = {512, 2, 4, 16, 16};
        cuuint64_t gs[4] = {1024, 32 * 1024, 2 * 1024, 128 * 1024};
        cuuint32_t bx[5] = {64, 2, 4, 8, 1};
        cuuint32_t es[5] = {1, 1, 1, 1, 1};
        enc(&tx, CU_TENSOR_MAP_DATA_TYPE_BFLOAT16, 5, d_in[0], gd, gs, bx, es, CU_TENSOR_MAP_INTERLEAVE_NONE,
            CU_TENSOR_MAP_SWIZZLE_128B, CU_TENSOR_MAP_L2_PROMOTION_L2_128B, CU_TENSOR_MAP_FLOAT_OOB_FILL_NONE);
    }
    auto mk2 = [&](CUtensorMap* m, void* ptr, cuuint32_t rows) {
        cuuint64_t gd[2] = {512, 512};
        cuuint64_t gs[1] = {1024};
        cuuint32_t bx[2] = {64, rows};
        cuuint32_t es[2] = {1, 1};
        enc(m, CU_TENSOR_MAP_DATA_TYPE_BFLOAT16, 2, ptr, gd, gs, bx, es, CU_TENSOR_MAP_INTERLEAVE_NONE,
            CU_TENSOR_MAP_SWIZZLE_128B, CU_TENSOR_MAP_L2_PROMOTION_L2_128B, CU_TENSOR_MAP_FLOAT_OOB_FILL_NONE);
    };
    mk2(&tbr, d_in[6], 32);
    mk2(&tbi, d_in[7], 32);
    mk2(&tcr, d_in[8], 64);
    mk2(&tci, d_in[9], 64);
    Params p;
    p.x0 = (const __nv_bfloat16*)d_in[0];
    p.w_r = (const __nv_bfloat16*)d_in[1];
    p.w_i = (const __nv_bfloat16*)d_in[2];
    p.lam_re = (const __nv_bfloat16*)d_in[4];
    p.lam_im = (const __nv_bfloat16*)d_in[5];
    p.log_dt = (const __nv_bfloat16*)d_in[10];
    p.dskip = (const __nv_bfloat16*)d_in[11];
    p.out = (float*)d_out;
    p.stop = stop;
    cudaLaunchConfig_t cfg = {};
    cfg.gridDim = dim3(NCTA); cfg.blockDim = dim3(NTHREADS); cfg.dynamicSmemBytes = SM_TOTAL; cfg.stream = cudaStreamPerThread;
    cudaLaunchAttribute at[1];
    at[0].id = cudaLaunchAttributeClusterDimension;
    at[0].val.clusterDim.x = 2; at[0].val.clusterDim.y = 1; at[0].val.clusterDim.z = 1;
    cfg.attrs = at; cfg.numAttrs = 1;
    cudaLaunchKernelEx(&cfg, fused_kernel, tx, tbr, tbi, tcr, tci, tcol, p);
}

}

extern "C" void kernel_launch(void* const* d_in, const int* in_sizes, int n_in, void* d_out, int out_size) {
    (void)in_sizes; (void)n_in; (void)out_size;
    launch_impl(d_in, d_out, 100);
}
```

```cpp
#include <cuda_runtime.h>
#include <cuda_bf16.h>
#include <cuda.h>
#include <stdint.h>

namespace {

constexpr int NCTA = 128;
constexpr int NTHREADS = 512;
constexpr int SM_A = 0;
constexpr int SM_X = 131072;
constexpr int SM_H = 196608;
constexpr int SM_HH = SM_X + 32768;
constexpr int SM_M = 229376;
constexpr int SM_TOTAL = 232448;
constexpr int SM_BAR = SM_M;
constexpr int SM_TGT = SM_M + 392;
constexpr int SM_LAM = SM_M + 416;
constexpr int SM_TAB = SM_M + 928;
constexpr int SM_RSTD = SM_M + 1920;
constexpr int SM_MEAN = SM_TAB;
constexpr int SM_T64 = SM_M + 2944;
constexpr int SM_B1ST = SM_H + 24576;
constexpr int SM_RAW = SM_X + 40960;
constexpr int SM_SSQ = SM_X + 57344;
constexpr int B_FULL0 = 0;
constexpr int B_EMPTY0 = 8;
constexpr int B_FULLC = 12;
constexpr int B_AFULL = 13;
constexpr int B_AEMPTY = 21;
constexpr int B_XFULL = 29;
constexpr int B_XEMPTY = 33;
constexpr int B_AFREE = 37;
constexpr int B_COL = 38;
constexpr int B_SSQ = 39;
constexpr int B_HPEER = 40;
constexpr int B_RFREE = 41;
constexpr int B_HDONE = 42;
constexpr int B_WRDY = 43;
constexpr int B_HPEER1 = 44;
constexpr int B_FULLB = 45;
constexpr int B_BFREE = 46;
constexpr int B_SETUP = 47;
constexpr int B_B1DONE = 48;
constexpr int NBARS = 49;

__device__ __align__(1024) uint8_t g_X[2 * 16 * 8 * 16384];
__device__ __align__(1024) uint8_t g_A1[8 * 8 * 16384];
__device__ __align__(1024) uint8_t g_A2[8 * 8 * 16384];
__device__ __align__(1024) uint8_t g_E[2 * 8 * 8 * 8192];
__device__ __align__(16) float g_ssq[2 * 2048];
__device__ __align__(16) float g_ssqc[2 * 16 * 2048];
__device__ __align__(16) float g_Dh[512];
__device__ __align__(16) uint4 g_Wfrag[128 * 4 * 256];
__device__ __align__(16) float4 g_Ebuf[2 * 16 * 512];
__device__ __align__(16) uint4 g_P[16 * 8 * 4 * 1024];
__device__ unsigned g_bar[8];
__device__ unsigned g_err;
#define TX(i)
#define TQ(i)
#define TS(i)
#define TC(i)

constexpr unsigned SPIN_LIMIT = 1u << 22;

__device__ __forceinline__ uint32_t s2u(const void* p) { return (uint32_t)__cvta_generic_to_shared(p); }
__device__ __forceinline__ void mbar_init(uint32_t a, uint32_t c) {
    asm volatile("mbarrier.init.shared::cta.b64 [%0], %1;" ::"r"(a), "r"(c) : "memory");
}
__device__ __forceinline__ void mbar_expect(uint32_t a, uint32_t bytes) {
    asm volatile("mbarrier.arrive.expect_tx.shared::cta.b64 _, [%0], %1;" ::"r"(a), "r"(bytes) : "memory");
}
__device__ __forceinline__ void mbar_arrive(uint32_t a, uint32_t cnt) {
    asm volatile("mbarrier.arrive.shared::cta.b64 _, [%0], %1;" ::"r"(a), "r"(cnt) : "memory");
}
__device__ __forceinline__ bool mbar_try(uint32_t a, uint32_t parity) {
    uint32_t ok;
    asm volatile("{\n.reg .pred p;\nmbarrier.try_wait.parity.shared::cta.b64 p, [%1], %2;\nselp.u32 %0, 1, 0, p;\n}"
                 : "=r"(ok) : "r"(a), "r"(parity) : "memory");
    return ok != 0;
}
__device__ __forceinline__ void mbar_wait(uint32_t a, uint32_t parity) {
    asm volatile("{\n.reg .pred p, q;\n.reg .u32 n;\nmov.u32 n, 0;\n"
                 "W_%=:\nmbarrier.try_wait.parity.shared::cta.b64 p, [%0], %1;\n@p bra D_%=;\n"
                 "add.u32 n, n, 1;\nsetp.lt.u32 q, n, 4194304;\n@q bra W_%=;\nD_%=:\n}" ::"r"(a), "r"(parity) : "memory");
}
__device__ __forceinline__ void bulk_g2s(uint32_t dst, const void* src, uint32_t bytes, uint32_t bar) {
    asm volatile("cp.async.bulk.shared::cluster.global.mbarrier::complete_tx::bytes [%0], [%1], %2, [%3];" ::"r"(dst),
                 "l"(src), "r"(bytes), "r"(bar) : "memory");
}
__device__ __forceinline__ void tma_2d(uint32_t dst, const CUtensorMap* m, int c0, int c1, uint32_t bar) {
    asm volatile("cp.async.bulk.tensor.2d.shared::cluster.global.mbarrier::complete_tx::bytes [%0], [%1, {%3,%4}], [%2];" ::"r"(dst),
                 "l"(m), "r"(bar), "r"(c0), "r"(c1) : "memory");
}
__device__ __forceinline__ void tma_5d(uint32_t dst, const CUtensorMap* m, int c0, int c1, int c2, int c3, int c4, uint32_t bar) {
    asm volatile("cp.async.bulk.tensor.5d.shared::cluster.global.mbarrier::complete_tx::bytes [%0], [%1, {%3,%4,%5,%6,%7}], [%2];" ::"r"(dst),
                 "l"(m), "r"(bar), "r"(c0), "r"(c1), "r"(c2), "r"(c3), "r"(c4) : "memory");
}
__device__ __forceinline__ void tma_2d_mc(uint32_t dst, const CUtensorMap* m, int c0, int c1, uint32_t bar) {
    asm volatile("cp.async.bulk.tensor.2d.shared::cluster.global.mbarrier::complete_tx::bytes.multicast::cluster [%0], [%1, {%3,%4}], [%2], %5;" ::"r"(dst),
                 "l"(m), "r"(bar), "r"(c0), "r"(c1), "h"((unsigned short)3) : "memory");
}
__device__ __forceinline__ void tma_5d_mc(uint32_t dst, const CUtensorMap* m, int c0, int c1, int c2, int c3, int c4, uint32_t bar) {
    asm volatile("cp.async.bulk.tensor.5d.shared::cluster.global.mbarrier::complete_tx::bytes.multicast::cluster [%0], [%1, {%3,%4,%5,%6,%7}], [%2], %8;" ::"r"(dst),
                 "l"(m), "r"(bar), "r"(c0), "r"(c1), "r"(c2), "r"(c3), "r"(c4), "h"((unsigned short)3) : "memory");
}
__device__ __forceinline__ void bulk_g2s_mc(uint32_t dst, const void* src, uint32_t bytes, uint32_t bar) {
    asm volatile("cp.async.bulk.shared::cluster.global.mbarrier::complete_tx::bytes.multicast::cluster [%0], [%1], %2, [%3], %4;" ::"r"(dst),
                 "l"(src), "r"(bytes), "r"(bar), "h"((unsigned short)3) : "memory");
}
__device__ __forceinline__ void tma_store_5d(const CUtensorMap* m, int c0, int c1, int c2, int c3, int c4, uint32_t src) {
    asm volatile("cp.async.bulk.tensor.5d.global.shared::cta.bulk_group [%0, {%2,%3,%4,%5,%6}], [%1];" ::"l"(m), "r"(src),
                 "r"(c0), "r"(c1), "r"(c2), "r"(c3), "r"(c4) : "memory");
}
__device__ __forceinline__ uint32_t lds32(uint32_t a) { uint32_t v; asm volatile("ld.shared.u32 %0, [%1];" : "=r"(v) : "r"(a) : "memory"); return v; }
__device__ __forceinline__ uint4 ld_relaxed_u4(const uint4* p) {
    uint4 v;
    asm volatile("ld.relaxed.gpu.global.v4.u32 {%0,%1,%2,%3}, [%4];" : "=r"(v.x), "=r"(v.y), "=r"(v.z), "=r"(v.w) : "l"(p) : "memory");
    return v;
}
__device__ __forceinline__ void fence_async() { asm volatile("fence.proxy.async.global;" ::: "memory"); }
__device__ __forceinline__ void red_relaxed(unsigned* p, unsigned v) {
    asm volatile("red.relaxed.gpu.global.add.u32 [%0], %1;" ::"l"(p), "r"(v) : "memory");
}
__device__ __forceinline__ uint32_t mapa(uint32_t a, uint32_t rank) {
    uint32_t d;
    asm("mapa.shared::cluster.u32 %0, %1, %2;" : "=r"(d) : "r"(a), "r"(rank));
    return d;
}
__device__ __forceinline__ void mbar_arrive_remote(uint32_t ra) {
    asm volatile("mbarrier.arrive.relaxed.cluster.shared::cluster.b64 _, [%0];" ::"r"(ra) : "memory");
}
__device__ __forceinline__ void mbar_wait_cluster(uint32_t a, uint32_t parity) {
    asm volatile("{\n.reg .pred p, q;\n.reg .u32 n;\nmov.u32 n, 0;\n"
                 "W_%=:\nmbarrier.try_wait.parity.acquire.cluster.shared::cta.b64 p, [%0], %1;\n@p bra D_%=;\n"
                 "add.u32 n, n, 1;\nsetp.lt.u32 q, n, 4194304;\n@q bra W_%=;\nD_%=:\n}" ::"r"(a), "r"(parity) : "memory");
}
__device__ __forceinline__ void bulk_s2peer(uint32_t rdst, uint32_t src, uint32_t bytes, uint32_t rbar) {
    asm volatile("cp.async.bulk.shared::cluster.shared::cta.mbarrier::complete_tx::bytes [%0], [%1], %2, [%3];" ::"r"(rdst),
                 "r"(src), "r"(bytes), "r"(rbar) : "memory");
}
__device__ __forceinline__ void fence_async_smem() { asm volatile("fence.proxy.async.shared::cta;" ::: "memory"); }
__device__ __forceinline__ void wg_fence() { asm volatile("wgmma.fence.sync.aligned;" ::: "memory"); }
__device__ __forceinline__ void wg_commit() { asm volatile("wgmma.commit_group.sync.aligned;" ::: "memory"); }
template <int N> __device__ __forceinline__ void wg_wait() { asm volatile("wgmma.wait_group.sync.aligned %0;" ::"n"(N) : "memory"); }
__device__ __forceinline__ void bar_sync(int id, int n) { asm volatile("bar.sync %0, %1;" ::"r"(id), "r"(n) : "memory"); }
__device__ __forceinline__ void bar_arrive(int id, int n) { asm volatile("bar.arrive %0, %1;" ::"r"(id), "r"(n) : "memory"); }
__device__ __forceinline__ unsigned ld_acquire(const unsigned* p) {
    unsigned v;
    asm volatile("ld.acquire.gpu.global.u32 %0, [%1];" : "=r"(v) : "l"(p) : "memory");
    return v;
}
__device__ __forceinline__ void red_release(unsigned* p, unsigned v) {
    asm volatile("red.release.gpu.global.add.u32 [%0], %1;" ::"l"(p), "r"(v) : "memory");
}
__device__ __forceinline__ void wait_count(const unsigned* p, unsigned target) {
    unsigned n = 0;
#pragma unroll 1
    while ((int)(ld_acquire(p) - target) < 0 && ++n < SPIN_LIMIT) {}
}
__device__ __forceinline__ float4 ld_relaxed_f4(const float4* p) {
    float4 v;
    asm volatile("ld.relaxed.gpu.global.v4.f32 {%0,%1,%2,%3}, [%4];" : "=f"(v.x), "=f"(v.y), "=f"(v.z), "=f"(v.w) : "l"(p) : "memory");
    return v;
}
__device__ __forceinline__ void st_relaxed_f4(float4* p, float4 v) {
    asm volatile("st.relaxed.gpu.global.v4.f32 [%0], {%1,%2,%3,%4};" ::"l"(p), "f"(v.x), "f"(v.y), "f"(v.z), "f"(v.w) : "memory");
}
__device__ __forceinline__ uint32_t pack_bf16(float lo, float hi) {
    uint32_t r;
    asm("cvt.rn.bf16x2.f32 %0, %1, %2;" : "=r"(r) : "f"(hi), "f"(lo));
    return r;
}
__device__ __forceinline__ uint32_t hmul2(uint32_t a, uint32_t b) {
    uint32_t r;
    asm("mul.rn.bf16x2 %0, %1, %2;" : "=r"(r) : "r"(a), "r"(b));
    return r;
}
__device__ __forceinline__ uint32_t hfma2(uint32_t a, uint32_t b, uint32_t c) {
    uint32_t r;
    asm("fma.rn.bf16x2 %0, %1, %2, %3;" : "=r"(r) : "r"(a), "r"(b), "r"(c));
    return r;
}
__device__ __forceinline__ float bf_lo(uint32_t v) { return __uint_as_float(v << 16); }
__device__ __forceinline__ float bf_hi(uint32_t v) { return __uint_as_float(v & 0xffff0000u); }
__device__ __forceinline__ void sts32(uint32_t a, uint32_t v) { asm volatile("st.shared.u32 [%0], %1;" ::"r"(a), "r"(v) : "memory"); }
__device__ __forceinline__ void sts128(uint32_t a, uint4 v) {
    asm volatile("st.shared.v4.u32 [%0], {%1,%2,%3,%4};" ::"r"(a), "r"(v.x), "r"(v.y), "r"(v.z), "r"(v.w) : "memory");
}

__device__ __forceinline__ uint64_t desc_ni(uint32_t addr, uint32_t lbo, uint32_t sbo) {
    return (uint64_t)((addr & 0x3FFFF) >> 4) | ((uint64_t)(lbo >> 4) << 16) | ((uint64_t)(sbo >> 4) << 32);
}
__device__ __forceinline__ uint64_t desc_a(uint32_t addr) { return desc_ni(addr, 128, 1024); }
template <int N> __device__ __forceinline__ uint64_t desc_b(uint32_t addr) { return desc_ni(addr, 16 * N, 128); }
__device__ __forceinline__ uint64_t desc_k(uint32_t addr) {
    return (uint64_t)((addr & 0x3FFFF) >> 4) | (1ull << 16) | (64ull << 32) | (1ull << 62);
}
__device__ __forceinline__ uint64_t desc_mn(uint32_t addr, uint32_t lbo) {
    return (uint64_t)((addr & 0x3FFFF) >> 4) | ((uint64_t)(lbo >> 4) << 16) | (64ull << 32) | (1ull << 62);
}

#define ACC8(d, o) "+f"(d[o + 0]), "+f"(d[o + 1]), "+f"(d[o + 2]), "+f"(d[o + 3]), "+f"(d[o + 4]), "+f"(d[o + 5]), "+f"(d[o + 6]), "+f"(d[o + 7])
template <int TB, int SA = 1>
__device__ __forceinline__ void wgmma_n128(float (&d)[64], uint64_t da, uint64_t db, int sd) {
    asm volatile(
        "{\n.reg .pred p;\nsetp.ne.b32 p, %66, 0;\n"
        "wgmma.mma_async.sync.aligned.m64n128k16.f32.bf16.bf16 "
        "{%0,%1,%2,%3,%4,%5,%6,%7,%8,%9,%10,%11,%12,%13,%14,%15,%16,%17,%18,%19,%20,%21,%22,%23,%24,%25,%26,%27,%28,%29,%30,%31,"
        "%32,%33,%34,%35,%36,%37,%38,%39,%40,%41,%42,%43,%44,%45,%46,%47,%48,%49,%50,%51,%52,%53,%54,%55,%56,%57,%58,%59,%60,%61,%62,%63},"
        " %64, %65, p, %68, 1, 0, %67;\n}"
        : ACC8(d, 0), ACC8(d, 8), ACC8(d, 16), ACC8(d, 24), ACC8(d, 32), ACC8(d, 40), ACC8(d, 48), ACC8(d, 56)
        : "l"(da), "l"(db), "r"(sd), "n"(TB), "n"(SA));
}
template <int N> __device__ __forceinline__ void acc_def(float (&d)[N]) {
#pragma unroll
    for (int i = 0; i < N; i++) d[i] = 0.f;
}
template <int TB>
__device__ __forceinline__ void wgmma_n64(float (&d)[32], uint64_t da, uint64_t db, int sd) {
    asm volatile(
        "{\n.reg .pred p;\nsetp.ne.b32 p, %34, 0;\n"
        "wgmma.mma_async.sync.aligned.m64n64k16.f32.bf16.bf16 "
        "{%0,%1,%2,%3,%4,%5,%6,%7,%8,%9,%10,%11,%12,%13,%14,%15,%16,%17,%18,%19,%20,%21,%22,%23,%24,%25,%26,%27,%28,%29,%30,%31},"
        " %32, %33, p, 1, 1, 0, %35;\n}"
        : ACC8(d, 0), ACC8(d, 8), ACC8(d, 16), ACC8(d, 24)
        : "l"(da), "l"(db), "r"(sd), "n"(TB));
}
template <int SA>
__device__ __forceinline__ void wgmma_n64s(float (&d)[32], uint64_t da, uint64_t db, int sd) {
    asm volatile(
        "{\n.reg .pred p;\nsetp.ne.b32 p, %34, 0;\n"
        "wgmma.mma_async.sync.aligned.m64n64k16.f32.bf16.bf16 "
        "{%0,%1,%2,%3,%4,%5,%6,%7,%8,%9,%10,%11,%12,%13,%14,%15,%16,%17,%18,%19,%20,%21,%22,%23,%24,%25,%26,%27,%28,%29,%30,%31},"
        " %32, %33, p, %35, 1, 0, 1;\n}"
        : ACC8(d, 0), ACC8(d, 8), ACC8(d, 16), ACC8(d, 24)
        : "l"(da), "l"(db), "r"(sd), "n"(SA));
}
__device__ __forceinline__ void wgmma_n64_rs(float (&d)[32], uint32_t a0, uint32_t a1, uint32_t a2, uint32_t a3, uint64_t db, int sd) {
    asm volatile(
        "{\n.reg .pred p;\nsetp.ne.b32 p, %37, 0;\n"
        "wgmma.mma_async.sync.aligned.m64n64k16.f32.bf16.bf16 "
        "{%0,%1,%2,%3,%4,%5,%6,%7,%8,%9,%10,%11,%12,%13,%14,%15,%16,%17,%18,%19,%20,%21,%22,%23,%24,%25,%26,%27,%28,%29,%30,%31},"
        " {%32,%33,%34,%35}, %36, p, 1, 1, 1;\n}"
        : ACC8(d, 0), ACC8(d, 8), ACC8(d, 16), ACC8(d, 24)
        : "r"(a0), "r"(a1), "r"(a2), "r"(a3), "l"(db), "r"(sd));
}

struct Params {
    const __nv_bfloat16* x0;
    const __nv_bfloat16* w_r;
    const __nv_bfloat16* w_i;
    const __nv_bfloat16* lam_re;
    const __nv_bfloat16* lam_im;
    const __nv_bfloat16* log_dt;
    const __nv_bfloat16* dskip;
    float* out;
    int stop;
};

__device__ __forceinline__ float ldbf(const __nv_bfloat16* p) { return __bfloat162float(*p); }

__device__ __forceinline__ void dft_fp(int j, int& f, int& ph) {
    int cs = j >> 1;
    if (j == 1) { f = 256; ph = 0; }
    else { f = cs; ph = (j & 1) ? 128 : 0; }
}

__device__ __forceinline__ void gen_col_consts(uint32_t sb, int tid) {
#pragma unroll 1
    for (int task = tid; task < 640; task += 256) {
        int f, c8;
        uint32_t a_cc, d_pi, d_po;
        if (task < 512) {
            f = task & 63; c8 = task >> 6;
            a_cc = sb + SM_X + (f >> 5) * 16384 + ((f >> 3) & 3) * 2048 + c8 * 128 + (f & 7) * 16;
            d_pi = 8192; d_po = 1024;
        } else {
            int n2 = task & 31;
            f = 2 * n2; c8 = (task >> 5) & 3;
            a_cc = sb + SM_X + 32768 + (n2 >> 3) * 1024 + c8 * 128 + (n2 & 7) * 16;
            d_pi = 4096; d_po = 512;
        }
        float cd, sd, cs, sn;
        __sincosf((float)(f >= 32 ? f - 64 : f) * (6.283185307179586f / 64.f), &sd, &cd);
        int a = (8 * c8 * f) & 63;
        __sincosf((float)(a >= 32 ? a - 64 : a) * (6.283185307179586f / 64.f), &sn, &cs);
        float cv[8], sv[8];
#pragma unroll
        for (int e = 0; e < 8; e++) {
            cv[e] = cs; sv[e] = sn;
            float t = cs * cd - sn * sd;
            sn = sn * cd + cs * sd;
            cs = t;
        }
        uint4 oc = make_uint4(pack_bf16(cv[0], cv[1]), pack_bf16(cv[2], cv[3]), pack_bf16(cv[4], cv[5]), pack_bf16(cv[6], cv[7]));
        uint4 os = make_uint4(pack_bf16(sv[0], sv[1]), pack_bf16(sv[2], sv[3]), pack_bf16(sv[4], sv[5]), pack_bf16(sv[6], sv[7]));
        sts128(a_cc, oc);
        sts128(a_cc + d_pi, os);
        sts128(a_cc + d_po, make_uint4(os.x ^ 0x80008000u, os.y ^ 0x80008000u, os.z ^ 0x80008000u, os.w ^ 0x80008000u));
        sts128(a_cc + d_pi + d_po, oc);
    }
}

__global__ void __launch_bounds__(NTHREADS, 1)
fused_kernel(const __grid_constant__ CUtensorMap tm_x, const __grid_constant__ CUtensorMap tm_bre,
             const __grid_constant__ CUtensorMap tm_bim, const __grid_constant__ CUtensorMap tm_cre,
             const __grid_constant__ CUtensorMap tm_cim, const __grid_constant__ CUtensorMap tm_col, const Params p) {
    extern __shared__ __align__(1024) uint8_t sm[];
    const uint32_t sb = s2u(sm);
    const int tid = threadIdx.x, b = blockIdx.x;
    const int c = b >> 3, r = b & 7;
    const int par = r & 1, pi_ = r >> 1, own = 4 * par + pi_;
    const int wg = __shfl_sync(~0u, tid >> 7, 0), w = __shfl_sync(~0u, (tid >> 5) & 3, 0), lane = tid & 31, g = lane >> 2, q = lane & 3;
    auto BAR = [&](int i) { return sb + SM_BAR + 8 * i; };
    unsigned* s_tgt = (unsigned*)(sm + SM_TGT);

    if (tid < NBARS) {
        int cnt = 1;
        if (tid >= B_EMPTY0 && tid < B_EMPTY0 + 4) cnt = 16;
        if (tid >= B_XEMPTY && tid < B_XEMPTY + 4) cnt = 24;
        if (tid == B_RFREE) cnt = 12;
        if (tid == B_HDONE) cnt = 2;
        if (tid == B_SETUP) cnt = 3;
        if ((tid >= B_AEMPTY && tid < B_AEMPTY + 8) || tid == B_BFREE) cnt = 8;
        if (tid == B_AFREE) cnt = 4;
        mbar_init(BAR(tid), cnt);
        asm volatile("fence.mbarrier_init.release.cluster;" ::: "memory");
    }
    asm volatile("barrier.cluster.arrive.release.aligned;" ::: "memory");

    if (wg == 3) {
        asm volatile("setmaxnreg.dec.sync.aligned.u32 56;");
        if (w == 0 && lane < 6) {
            const CUtensorMap* tm = lane == 0 ? &tm_x : lane == 1 ? &tm_bre : lane == 2 ? &tm_bim : lane == 3 ? &tm_cre : lane == 4 ? &tm_cim : &tm_col;
            asm volatile("prefetch.tensormap [%0];" ::"l"(tm) : "memory");
        }
        __syncwarp();
        asm volatile("barrier.cluster.wait.acquire.aligned;" ::: "memory");
        if (w > 0) {
            {
                int i = tid - 416;
                int ps = i < 64 ? 64 * r + i : 32 * c + i - 64;
                float lr = ldbf(p.lam_re + ps), li = ldbf(p.lam_im + ps);
                float dt = __bfloat162float(__float2bfloat16(expf(ldbf(p.log_dt + ps))));
                if (i < 6) s_tgt[i] = ((ld_acquire(&g_bar[i]) >> 7) + 1u) << 7;
                float mag = expf(lr * dt), t = li * dt * 0.15915494309189535f, sn, cs;
                t -= rintf(t);
                sincospif(2.f * t, &sn, &cs);
                float er = mag * cs, ei = mag * sn;
                if (i < 64) {
                    *(float2*)(sm + SM_LAM + i * 8) = make_float2(er, ei);
                } else {
                    er -= 1.f;
                    float inv = 1.f / (lr * lr + li * li);
                    *(float2*)(sm + SM_TAB + (i - 64) * 8) = make_float2((er * lr + ei * li) * inv, (ei * lr - er * li) * inv);
                }
            }
            __syncwarp();
            bar_arrive(15, 224);
            if (lane == 0) mbar_arrive(BAR(B_SETUP), 1);
            if (w == 2) {
                const int kq = 2 * b + (lane >> 4), row = (kq >> 2) + 128 * (kq & 3) + 512 * ((lane >> 1) & 3) + 64 * (lane & 1);
                const char* src = (const char*)(((lane >> 3) & 1) ? p.w_i : p.w_r) + (size_t)row * 514;
                size_t a0 = (size_t)src & ~(size_t)15;
                int bytes = row == 2047 ? 512 : 544;
                asm volatile("cp.async.bulk.prefetch.L2.global [%0], %1;" ::"l"(a0), "r"(bytes) : "memory");
            }
#pragma unroll 1
            for (int i = tid - 448; i < 96 + 128 && w > 1; i += 64) {
                if (i < 96) g_P[(uint32_t)(b * 4 + i / 24) * 1024 + 640 + ((i % 24) >> 1) * 32 + 30 + (i & 1)] = make_uint4(0, 0, 0, 0);
                else g_Ebuf[b * 128 + i - 96] = make_float4(0.f, 0.f, 0.f, 0.f);
            }
#pragma unroll 1
            for (int task = tid - 448; task < 256 && w > 1; task += 64) {
                const int cb = task & 127, kq = 2 * b + (task >> 7), k1 = kq >> 2, qq = kq & 3;
                const unsigned short* wr_ = (const unsigned short*)p.w_r + (k1 + 128 * qq) * 257;
                const unsigned short* wi_ = (const unsigned short*)p.w_i + (k1 + 128 * qq) * 257;
                const int c0 = cb == 0 ? 256 : 2 * cb, c1 = 2 * cb + 1;
                uint32_t wf[16];
#pragma unroll
                for (int i = 0; i < 4; i++) {
                    int o = 512 * i * 257;
                    wf[2 * i] = (uint32_t)__ldg(wr_ + o + c0) | ((uint32_t)__ldg(wr_ + o + 64 * 257 + c0) << 16);
                    wf[2 * i + 1] = ((uint32_t)__ldg(wi_ + o + c0) | ((uint32_t)__ldg(wi_ + o + 64 * 257 + c0) << 16)) ^ 0x80008000u;
                    wf[8 + 2 * i] = (uint32_t)__ldg(wr_ + o + c1) | ((uint32_t)__ldg(wr_ + o + 64 * 257 + c1) << 16);
                    wf[8 + 2 * i + 1] = ((uint32_t)__ldg(wi_ + o + c1) | ((uint32_t)__ldg(wi_ + o + 64 * 257 + c1) << 16)) ^ 0x80008000u;
                }
                uint4* wd = g_Wfrag + (uint32_t)(cb * 1024 + kq);
#pragma unroll
                for (int i = 0; i < 4; i++) wd[i * 256] = make_uint4(wf[4 * i], wf[4 * i + 1], wf[4 * i + 2], wf[4 * i + 3]);
            }
            __syncwarp();
            if (w == 3) bar_arrive(11, 192);
            if (w == 2) {
                bar_sync(11, 192);
                if (lane == 0) red_release(&g_bar[4], 1);
            }
            if (w == 3) {
#pragma unroll 1
                for (int it = 0; it < 8; it++) {
                    const int m = 4 * c + (it >> 1), d = 64 * r + m, ch = lane + 32 * (it & 1);
                    float v[8];
#pragma unroll
                    for (int e = 0; e < 8; e++) {
                        int j = 8 * ch + e, f, ph;
                        dft_fp(j, f, ph);
                        int a = (d * f + ph) & 511;
                        a = a >= 256 ? a - 512 : a;
                        float wj = j == 0 ? 0.f : (j == 1 ? 1.f / 512.f : 2.f / 512.f);
                        v[e] = wj * __cosf((float)a * (6.283185307179586f / 512.f));
                    }
                    uint32_t off = (uint32_t)(64 + r * 8 + (ch >> 3)) * 8192 + (m >> 3) * 1024 + (ch & 7) * 128 + (m & 7) * 16;
                    *(uint4*)(g_E + off) = make_uint4(pack_bf16(v[0], v[1]), pack_bf16(v[2], v[3]), pack_bf16(v[4], v[5]), pack_bf16(v[6], v[7]));
                }
                __syncwarp();
                if (lane == 0) { fence_async(); red_release(&g_bar[6], 1); }
                return;
            }
            if (w == 2) {
#pragma unroll 1
                for (int it = 0; it < 4; it++) {
                    const int hf = it & 1;
                    __syncwarp();
                    if (hf == 0) bar_sync(13, 288); else bar_sync(6, 416);
                    if (lane == 0) {
                        const uint32_t src = sb + SM_HH + par * 32768 + hf * 16384;
                        bulk_s2peer(mapa(src, par ^ 1), src, 16384, mapa(BAR(hf ? B_HPEER1 : B_HPEER), par ^ 1));
                    }
                }
                return;
            }
            bar_sync(2, 288);
            if (lane == 0) {
                TX(5);
                fence_async();
                red_release(&g_bar[0], 1);
                TX(6);
            }
            __syncwarp();

            bar_sync(12, 160);
            if (lane == 0) {
                asm volatile("cp.async.bulk.global.shared::cta.bulk_group [%0], [%1], 8192;" ::"l"(g_A1 + (uint32_t)(((c >> 1) * 8 + r) * 16384 + (c & 1) * 8192)),
                             "r"(sb + SM_B1ST) : "memory");
                asm volatile("cp.async.bulk.commit_group;" ::: "memory");
                asm volatile("cp.async.bulk.wait_group 0;" ::: "memory");
                mbar_arrive(BAR(B_B1DONE), 1);
                fence_async();
                red_release(&g_bar[7], 1);
            }
#pragma unroll 1
            for (int layer = 0; layer < 2; layer++) {
                __syncwarp();
                bar_sync(5, 416);
                if (lane == 0) {
                    TX(0 + 8 * layer);
                    tma_store_5d(&tm_col, 32 * (b & 1), 0, b >> 1, 0, layer, sb + SM_RAW);
                    asm volatile("cp.reduce.async.bulk.global.shared::cta.bulk_group.add.f32 [%0], [%1], 8192;" ::"l"(g_ssqc + (layer * 16 + (b & 15)) * 2048),
                                 "r"(sb + SM_SSQ) : "memory");
                    asm volatile("cp.async.bulk.commit_group;" ::: "memory");
                    asm volatile("cp.async.bulk.wait_group 0;" ::: "memory");
                    TX(1 + 8 * layer);
                    fence_async();
                    red_release(&g_bar[1 + 2 * layer], 1);
                    TX(2 + 8 * layer);
                }
            }
        } else if (tid == 384) {
#pragma unroll 1
            for (int kb = 0; kb < 8; kb++) {
                uint32_t fb = BAR(B_FULL0 + kb);
                mbar_expect(fb, 16384);
                tma_5d_mc(sb + SM_A + 65536 + kb * 16384 + par * 8192, &tm_x, kb * 64, 0, 0, 8 * par, c, fb);
            }
#pragma unroll 1
            for (int k2 = 0; k2 < 8; k2++) {
                asm volatile("cp.async.bulk.prefetch.tensor.2d.L2.global [%0, {%1,%2}];" ::"l"(par ? &tm_bim : &tm_bre), "r"(k2 * 64), "r"(32 * c) : "memory");
                if ((k2 & 1) == par)
                    asm volatile("cp.async.bulk.prefetch.tensor.2d.L2.global [%0, {%1,%2}];" ::"l"((c & 1) ? &tm_cim : &tm_cre), "r"(64 * (c >> 1)), "r"(k2 * 64) : "memory");
            }
            mbar_wait(BAR(B_SETUP), 0);
#pragma unroll 1
            for (int layer = 0; layer < 2; layer++) {
                wait_count(&g_bar[2 * layer], s_tgt[2 * layer]);
                TX(4 + 8 * layer);
                fence_async();
                mbar_expect(BAR(B_COL), 16384 + 8192);
                tma_5d(sb + SM_RAW, &tm_col, 32 * (b & 1), 0, b >> 1, 0, layer, BAR(B_COL));
                bulk_g2s(sb + SM_SSQ, g_ssq + layer * 2048, 8192, BAR(B_COL));
                if (layer == 0) {
                    wait_count(&g_bar[4], s_tgt[4]);
                    mbar_arrive(BAR(B_WRDY), 1);
                    wait_count(&g_bar[7], s_tgt[4]);
                    fence_async();
                }
                if (layer == 0) mbar_wait(BAR(B_AFREE), 0);
                mbar_wait(BAR(B_COL), layer);
#pragma unroll 1
                for (int s = 0; s < 8; s++) {
                    if (layer == 1) mbar_wait(BAR(B_AEMPTY + s), 1);
                    if (s >= 2) mbar_wait(BAR(B_AFULL + s - 2), 0);
                    mbar_expect(BAR(B_AFULL + s), 16384);
                    bulk_g2s(sb + SM_A + s * 16384, g_A1 + (uint32_t)(r * 8 + s) * 16384, 16384, BAR(B_AFULL + s));
                }
                if (layer == 1) wait_count(&g_bar[6], s_tgt[4]);
                wait_count(&g_bar[1 + 2 * layer], s_tgt[1 + 2 * layer]);
                TX(3 + 8 * layer);
                fence_async();
                const uint8_t* xsrc = g_X + (uint32_t)(layer * 16 + c) * 8 * 16384;
                const uint8_t* esrc = g_E + (uint32_t)(layer * 8 + own) * 8 * 8192;
                mbar_arrive(BAR(B_SSQ), 1);
                mbar_expect(BAR(B_HPEER), 16384);
                mbar_expect(BAR(B_HPEER1), 16384);
#pragma unroll 1
                for (int it = 0; it < 16; it++) {
                    if (it < 8) {
                        int st = it & 3, f = layer * 2 + (it >> 2);
                        if (f > 0) mbar_wait_cluster(BAR(B_XEMPTY + st), (f - 1) & 1);
                        mbar_expect(BAR(B_XFULL + st), 24576);
                        bulk_g2s_mc(sb + SM_X + st * 24576 + par * 8192, xsrc + (uint32_t)it * 16384 + par * 8192, 8192, BAR(B_XFULL + st));
                        bulk_g2s(sb + SM_X + st * 24576 + 16384, esrc + (uint32_t)it * 8192, 8192, BAR(B_XFULL + st));
                    }
                    if (it >= 8) {
                        if (it == 8) mbar_wait(BAR(B_AEMPTY + 5), 0);
                        int s = it - 8, tile = 4 * par + ((pi_ + 1 + (s >> 1)) & 3), sl = r ^ (s & 1);
                        mbar_wait(BAR(B_AEMPTY + s), 0);
                        uint32_t fb = BAR(B_AFULL + s), dst = sb + SM_A + s * 16384;
                        mbar_expect(fb, 16384);
                        if (layer == 1) {
                            tma_2d(dst, &tm_cre, 64 * sl, 64 * tile, fb);
                            tma_2d(dst + 8192, &tm_cim, 64 * sl, 64 * tile, fb);
                        } else {
                            bulk_g2s(dst, g_A2 + (uint32_t)(sl * 8 + tile) * 16384, 16384, fb);
                        }
                    }
                }
            }
        }
        return;
    }

    asm volatile("setmaxnreg.inc.sync.aligned.u32 152;");
    if (tid >= 96 && tid < 112) g_ssq[2048 + 16 * b + tid - 96] = 0.f;
    if (tid >= 128 && tid < 256) ((float4*)g_ssqc)[b * 128 + tid - 128] = make_float4(0.f, 0.f, 0.f, 0.f);
    TS(0);
    if (wg == 0) TC(30);
    {
        const int f = 32 * r + lane;
        float cd, sd;
        __sincosf((float)f * (6.283185307179586f / 512.f), &sd, &cd);
        const uint32_t dst = sb + SM_A + (lane >> 2) * 1024 + (lane & 3) * 32;
#pragma unroll 1
        for (int ch = tid >> 5; ch < 64; ch += 12) {
            int a = (8 * ch * f) & 511;
            a = a >= 256 ? a - 512 : a;
            float cs, sn;
            __sincosf((float)a * (6.283185307179586f / 512.f), &sn, &cs);
            float cv[8], sv[8];
#pragma unroll
            for (int e = 0; e < 8; e++) {
                cv[e] = cs; sv[e] = -sn;
                float t = cs * cd - sn * sd;
                sn = sn * cd + cs * sd;
                cs = t;
            }
            uint4 o1 = make_uint4(pack_bf16(sv[0], sv[1]), pack_bf16(sv[2], sv[3]), pack_bf16(sv[4], sv[5]), pack_bf16(sv[6], sv[7]));
            if (f == 0) o1 = make_uint4(0xbf803f80u, 0xbf803f80u, 0xbf803f80u, 0xbf803f80u);
            uint32_t a0 = dst + (ch >> 3) * 8192 + (ch & 7) * 128;
            sts128(a0, make_uint4(pack_bf16(cv[0], cv[1]), pack_bf16(cv[2], cv[3]), pack_bf16(cv[4], cv[5]), pack_bf16(cv[6], cv[7])));
            sts128(a0 + 16, o1);
        }
    }
    fence_async_smem();
    asm volatile("barrier.cluster.wait.acquire.aligned;" ::: "memory");
    bar_sync(10, 384);
    TS(1);
    if (wg < 2) {
        float acc[32];
        acc_def(acc);
        const int npos = 16 * r + 8 * wg + 2 * w;
        float sh0 = 0.f, sh1 = 0.f, s0 = 0.f, s1 = 0.f, q0 = 0.f, q1 = 0.f;
#pragma unroll 1
        for (int kb = 0; kb < 8; kb++) {
            uint32_t slot = sb + SM_A + 65536 + kb * 16384;
            mbar_wait(BAR(B_FULL0 + kb), 0);
            wg_fence();
#pragma unroll
            for (int ks = 0; ks < 4; ks++)
                wgmma_n64<0>(acc, desc_a(sb + SM_A + kb * 8192 + ks * 256), desc_k(slot + wg * 8192 + ks * 32), 1);
            wg_commit();
            {
                uint32_t v0 = lds32(slot + npos * 128 + lane * 4), v1 = lds32(slot + npos * 128 + 128 + lane * 4);
                if (kb == 0) { sh0 = __shfl_sync(~0u, bf_lo(v0), 0); sh1 = __shfl_sync(~0u, bf_lo(v1), 0); }
                float a = bf_lo(v0) - sh0, bq = bf_hi(v0) - sh0, cq = bf_lo(v1) - sh1, d = bf_hi(v1) - sh1;
                s0 += a + bq; q0 += a * a + bq * bq; s1 += cq + d; q1 += cq * cq + d * d;
            }
            wg_wait<1>();
            if (kb > 0 && kb <= 4 && lane == 0) { mbar_arrive(BAR(B_EMPTY0 + kb - 1), 1); mbar_arrive_remote(mapa(BAR(B_EMPTY0 + kb - 1), par ^ 1)); }
        }
#pragma unroll
        for (int o = 16; o; o >>= 1) {
            s0 += __shfl_xor_sync(~0u, s0, o); q0 += __shfl_xor_sync(~0u, q0, o);
            s1 += __shfl_xor_sync(~0u, s1, o); q1 += __shfl_xor_sync(~0u, q1, o);
        }
        if (lane == 0) *(float2*)(g_ssq + 128 * c + npos) = make_float2(fmaxf(q0 - s0 * s0 * (1.f / 512.f), 0.f), fmaxf(q1 - s1 * s1 * (1.f / 512.f), 0.f));
        wg_wait<0>();
        TS(2);
        uint8_t* dst = g_X + (uint32_t)((c * 8 + r) * 16384 + w * 4096 + wg * 1024 + g * 16 + 4 * q);
#pragma unroll
        for (int i = 0; i < 8; i++) {
            *(uint32_t*)(dst + i * 128) = pack_bf16(acc[4 * i], acc[4 * i + 1]);
            *(uint32_t*)(dst + 2048 + i * 128) = pack_bf16(acc[4 * i + 2], acc[4 * i + 3]);
        }
        bar_sync(2, 288);
        mbar_wait(BAR(B_SETUP), 0);
        TS(3);
    }

    if (wg == 2) {
        {
            uint4 p0 = __ldg((const uint4*)p.dskip + 2 * lane), p1 = __ldg((const uint4*)p.dskip + 2 * lane + 1);
            uint32_t u[8] = {p0.x, p0.y, p0.z, p0.w, p1.x, p1.y, p1.z, p1.w};
            int j = 64 * r + 4 * c + w, f, ph;
            dft_fp(j, f, ph);
            float s = 0.f;
            int idx = 16 * lane * f + ph;
#pragma unroll
            for (int i = 0; i < 16; i++) {
                int a = idx & 511;
                idx += f;
                a = a >= 256 ? a - 512 : a;
                s += ((i & 1) ? bf_hi(u[i >> 1]) : bf_lo(u[i >> 1])) * __cosf((float)a * (6.283185307179586f / 512.f));
            }
#pragma unroll
            for (int o = 16; o; o >>= 1) s += __shfl_xor_sync(~0u, s, o);
            if (lane == 0) g_Dh[j] = s;
            bar_arrive(11, 192);
        }
        bar_sync(15, 224);
        float acc[32];
        acc_def(acc);
        if (tid == 256) {
#pragma unroll 1
            for (int s = 0; s < 4; s++) mbar_wait_cluster(BAR(B_EMPTY0 + s), 0);
            mbar_expect(BAR(B_FULLB), 65536);
#pragma unroll 1
            for (int k2 = 0; k2 < 8; k2++)
                tma_2d_mc(sb + SM_A + 65536 + k2 * 8192 + par * 4096, par ? &tm_bim : &tm_bre, k2 * 64, 32 * c, BAR(B_FULLB));
        }
        __syncwarp();
        mbar_wait(BAR(B_FULLB), 0);
        wg_fence();
#pragma unroll 1
        for (int kb = 0; kb < 8; kb++) {
#pragma unroll
            for (int ks = 0; ks < 4; ks++)
                wgmma_n64<0>(acc, desc_a(sb + SM_A + kb * 8192 + ks * 256), desc_k(sb + SM_A + 65536 + kb * 8192 + ks * 32), 1);
            wg_commit();
        }
        wg_wait<0>();
        if (lane == 0) { mbar_arrive(BAR(B_BFREE), 1); mbar_arrive_remote(mapa(BAR(B_BFREE), par ^ 1)); }
        if (tid == 256) {
            mbar_wait_cluster(BAR(B_BFREE), 0);
            mbar_expect(BAR(B_FULLC), 65536);
#pragma unroll 1
            for (int k2 = par; k2 < 8; k2 += 2)
                tma_2d_mc(sb + SM_A + 65536 + k2 * 8192, (c & 1) ? &tm_cim : &tm_cre, 64 * (c >> 1), k2 * 64, BAR(B_FULLC));
        }
        __syncwarp();
        {
            uint8_t* dst = sm + SM_B1ST + w * 256 + q * 32 + g * 2;
            const float wj0 = (r == 0 && w == 0 && g < 2) ? (g == 0 ? 0.f : 1.f / 512.f) : 2.f / 512.f;
#pragma unroll
            for (int i = 0; i < 4; i++) {
#pragma unroll
                for (int e = 0; e < 2; e++) {
                    float2 cf = *(const float2*)(sm + SM_TAB + (8 * i + 2 * q + e) * 8);
#pragma unroll
                    for (int h = 0; h < 2; h++) {
                        float wj = h == 0 ? wj0 : 2.f / 512.f;
                        float pr = acc[4 * i + 2 * h + e] * wj, pi = acc[16 + 4 * i + 2 * h + e] * wj;
                        uint8_t* d2 = dst + i * 2048 + h * 128 + e * 16;
                        *(__nv_bfloat16*)(d2) = __float2bfloat16(cf.x * pr - cf.y * pi);
                        *(__nv_bfloat16*)(d2 + 1024) = __float2bfloat16(cf.x * pi + cf.y * pr);
                    }
                }
            }
            fence_async_smem();
            bar_arrive(12, 160);
        }
        acc_def(acc);
        mbar_wait(BAR(B_FULLC), 0);
        wg_fence();
#pragma unroll 1
        for (int kb = 0; kb < 8; kb++) {
#pragma unroll
            for (int ks = 0; ks < 4; ks++)
                wgmma_n64<1>(acc, desc_a(sb + SM_A + kb * 8192 + ks * 256), desc_mn(sb + SM_A + 65536 + kb * 8192 + ks * 2048, 8192), 1);
            wg_commit();
        }
        wg_wait<0>();
        fence_async_smem();
        if (lane == 0) mbar_arrive(BAR(B_AFREE), 1);
        uint8_t* dst = g_A2 + (uint32_t)(((c >> 1) * 8 + r) * 16384 + (c & 1) * 8192 + w * 2048 + g * 16 + 4 * q);
#pragma unroll
        for (int i = 0; i < 8; i++) {
            *(uint32_t*)(dst + i * 128) = pack_bf16(acc[4 * i], acc[4 * i + 1]);
            *(uint32_t*)(dst + 1024 + i * 128) = pack_bf16(acc[4 * i + 2], acc[4 * i + 3]);
        }
        {
            const int m = 4 * c + w, jp = 64 * r + m;
            int fp, php;
            dft_fp(jp, fp, php);
            const __nv_bfloat16* dh = (const __nv_bfloat16*)(sm + SM_RSTD);
            if (tid == 256) wait_count(&g_bar[4], s_tgt[4]);
            bar_sync(3, 128);
            float4 d4 = __ldcg((const float4*)g_Dh + (tid - 256));
            *(uint2*)(sm + SM_RSTD + (tid - 256) * 8) = make_uint2(pack_bf16(d4.x, d4.y), pack_bf16(d4.z, d4.w));
            bar_sync(3, 128);
#pragma unroll 1
            for (int it = 0; it < 2; it++) {
                const int ch = lane + 32 * it;
                float v[8];
#pragma unroll
                for (int e = 0; e < 8; e++) {
                    int j = 8 * ch + e, f, ph;
                    dft_fp(j, f, ph);
                    float wj = j == 0 ? 0.f : (j == 1 ? 1.f / 512.f : 2.f / 512.f);
                    float gsum = 0.f;
#pragma unroll
                    for (int sgn = 0; sgn < 2; sgn++) {
                        int mm = (sgn ? f - fp : f + fp) & 511, pp = (sgn ? ph - php : ph + php) & 511;
                        if (mm > 256) { mm = 512 - mm; pp = (512 - pp) & 511; }
                        int odd = (pp >> 7) & 1;
                        float t = __bfloat162float(dh[mm == 256 ? 1 : 2 * mm + odd]);
                        if (odd && (mm & 255) == 0) t = 0.f;
                        gsum += (pp & 256) ? -t : t;
                    }
                    v[e] = 0.5f * wj * gsum;
                }
                uint32_t off = (uint32_t)(r * 8 + (ch >> 3)) * 8192 + (m >> 3) * 1024 + (ch & 7) * 128 + (m & 7) * 16;
                *(uint4*)(g_E + off) = make_uint4(pack_bf16(v[0], v[1]), pack_bf16(v[2], v[3]), pack_bf16(v[4], v[5]), pack_bf16(v[6], v[7]));
            }
        }
    }

#pragma unroll 1
    for (int layer = 0; layer < 2; layer++) {
        if (wg < 2) {
            const int n1 = 32 * wg + 8 * w + g;
            const int ct = n1 >> 2;
            gen_col_consts(sb, tid);
            uint32_t tr2[4], ti2[4], tn2[4];
#pragma unroll
            for (int i = 0; i < 4; i++) {
                float cr[2], ci[2];
#pragma unroll
                for (int e = 0; e < 2; e++) {
                    int a = (n1 * (8 * i + 2 * q + e)) & 2047;
                    a = a >= 1024 ? a - 2048 : a;
                    float ang = (float)a * (-6.283185307179586f / 2048.f);
                    cr[e] = __cosf(ang); ci[e] = __sinf(ang);
                }
                tr2[i] = pack_bf16(cr[0], cr[1]); ti2[i] = pack_bf16(ci[0], ci[1]); tn2[i] = ti2[i] ^ 0x80008000u;
            }
            uint32_t wf[16];
            const uint4* ws = g_Wfrag + (uint32_t)(b * 1024 + n1 * 4 + q);
#pragma unroll
            for (int i = 0; i < 4; i++) {
                uint4 v = make_uint4(0, 0, 0, 0);
                if (layer == 1) v = __ldcg(ws + i * 256);
                wf[4 * i] = v.x; wf[4 * i + 1] = v.y; wf[4 * i + 2] = v.z; wf[4 * i + 3] = v.w;
            }
            mbar_wait(BAR(B_COL), layer);
            TS(4 + 12 * layer);
            if (wg == 0) TC(0 + 10 * layer);
            const uint32_t rw0 = sb + SM_RAW + ct * 1024 + q * 64 + ((q >> 1) << 4) + (g & 3) * 4, rw1 = rw0 ^ 16;
            const int pos0 = 128 * ct + 8 * q + 2 * (g & 3);
            const int sw = b == 0 ? 1 : 0;
            uint32_t xr[4][4];
            const uint32_t st0 = sb + SM_H + (n1 >> 3) * 1024 + g * 16 + 4 * q;
#pragma unroll
            for (int i = 0; i < 4; i++) {
                float2 sq = *(const float2*)(sm + SM_SSQ + (pos0 + 32 * i) * 4);
                const uint32_t rs2 = pack_bf16(rsqrtf(sq.x * (1.f / 512.f) + 1e-5f), rsqrtf(sq.y * (1.f / 512.f) + 1e-5f));
#pragma unroll
                for (int jj = 0; jj < 4; jj++) {
                    const int K = jj ^ (2 * (i & 1));
                    uint32_t a = ((K & 1) ? rw1 : rw0) + i * 256 + (K & 2) * 16;
                    if (jj < 2) a ^= sw << 4;
                    uint32_t v = lds32(a);
                    xr[jj][i] = v;
                    uint32_t o = hmul2(v, rs2);
                    if (jj == 1 && sw) o = 0u;
                    sts32(st0 + (jj & 1) * 8192 + (4 * (jj >> 1) + i) * 128, o);
                }
            }
            if (wg == 0) TC(1 + 10 * layer);
            fence_async_smem();
            bar_sync(1, 256);
            float acc[32];
            const uint32_t s1a = sb + SM_X + wg * 16384, s2b = sb + SM_X + 32768;
            wg_fence();
#pragma unroll
            for (int ks = 0; ks < 8; ks++)
                wgmma_n64<1>(acc, desc_a(s1a + (ks >> 2) * 8192 + (ks & 3) * 256), desc_b<64>(sb + SM_H + ks * 2048), ks != 0);
            wg_commit();
            if (layer == 0) {
                mbar_wait(BAR(B_WRDY), 0);
#pragma unroll
                for (int i = 0; i < 4; i++) {
                    uint4 v = __ldcg(ws + i * 256);
                    wf[4 * i] = v.x; wf[4 * i + 1] = v.y; wf[4 * i + 2] = v.z; wf[4 * i + 3] = v.w;
                }
            }
            wg_wait<0>();
            if (wg == 0) TC(2 + 10 * layer);
            uint32_t are[2][4], aim[2][4];
#pragma unroll
            for (int col = 0; col < 2; col++) {
#pragma unroll
                for (int i = 0; i < 4; i++) {
                    int o = 4 * (4 * col + i);
                    uint32_t zr = pack_bf16(acc[o], acc[o + 1]), zi = pack_bf16(acc[o + 2], acc[o + 3]);
                    are[col][i] = hfma2(zr, tr2[i], hmul2(zi, tn2[i]));
                    aim[col][i] = hfma2(zr, ti2[i], hmul2(zi, tr2[i]));
                }
            }
            wg_fence();
#pragma unroll
            for (int ks = 0; ks < 2; ks++)
                wgmma_n64_rs(acc, are[0][2 * ks], are[1][2 * ks], are[0][2 * ks + 1], are[1][2 * ks + 1], desc_b<64>(s2b + ks * 2048), ks != 0);
#pragma unroll
            for (int ks = 0; ks < 2; ks++)
                wgmma_n64_rs(acc, aim[0][2 * ks], aim[1][2 * ks], aim[0][2 * ks + 1], aim[1][2 * ks + 1], desc_b<64>(s2b + 4096 + ks * 2048), 1);
            wg_commit();
            wg_wait<0>();
            if (wg == 0) TC(3 + 10 * layer);
#pragma unroll
            for (int col = 0; col < 2; col++) {
#pragma unroll
                for (int i = 0; i < 4; i++) {
                    uint32_t wr = wf[col * 8 + 2 * i], wn = wf[col * 8 + 2 * i + 1];
                    uint32_t zr = pack_bf16(acc[4 * i + 2 * col], acc[4 * i + 2 * col + 1]);
                    uint32_t zi = pack_bf16(acc[16 + 4 * i + 2 * col], acc[16 + 4 * i + 2 * col + 1]);
                    are[col][i] = hfma2(zr, wr, hmul2(zi, wn));
                    aim[col][i] = hfma2(zr, wn, hmul2(zi ^ 0x80008000u, wr));
                }
            }
            wg_fence();
#pragma unroll
            for (int ks = 0; ks < 2; ks++)
                wgmma_n64_rs(acc, are[0][2 * ks], are[1][2 * ks], are[0][2 * ks + 1], are[1][2 * ks + 1], desc_b<64>(s2b + ks * 2048), ks != 0);
#pragma unroll
            for (int ks = 0; ks < 2; ks++)
                wgmma_n64_rs(acc, aim[0][2 * ks], aim[1][2 * ks], aim[0][2 * ks + 1], aim[1][2 * ks + 1], desc_b<64>(s2b + 4096 + ks * 2048), 1);
            wg_commit();
            wg_wait<0>();
            if (wg == 0) TC(4 + 10 * layer);
            mbar_wait(BAR(B_B1DONE), 0);
#pragma unroll
            for (int col = 0; col < 2; col++) {
#pragma unroll
                for (int i = 0; i < 4; i++) {
                    uint32_t zr = pack_bf16(acc[4 * i + 2 * col], acc[4 * i + 2 * col + 1]);
                    uint32_t zi = pack_bf16(acc[16 + 4 * i + 2 * col], acc[16 + 4 * i + 2 * col + 1]);
                    sts32(st0 + 16384 + (4 * col + i) * 128, hfma2(zr, tr2[i], hmul2(zi, tn2[i])));
                    sts32(st0 + 16384 + 8192 + (4 * col + i) * 128, hfma2(zr, ti2[i], hmul2(zi, tr2[i])));
                }
            }
            if (wg == 0) TC(5 + 10 * layer);
            fence_async_smem();
            bar_sync(1, 256);
            wg_fence();
#pragma unroll
            for (int ks = 0; ks < 8; ks++)
                wgmma_n64<1>(acc, desc_a(s1a + (ks >> 2) * 8192 + (ks & 3) * 256), desc_b<64>(sb + SM_H + 16384 + ks * 2048), ks != 0);
            wg_commit();
            wg_wait<0>();
            if (wg == 0) TC(6 + 10 * layer);
            const float sc = 1.f / 2048.f;
            const float sci0 = sw ? 0.f : -sc;
            const float wr0 = sw ? 0.5f : 1.f, wi0 = sw ? 0.f : 1.f;
#pragma unroll
            for (int i = 0; i < 4; i++) {
                float ss0, ss1;
#pragma unroll
                for (int col = 0; col < 2; col++) {
                    int o = 4 * (4 * col + i);
                    uint32_t vr = xr[2 * col][i], vi = xr[2 * col + 1][i];
                    float si = col == 0 ? sci0 : -sc;
                    uint32_t nr = pack_bf16(fmaf(acc[o], sc, bf_lo(vr)), fmaf(acc[o + 1], sc, bf_hi(vr)));
                    uint32_t ni = pack_bf16(fmaf(acc[o + 2], si, bf_lo(vi)), fmaf(acc[o + 3], si, bf_hi(vi)));
                    float a0 = bf_lo(nr), a1 = bf_hi(nr), b0 = bf_lo(ni), b1 = bf_hi(ni);
                    if (col == 0) {
                        ss0 = wr0 * a0 * a0 + wi0 * b0 * b0;
                        ss1 = wr0 * a1 * a1 + wi0 * b1 * b1;
                    } else {
                        ss0 += a0 * a0 + b0 * b0;
                        ss1 += a1 * a1 + b1 * b1;
                    }
                    const int K = (2 * col) ^ (2 * (i & 1));
                    uint32_t a = rw0 + i * 256 + K * 16;
                    if (col == 0) a ^= sw << 4;
                    sts32(a, nr);
                    sts32(a ^ 16, ni);
                }
                *(float2*)(sm + SM_SSQ + (pos0 + 32 * i) * 4) = make_float2(ss0 * (2.f / 512.f), ss1 * (2.f / 512.f));
            }
            fence_async_smem();
        }
        TS(5 + 12 * layer);
        if (wg == 0) TC(7 + 10 * layer);
        bar_arrive(5, 416);

        float acc[64];
        float* s_rstd = (float*)(sm + SM_RSTD);
        float* s_mean = (float*)(sm + SM_MEAN);
        const unsigned epoch = s_tgt[0] >> 7;
        const uint32_t pt3 = 1u + (2u * epoch + layer) % 3u;
        const uint32_t ptag = (pt3 & 1u) | ((pt3 & 2u) << 15);
        const uint64_t dstep = layer == 0 ? 16 : 2;
        auto c_desc = [&](int s) { return layer == 0 ? desc_a(sb + SM_A + s * 16384) : desc_k(sb + SM_A + s * 16384); };
        if (wg < 2) {
            const int prow = 32 * wg + 8 * w + g;
            const float2 l1 = *(const float2*)(sm + SM_LAM + prow * 8);
            float lr32 = l1.x, li32 = l1.y;
#pragma unroll
            for (int i = 0; i < 5; i++) { float t = lr32 * lr32 - li32 * li32; li32 = 2.f * lr32 * li32; lr32 = t; }
            float lr128 = lr32, li128 = li32;
#pragma unroll
            for (int i = 0; i < 2; i++) { float t = lr128 * lr128 - li128 * li128; li128 = 2.f * lr128 * li128; lr128 = t; }
            const float lr1 = l1.x, li1 = l1.y;
            acc_def(acc);
#pragma unroll 1
            for (int kb = 0; kb < 8; kb++) {
                mbar_wait(BAR(B_AFULL + kb), 0);
                mbar_wait(BAR(B_XFULL + (kb & 3)), (kb >> 2) & 1);
                wg_fence();
#pragma unroll
                for (int ks = 0; ks < 4; ks++)
                    wgmma_n128<1>(acc, desc_a(sb + SM_A + kb * 16384 + wg * 8192 + ks * 256),
                                  desc_b<128>(sb + SM_X + (kb & 3) * 24576 + ks * 4096), 1);
                wg_commit();
                wg_wait<1>();
                if (kb > 0 && lane == 0) {
                    mbar_arrive(BAR(B_AEMPTY + kb - 1), 1); mbar_arrive(BAR(B_XEMPTY + ((kb - 1) & 3)), 1);
                    mbar_arrive_remote(mapa(BAR(B_XEMPTY + ((kb - 1) & 3)), par ^ 1));
                }
            }
            wg_wait<0>();
            if (lane == 0) {
                mbar_arrive(BAR(B_AEMPTY + 7), 1); mbar_arrive(BAR(B_XEMPTY + 3), 1);
                mbar_arrive_remote(mapa(BAR(B_XEMPTY + 3), par ^ 1)); mbar_arrive_remote(mapa(BAR(B_RFREE), par ^ 1));
            }
            bar_arrive(14, 384);
            TS(6 + 12 * layer);
            bar_sync(4, 384);
            TS(7 + 12 * layer);
            float er = 0.f, ei = 0.f;
#pragma unroll
            for (int i = 0; i < 16; i++) {
                float2 rs = *(const float2*)(s_rstd + 128 + 8 * i + 2 * q);
                acc[4 * i] *= rs.x; acc[4 * i + 1] *= rs.y; acc[4 * i + 2] *= rs.x; acc[4 * i + 3] *= rs.y;
                float nr = lr1 * er - li1 * ei + acc[4 * i], ni = lr1 * ei + li1 * er + acc[4 * i + 2];
                er = lr1 * nr - li1 * ni + acc[4 * i + 1];
                ei = lr1 * ni + li1 * nr + acc[4 * i + 3];
            }
            float cr = 0.f, ci = 0.f, tr = 0.f, ti = 0.f;
#pragma unroll
            for (int qq = 0; qq < 4; qq++) {
                float xr_ = __shfl_sync(~0u, er, (lane & ~3) | qq), xi_ = __shfl_sync(~0u, ei, (lane & ~3) | qq);
                if (qq == q) { cr = tr; ci = ti; }
                float nr = lr32 * tr - li32 * ti + xr_, ni = lr32 * ti + li32 * tr + xi_;
                tr = nr; ti = ni;
            }
            float4* eb = g_Ebuf + (uint32_t)(layer * 16 * 512 + 64 * r + prow);
            if (q == 0 && c < 15) st_relaxed_f4(eb + c * 512, make_float4(tr, ti, __uint_as_float(epoch), 0.f));
            TS(8 + 12 * layer);
            float pr[4], pi[4];
            {
                unsigned n = 0;
                bool ok;
#pragma unroll 1
                do {
                    ok = true;
#pragma unroll
                    for (int k = 0; k < 4; k++) {
                        float4 v = make_float4(0.f, 0.f, __uint_as_float(epoch), 0.f);
                        if (4 * k + q < c) v = ld_relaxed_f4(eb + (4 * k + q) * 512);
                        pr[k] = v.x; pi[k] = v.y;
                        ok = ok && __float_as_uint(v.z) == epoch;
                    }
                } while (!ok && ++n < SPIN_LIMIT);
            }
            __syncwarp();
            TS(9 + 12 * layer);
            float hr = 0.f, hi = 0.f;
#pragma unroll
            for (int cc = 0; cc < 15; cc++) {
                float xr_ = __shfl_sync(~0u, pr[cc >> 2], (lane & ~3) | (cc & 3)), xi_ = __shfl_sync(~0u, pi[cc >> 2], (lane & ~3) | (cc & 3));
                if (cc < c) {
                    float nr = lr128 * hr - li128 * hi + xr_, ni = lr128 * hi + li128 * hr + xi_;
                    hr = nr; hi = ni;
                }
            }
#pragma unroll
            for (int qq = 0; qq < 3; qq++) {
                if (qq < q) { float nr = lr32 * hr - li32 * hi, ni = lr32 * hi + li32 * hr; hr = nr; hi = ni; }
            }
            er = cr + hr; ei = ci + hi;
            bar_sync(7, 384);
            mbar_wait_cluster(BAR(B_RFREE), layer);
            const uint32_t ha = sb + SM_HH + par * 32768 + (prow >> 3) * 1024 + g * 16 + 4 * q;
#pragma unroll
            for (int i = 0; i < 16; i++) {
                float nr = lr1 * er - li1 * ei + acc[4 * i], ni = lr1 * ei + li1 * er + acc[4 * i + 2];
                er = lr1 * nr - li1 * ni + acc[4 * i + 1];
                ei = lr1 * ni + li1 * nr + acc[4 * i + 3];
                sts32(ha + (i >> 3) * 16384 + (i & 7) * 128, pack_bf16(nr, er));
                sts32(ha + (i >> 3) * 16384 + 8192 + (i & 7) * 128, pack_bf16(ni, ei));
                if (i == 7) { fence_async_smem(); bar_arrive(13, 288); }
            }
            fence_async_smem();
            acc_def(acc);
            float acc2[32];
            acc_def(acc2);
            TS(10 + 12 * layer);
            bar_sync(6, 416);
            TS(11 + 12 * layer);
            float (&a0)[32] = *reinterpret_cast<float (*)[32]>(&acc[0]);
            float (&a1)[32] = *reinterpret_cast<float (*)[32]>(&acc[32]);
            auto tile_mma = [&](float (&d)[32], int u) {
#pragma unroll 1
                for (int k = 0; k < 2; k++) {
                    const uint32_t hb = sb + SM_HH + (par ^ k) * 32768 + wg * 16384;
                    if (k == 1) mbar_wait(BAR(wg ? B_HPEER1 : B_HPEER), layer);
                    mbar_wait(BAR(B_AFULL + 2 * u + k), 1);
                    const uint64_t da = c_desc(2 * u + k);
                    wg_fence();
#pragma unroll
                    for (int ks = 0; ks < 4; ks++) wgmma_n64s<1>(d, da + ks * dstep, desc_b<64>(hb + ks * 2048), 1);
#pragma unroll
                    for (int ks = 0; ks < 4; ks++) wgmma_n64s<-1>(d, da + 512 + ks * dstep, desc_b<64>(hb + 8192 + ks * 2048), 1);
                }
                wg_commit();
            };
            auto tile_ship = [&](float (&d)[32], int u) {
                uint4* dst = g_P + (uint32_t)(((c * 8 + 2 * ((pi_ + 1 + u) & 3) + par) * 4 + pi_) * 1024 + wg * 512 + (tid & 127));
#pragma unroll
                for (int i = 0; i < 4; i++)
                    dst[i * 128] = make_uint4((pack_bf16(d[8 * i], d[8 * i + 1]) & 0xfffefffeu) | ptag, pack_bf16(d[8 * i + 2], d[8 * i + 3]),
                                              pack_bf16(d[8 * i + 4], d[8 * i + 5]), pack_bf16(d[8 * i + 6], d[8 * i + 7]));
            };
            tile_mma(a0, 0);
            if ((tid & 127) == 0) mbar_arrive_remote(mapa(BAR(B_HDONE), par ^ 1));
            __syncwarp();
            tile_mma(a1, 1);
            wg_wait<1>();
            tile_ship(a0, 0);
            tile_mma(acc2, 2);
            bar_arrive(12, 384);
            wg_wait<1>();
            tile_ship(a1, 1);
            wg_wait<0>();
            tile_ship(acc2, 2);
            if (lane < 6) mbar_arrive(BAR(B_AEMPTY + lane), 1);
            TS(12 + 12 * layer);
        } else {
            const int t2 = tid - 256;
            const uint8_t* ximg = g_X + (uint32_t)layer * 16 * 8 * 16384;
            mbar_wait(BAR(B_SSQ), layer);
            TS(6 + 12 * layer);
            float sqv[16];
#pragma unroll
            for (int i = 0; i < 16; i++) sqv[i] = __ldcg(g_ssqc + (layer * 16 + i) * 2048 + 128 * c + t2);
            const unsigned short xm = __ldcg((const unsigned short*)(ximg + (uint32_t)(c * 8 * 16384 + (t2 >> 3) * 128 + (t2 & 7) * 2)));
            acc_def(acc);
#pragma unroll 1
            for (int kb = 0; kb < 8; kb++) {
                if (kb == 4) {
                    wg_wait<0>();
                    if (lane == 0) { mbar_arrive(BAR(B_XEMPTY + 3), 1); mbar_arrive_remote(mapa(BAR(B_XEMPTY + 3), par ^ 1)); }
                    float tot = 0.f;
#pragma unroll
                    for (int i = 0; i < 16; i++) tot += sqv[i];
                    float rs = rsqrtf(tot * (1.f / 512.f) + 1e-5f);
                    s_rstd[t2] = rs;
                    s_rstd[128 + t2] = 2.f * rs;
                    s_mean[t2] = layer == 0 ? 0.f : __uint_as_float((uint32_t)xm << 16) * (1.f / 512.f);
                    TS(7 + 12 * layer);
                    bar_arrive(4, 384);
                    bar_sync(14, 384);
                }
                mbar_wait(BAR(B_XFULL + (kb & 3)), (kb >> 2) & 1);
                wg_fence();
#pragma unroll
                for (int ks = 0; ks < 4; ks++)
                    wgmma_n128<1>(acc, desc_a(sb + SM_X + (kb & 3) * 24576 + 16384 + ks * 256), desc_b<128>(sb + SM_X + (kb & 3) * 24576 + ks * 4096), 1);
                wg_commit();
                wg_wait<1>();
                if ((kb & 3) != 0 && lane == 0) { mbar_arrive(BAR(B_XEMPTY + ((kb - 1) & 3)), 1); mbar_arrive_remote(mapa(BAR(B_XEMPTY + ((kb - 1) & 3)), par ^ 1)); }
            }
            wg_wait<0>();
            if (lane == 0) { mbar_arrive(BAR(B_XEMPTY + 3), 1); mbar_arrive_remote(mapa(BAR(B_XEMPTY + 3), par ^ 1)); mbar_arrive_remote(mapa(BAR(B_RFREE), par ^ 1)); }
            bar_arrive(7, 384);
            bar_sync(3, 128);
            TS(9 + 12 * layer);
            const int m0 = 16 * w + g;
            const uint32_t xoff = (uint32_t)((c * 8 + own) * 16384 + w * 4096 + g * 16 + 4 * q);
            if (layer == 0) {
                const uint8_t* xs = g_X + xoff;
#pragma unroll
                for (int i = 0; i < 16; i++) {
                    float2 rs = *(const float2*)(s_rstd + 8 * i + 2 * q);
                    uint32_t x0v = __ldcg((const uint32_t*)(xs + i * 128)), x1v = __ldcg((const uint32_t*)(xs + 2048 + i * 128));
                    acc[4 * i] = acc[4 * i] * rs.x + bf_lo(x0v);
                    acc[4 * i + 1] = acc[4 * i + 1] * rs.y + bf_hi(x0v);
                    acc[4 * i + 2] = acc[4 * i + 2] * rs.x + bf_lo(x1v);
                    acc[4 * i + 3] = acc[4 * i + 3] * rs.y + bf_hi(x1v);
                }
            } else {
                float d0 = ldbf(p.dskip + 64 * own + m0), d1 = ldbf(p.dskip + 64 * own + m0 + 8);
#pragma unroll
                for (int i = 0; i < 16; i++) {
                    float2 rs = *(const float2*)(s_rstd + 8 * i + 2 * q);
                    float2 mn = *(const float2*)(s_mean + 8 * i + 2 * q);
                    acc[4 * i] = acc[4 * i] * (1.f + rs.x * d0) + mn.x;
                    acc[4 * i + 1] = acc[4 * i + 1] * (1.f + rs.y * d0) + mn.y;
                    acc[4 * i + 2] = acc[4 * i + 2] * (1.f + rs.x * d1) + mn.x;
                    acc[4 * i + 3] = acc[4 * i + 3] * (1.f + rs.y * d1) + mn.y;
                }
            }
            TS(10 + 12 * layer);
            bar_sync(6, 416);
            TS(11 + 12 * layer);
            {
                float (&a0)[32] = *reinterpret_cast<float (*)[32]>(&acc[0]);
                float (&a1)[32] = *reinterpret_cast<float (*)[32]>(&acc[32]);
#pragma unroll 1
                for (int k = 0; k < 2; k++) {
                    const uint32_t hb = sb + SM_HH + (par ^ k) * 32768;
                    if (k == 1) {
                        mbar_wait(BAR(B_HPEER), layer);
                        mbar_wait(BAR(B_HPEER1), layer);
                        bar_sync(12, 384);
                    }
                    mbar_wait(BAR(B_AFULL + 6 + k), 1);
                    const uint64_t da = c_desc(6 + k);
                    wg_fence();
#pragma unroll
                    for (int ks = 0; ks < 4; ks++) {
                        wgmma_n64s<1>(a0, da + ks * dstep, desc_b<64>(hb + ks * 2048), 1);
                        wgmma_n64s<1>(a1, da + ks * dstep, desc_b<64>(hb + 16384 + ks * 2048), 1);
                    }
#pragma unroll
                    for (int ks = 0; ks < 4; ks++) {
                        wgmma_n64s<-1>(a0, da + 512 + ks * dstep, desc_b<64>(hb + 8192 + ks * 2048), 1);
                        wgmma_n64s<-1>(a1, da + 512 + ks * dstep, desc_b<64>(hb + 16384 + 8192 + ks * 2048), 1);
                    }
                    wg_commit();
                }
                wg_wait<0>();
            }
#pragma unroll
            for (int i = 0; i < 16; i++)
                *(float4*)(sm + SM_A + 6 * 16384 + i * 2048 + t2 * 16) = make_float4(acc[4 * i], acc[4 * i + 1], acc[4 * i + 2], acc[4 * i + 3]);
            TS(12 + 12 * layer);
        }
        {
            const int t = tid & 127;
            const int nch = wg == 2 ? 2 : 3;
            const uint4* pb = g_P + (uint32_t)((c * 8 + r) * 4 * 1024 + wg * 128 + t);
            uint4 v[3][3];
            unsigned n = 0;
#pragma unroll 1
            while (true) {
                if (lane == 31) {
#pragma unroll 1
                    while (true) {
                        uint32_t bad = 0;
#pragma unroll
                        for (int sx = 0; sx < 3; sx++) {
                            uint32_t t0;
                            asm volatile("ld.relaxed.gpu.global.u32 %0, [%1];" : "=r"(t0) : "l"(pb + ((pi_ + 1 + sx) & 3) * 1024 + (nch - 1) * 384) : "memory");
                            bad |= t0 ^ ptag;
                        }
                        if (!(bad & 0x00010001u) || ++n >= SPIN_LIMIT) break;
                    }
                }
                __syncwarp();
                uint32_t bad = 0;
#pragma unroll
                for (int k = 0; k < 3; k++)
#pragma unroll
                    for (int sx = 0; sx < 3; sx++) {
                        v[k][sx] = make_uint4(ptag, 0, 0, 0);
                        if (k < nch) v[k][sx] = ld_relaxed_u4(pb + ((pi_ + 1 + sx) & 3) * 1024 + k * 384);
                        bad |= v[k][sx].x ^ ptag;
                    }
                if (!__any_sync(~0u, bad & 0x00010001u) || ++n >= SPIN_LIMIT) break;
            }
            bar_sync(8, 384);
            TS(13 + 12 * layer);
            const int m0 = 16 * w + g;
            const float w0 = (own == 0 && m0 < 2) ? (m0 == 0 ? 0.f : 0.5f) : 1.f;
#pragma unroll
            for (int k = 0; k < 3; k++) {
                if (k < nch) {
                    const int i = wg + 3 * k;
                    float4 a = *(const float4*)(sm + SM_A + 6 * 16384 + (2 * i) * 2048 + t * 16);
                    float4 bq = *(const float4*)(sm + SM_A + 6 * 16384 + (2 * i + 1) * 2048 + t * 16);
#pragma unroll
                    for (int sx = 0; sx < 3; sx++) {
                        a.x += bf_lo(v[k][sx].x); a.y += bf_hi(v[k][sx].x); a.z += bf_lo(v[k][sx].y); a.w += bf_hi(v[k][sx].y);
                        bq.x += bf_lo(v[k][sx].z); bq.y += bf_hi(v[k][sx].z); bq.z += bf_lo(v[k][sx].w); bq.w += bf_hi(v[k][sx].w);
                    }
                    if (layer == 0) {
                        uint8_t* xd = g_X + (uint32_t)((16 * 8 + c * 8 + own) * 16384 + w * 4096 + g * 16 + 4 * q + i * 256);
                        uint32_t v0 = pack_bf16(a.x, a.y), v1 = pack_bf16(a.z, a.w), v2 = pack_bf16(bq.x, bq.y), v3 = pack_bf16(bq.z, bq.w);
                        *(uint32_t*)(xd) = v0; *(uint32_t*)(xd + 2048) = v1; *(uint32_t*)(xd + 128) = v2; *(uint32_t*)(xd + 2048 + 128) = v3;
                        float sq[4];
                        sq[0] = w0 * bf_lo(v0) * bf_lo(v0) + bf_lo(v1) * bf_lo(v1);
                        sq[1] = w0 * bf_hi(v0) * bf_hi(v0) + bf_hi(v1) * bf_hi(v1);
                        sq[2] = w0 * bf_lo(v2) * bf_lo(v2) + bf_lo(v3) * bf_lo(v3);
                        sq[3] = w0 * bf_hi(v2) * bf_hi(v2) + bf_hi(v3) * bf_hi(v3);
                        float u0 = (g & 1) ? sq[2] : sq[0], u1 = (g & 1) ? sq[3] : sq[1];
                        u0 += __shfl_xor_sync(~0u, (g & 1) ? sq[0] : sq[2], 4);
                        u1 += __shfl_xor_sync(~0u, (g & 1) ? sq[1] : sq[3], 4);
                        float z = (g & 2) ? u1 : u0;
                        z += __shfl_xor_sync(~0u, (g & 2) ? u0 : u1, 8);
                        z += __shfl_xor_sync(~0u, z, 16);
                        if (g < 4) atomicAdd(s_mean + 16 * i + 8 * (g & 1) + 2 * q + (g >> 1), z);
                    } else {
                        float* o = p.out + (uint32_t)((128 * c + 32 * q + 4 * i) * 512 + 64 * own + m0);
                        o[0] = a.x; o[512] = a.y; o[8] = a.z; o[512 + 8] = a.w;
                        o[1024] = bq.x; o[1536] = bq.y; o[1024 + 8] = bq.z; o[1536 + 8] = bq.w;
                    }
                }
            }
            if (wg < 2) mbar_wait_cluster(BAR(B_HDONE), layer);
            if (layer == 0) {
                fence_async_smem();
                bar_sync(9, 384);
                TS(14 + 12 * layer);
                if (wg == 2) {
                    atomicAdd(g_ssq + 2048 + 128 * c + t, s_mean[t] * (2.f / 512.f));
                    bar_sync(3, 128);
                    if (lane == 0) { mbar_arrive(BAR(B_AEMPTY + 6), 2); mbar_arrive(BAR(B_AEMPTY + 7), 2); }
                    if (t == 0) { fence_async(); red_release(&g_bar[2], 1); }
                }
            }
        }
        TS(15 + 12 * layer);
        if (wg == 0) TC(31);
    }
}

typedef CUresult (*EncFn)(CUtensorMap*, CUtensorMapDataType, cuuint32_t, void*, const cuuint64_t*, const cuuint64_t*,
                          const cuuint32_t*, const cuuint32_t*, CUtensorMapInterleave, CUtensorMapSwizzle,
                          CUtensorMapL2promotion, CUtensorMapFloatOOBfill);

void launch_impl(void* const* d_in, void* d_out, int stop) {
    static EncFn enc = nullptr;
    if (!enc) {
        void* fn = nullptr;
        cudaDriverEntryPointQueryResult qr;
        cudaGetDriverEntryPoint("cuTensorMapEncodeTiled", &fn, cudaEnableDefault, &qr);
        enc = (EncFn)fn;
        cudaFuncSetAttribute(fused_kernel, cudaFuncAttributeMaxDynamicSharedMemorySize, SM_TOTAL);
    }
    CUtensorMap tx, tbr, tbi, tcr, tci, tcol;
    {
        void* gx = nullptr;
        cudaGetSymbolAddress(&gx, g_X);
        cuuint64_t gd[5] = {64, 16, 64, 16, 2};
        cuuint64_t gs[4] = {128, 2048, 128 * 1024, 2048 * 1024};
        cuuint32_t bx[5] = {32, 16, 1, 16, 1};
        cuuint32_t es[5] = {1, 1, 1, 1, 1};
        enc(&tcol, CU_TENSOR_MAP_DATA_TYPE_BFLOAT16, 5, gx, gd, gs, bx, es, CU_TENSOR_MAP_INTERLEAVE_NONE,
            CU_TENSOR_MAP_SWIZZLE_64B, CU_TENSOR_MAP_L2_PROMOTION_NONE, CU_TENSOR_MAP_FLOAT_OOB_FILL_NONE);
    }
    {
        cuuint64_t gd[5] = {512, 2, 4, 16, 16};
        cuuint64_t gs[4] = {1024, 32 * 1024, 2 * 1024, 128 * 1024};
        cuuint32_t bx[5] = {64, 2, 4, 8, 1};
        cuuint32_t es[5] = {1, 1, 1, 1, 1};
        enc(&tx, CU_TENSOR_MAP_DATA_TYPE_BFLOAT16, 5, d_in[0], gd, gs, bx, es, CU_TENSOR_MAP_INTERLEAVE_NONE,
            CU_TENSOR_MAP_SWIZZLE_128B, CU_TENSOR_MAP_L2_PROMOTION_L2_128B, CU_TENSOR_MAP_FLOAT_OOB_FILL_NONE);
    }
    auto mk2 = [&](CUtensorMap* m, void* ptr, cuuint32_t rows) {
        cuuint64_t gd[2] = {512, 512};
        cuuint64_t gs[1] = {1024};
        cuuint32_t bx[2] = {64, rows};
        cuuint32_t es[2] = {1, 1};
        enc(m, CU_TENSOR_MAP_DATA_TYPE_BFLOAT16, 2, ptr, gd, gs, bx, es, CU_TENSOR_MAP_INTERLEAVE_NONE,
            CU_TENSOR_MAP_SWIZZLE_128B, CU_TENSOR_MAP_L2_PROMOTION_L2_128B, CU_TENSOR_MAP_FLOAT_OOB_FILL_NONE);
    };
    mk2(&tbr, d_in[6], 32);
    mk2(&tbi, d_in[7], 32);
    mk2(&tcr, d_in[8], 64);
    mk2(&tci, d_in[9], 64);
    Params p;
    p.x0 = (const __nv_bfloat16*)d_in[0];
    p.w_r = (const __nv_bfloat16*)d_in[1];
    p.w_i = (const __nv_bfloat16*)d_in[2];
    p.lam_re = (const __nv_bfloat16*)d_in[4];
    p.lam_im = (const __nv_bfloat16*)d_in[5];
    p.log_dt = (const __nv_bfloat16*)d_in[10];
    p.dskip = (const __nv_bfloat16*)d_in[11];
    p.out = (float*)d_out;
    p.stop = stop;
    cudaLaunchConfig_t cfg = {};
    cfg.gridDim = dim3(NCTA); cfg.blockDim = dim3(NTHREADS); cfg.dynamicSmemBytes = SM_TOTAL; cfg.stream = cudaStreamPerThread;
    cudaLaunchAttribute at[1];
    at[0].id = cudaLaunchAttributeClusterDimension;
    at[0].val.clusterDim.x = 2; at[0].val.clusterDim.y = 1; at[0].val.clusterDim.z = 1;
    cfg.attrs = at; cfg.numAttrs = 1;
    cudaLaunchKernelEx(&cfg, fused_kernel, tx, tbr, tbi, tcr, tci, tcol, p);
}

}

extern "C" void kernel_launch(void* const* d_in, const int* in_sizes, int n_in, void* d_out, int out_size) {
    (void)in_sizes; (void)n_in; (void)out_size;
    launch_impl(d_in, d_out, 100);
}
```

```cpp
#include <cuda_runtime.h>
#include <cuda_bf16.h>
#include <cuda.h>
#include <stdint.h>

namespace {

constexpr int NCTA = 128;
constexpr int NTHREADS = 512;
constexpr int SM_A = 0;
constexpr int SM_X = 131072;
constexpr int SM_H = 196608;
constexpr int SM_HH = SM_X + 32768;
constexpr int SM_M = 229376;
constexpr int SM_TOTAL = 232448;
constexpr int SM_BAR = SM_M;
constexpr int SM_TGT = SM_M + 392;
constexpr int SM_LAM = SM_M + 416;
constexpr int SM_TAB = SM_M + 928;
constexpr int SM_RSTD = SM_M + 1920;
constexpr int SM_MEAN = SM_TAB;
constexpr int SM_T64 = SM_M + 2944;
constexpr int SM_B1ST = SM_H + 24576;
constexpr int SM_RAW = SM_X + 40960;
constexpr int SM_SSQ = SM_X + 57344;
constexpr int B_FULL0 = 0;
constexpr int B_EMPTY0 = 8;
constexpr int B_FULLC = 12;
constexpr int B_AFULL = 13;
constexpr int B_AEMPTY = 21;
constexpr int B_XFULL = 29;
constexpr int B_XEMPTY = 33;
constexpr int B_AFREE = 37;
constexpr int B_COL = 38;
constexpr int B_SSQ = 39;
constexpr int B_HPEER = 40;
constexpr int B_RFREE = 41;
constexpr int B_HDONE = 42;
constexpr int B_WRDY = 43;
constexpr int B_HPEER1 = 44;
constexpr int B_FULLB = 45;
constexpr int B_BFREE = 46;
constexpr int B_SETUP = 47;
constexpr int B_B1DONE = 48;
constexpr int NBARS = 49;

__device__ __align__(1024) uint8_t g_X[2 * 16 * 8 * 16384];
__device__ __align__(1024) uint8_t g_A1[8 * 8 * 16384];
__device__ __align__(1024) uint8_t g_A2[8 * 8 * 16384];
__device__ __align__(1024) uint8_t g_E[2 * 8 * 8 * 8192];
__device__ __align__(16) float g_ssq[2 * 2048];
__device__ __align__(16) float g_ssqc[2 * 16 * 2048];
__device__ __align__(16) float g_Dh[512];
__device__ __align__(16) uint4 g_Wfrag[128 * 4 * 256];
__device__ __align__(16) float4 g_Ebuf[2 * 16 * 512];
__device__ __align__(16) uint4 g_P[16 * 8 * 4 * 1024];
__device__ unsigned g_bar[8];
__device__ unsigned g_err;
#define TX(i)
#define TQ(i)
#define TS(i)
#define TC(i)

constexpr unsigned SPIN_LIMIT = 1u << 22;

__device__ __forceinline__ uint32_t s2u(const void* p) { return (uint32_t)__cvta_generic_to_shared(p); }
__device__ __forceinline__ void mbar_init(uint32_t a, uint32_t c) {
    asm volatile("mbarrier.init.shared::cta.b64 [%0], %1;" ::"r"(a), "r"(c) : "memory");
}
__device__ __forceinline__ void mbar_expect(uint32_t a, uint32_t bytes) {
    asm volatile("mbarrier.arrive.expect_tx.shared::cta.b64 _, [%0], %1;" ::"r"(a), "r"(bytes) : "memory");
}
__device__ __forceinline__ void mbar_arrive(uint32_t a, uint32_t cnt) {
    asm volatile("mbarrier.arrive.shared::cta.b64 _, [%0], %1;" ::"r"(a), "r"(cnt) : "memory");
}
__device__ __forceinline__ bool mbar_try(uint32_t a, uint32_t parity) {
    uint32_t ok;
    asm volatile("{\n.reg .pred p;\nmbarrier.try_wait.parity.shared::cta.b64 p, [%1], %2;\nselp.u32 %0, 1, 0, p;\n}"
                 : "=r"(ok) : "r"(a), "r"(parity) : "memory");
    return ok != 0;
}
__device__ __forceinline__ void mbar_wait(uint32_t a, uint32_t parity) {
    asm volatile("{\n.reg .pred p, q;\n.reg .u32 n;\nmov.u32 n, 0;\n"
                 "W_%=:\nmbarrier.try_wait.parity.shared::cta.b64 p, [%0], %1;\n@p bra D_%=;\n"
                 "add.u32 n, n, 1;\nsetp.lt.u32 q, n, 4194304;\n@q bra W_%=;\nD_%=:\n}" ::"r"(a), "r"(parity) : "memory");
}
__device__ __forceinline__ void bulk_g2s(uint32_t dst, const void* src, uint32_t bytes, uint32_t bar) {
    asm volatile("cp.async.bulk.shared::cluster.global.mbarrier::complete_tx::bytes [%0], [%1], %2, [%3];" ::"r"(dst),
                 "l"(src), "r"(bytes), "r"(bar) : "memory");
}
__device__ __forceinline__ void tma_2d(uint32_t dst, const CUtensorMap* m, int c0, int c1, uint32_t bar) {
    asm volatile("cp.async.bulk.tensor.2d.shared::cluster.global.mbarrier::complete_tx::bytes [%0], [%1, {%3,%4}], [%2];" ::"r"(dst),
                 "l"(m), "r"(bar), "r"(c0), "r"(c1) : "memory");
}
__device__ __forceinline__ void tma_5d(uint32_t dst, const CUtensorMap* m, int c0, int c1, int c2, int c3, int c4, uint32_t bar) {
    asm volatile("cp.async.bulk.tensor.5d.shared::cluster.global.mbarrier::complete_tx::bytes [%0], [%1, {%3,%4,%5,%6,%7}], [%2];" ::"r"(dst),
                 "l"(m), "r"(bar), "r"(c0), "r"(c1), "r"(c2), "r"(c3), "r"(c4) : "memory");
}
__device__ __forceinline__ void tma_2d_mc(uint32_t dst, const CUtensorMap* m, int c0, int c1, uint32_t bar) {
    asm volatile("cp.async.bulk.tensor.2d.shared::cluster.global.mbarrier::complete_tx::bytes.multicast::cluster [%0], [%1, {%3,%4}], [%2], %5;" ::"r"(dst),
                 "l"(m), "r"(bar), "r"(c0), "r"(c1), "h"((unsigned short)3) : "memory");
}
__device__ __forceinline__ void tma_5d_mc(uint32_t dst, const CUtensorMap* m, int c0, int c1, int c2, int c3, int c4, uint32_t bar) {
    asm volatile("cp.async.bulk.tensor.5d.shared::cluster.global.mbarrier::complete_tx::bytes.multicast::cluster [%0], [%1, {%3,%4,%5,%6,%7}], [%2], %8;" ::"r"(dst),
                 "l"(m), "r"(bar), "r"(c0), "r"(c1), "r"(c2), "r"(c3), "r"(c4), "h"((unsigned short)3) : "memory");
}
__device__ __forceinline__ void bulk_g2s_mc(uint32_t dst, const void* src, uint32_t bytes, uint32_t bar) {
    asm volatile("cp.async.bulk.shared::cluster.global.mbarrier::complete_tx::bytes.multicast::cluster [%0], [%1], %2, [%3], %4;" ::"r"(dst),
                 "l"(src), "r"(bytes), "r"(bar), "h"((unsigned short)3) : "memory");
}
__device__ __forceinline__ void tma_store_5d(const CUtensorMap* m, int c0, int c1, int c2, int c3, int c4, uint32_t src) {
    asm volatile("cp.async.bulk.tensor.5d.global.shared::cta.bulk_group [%0, {%2,%3,%4,%5,%6}], [%1];" ::"l"(m), "r"(src),
                 "r"(c0), "r"(c1), "r"(c2), "r"(c3), "r"(c4) : "memory");
}
__device__ __forceinline__ uint32_t lds32(uint32_t a) { uint32_t v; asm volatile("ld.shared.u32 %0, [%1];" : "=r"(v) : "r"(a) : "memory"); return v; }
__device__ __forceinline__ uint4 ld_relaxed_u4(const uint4* p) {
    uint4 v;
    asm volatile("ld.relaxed.gpu.global.v4.u32 {%0,%1,%2,%3}, [%4];" : "=r"(v.x), "=r"(v.y), "=r"(v.z), "=r"(v.w) : "l"(p) : "memory");
    return v;
}
__device__ __forceinline__ void fence_async() { asm volatile("fence.proxy.async.global;" ::: "memory"); }
__device__ __forceinline__ void red_relaxed(unsigned* p, unsigned v) {
    asm volatile("red.relaxed.gpu.global.add.u32 [%0], %1;" ::"l"(p), "r"(v) : "memory");
}
__device__ __forceinline__ uint32_t mapa(uint32_t a, uint32_t rank) {
    uint32_t d;
    asm("mapa.shared::cluster.u32 %0, %1, %2;" : "=r"(d) : "r"(a), "r"(rank));
    return d;
}
__device__ __forceinline__ void mbar_arrive_remote(uint32_t ra) {
    asm volatile("mbarrier.arrive.relaxed.cluster.shared::cluster.b64 _, [%0];" ::"r"(ra) : "memory");
}
__device__ __forceinline__ void mbar_wait_cluster(uint32_t a, uint32_t parity) {
    asm volatile("{\n.reg .pred p, q;\n.reg .u32 n;\nmov.u32 n, 0;\n"
                 "W_%=:\nmbarrier.try_wait.parity.acquire.cluster.shared::cta.b64 p, [%0], %1;\n@p bra D_%=;\n"
                 "add.u32 n, n, 1;\nsetp.lt.u32 q, n, 4194304;\n@q bra W_%=;\nD_%=:\n}" ::"r"(a), "r"(parity) : "memory");
}
__device__ __forceinline__ void bulk_s2peer(uint32_t rdst, uint32_t src, uint32_t bytes, uint32_t rbar) {
    asm volatile("cp.async.bulk.shared::cluster.shared::cta.mbarrier::complete_tx::bytes [%0], [%1], %2, [%3];" ::"r"(rdst),
                 "r"(src), "r"(bytes), "r"(rbar) : "memory");
}
__device__ __forceinline__ void fence_async_smem() { asm volatile("fence.proxy.async.shared::cta;" ::: "memory"); }
__device__ __forceinline__ void wg_fence() { asm volatile("wgmma.fence.sync.aligned;" ::: "memory"); }
__device__ __forceinline__ void wg_commit() { asm volatile("wgmma.commit_group.sync.aligned;" ::: "memory"); }
template <int N> __device__ __forceinline__ void wg_wait() { asm volatile("wgmma.wait_group.sync.aligned %0;" ::"n"(N) : "memory"); }
__device__ __forceinline__ void bar_sync(int id, int n) { asm volatile("bar.sync %0, %1;" ::"r"(id), "r"(n) : "memory"); }
__device__ __forceinline__ void bar_arrive(int id, int n) { asm volatile("bar.arrive %0, %1;" ::"r"(id), "r"(n) : "memory"); }
__device__ __forceinline__ unsigned ld_acquire(const unsigned* p) {
    unsigned v;
    asm volatile("ld.acquire.gpu.global.u32 %0, [%1];" : "=r"(v) : "l"(p) : "memory");
    return v;
}
__device__ __forceinline__ void red_release(unsigned* p, unsigned v) {
    asm volatile("red.release.gpu.global.add.u32 [%0], %1;" ::"l"(p), "r"(v) : "memory");
}
__device__ __forceinline__ void wait_count(const unsigned* p, unsigned target) {
    unsigned n = 0;
#pragma unroll 1
    while ((int)(ld_acquire(p) - target) < 0 && ++n < SPIN_LIMIT) {}
}
__device__ __forceinline__ float4 ld_relaxed_f4(const float4* p) {
    float4 v;
    asm volatile("ld.relaxed.gpu.global.v4.f32 {%0,%1,%2,%3}, [%4];" : "=f"(v.x), "=f"(v.y), "=f"(v.z), "=f"(v.w) : "l"(p) : "memory");
    return v;
}
__device__ __forceinline__ void st_relaxed_f4(float4* p, float4 v) {
    asm volatile("st.relaxed.gpu.global.v4.f32 [%0], {%1,%2,%3,%4};" ::"l"(p), "f"(v.x), "f"(v.y), "f"(v.z), "f"(v.w) : "memory");
}
__device__ __forceinline__ uint32_t pack_bf16(float lo, float hi) {
    uint32_t r;
    asm("cvt.rn.bf16x2.f32 %0, %1, %2;" : "=r"(r) : "f"(hi), "f"(lo));
    return r;
}
__device__ __forceinline__ uint32_t hmul2(uint32_t a, uint32_t b) {
    uint32_t r;
    asm("mul.rn.bf16x2 %0, %1, %2;" : "=r"(r) : "r"(a), "r"(b));
    return r;
}
__device__ __forceinline__ uint32_t hfma2(uint32_t a, uint32_t b, uint32_t c) {
    uint32_t r;
    asm("fma.rn.bf16x2 %0, %1, %2, %3;" : "=r"(r) : "r"(a), "r"(b), "r"(c));
    return r;
}
__device__ __forceinline__ float bf_lo(uint32_t v) { return __uint_as_float(v << 16); }
__device__ __forceinline__ float bf_hi(uint32_t v) { return __uint_as_float(v & 0xffff0000u); }
__device__ __forceinline__ void sts32(uint32_t a, uint32_t v) { asm volatile("st.shared.u32 [%0], %1;" ::"r"(a), "r"(v) : "memory"); }
__device__ __forceinline__ void sts128(uint32_t a, uint4 v) {
    asm volatile("st.shared.v4.u32 [%0], {%1,%2,%3,%4};" ::"r"(a), "r"(v.x), "r"(v.y), "r"(v.z), "r"(v.w) : "memory");
}

__device__ __forceinline__ uint64_t desc_ni(uint32_t addr, uint32_t lbo, uint32_t sbo) {
    return (uint64_t)((addr & 0x3FFFF) >> 4) | ((uint64_t)(lbo >> 4) << 16) | ((uint64_t)(sbo >> 4) << 32);
}
__device__ __forceinline__ uint64_t desc_a(uint32_t addr) { return desc_ni(addr, 128, 1024); }
template <int N> __device__ __forceinline__ uint64_t desc_b(uint32_t addr) { return desc_ni(addr, 16 * N, 128); }
__device__ __forceinline__ uint64_t desc_k(uint32_t addr) {
    return (uint64_t)((addr & 0x3FFFF) >> 4) | (1ull << 16) | (64ull << 32) | (1ull << 62);
}
__device__ __forceinline__ uint64_t desc_mn(uint32_t addr, uint32_t lbo) {
    return (uint64_t)((addr & 0x3FFFF) >> 4) | ((uint64_t)(lbo >> 4) << 16) | (64ull << 32) | (1ull << 62);
}

#define ACC8(d, o) "+f"(d[o + 0]), "+f"(d[o + 1]), "+f"(d[o + 2]), "+f"(d[o + 3]), "+f"(d[o + 4]), "+f"(d[o + 5]), "+f"(d[o + 6]), "+f"(d[o + 7])
template <int TB, int SA = 1>
__device__ __forceinline__ void wgmma_n128(float (&d)[64], uint64_t da, uint64_t db, int sd) {
    asm volatile(
        "{\n.reg .pred p;\nsetp.ne.b32 p, %66, 0;\n"
        "wgmma.mma_async.sync.aligned.m64n128k16.f32.bf16.bf16 "
        "{%0,%1,%2,%3,%4,%5,%6,%7,%8,%9,%10,%11,%12,%13,%14,%15,%16,%17,%18,%19,%20,%21,%22,%23,%24,%25,%26,%27,%28,%29,%30,%31,"
        "%32,%33,%34,%35,%36,%37,%38,%39,%40,%41,%42,%43,%44,%45,%46,%47,%48,%49,%50,%51,%52,%53,%54,%55,%56,%57,%58,%59,%60,%61,%62,%63},"
        " %64, %65, p, %68, 1, 0, %67;\n}"
        : ACC8(d, 0), ACC8(d, 8), ACC8(d, 16), ACC8(d, 24), ACC8(d, 32), ACC8(d, 40), ACC8(d, 48), ACC8(d, 56)
        : "l"(da), "l"(db), "r"(sd), "n"(TB), "n"(SA));
}
template <int N> __device__ __forceinline__ void acc_def(float (&d)[N]) {
#pragma unroll
    for (int i = 0; i < N; i++) d[i] = 0.f;
}
template <int TB>
__device__ __forceinline__ void wgmma_n64(float (&d)[32], uint64_t da, uint64_t db, int sd) {
    asm volatile(
        "{\n.reg .pred p;\nsetp.ne.b32 p, %34, 0;\n"
        "wgmma.mma_async.sync.aligned.m64n64k16.f32.bf16.bf16 "
        "{%0,%1,%2,%3,%4,%5,%6,%7,%8,%9,%10,%11,%12,%13,%14,%15,%16,%17,%18,%19,%20,%21,%22,%23,%24,%25,%26,%27,%28,%29,%30,%31},"
        " %32, %33, p, 1, 1, 0, %35;\n}"
        : ACC8(d, 0), ACC8(d, 8), ACC8(d, 16), ACC8(d, 24)
        : "l"(da), "l"(db), "r"(sd), "n"(TB));
}
template <int SA>
__device__ __forceinline__ void wgmma_n64s(float (&d)[32], uint64_t da, uint64_t db, int sd) {
    asm volatile(
        "{\n.reg .pred p;\nsetp.ne.b32 p, %34, 0;\n"
        "wgmma.mma_async.sync.aligned.m64n64k16.f32.bf16.bf16 "
        "{%0,%1,%2,%3,%4,%5,%6,%7,%8,%9,%10,%11,%12,%13,%14,%15,%16,%17,%18,%19,%20,%21,%22,%23,%24,%25,%26,%27,%28,%29,%30,%31},"
        " %32, %33, p, %35, 1, 0, 1;\n}"
        : ACC8(d, 0), ACC8(d, 8), ACC8(d, 16), ACC8(d, 24)
        : "l"(da), "l"(db), "r"(sd), "n"(SA));
}
__device__ __forceinline__ void wgmma_n64_rs(float (&d)[32], uint32_t a0, uint32_t a1, uint32_t a2, uint32_t a3, uint64_t db, int sd) {
    asm volatile(
        "{\n.reg .pred p;\nsetp.ne.b32 p, %37, 0;\n"
        "wgmma.mma_async.sync.aligned.m64n64k16.f32.bf16.bf16 "
        "{%0,%1,%2,%3,%4,%5,%6,%7,%8,%9,%10,%11,%12,%13,%14,%15,%16,%17,%18,%19,%20,%21,%22,%23,%24,%25,%26,%27,%28,%29,%30,%31},"
        " {%32,%33,%34,%35}, %36, p, 1, 1, 1;\n}"
        : ACC8(d, 0), ACC8(d, 8), ACC8(d, 16), ACC8(d, 24)
        : "r"(a0), "r"(a1), "r"(a2), "r"(a3), "l"(db), "r"(sd));
}

struct Params {
    const __nv_bfloat16* x0;
    const __nv_bfloat16* w_r;
    const __nv_bfloat16* w_i;
    const __nv_bfloat16* lam_re;
    const __nv_bfloat16* lam_im;
    const __nv_bfloat16* log_dt;
    const __nv_bfloat16* dskip;
    float* out;
    int stop;
};

__device__ __forceinline__ float ldbf(const __nv_bfloat16* p) { return __bfloat162float(*p); }

__device__ __forceinline__ void dft_fp(int j, int& f, int& ph) {
    int cs = j >> 1;
    if (j == 1) { f = 256; ph = 0; }
    else { f = cs; ph = (j & 1) ? 128 : 0; }
}

__device__ __forceinline__ void gen_col_consts(uint32_t sb, int tid) {
#pragma unroll 1
    for (int task = tid; task < 640; task += 256) {
        int f, c8;
        uint32_t a_cc, d_pi, d_po;
        if (task < 512) {
            f = task & 63; c8 = task >> 6;
            a_cc = sb + SM_X + (f >> 5) * 16384 + ((f >> 3) & 3) * 2048 + c8 * 128 + (f & 7) * 16;
            d_pi = 8192; d_po = 1024;
        } else {
            int n2 = task & 31;
            f = 2 * n2; c8 = (task >> 5) & 3;
            a_cc = sb + SM_X + 32768 + (n2 >> 3) * 1024 + c8 * 128 + (n2 & 7) * 16;
            d_pi = 4096; d_po = 512;
        }
        float cd, sd, cs, sn;
        __sincosf((float)(f >= 32 ? f - 64 : f) * (6.283185307179586f / 64.f), &sd, &cd);
        int a = (8 * c8 * f) & 63;
        __sincosf((float)(a >= 32 ? a - 64 : a) * (6.283185307179586f / 64.f), &sn, &cs);
        float cv[8], sv[8];
#pragma unroll
        for (int e = 0; e < 8; e++) {
            cv[e] = cs; sv[e] = sn;
            float t = cs * cd - sn * sd;
            sn = sn * cd + cs * sd;
            cs = t;
        }
        uint4 oc = make_uint4(pack_bf16(cv[0], cv[1]), pack_bf16(cv[2], cv[3]), pack_bf16(cv[4], cv[5]), pack_bf16(cv[6], cv[7]));
        uint4 os = make_uint4(pack_bf16(sv[0], sv[1]), pack_bf16(sv[2], sv[3]), pack_bf16(sv[4], sv[5]), pack_bf16(sv[6], sv[7]));
        sts128(a_cc, oc);
        sts128(a_cc + d_pi, os);
        sts128(a_cc + d_po, make_uint4(os.x ^ 0x80008000u, os.y ^ 0x80008000u, os.z ^ 0x80008000u, os.w ^ 0x80008000u));
        sts128(a_cc + d_pi + d_po, oc);
    }
}

__global__ void __launch_bounds__(NTHREADS, 1)
fused_kernel(const __grid_constant__ CUtensorMap tm_x, const __grid_constant__ CUtensorMap tm_bre,
             const __grid_constant__ CUtensorMap tm_bim, const __grid_constant__ CUtensorMap tm_cre,
             const __grid_constant__ CUtensorMap tm_cim, const __grid_constant__ CUtensorMap tm_col, const Params p) {
    extern __shared__ __align__(1024) uint8_t sm[];
    const uint32_t sb = s2u(sm);
    const int tid = threadIdx.x, b = blockIdx.x;
    const int c = b >> 3, r = b & 7;
    const int par = r & 1, pi_ = r >> 1, own = 4 * par + pi_;
    const int wg = __shfl_sync(~0u, tid >> 7, 0), w = __shfl_sync(~0u, (tid >> 5) & 3, 0), lane = tid & 31, g = lane >> 2, q = lane & 3;
    auto BAR = [&](int i) { return sb + SM_BAR + 8 * i; };
    unsigned* s_tgt = (unsigned*)(sm + SM_TGT);

    if (tid < NBARS) {
        int cnt = 1;
        if (tid >= B_EMPTY0 && tid < B_EMPTY0 + 4) cnt = 16;
        if (tid >= B_XEMPTY && tid < B_XEMPTY + 4) cnt = 24;
        if (tid == B_RFREE) cnt = 12;
        if (tid == B_HDONE) cnt = 2;
        if ((tid >= B_AEMPTY && tid < B_AEMPTY + 8) || tid == B_BFREE) cnt = 8;
        if (tid == B_AFREE) cnt = 4;
        mbar_init(BAR(tid), cnt);
        asm volatile("fence.mbarrier_init.release.cluster;" ::: "memory");
    }
    asm volatile("barrier.cluster.arrive.release.aligned;" ::: "memory");

    if (wg == 3) {
        asm volatile("setmaxnreg.dec.sync.aligned.u32 56;");
        if (w == 0 && lane < 6) {
            const CUtensorMap* tm = lane == 0 ? &tm_x : lane == 1 ? &tm_bre : lane == 2 ? &tm_bim : lane == 3 ? &tm_cre : lane == 4 ? &tm_cim : &tm_col;
            asm volatile("prefetch.tensormap [%0];" ::"l"(tm) : "memory");
        }
        __syncwarp();
        asm volatile("barrier.cluster.wait.acquire.aligned;" ::: "memory");
        if (w > 0) {
            if (w == 1) {
                float lr[3], li[3], ld[3];
#pragma unroll
                for (int k = 0; k < 3; k++) {
                    int ps = k < 2 ? 64 * r + 32 * k + lane : 32 * c + lane;
                    lr[k] = ldbf(p.lam_re + ps); li[k] = ldbf(p.lam_im + ps); ld[k] = ldbf(p.log_dt + ps);
                }
                if (lane < 6) s_tgt[lane] = ((ld_acquire(&g_bar[lane]) >> 7) + 1u) << 7;
#pragma unroll 1
                for (int k = 0; k < 3; k++) {
                    float a = k == 0 ? lr[0] : (k == 1 ? lr[1] : lr[2]), bq = k == 0 ? li[0] : (k == 1 ? li[1] : li[2]);
                    float dt = __bfloat162float(__float2bfloat16(expf(k == 0 ? ld[0] : (k == 1 ? ld[1] : ld[2]))));
                    float mag = expf(a * dt), t = bq * dt * 0.15915494309189535f, sn, cs;
                    t -= rintf(t);
                    sincospif(2.f * t, &sn, &cs);
                    float er = mag * cs, ei = mag * sn;
                    if (k < 2) {
                        *(float2*)(sm + SM_LAM + (32 * k + lane) * 8) = make_float2(er, ei);
                    } else {
                        er -= 1.f;
                        float inv = 1.f / (a * a + bq * bq);
                        *(float2*)(sm + SM_TAB + lane * 8) = make_float2((er * a + ei * bq) * inv, (ei * a - er * bq) * inv);
                    }
                }
                __syncwarp();
                bar_arrive(15, 160);
                if (lane == 0) mbar_arrive(BAR(B_SETUP), 1);
            }
            if (w == 2) {
                const int kq = 2 * b + (lane >> 4), row = (kq >> 2) + 128 * (kq & 3) + 512 * ((lane >> 1) & 3) + 64 * (lane & 1);
                const char* src = (const char*)(((lane >> 3) & 1) ? p.w_i : p.w_r) + (size_t)row * 514;
                size_t a0 = (size_t)src & ~(size_t)15;
                int bytes = row == 2047 ? 512 : 544;
                asm volatile("cp.async.bulk.prefetch.L2.global [%0], %1;" ::"l"(a0), "r"(bytes) : "memory");
            }
#pragma unroll 1
            for (int task = tid - 448; task < 256 && w > 1; task += 64) {
                const int cb = task & 127, kq = 2 * b + (task >> 7), k1 = kq >> 2, qq = kq & 3;
                const unsigned short* wr_ = (const unsigned short*)p.w_r + (k1 + 128 * qq) * 257;
                const unsigned short* wi_ = (const unsigned short*)p.w_i + (k1 + 128 * qq) * 257;
                const int c0 = cb == 0 ? 256 : 2 * cb, c1 = 2 * cb + 1;
                uint32_t wf[16];
#pragma unroll
                for (int i = 0; i < 4; i++) {
                    int o = 512 * i * 257;
                    wf[2 * i] = (uint32_t)__ldg(wr_ + o + c0) | ((uint32_t)__ldg(wr_ + o + 64 * 257 + c0) << 16);
                    wf[2 * i + 1] = ((uint32_t)__ldg(wi_ + o + c0) | ((uint32_t)__ldg(wi_ + o + 64 * 257 + c0) << 16)) ^ 0x80008000u;
                    wf[8 + 2 * i] = (uint32_t)__ldg(wr_ + o + c1) | ((uint32_t)__ldg(wr_ + o + 64 * 257 + c1) << 16);
                    wf[8 + 2 * i + 1] = ((uint32_t)__ldg(wi_ + o + c1) | ((uint32_t)__ldg(wi_ + o + 64 * 257 + c1) << 16)) ^ 0x80008000u;
                }
                uint4* wd = g_Wfrag + (uint32_t)(cb * 1024 + kq);
#pragma unroll
                for (int i = 0; i < 4; i++) wd[i * 256] = make_uint4(wf[4 * i], wf[4 * i + 1], wf[4 * i + 2], wf[4 * i + 3]);
            }
#pragma unroll 1
            for (int i = tid - 448; i < 96 + 128 && w > 1; i += 64) {
                if (i < 96) g_P[(uint32_t)(b * 4 + i / 24) * 1024 + 640 + ((i % 24) >> 1) * 32 + 30 + (i & 1)] = make_uint4(0, 0, 0, 0);
                else g_Ebuf[b * 128 + i - 96] = make_float4(0.f, 0.f, 0.f, 0.f);
            }
            __syncwarp();
            if (w == 3) bar_arrive(11, 192);
            if (w == 2) {
                bar_sync(11, 192);
                if (lane == 0) red_release(&g_bar[4], 1);
            }
            if (w == 3) {
#pragma unroll 1
                for (int it = 0; it < 8; it++) {
                    const int m = 4 * c + (it >> 1), d = 64 * r + m, ch = lane + 32 * (it & 1);
                    float v[8];
#pragma unroll
                    for (int e = 0; e < 8; e++) {
                        int j = 8 * ch + e, f, ph;
                        dft_fp(j, f, ph);
                        int a = (d * f + ph) & 511;
                        a = a >= 256 ? a - 512 : a;
                        float wj = j == 0 ? 0.f : (j == 1 ? 1.f / 512.f : 2.f / 512.f);
                        v[e] = wj * __cosf((float)a * (6.283185307179586f / 512.f));
                    }
                    uint32_t off = (uint32_t)(64 + r * 8 + (ch >> 3)) * 8192 + (m >> 3) * 1024 + (ch & 7) * 128 + (m & 7) * 16;
                    *(uint4*)(g_E + off) = make_uint4(pack_bf16(v[0], v[1]), pack_bf16(v[2], v[3]), pack_bf16(v[4], v[5]), pack_bf16(v[6], v[7]));
                }
                __syncwarp();
                if (lane == 0) { fence_async(); red_release(&g_bar[6], 1); }
                return;
            }
            if (w == 2) {
#pragma unroll 1
                for (int it = 0; it < 4; it++) {
                    const int hf = it & 1;
                    __syncwarp();
                    if (hf == 0) bar_sync(13, 288); else bar_sync(6, 416);
                    if (lane == 0) {
                        const uint32_t src = sb + SM_HH + par * 32768 + hf * 16384;
                        bulk_s2peer(mapa(src, par ^ 1), src, 16384, mapa(BAR(hf ? B_HPEER1 : B_HPEER), par ^ 1));
                    }
                }
                return;
            }
            bar_sync(2, 288);
            if (lane == 0) {
                TX(5);
                fence_async();
                red_release(&g_bar[0], 1);
                TX(6);
            }
            __syncwarp();

            bar_sync(12, 160);
            if (lane == 0) {
                asm volatile("cp.async.bulk.global.shared::cta.bulk_group [%0], [%1], 8192;" ::"l"(g_A1 + (uint32_t)(((c >> 1) * 8 + r) * 16384 + (c & 1) * 8192)),
                             "r"(sb + SM_B1ST) : "memory");
                asm volatile("cp.async.bulk.commit_group;" ::: "memory");
                asm volatile("cp.async.bulk.wait_group 0;" ::: "memory");
                mbar_arrive(BAR(B_B1DONE), 1);
                fence_async();
                red_release(&g_bar[7], 1);
            }
#pragma unroll 1
            for (int layer = 0; layer < 2; layer++) {
                __syncwarp();
                bar_sync(5, 416);
                if (lane == 0) {
                    TX(0 + 8 * layer);
                    tma_store_5d(&tm_col, 32 * (b & 1), 0, b >> 1, 0, layer, sb + SM_RAW);
                    asm volatile("cp.reduce.async.bulk.global.shared::cta.bulk_group.add.f32 [%0], [%1], 8192;" ::"l"(g_ssqc + (layer * 16 + (b & 15)) * 2048),
                                 "r"(sb + SM_SSQ) : "memory");
                    asm volatile("cp.async.bulk.commit_group;" ::: "memory");
                    asm volatile("cp.async.bulk.wait_group 0;" ::: "memory");
                    TX(1 + 8 * layer);
                    fence_async();
                    red_release(&g_bar[1 + 2 * layer], 1);
                    TX(2 + 8 * layer);
                }
            }
        } else if (tid == 384) {
#pragma unroll 1
            for (int kb = 0; kb < 8; kb++) {
                uint32_t fb = BAR(B_FULL0 + kb);
                mbar_expect(fb, 16384);
                tma_5d_mc(sb + SM_A + 65536 + kb * 16384 + par * 8192, &tm_x, kb * 64, 0, 0, 8 * par, c, fb);
            }
#pragma unroll 1
            for (int k2 = 0; k2 < 8; k2++) {
                asm volatile("cp.async.bulk.prefetch.tensor.2d.L2.global [%0, {%1,%2}];" ::"l"(par ? &tm_bim : &tm_bre), "r"(k2 * 64), "r"(32 * c) : "memory");
                if ((k2 & 1) == par)
                    asm volatile("cp.async.bulk.prefetch.tensor.2d.L2.global [%0, {%1,%2}];" ::"l"((c & 1) ? &tm_cim : &tm_cre), "r"(64 * (c >> 1)), "r"(k2 * 64) : "memory");
            }
            mbar_wait(BAR(B_SETUP), 0);
#pragma unroll 1
            for (int layer = 0; layer < 2; layer++) {
                wait_count(&g_bar[2 * layer], s_tgt[2 * layer]);
                TX(4 + 8 * layer);
                fence_async();
                mbar_expect(BAR(B_COL), 16384 + 8192);
                tma_5d(sb + SM_RAW, &tm_col, 32 * (b & 1), 0, b >> 1, 0, layer, BAR(B_COL));
                bulk_g2s(sb + SM_SSQ, g_ssq + layer * 2048, 8192, BAR(B_COL));
                if (layer == 0) {
                    wait_count(&g_bar[4], s_tgt[4]);
                    mbar_arrive(BAR(B_WRDY), 1);
                    wait_count(&g_bar[7], s_tgt[4]);
                    fence_async();
                }
                if (layer == 0) mbar_wait(BAR(B_AFREE), 0);
                mbar_wait(BAR(B_COL), layer);
#pragma unroll 1
                for (int s = 0; s < 8; s++) {
                    if (layer == 1) mbar_wait(BAR(B_AEMPTY + s), 1);
                    if (s >= 2) mbar_wait(BAR(B_AFULL + s - 2), 0);
                    mbar_expect(BAR(B_AFULL + s), 16384);
                    bulk_g2s(sb + SM_A + s * 16384, g_A1 + (uint32_t)(r * 8 + s) * 16384, 16384, BAR(B_AFULL + s));
                }
                if (layer == 1) wait_count(&g_bar[6], s_tgt[4]);
                wait_count(&g_bar[1 + 2 * layer], s_tgt[1 + 2 * layer]);
                TX(3 + 8 * layer);
                fence_async();
                const uint8_t* xsrc = g_X + (uint32_t)(layer * 16 + c) * 8 * 16384;
                const uint8_t* esrc = g_E + (uint32_t)(layer * 8 + own) * 8 * 8192;
                mbar_arrive(BAR(B_SSQ), 1);
                mbar_expect(BAR(B_HPEER), 16384);
                mbar_expect(BAR(B_HPEER1), 16384);
#pragma unroll 1
                for (int it = 0; it < 16; it++) {
                    if (it < 8) {
                        int st = it & 3, f = layer * 2 + (it >> 2);
                        if (f > 0) mbar_wait_cluster(BAR(B_XEMPTY + st), (f - 1) & 1);
                        mbar_expect(BAR(B_XFULL + st), 24576);
                        bulk_g2s_mc(sb + SM_X + st * 24576 + par * 8192, xsrc + (uint32_t)it * 16384 + par * 8192, 8192, BAR(B_XFULL + st));
                        bulk_g2s(sb + SM_X + st * 24576 + 16384, esrc + (uint32_t)it * 8192, 8192, BAR(B_XFULL + st));
                    }
                    if (it >= 8) {
                        if (it == 8) mbar_wait(BAR(B_AEMPTY + 5), 0);
                        int s = it - 8, tile = 4 * par + ((pi_ + 1 + (s >> 1)) & 3), sl = r ^ (s & 1);
                        mbar_wait(BAR(B_AEMPTY + s), 0);
                        uint32_t fb = BAR(B_AFULL + s), dst = sb + SM_A + s * 16384;
                        mbar_expect(fb, 16384);
                        if (layer == 1) {
                            tma_2d(dst, &tm_cre, 64 * sl, 64 * tile, fb);
                            tma_2d(dst + 8192, &tm_cim, 64 * sl, 64 * tile, fb);
                        } else {
                            bulk_g2s(dst, g_A2 + (uint32_t)(sl * 8 + tile) * 16384, 16384, fb);
                        }
                    }
                }
            }
        }
        return;
    }

    asm volatile("setmaxnreg.inc.sync.aligned.u32 152;");
    if (tid >= 96 && tid < 112) g_ssq[2048 + 16 * b + tid - 96] = 0.f;
    if (tid >= 128 && tid < 256) ((float4*)g_ssqc)[b * 128 + tid - 128] = make_float4(0.f, 0.f, 0.f, 0.f);
    TS(0);
    if (wg == 0) TC(30);
    {
        const int f = 32 * r + lane;
        float cd, sd;
        __sincosf((float)f * (6.283185307179586f / 512.f), &sd, &cd);
        const uint32_t dst = sb + SM_A + (lane >> 2) * 1024 + (lane & 3) * 32;
#pragma unroll 1
        for (int ch = tid >> 5; ch < 64; ch += 12) {
            int a = (8 * ch * f) & 511;
            a = a >= 256 ? a - 512 : a;
            float cs, sn;
            __sincosf((float)a * (6.283185307179586f / 512.f), &sn, &cs);
            float cv[8], sv[8];
#pragma unroll
            for (int e = 0; e < 8; e++) {
                cv[e] = cs; sv[e] = -sn;
                float t = cs * cd - sn * sd;
                sn = sn * cd + cs * sd;
                cs = t;
            }
            uint4 o1 = make_uint4(pack_bf16(sv[0], sv[1]), pack_bf16(sv[2], sv[3]), pack_bf16(sv[4], sv[5]), pack_bf16(sv[6], sv[7]));
            if (f == 0) o1 = make_uint4(0xbf803f80u, 0xbf803f80u, 0xbf803f80u, 0xbf803f80u);
            uint32_t a0 = dst + (ch >> 3) * 8192 + (ch & 7) * 128;
            sts128(a0, make_uint4(pack_bf16(cv[0], cv[1]), pack_bf16(cv[2], cv[3]), pack_bf16(cv[4], cv[5]), pack_bf16(cv[6], cv[7])));
            sts128(a0 + 16, o1);
        }
    }
    fence_async_smem();
    asm volatile("barrier.cluster.wait.acquire.aligned;" ::: "memory");
    bar_sync(10, 384);
    TS(1);
    if (wg < 2) {
        float acc[32];
        acc_def(acc);
        const int npos = 16 * r + 8 * wg + 2 * w;
        float sh0 = 0.f, sh1 = 0.f, s0 = 0.f, s1 = 0.f, q0 = 0.f, q1 = 0.f;
#pragma unroll 1
        for (int kb = 0; kb < 8; kb++) {
            uint32_t slot = sb + SM_A + 65536 + kb * 16384;
            mbar_wait(BAR(B_FULL0 + kb), 0);
            wg_fence();
#pragma unroll
            for (int ks = 0; ks < 4; ks++)
                wgmma_n64<0>(acc, desc_a(sb + SM_A + kb * 8192 + ks * 256), desc_k(slot + wg * 8192 + ks * 32), 1);
            wg_commit();
            {
                uint32_t v0 = lds32(slot + npos * 128 + lane * 4), v1 = lds32(slot + npos * 128 + 128 + lane * 4);
                if (kb == 0) { sh0 = __shfl_sync(~0u, bf_lo(v0), 0); sh1 = __shfl_sync(~0u, bf_lo(v1), 0); }
                float a = bf_lo(v0) - sh0, bq = bf_hi(v0) - sh0, cq = bf_lo(v1) - sh1, d = bf_hi(v1) - sh1;
                s0 += a + bq; q0 += a * a + bq * bq; s1 += cq + d; q1 += cq * cq + d * d;
            }
            wg_wait<1>();
            if (kb > 0 && kb <= 4 && lane == 0) { mbar_arrive(BAR(B_EMPTY0 + kb - 1), 1); mbar_arrive_remote(mapa(BAR(B_EMPTY0 + kb - 1), par ^ 1)); }
        }
#pragma unroll
        for (int o = 16; o; o >>= 1) {
            s0 += __shfl_xor_sync(~0u, s0, o); q0 += __shfl_xor_sync(~0u, q0, o);
            s1 += __shfl_xor_sync(~0u, s1, o); q1 += __shfl_xor_sync(~0u, q1, o);
        }
        if (lane == 0) *(float2*)(g_ssq + 128 * c + npos) = make_float2(fmaxf(q0 - s0 * s0 * (1.f / 512.f), 0.f), fmaxf(q1 - s1 * s1 * (1.f / 512.f), 0.f));
        wg_wait<0>();
        TS(2);
        uint8_t* dst = g_X + (uint32_t)((c * 8 + r) * 16384 + w * 4096 + wg * 1024 + g * 16 + 4 * q);
#pragma unroll
        for (int i = 0; i < 8; i++) {
            *(uint32_t*)(dst + i * 128) = pack_bf16(acc[4 * i], acc[4 * i + 1]);
            *(uint32_t*)(dst + 2048 + i * 128) = pack_bf16(acc[4 * i + 2], acc[4 * i + 3]);
        }
        bar_sync(2, 288);
        mbar_wait(BAR(B_SETUP), 0);
        TS(3);
    }

    if (wg == 2) {
        {
            uint4 p0 = __ldg((const uint4*)p.dskip + 2 * lane), p1 = __ldg((const uint4*)p.dskip + 2 * lane + 1);
            uint32_t u[8] = {p0.x, p0.y, p0.z, p0.w, p1.x, p1.y, p1.z, p1.w};
            int j = 64 * r + 4 * c + w, f, ph;
            dft_fp(j, f, ph);
            float s = 0.f;
            int idx = 16 * lane * f + ph;
#pragma unroll
            for (int i = 0; i < 16; i++) {
                int a = idx & 511;
                idx += f;
                a = a >= 256 ? a - 512 : a;
                s += ((i & 1) ? bf_hi(u[i >> 1]) : bf_lo(u[i >> 1])) * __cosf((float)a * (6.283185307179586f / 512.f));
            }
#pragma unroll
            for (int o = 16; o; o >>= 1) s += __shfl_xor_sync(~0u, s, o);
            if (lane == 0) g_Dh[j] = s;
            bar_arrive(11, 192);
        }
        bar_sync(15, 160);
        float acc[32];
        acc_def(acc);
        if (tid == 256) {
#pragma unroll 1
            for (int s = 0; s < 4; s++) mbar_wait_cluster(BAR(B_EMPTY0 + s), 0);
            mbar_expect(BAR(B_FULLB), 65536);
#pragma unroll 1
            for (int k2 = 0; k2 < 8; k2++)
                tma_2d_mc(sb + SM_A + 65536 + k2 * 8192 + par * 4096, par ? &tm_bim : &tm_bre, k2 * 64, 32 * c, BAR(B_FULLB));
        }
        __syncwarp();
        mbar_wait(BAR(B_FULLB), 0);
        wg_fence();
#pragma unroll 1
        for (int kb = 0; kb < 8; kb++) {
#pragma unroll
            for (int ks = 0; ks < 4; ks++)
                wgmma_n64<0>(acc, desc_a(sb + SM_A + kb * 8192 + ks * 256), desc_k(sb + SM_A + 65536 + kb * 8192 + ks * 32), 1);
            wg_commit();
        }
        wg_wait<0>();
        if (lane == 0) { mbar_arrive(BAR(B_BFREE), 1); mbar_arrive_remote(mapa(BAR(B_BFREE), par ^ 1)); }
        if (tid == 256) {
            mbar_wait_cluster(BAR(B_BFREE), 0);
            mbar_expect(BAR(B_FULLC), 65536);
#pragma unroll 1
            for (int k2 = par; k2 < 8; k2 += 2)
                tma_2d_mc(sb + SM_A + 65536 + k2 * 8192, (c & 1) ? &tm_cim : &tm_cre, 64 * (c >> 1), k2 * 64, BAR(B_FULLC));
        }
        __syncwarp();
        {
            uint8_t* dst = sm + SM_B1ST + w * 256 + q * 32 + g * 2;
            const float wj0 = (r == 0 && w == 0 && g < 2) ? (g == 0 ? 0.f : 1.f / 512.f) : 2.f / 512.f;
#pragma unroll
            for (int i = 0; i < 4; i++) {
#pragma unroll
                for (int e = 0; e < 2; e++) {
                    float2 cf = *(const float2*)(sm + SM_TAB + (8 * i + 2 * q + e) * 8);
#pragma unroll
                    for (int h = 0; h < 2; h++) {
                        float wj = h == 0 ? wj0 : 2.f / 512.f;
                        float pr = acc[4 * i + 2 * h + e] * wj, pi = acc[16 + 4 * i + 2 * h + e] * wj;
                        uint8_t* d2 = dst + i * 2048 + h * 128 + e * 16;
                        *(__nv_bfloat16*)(d2) = __float2bfloat16(cf.x * pr - cf.y * pi);
                        *(__nv_bfloat16*)(d2 + 1024) = __float2bfloat16(cf.x * pi + cf.y * pr);
                    }
                }
            }
            fence_async_smem();
            bar_arrive(12, 160);
        }
        acc_def(acc);
        mbar_wait(BAR(B_FULLC), 0);
        wg_fence();
#pragma unroll 1
        for (int kb = 0; kb < 8; kb++) {
#pragma unroll
            for (int ks = 0; ks < 4; ks++)
                wgmma_n64<1>(acc, desc_a(sb + SM_A + kb * 8192 + ks * 256), desc_mn(sb + SM_A + 65536 + kb * 8192 + ks * 2048, 8192), 1);
            wg_commit();
        }
        wg_wait<0>();
        fence_async_smem();
        if (lane == 0) mbar_arrive(BAR(B_AFREE), 1);
        uint8_t* dst = g_A2 + (uint32_t)(((c >> 1) * 8 + r) * 16384 + (c & 1) * 8192 + w * 2048 + g * 16 + 4 * q);
#pragma unroll
        for (int i = 0; i < 8; i++) {
            *(uint32_t*)(dst + i * 128) = pack_bf16(acc[4 * i], acc[4 * i + 1]);
            *(uint32_t*)(dst + 1024 + i * 128) = pack_bf16(acc[4 * i + 2], acc[4 * i + 3]);
        }
        {
            const int m = 4 * c + w, jp = 64 * r + m;
            int fp, php;
            dft_fp(jp, fp, php);
            const __nv_bfloat16* dh = (const __nv_bfloat16*)(sm + SM_RSTD);
            if (tid == 256) wait_count(&g_bar[4], s_tgt[4]);
            bar_sync(3, 128);
            float4 d4 = __ldcg((const float4*)g_Dh + (tid - 256));
            *(uint2*)(sm + SM_RSTD + (tid - 256) * 8) = make_uint2(pack_bf16(d4.x, d4.y), pack_bf16(d4.z, d4.w));
            bar_sync(3, 128);
#pragma unroll 1
            for (int it = 0; it < 2; it++) {
                const int ch = lane + 32 * it;
                float v[8];
#pragma unroll
                for (int e = 0; e < 8; e++) {
                    int j = 8 * ch + e, f, ph;
                    dft_fp(j, f, ph);
                    float wj = j == 0 ? 0.f : (j == 1 ? 1.f / 512.f : 2.f / 512.f);
                    float gsum = 0.f;
#pragma unroll
                    for (int sgn = 0; sgn < 2; sgn++) {
                        int mm = (sgn ? f - fp : f + fp) & 511, pp = (sgn ? ph - php : ph + php) & 511;
                        if (mm > 256) { mm = 512 - mm; pp = (512 - pp) & 511; }
                        int odd = (pp >> 7) & 1;
                        float t = __bfloat162float(dh[mm == 256 ? 1 : 2 * mm + odd]);
                        if (odd && (mm & 255) == 0) t = 0.f;
                        gsum += (pp & 256) ? -t : t;
                    }
                    v[e] = 0.5f * wj * gsum;
                }
                uint32_t off = (uint32_t)(r * 8 + (ch >> 3)) * 8192 + (m >> 3) * 1024 + (ch & 7) * 128 + (m & 7) * 16;
                *(uint4*)(g_E + off) = make_uint4(pack_bf16(v[0], v[1]), pack_bf16(v[2], v[3]), pack_bf16(v[4], v[5]), pack_bf16(v[6], v[7]));
            }
        }
    }

#pragma unroll 1
    for (int layer = 0; layer < 2; layer++) {
        if (wg < 2) {
            const int n1 = 32 * wg + 8 * w + g;
            const int ct = n1 >> 2;
            gen_col_consts(sb, tid);
            uint32_t tr2[4], ti2[4], tn2[4];
#pragma unroll
            for (int i = 0; i < 4; i++) {
                float cr[2], ci[2];
#pragma unroll
                for (int e = 0; e < 2; e++) {
                    int a = (n1 * (8 * i + 2 * q + e)) & 2047;
                    a = a >= 1024 ? a - 2048 : a;
                    float ang = (float)a * (-6.283185307179586f / 2048.f);
                    cr[e] = __cosf(ang); ci[e] = __sinf(ang);
                }
                tr2[i] = pack_bf16(cr[0], cr[1]); ti2[i] = pack_bf16(ci[0], ci[1]); tn2[i] = ti2[i] ^ 0x80008000u;
            }
            uint32_t wf[16];
            const uint4* ws = g_Wfrag + (uint32_t)(b * 1024 + n1 * 4 + q);
#pragma unroll
            for (int i = 0; i < 4; i++) {
                uint4 v = make_uint4(0, 0, 0, 0);
                if (layer == 1) v = __ldcg(ws + i * 256);
                wf[4 * i] = v.x; wf[4 * i + 1] = v.y; wf[4 * i + 2] = v.z; wf[4 * i + 3] = v.w;
            }
            mbar_wait(BAR(B_COL), layer);
            TS(4 + 12 * layer);
            if (wg == 0) TC(0 + 10 * layer);
            const uint32_t rw0 = sb + SM_RAW + ct * 1024 + q * 64 + ((q >> 1) << 4) + (g & 3) * 4, rw1 = rw0 ^ 16;
            const int pos0 = 128 * ct + 8 * q + 2 * (g & 3);
            const int sw = b == 0 ? 1 : 0;
            uint32_t xr[4][4];
            const uint32_t st0 = sb + SM_H + (n1 >> 3) * 1024 + g * 16 + 4 * q;
#pragma unroll
            for (int i = 0; i < 4; i++) {
                float2 sq = *(const float2*)(sm + SM_SSQ + (pos0 + 32 * i) * 4);
                const uint32_t rs2 = pack_bf16(rsqrtf(sq.x * (1.f / 512.f) + 1e-5f), rsqrtf(sq.y * (1.f / 512.f) + 1e-5f));
#pragma unroll
                for (int jj = 0; jj < 4; jj++) {
                    const int K = jj ^ (2 * (i & 1));
                    uint32_t a = ((K & 1) ? rw1 : rw0) + i * 256 + (K & 2) * 16;
                    if (jj < 2) a ^= sw << 4;
                    uint32_t v = lds32(a);
                    xr[jj][i] = v;
                    uint32_t o = hmul2(v, rs2);
                    if (jj == 1 && sw) o = 0u;
                    sts32(st0 + (jj & 1) * 8192 + (4 * (jj >> 1) + i) * 128, o);
                }
            }
            if (wg == 0) TC(1 + 10 * layer);
            fence_async_smem();
            bar_sync(1, 256);
            float acc[32];
            const uint32_t s1a = sb + SM_X + wg * 16384, s2b = sb + SM_X + 32768;
            wg_fence();
#pragma unroll
            for (int ks = 0; ks < 8; ks++)
                wgmma_n64<1>(acc, desc_a(s1a + (ks >> 2) * 8192 + (ks & 3) * 256), desc_b<64>(sb + SM_H + ks * 2048), ks != 0);
            wg_commit();
            if (layer == 0) {
                mbar_wait(BAR(B_WRDY), 0);
#pragma unroll
                for (int i = 0; i < 4; i++) {
                    uint4 v = __ldcg(ws + i * 256);
                    wf[4 * i] = v.x; wf[4 * i + 1] = v.y; wf[4 * i + 2] = v.z; wf[4 * i + 3] = v.w;
                }
            }
            wg_wait<0>();
            if (wg == 0) TC(2 + 10 * layer);
            uint32_t are[2][4], aim[2][4];
#pragma unroll
            for (int col = 0; col < 2; col++) {
#pragma unroll
                for (int i = 0; i < 4; i++) {
                    int o = 4 * (4 * col + i);
                    uint32_t zr = pack_bf16(acc[o], acc[o + 1]), zi = pack_bf16(acc[o + 2], acc[o + 3]);
                    are[col][i] = hfma2(zr, tr2[i], hmul2(zi, tn2[i]));
                    aim[col][i] = hfma2(zr, ti2[i], hmul2(zi, tr2[i]));
                }
            }
            wg_fence();
#pragma unroll
            for (int ks = 0; ks < 2; ks++)
                wgmma_n64_rs(acc, are[0][2 * ks], are[1][2 * ks], are[0][2 * ks + 1], are[1][2 * ks + 1], desc_b<64>(s2b + ks * 2048), ks != 0);
#pragma unroll
            for (int ks = 0; ks < 2; ks++)
                wgmma_n64_rs(acc, aim[0][2 * ks], aim[1][2 * ks], aim[0][2 * ks + 1], aim[1][2 * ks + 1], desc_b<64>(s2b + 4096 + ks * 2048), 1);
            wg_commit();
            wg_wait<0>();
            if (wg == 0) TC(3 + 10 * layer);
#pragma unroll
            for (int col = 0; col < 2; col++) {
#pragma unroll
                for (int i = 0; i < 4; i++) {
                    uint32_t wr = wf[col * 8 + 2 * i], wn = wf[col * 8 + 2 * i + 1];
                    uint32_t zr = pack_bf16(acc[4 * i + 2 * col], acc[4 * i + 2 * col + 1]);
                    uint32_t zi = pack_bf16(acc[16 + 4 * i + 2 * col], acc[16 + 4 * i + 2 * col + 1]);
                    are[col][i] = hfma2(zr, wr, hmul2(zi, wn));
                    aim[col][i] = hfma2(zr, wn, hmul2(zi ^ 0x80008000u, wr));
                }
            }
            wg_fence();
#pragma unroll
            for (int ks = 0; ks < 2; ks++)
                wgmma_n64_rs(acc, are[0][2 * ks], are[1][2 * ks], are[0][2 * ks + 1], are[1][2 * ks + 1], desc_b<64>(s2b + ks * 2048), ks != 0);
#pragma unroll
            for (int ks = 0; ks < 2; ks++)
                wgmma_n64_rs(acc, aim[0][2 * ks], aim[1][2 * ks], aim[0][2 * ks + 1], aim[1][2 * ks + 1], desc_b<64>(s2b + 4096 + ks * 2048), 1);
            wg_commit();
            wg_wait<0>();
            if (wg == 0) TC(4 + 10 * layer);
            mbar_wait(BAR(B_B1DONE), 0);
#pragma unroll
            for (int col = 0; col < 2; col++) {
#pragma unroll
                for (int i = 0; i < 4; i++) {
                    uint32_t zr = pack_bf16(acc[4 * i + 2 * col], acc[4 * i + 2 * col + 1]);
                    uint32_t zi = pack_bf16(acc[16 + 4 * i + 2 * col], acc[16 + 4 * i + 2 * col + 1]);
                    sts32(st0 + 16384 + (4 * col + i) * 128, hfma2(zr, tr2[i], hmul2(zi, tn2[i])));
                    sts32(st0 + 16384 + 8192 + (4 * col + i) * 128, hfma2(zr, ti2[i], hmul2(zi, tr2[i])));
                }
            }
            if (wg == 0) TC(5 + 10 * layer);
            fence_async_smem();
            bar_sync(1, 256);
            wg_fence();
#pragma unroll
            for (int ks = 0; ks < 8; ks++)
                wgmma_n64<1>(acc, desc_a(s1a + (ks >> 2) * 8192 + (ks & 3) * 256), desc_b<64>(sb + SM_H + 16384 + ks * 2048), ks != 0);
            wg_commit();
            wg_wait<0>();
            if (wg == 0) TC(6 + 10 * layer);
            const float sc = 1.f / 2048.f;
            const float sci0 = sw ? 0.f : -sc;
            const float wr0 = sw ? 0.5f : 1.f, wi0 = sw ? 0.f : 1.f;
#pragma unroll
            for (int i = 0; i < 4; i++) {
                float ss0, ss1;
#pragma unroll
                for (int col = 0; col < 2; col++) {
                    int o = 4 * (4 * col + i);
                    uint32_t vr = xr[2 * col][i], vi = xr[2 * col + 1][i];
                    float si = col == 0 ? sci0 : -sc;
                    uint32_t nr = pack_bf16(fmaf(acc[o], sc, bf_lo(vr)), fmaf(acc[o + 1], sc, bf_hi(vr)));
                    uint32_t ni = pack_bf16(fmaf(acc[o + 2], si, bf_lo(vi)), fmaf(acc[o + 3], si, bf_hi(vi)));
                    float a0 = bf_lo(nr), a1 = bf_hi(nr), b0 = bf_lo(ni), b1 = bf_hi(ni);
                    if (col == 0) {
                        ss0 = wr0 * a0 * a0 + wi0 * b0 * b0;
                        ss1 = wr0 * a1 * a1 + wi0 * b1 * b1;
                    } else {
                        ss0 += a0 * a0 + b0 * b0;
                        ss1 += a1 * a1 + b1 * b1;
                    }
                    const int K = (2 * col) ^ (2 * (i & 1));
                    uint32_t a = rw0 + i * 256 + K * 16;
                    if (col == 0) a ^= sw << 4;
                    sts32(a, nr);
                    sts32(a ^ 16, ni);
                }
                *(float2*)(sm + SM_SSQ + (pos0 + 32 * i) * 4) = make_float2(ss0 * (2.f / 512.f), ss1 * (2.f / 512.f));
            }
            fence_async_smem();
        }
        TS(5 + 12 * layer);
        if (wg == 0) TC(7 + 10 * layer);
        bar_arrive(5, 416);

        float acc[64];
        float* s_rstd = (float*)(sm + SM_RSTD);
        float* s_mean = (float*)(sm + SM_MEAN);
        const unsigned epoch = s_tgt[0] >> 7;
        const uint32_t pt3 = 1u + (2u * epoch + layer) % 3u;
        const uint32_t ptag = (pt3 & 1u) | ((pt3 & 2u) << 15);
        const uint64_t dstep = layer == 0 ? 16 : 2;
        auto c_desc = [&](int s) { return layer == 0 ? desc_a(sb + SM_A + s * 16384) : desc_k(sb + SM_A + s * 16384); };
        if (wg < 2) {
            const int prow = 32 * wg + 8 * w + g;
            const float2 l1 = *(const float2*)(sm + SM_LAM + prow * 8);
            float lr32 = l1.x, li32 = l1.y;
#pragma unroll
            for (int i = 0; i < 5; i++) { float t = lr32 * lr32 - li32 * li32; li32 = 2.f * lr32 * li32; lr32 = t; }
            float lr128 = lr32, li128 = li32;
#pragma unroll
            for (int i = 0; i < 2; i++) { float t = lr128 * lr128 - li128 * li128; li128 = 2.f * lr128 * li128; lr128 = t; }
            const float lr1 = l1.x, li1 = l1.y;
            acc_def(acc);
#pragma unroll 1
            for (int kb = 0; kb < 8; kb++) {
                mbar_wait(BAR(B_AFULL + kb), 0);
                mbar_wait(BAR(B_XFULL + (kb & 3)), (kb >> 2) & 1);
                wg_fence();
#pragma unroll
                for (int ks = 0; ks < 4; ks++)
                    wgmma_n128<1>(acc, desc_a(sb + SM_A + kb * 16384 + wg * 8192 + ks * 256),
                                  desc_b<128>(sb + SM_X + (kb & 3) * 24576 + ks * 4096), 1);
                wg_commit();
                wg_wait<1>();
                if (kb > 0 && lane == 0) {
                    mbar_arrive(BAR(B_AEMPTY + kb - 1), 1); mbar_arrive(BAR(B_XEMPTY + ((kb - 1) & 3)), 1);
                    mbar_arrive_remote(mapa(BAR(B_XEMPTY + ((kb - 1) & 3)), par ^ 1));
                }
            }
            wg_wait<0>();
            if (lane == 0) {
                mbar_arrive(BAR(B_AEMPTY + 7), 1); mbar_arrive(BAR(B_XEMPTY + 3), 1);
                mbar_arrive_remote(mapa(BAR(B_XEMPTY + 3), par ^ 1)); mbar_arrive_remote(mapa(BAR(B_RFREE), par ^ 1));
            }
            bar_arrive(14, 384);
            TS(6 + 12 * layer);
            bar_sync(4, 384);
            TS(7 + 12 * layer);
            float er = 0.f, ei = 0.f;
#pragma unroll
            for (int i = 0; i < 16; i++) {
                float2 rs = *(const float2*)(s_rstd + 128 + 8 * i + 2 * q);
                acc[4 * i] *= rs.x; acc[4 * i + 1] *= rs.y; acc[4 * i + 2] *= rs.x; acc[4 * i + 3] *= rs.y;
                float nr = lr1 * er - li1 * ei + acc[4 * i], ni = lr1 * ei + li1 * er + acc[4 * i + 2];
                er = lr1 * nr - li1 * ni + acc[4 * i + 1];
                ei = lr1 * ni + li1 * nr + acc[4 * i + 3];
            }
            float cr = 0.f, ci = 0.f, tr = 0.f, ti = 0.f;
#pragma unroll
            for (int qq = 0; qq < 4; qq++) {
                float xr_ = __shfl_sync(~0u, er, (lane & ~3) | qq), xi_ = __shfl_sync(~0u, ei, (lane & ~3) | qq);
                if (qq == q) { cr = tr; ci = ti; }
                float nr = lr32 * tr - li32 * ti + xr_, ni = lr32 * ti + li32 * tr + xi_;
                tr = nr; ti = ni;
            }
            float4* eb = g_Ebuf + (uint32_t)(layer * 16 * 512 + 64 * r + prow);
            if (q == 0 && c < 15) st_relaxed_f4(eb + c * 512, make_float4(tr, ti, __uint_as_float(epoch), 0.f));
            TS(8 + 12 * layer);
            float pr[4], pi[4];
            {
                unsigned n = 0;
                bool ok;
#pragma unroll 1
                do {
                    ok = true;
#pragma unroll
                    for (int k = 0; k < 4; k++) {
                        float4 v = make_float4(0.f, 0.f, __uint_as_float(epoch), 0.f);
                        if (4 * k + q < c) v = ld_relaxed_f4(eb + (4 * k + q) * 512);
                        pr[k] = v.x; pi[k] = v.y;
                        ok = ok && __float_as_uint(v.z) == epoch;
                    }
                } while (!ok && ++n < SPIN_LIMIT);
            }
            __syncwarp();
            TS(9 + 12 * layer);
            float hr = 0.f, hi = 0.f;
#pragma unroll
            for (int cc = 0; cc < 15; cc++) {
                float xr_ = __shfl_sync(~0u, pr[cc >> 2], (lane & ~3) | (cc & 3)), xi_ = __shfl_sync(~0u, pi[cc >> 2], (lane & ~3) | (cc & 3));
                if (cc < c) {
                    float nr = lr128 * hr - li128 * hi + xr_, ni = lr128 * hi + li128 * hr + xi_;
                    hr = nr; hi = ni;
                }
            }
#pragma unroll
            for (int qq = 0; qq < 3; qq++) {
                if (qq < q) { float nr = lr32 * hr - li32 * hi, ni = lr32 * hi + li32 * hr; hr = nr; hi = ni; }
            }
            er = cr + hr; ei = ci + hi;
            bar_sync(7, 384);
            mbar_wait_cluster(BAR(B_RFREE), layer);
            const uint32_t ha = sb + SM_HH + par * 32768 + (prow >> 3) * 1024 + g * 16 + 4 * q;
#pragma unroll
            for (int i = 0; i < 16; i++) {
                float nr = lr1 * er - li1 * ei + acc[4 * i], ni = lr1 * ei + li1 * er + acc[4 * i + 2];
                er = lr1 * nr - li1 * ni + acc[4 * i + 1];
                ei = lr1 * ni + li1 * nr + acc[4 * i + 3];
                sts32(ha + (i >> 3) * 16384 + (i & 7) * 128, pack_bf16(nr, er));
                sts32(ha + (i >> 3) * 16384 + 8192 + (i & 7) * 128, pack_bf16(ni, ei));
                if (i == 7) { fence_async_smem(); bar_arrive(13, 288); }
            }
            fence_async_smem();
            acc_def(acc);
            float acc2[32];
            acc_def(acc2);
            TS(10 + 12 * layer);
            bar_sync(6, 416);
            TS(11 + 12 * layer);
            float (&a0)[32] = *reinterpret_cast<float (*)[32]>(&acc[0]);
            float (&a1)[32] = *reinterpret_cast<float (*)[32]>(&acc[32]);
            auto tile_mma = [&](float (&d)[32], int u) {
#pragma unroll 1
                for (int k = 0; k < 2; k++) {
                    const uint32_t hb = sb + SM_HH + (par ^ k) * 32768 + wg * 16384;
                    if (k == 1) mbar_wait(BAR(wg ? B_HPEER1 : B_HPEER), layer);
                    mbar_wait(BAR(B_AFULL + 2 * u + k), 1);
                    const uint64_t da = c_desc(2 * u + k);
                    wg_fence();
#pragma unroll
                    for (int ks = 0; ks < 4; ks++) wgmma_n64s<1>(d, da + ks * dstep, desc_b<64>(hb + ks * 2048), 1);
#pragma unroll
                    for (int ks = 0; ks < 4; ks++) wgmma_n64s<-1>(d, da + 512 + ks * dstep, desc_b<64>(hb + 8192 + ks * 2048), 1);
                }
                wg_commit();
            };
            auto tile_ship = [&](float (&d)[32], int u) {
                uint4* dst = g_P + (uint32_t)(((c * 8 + 2 * ((pi_ + 1 + u) & 3) + par) * 4 + pi_) * 1024 + wg * 512 + (tid & 127));
#pragma unroll
                for (int i = 0; i < 4; i++)
                    dst[i * 128] = make_uint4((pack_bf16(d[8 * i], d[8 * i + 1]) & 0xfffefffeu) | ptag, pack_bf16(d[8 * i + 2], d[8 * i + 3]),
                                              pack_bf16(d[8 * i + 4], d[8 * i + 5]), pack_bf16(d[8 * i + 6], d[8 * i + 7]));
            };
            tile_mma(a0, 0);
            if ((tid & 127) == 0) mbar_arrive_remote(mapa(BAR(B_HDONE), par ^ 1));
            __syncwarp();
            tile_mma(a1, 1);
            wg_wait<1>();
            tile_ship(a0, 0);
            tile_mma(acc2, 2);
            bar_arrive(12, 384);
            wg_wait<1>();
            tile_ship(a1, 1);
            wg_wait<0>();
            tile_ship(acc2, 2);
            if (lane < 6) mbar_arrive(BAR(B_AEMPTY + lane), 1);
            TS(12 + 12 * layer);
        } else {
            const int t2 = tid - 256;
            const uint8_t* ximg = g_X + (uint32_t)layer * 16 * 8 * 16384;
            mbar_wait(BAR(B_SSQ), layer);
            TS(6 + 12 * layer);
            float sqv[16];
#pragma unroll
            for (int i = 0; i < 16; i++) sqv[i] = __ldcg(g_ssqc + (layer * 16 + i) * 2048 + 128 * c + t2);
            const unsigned short xm = __ldcg((const unsigned short*)(ximg + (uint32_t)(c * 8 * 16384 + (t2 >> 3) * 128 + (t2 & 7) * 2)));
            acc_def(acc);
#pragma unroll 1
            for (int kb = 0; kb < 8; kb++) {
                if (kb == 4) {
                    wg_wait<0>();
                    if (lane == 0) { mbar_arrive(BAR(B_XEMPTY + 3), 1); mbar_arrive_remote(mapa(BAR(B_XEMPTY + 3), par ^ 1)); }
                    float tot = 0.f;
#pragma unroll
                    for (int i = 0; i < 16; i++) tot += sqv[i];
                    float rs = rsqrtf(tot * (1.f / 512.f) + 1e-5f);
                    s_rstd[t2] = rs;
                    s_rstd[128 + t2] = 2.f * rs;
                    s_mean[t2] = layer == 0 ? 0.f : __uint_as_float((uint32_t)xm << 16) * (1.f / 512.f);
                    TS(7 + 12 * layer);
                    bar_arrive(4, 384);
                    bar_sync(14, 384);
                }
                mbar_wait(BAR(B_XFULL + (kb & 3)), (kb >> 2) & 1);
                wg_fence();
#pragma unroll
                for (int ks = 0; ks < 4; ks++)
                    wgmma_n128<1>(acc, desc_a(sb + SM_X + (kb & 3) * 24576 + 16384 + ks * 256), desc_b<128>(sb + SM_X + (kb & 3) * 24576 + ks * 4096), 1);
                wg_commit();
                wg_wait<1>();
                if ((kb & 3) != 0 && lane == 0) { mbar_arrive(BAR(B_XEMPTY + ((kb - 1) & 3)), 1); mbar_arrive_remote(mapa(BAR(B_XEMPTY + ((kb - 1) & 3)), par ^ 1)); }
            }
            wg_wait<0>();
            if (lane == 0) { mbar_arrive(BAR(B_XEMPTY + 3), 1); mbar_arrive_remote(mapa(BAR(B_XEMPTY + 3), par ^ 1)); mbar_arrive_remote(mapa(BAR(B_RFREE), par ^ 1)); }
            bar_arrive(7, 384);
            bar_sync(3, 128);
            TS(9 + 12 * layer);
            const int m0 = 16 * w + g;
            const uint32_t xoff = (uint32_t)((c * 8 + own) * 16384 + w * 4096 + g * 16 + 4 * q);
            if (layer == 0) {
                const uint8_t* xs = g_X + xoff;
#pragma unroll
                for (int i = 0; i < 16; i++) {
                    float2 rs = *(const float2*)(s_rstd + 8 * i + 2 * q);
                    uint32_t x0v = __ldcg((const uint32_t*)(xs + i * 128)), x1v = __ldcg((const uint32_t*)(xs + 2048 + i * 128));
                    acc[4 * i] = acc[4 * i] * rs.x + bf_lo(x0v);
                    acc[4 * i + 1] = acc[4 * i + 1] * rs.y + bf_hi(x0v);
                    acc[4 * i + 2] = acc[4 * i + 2] * rs.x + bf_lo(x1v);
                    acc[4 * i + 3] = acc[4 * i + 3] * rs.y + bf_hi(x1v);
                }
            } else {
                float d0 = ldbf(p.dskip + 64 * own + m0), d1 = ldbf(p.dskip + 64 * own + m0 + 8);
#pragma unroll
                for (int i = 0; i < 16; i++) {
                    float2 rs = *(const float2*)(s_rstd + 8 * i + 2 * q);
                    float2 mn = *(const float2*)(s_mean + 8 * i + 2 * q);
                    acc[4 * i] = acc[4 * i] * (1.f + rs.x * d0) + mn.x;
                    acc[4 * i + 1] = acc[4 * i + 1] * (1.f + rs.y * d0) + mn.y;
                    acc[4 * i + 2] = acc[4 * i + 2] * (1.f + rs.x * d1) + mn.x;
                    acc[4 * i + 3] = acc[4 * i + 3] * (1.f + rs.y * d1) + mn.y;
                }
            }
            TS(10 + 12 * layer);
            bar_sync(6, 416);
            TS(11 + 12 * layer);
            {
                float (&a0)[32] = *reinterpret_cast<float (*)[32]>(&acc[0]);
                float (&a1)[32] = *reinterpret_cast<float (*)[32]>(&acc[32]);
#pragma unroll 1
                for (int k = 0; k < 2; k++) {
                    const uint32_t hb = sb + SM_HH + (par ^ k) * 32768;
                    if (k == 1) {
                        mbar_wait(BAR(B_HPEER), layer);
                        mbar_wait(BAR(B_HPEER1), layer);
                        bar_sync(12, 384);
                    }
                    mbar_wait(BAR(B_AFULL + 6 + k), 1);
                    const uint64_t da = c_desc(6 + k);
                    wg_fence();
#pragma unroll
                    for (int ks = 0; ks < 4; ks++) {
                        wgmma_n64s<1>(a0, da + ks * dstep, desc_b<64>(hb + ks * 2048), 1);
                        wgmma_n64s<1>(a1, da + ks * dstep, desc_b<64>(hb + 16384 + ks * 2048), 1);
                    }
#pragma unroll
                    for (int ks = 0; ks < 4; ks++) {
                        wgmma_n64s<-1>(a0, da + 512 + ks * dstep, desc_b<64>(hb + 8192 + ks * 2048), 1);
                        wgmma_n64s<-1>(a1, da + 512 + ks * dstep, desc_b<64>(hb + 16384 + 8192 + ks * 2048), 1);
                    }
                    wg_commit();
                }
                wg_wait<0>();
            }
#pragma unroll
            for (int i = 0; i < 16; i++)
                *(float4*)(sm + SM_A + 6 * 16384 + i * 2048 + t2 * 16) = make_float4(acc[4 * i], acc[4 * i + 1], acc[4 * i + 2], acc[4 * i + 3]);
            TS(12 + 12 * layer);
        }
        {
            const int t = tid & 127;
            const int nch = wg == 2 ? 2 : 3;
            const uint4* pb = g_P + (uint32_t)((c * 8 + r) * 4 * 1024 + wg * 128 + t);
            uint4 v[3][3];
            unsigned n = 0;
#pragma unroll 1
            while (true) {
                if (lane == 31) {
#pragma unroll 1
                    while (true) {
                        uint32_t bad = 0;
#pragma unroll
                        for (int sx = 0; sx < 3; sx++) {
                            uint32_t t0;
                            asm volatile("ld.relaxed.gpu.global.u32 %0, [%1];" : "=r"(t0) : "l"(pb + ((pi_ + 1 + sx) & 3) * 1024 + (nch - 1) * 384) : "memory");
                            bad |= t0 ^ ptag;
                        }
                        if (!(bad & 0x00010001u) || ++n >= SPIN_LIMIT) break;
                    }
                }
                __syncwarp();
                uint32_t bad = 0;
#pragma unroll
                for (int k = 0; k < 3; k++)
#pragma unroll
                    for (int sx = 0; sx < 3; sx++) {
                        v[k][sx] = make_uint4(ptag, 0, 0, 0);
                        if (k < nch) v[k][sx] = ld_relaxed_u4(pb + ((pi_ + 1 + sx) & 3) * 1024 + k * 384);
                        bad |= v[k][sx].x ^ ptag;
                    }
                if (!__any_sync(~0u, bad & 0x00010001u) || ++n >= SPIN_LIMIT) break;
            }
            bar_sync(8, 384);
            TS(13 + 12 * layer);
            const int m0 = 16 * w + g;
            const float w0 = (own == 0 && m0 < 2) ? (m0 == 0 ? 0.f : 0.5f) : 1.f;
#pragma unroll
            for (int k = 0; k < 3; k++) {
                if (k < nch) {
                    const int i = wg + 3 * k;
                    float4 a = *(const float4*)(sm + SM_A + 6 * 16384 + (2 * i) * 2048 + t * 16);
                    float4 bq = *(const float4*)(sm + SM_A + 6 * 16384 + (2 * i + 1) * 2048 + t * 16);
#pragma unroll
                    for (int sx = 0; sx < 3; sx++) {
                        a.x += bf_lo(v[k][sx].x); a.y += bf_hi(v[k][sx].x); a.z += bf_lo(v[k][sx].y); a.w += bf_hi(v[k][sx].y);
                        bq.x += bf_lo(v[k][sx].z); bq.y += bf_hi(v[k][sx].z); bq.z += bf_lo(v[k][sx].w); bq.w += bf_hi(v[k][sx].w);
                    }
                    if (layer == 0) {
                        uint8_t* xd = g_X + (uint32_t)((16 * 8 + c * 8 + own) * 16384 + w * 4096 + g * 16 + 4 * q + i * 256);
                        uint32_t v0 = pack_bf16(a.x, a.y), v1 = pack_bf16(a.z, a.w), v2 = pack_bf16(bq.x, bq.y), v3 = pack_bf16(bq.z, bq.w);
                        *(uint32_t*)(xd) = v0; *(uint32_t*)(xd + 2048) = v1; *(uint32_t*)(xd + 128) = v2; *(uint32_t*)(xd + 2048 + 128) = v3;
                        float sq[4];
                        sq[0] = w0 * bf_lo(v0) * bf_lo(v0) + bf_lo(v1) * bf_lo(v1);
                        sq[1] = w0 * bf_hi(v0) * bf_hi(v0) + bf_hi(v1) * bf_hi(v1);
                        sq[2] = w0 * bf_lo(v2) * bf_lo(v2) + bf_lo(v3) * bf_lo(v3);
                        sq[3] = w0 * bf_hi(v2) * bf_hi(v2) + bf_hi(v3) * bf_hi(v3);
                        float u0 = (g & 1) ? sq[2] : sq[0], u1 = (g & 1) ? sq[3] : sq[1];
                        u0 += __shfl_xor_sync(~0u, (g & 1) ? sq[0] : sq[2], 4);
                        u1 += __shfl_xor_sync(~0u, (g & 1) ? sq[1] : sq[3], 4);
                        float z = (g & 2) ? u1 : u0;
                        z += __shfl_xor_sync(~0u, (g & 2) ? u0 : u1, 8);
                        z += __shfl_xor_sync(~0u, z, 16);
                        if (g < 4) atomicAdd(s_mean + 16 * i + 8 * (g & 1) + 2 * q + (g >> 1), z);
                    } else {
                        float* o = p.out + (uint32_t)((128 * c + 32 * q + 4 * i) * 512 + 64 * own + m0);
                        o[0] = a.x; o[512] = a.y; o[8] = a.z; o[512 + 8] = a.w;
                        o[1024] = bq.x; o[1536] = bq.y; o[1024 + 8] = bq.z; o[1536 + 8] = bq.w;
                    }
                }
            }
            if (wg < 2) mbar_wait_cluster(BAR(B_HDONE), layer);
            if (layer == 0) {
                fence_async_smem();
                bar_sync(9, 384);
                TS(14 + 12 * layer);
                if (wg == 2) {
                    atomicAdd(g_ssq + 2048 + 128 * c + t, s_mean[t] * (2.f / 512.f));
                    bar_sync(3, 128);
                    if (lane == 0) { mbar_arrive(BAR(B_AEMPTY + 6), 2); mbar_arrive(BAR(B_AEMPTY + 7), 2); }
                    if (t == 0) { fence_async(); red_release(&g_bar[2], 1); }
                }
            }
        }
        TS(15 + 12 * layer);
        if (wg == 0) TC(31);
    }
}

typedef CUresult (*EncFn)(CUtensorMap*, CUtensorMapDataType, cuuint32_t, void*, const cuuint64_t*, const cuuint64_t*,
                          const cuuint32_t*, const cuuint32_t*, CUtensorMapInterleave, CUtensorMapSwizzle,
                          CUtensorMapL2promotion, CUtensorMapFloatOOBfill);

void launch_impl(void* const* d_in, void* d_out, int stop) {
    static EncFn enc = nullptr;
    if (!enc) {
        void* fn = nullptr;
        cudaDriverEntryPointQueryResult qr;
        cudaGetDriverEntryPoint("cuTensorMapEncodeTiled", &fn, cudaEnableDefault, &qr);
        enc = (EncFn)fn;
        cudaFuncSetAttribute(fused_kernel, cudaFuncAttributeMaxDynamicSharedMemorySize, SM_TOTAL);
    }
    CUtensorMap tx, tbr, tbi, tcr, tci, tcol;
    {
        void* gx = nullptr;
        cudaGetSymbolAddress(&gx, g_X);
        cuuint64_t gd[5] = {64, 16, 64, 16, 2};
        cuuint64_t gs[4] = {128, 2048, 128 * 1024, 2048 * 1024};
        cuuint32_t bx[5] = {32, 16, 1, 16, 1};
        cuuint32_t es[5] = {1, 1, 1, 1, 1};
        enc(&tcol, CU_TENSOR_MAP_DATA_TYPE_BFLOAT16, 5, gx, gd, gs, bx, es, CU_TENSOR_MAP_INTERLEAVE_NONE,
            CU_TENSOR_MAP_SWIZZLE_64B, CU_TENSOR_MAP_L2_PROMOTION_NONE, CU_TENSOR_MAP_FLOAT_OOB_FILL_NONE);
    }
    {
        cuuint64_t gd[5] = {512, 2, 4, 16, 16};
        cuuint64_t gs[4] = {1024, 32 * 1024, 2 * 1024, 128 * 1024};
        cuuint32_t bx[5] = {64, 2, 4, 8, 1};
        cuuint32_t es[5] = {1, 1, 1, 1, 1};
        enc(&tx, CU_TENSOR_MAP_DATA_TYPE_BFLOAT16, 5, d_in[0], gd, gs, bx, es, CU_TENSOR_MAP_INTERLEAVE_NONE,
            CU_TENSOR_MAP_SWIZZLE_128B, CU_TENSOR_MAP_L2_PROMOTION_L2_128B, CU_TENSOR_MAP_FLOAT_OOB_FILL_NONE);
    }
    auto mk2 = [&](CUtensorMap* m, void* ptr, cuuint32_t rows) {
        cuuint64_t gd[2] = {512, 512};
        cuuint64_t gs[1] = {1024};
        cuuint32_t bx[2] = {64, rows};
        cuuint32_t es[2] = {1, 1};
        enc(m, CU_TENSOR_MAP_DATA_TYPE_BFLOAT16, 2, ptr, gd, gs, bx, es, CU_TENSOR_MAP_INTERLEAVE_NONE,
            CU_TENSOR_MAP_SWIZZLE_128B, CU_TENSOR_MAP_L2_PROMOTION_L2_128B, CU_TENSOR_MAP_FLOAT_OOB_FILL_NONE);
    };
    mk2(&tbr, d_in[6], 32);
    mk2(&tbi, d_in[7], 32);
    mk2(&tcr, d_in[8], 64);
    mk2(&tci, d_in[9], 64);
    Params p;
    p.x0 = (const __nv_bfloat16*)d_in[0];
    p.w_r = (const __nv_bfloat16*)d_in[1];
    p.w_i = (const __nv_bfloat16*)d_in[2];
    p.lam_re = (const __nv_bfloat16*)d_in[4];
    p.lam_im = (const __nv_bfloat16*)d_in[5];
    p.log_dt = (const __nv_bfloat16*)d_in[10];
    p.dskip = (const __nv_bfloat16*)d_in[11];
    p.out = (float*)d_out;
    p.stop = stop;
    cudaLaunchConfig_t cfg = {};
    cfg.gridDim = dim3(NCTA); cfg.blockDim = dim3(NTHREADS); cfg.dynamicSmemBytes = SM_TOTAL; cfg.stream = cudaStreamPerThread;
    cudaLaunchAttribute at[1];
    at[0].id = cudaLaunchAttributeClusterDimension;
    at[0].val.clusterDim.x = 2; at[0].val.clusterDim.y = 1; at[0].val.clusterDim.z = 1;
    cfg.attrs = at; cfg.numAttrs = 1;
    cudaLaunchKernelEx(&cfg, fused_kernel, tx, tbr, tbi, tcr, tci, tcol, p);
}

}

extern "C" void kernel_launch(void* const* d_in, const int* in_sizes, int n_in, void* d_out, int out_size) {
    (void)in_sizes; (void)n_in; (void)out_size;
    launch_impl(d_in, d_out, 100);
}
```

```cpp
#include <cuda_runtime.h>
#include <cuda_bf16.h>
#include <cuda.h>
#include <stdint.h>

namespace {

constexpr int NCTA = 128;
constexpr int NTHREADS = 512;
constexpr int SM_A = 0;
constexpr int SM_X = 131072;
constexpr int SM_H = 196608;
constexpr int SM_HH = SM_X + 32768;
constexpr int SM_M = 229376;
constexpr int SM_TOTAL = 232448;
constexpr int SM_BAR = SM_M;
constexpr int SM_TGT = SM_M + 400;
constexpr int SM_LAM = SM_M + 424;
constexpr int SM_TAB = SM_M + 944;
constexpr int SM_RSTD = SM_M + 1920;
constexpr int SM_MEAN = SM_TAB;
constexpr int SM_T64 = SM_M + 2944;
constexpr int SM_B1ST = SM_H + 24576;
constexpr int SM_RAW = SM_X + 40960;
constexpr int SM_SSQ = SM_X + 57344;
constexpr int B_FULL0 = 0;
constexpr int B_EMPTY0 = 8;
constexpr int B_FULLC = 12;
constexpr int B_AFULL = 13;
constexpr int B_AEMPTY = 21;
constexpr int B_XFULL = 29;
constexpr int B_XEMPTY = 33;
constexpr int B_AFREE = 37;
constexpr int B_COL = 38;
constexpr int B_SSQ = 39;
constexpr int B_HPEER = 40;
constexpr int B_RFREE = 41;
constexpr int B_HDONE = 42;
constexpr int B_WRDY = 43;
constexpr int B_HPEER1 = 44;
constexpr int B_FULLB = 45;
constexpr int B_BFREE = 46;
constexpr int B_SETUP = 47;
constexpr int B_B1DONE = 48;
constexpr int B_WST = 49;
constexpr int NBARS = 50;

__device__ __align__(1024) uint8_t g_X[2 * 16 * 8 * 16384];
__device__ __align__(1024) uint8_t g_A1[8 * 8 * 16384];
__device__ __align__(1024) uint8_t g_A2[8 * 8 * 16384];
__device__ __align__(1024) uint8_t g_E[2 * 8 * 8 * 8192];
__device__ __align__(16) float g_ssq[2 * 2048];
__device__ __align__(16) float g_ssqc[2 * 16 * 2048];
__device__ __align__(16) float g_Dh[512];
__device__ __align__(16) uint4 g_Wfrag[128 * 4 * 256];
__device__ __align__(16) float4 g_Ebuf[2 * 16 * 512];
__device__ __align__(16) uint4 g_P[16 * 8 * 4 * 1024];
__device__ unsigned g_bar[8];
__device__ unsigned g_err;
#define TX(i)
#define TQ(i)
#define TS(i)
#define TC(i)

constexpr unsigned SPIN_LIMIT = 1u << 22;

__device__ __forceinline__ uint32_t s2u(const void* p) { return (uint32_t)__cvta_generic_to_shared(p); }
__device__ __forceinline__ void mbar_init(uint32_t a, uint32_t c) {
    asm volatile("mbarrier.init.shared::cta.b64 [%0], %1;" ::"r"(a), "r"(c) : "memory");
}
__device__ __forceinline__ void mbar_expect(uint32_t a, uint32_t bytes) {
    asm volatile("mbarrier.arrive.expect_tx.shared::cta.b64 _, [%0], %1;" ::"r"(a), "r"(bytes) : "memory");
}
__device__ __forceinline__ void mbar_arrive(uint32_t a, uint32_t cnt) {
    asm volatile("mbarrier.arrive.shared::cta.b64 _, [%0], %1;" ::"r"(a), "r"(cnt) : "memory");
}
__device__ __forceinline__ bool mbar_try(uint32_t a, uint32_t parity) {
    uint32_t ok;
    asm volatile("{\n.reg .pred p;\nmbarrier.try_wait.parity.shared::cta.b64 p, [%1], %2;\nselp.u32 %0, 1, 0, p;\n}"
                 : "=r"(ok) : "r"(a), "r"(parity) : "memory");
    return ok != 0;
}
__device__ __forceinline__ void mbar_wait(uint32_t a, uint32_t parity) {
    asm volatile("{\n.reg .pred p, q;\n.reg .u32 n;\nmov.u32 n, 0;\n"
                 "W_%=:\nmbarrier.try_wait.parity.shared::cta.b64 p, [%0], %1;\n@p bra D_%=;\n"
                 "add.u32 n, n, 1;\nsetp.lt.u32 q, n, 4194304;\n@q bra W_%=;\nD_%=:\n}" ::"r"(a), "r"(parity) : "memory");
}
__device__ __forceinline__ void bulk_g2s(uint32_t dst, const void* src, uint32_t bytes, uint32_t bar) {
    asm volatile("cp.async.bulk.shared::cluster.global.mbarrier::complete_tx::bytes [%0], [%1], %2, [%3];" ::"r"(dst),
                 "l"(src), "r"(bytes), "r"(bar) : "memory");
}
__device__ __forceinline__ void tma_2d(uint32_t dst, const CUtensorMap* m, int c0, int c1, uint32_t bar) {
    asm volatile("cp.async.bulk.tensor.2d.shared::cluster.global.mbarrier::complete_tx::bytes [%0], [%1, {%3,%4}], [%2];" ::"r"(dst),
                 "l"(m), "r"(bar), "r"(c0), "r"(c1) : "memory");
}
__device__ __forceinline__ void tma_5d(uint32_t dst, const CUtensorMap* m, int c0, int c1, int c2, int c3, int c4, uint32_t bar) {
    asm volatile("cp.async.bulk.tensor.5d.shared::cluster.global.mbarrier::complete_tx::bytes [%0], [%1, {%3,%4,%5,%6,%7}], [%2];" ::"r"(dst),
                 "l"(m), "r"(bar), "r"(c0), "r"(c1), "r"(c2), "r"(c3), "r"(c4) : "memory");
}
__device__ __forceinline__ void tma_2d_mc(uint32_t dst, const CUtensorMap* m, int c0, int c1, uint32_t bar) {
    asm volatile("cp.async.bulk.tensor.2d.shared::cluster.global.mbarrier::complete_tx::bytes.multicast::cluster [%0], [%1, {%3,%4}], [%2], %5;" ::"r"(dst),
                 "l"(m), "r"(bar), "r"(c0), "r"(c1), "h"((unsigned short)3) : "memory");
}
__device__ __forceinline__ void tma_5d_mc(uint32_t dst, const CUtensorMap* m, int c0, int c1, int c2, int c3, int c4, uint32_t bar) {
    asm volatile("cp.async.bulk.tensor.5d.shared::cluster.global.mbarrier::complete_tx::bytes.multicast::cluster [%0], [%1, {%3,%4,%5,%6,%7}], [%2], %8;" ::"r"(dst),
                 "l"(m), "r"(bar), "r"(c0), "r"(c1), "r"(c2), "r"(c3), "r"(c4), "h"((unsigned short)3) : "memory");
}
__device__ __forceinline__ void bulk_g2s_mc(uint32_t dst, const void* src, uint32_t bytes, uint32_t bar) {
    asm volatile("cp.async.bulk.shared::cluster.global.mbarrier::complete_tx::bytes.multicast::cluster [%0], [%1], %2, [%3], %4;" ::"r"(dst),
                 "l"(src), "r"(bytes), "r"(bar), "h"((unsigned short)3) : "memory");
}
__device__ __forceinline__ void tma_store_5d(const CUtensorMap* m, int c0, int c1, int c2, int c3, int c4, uint32_t src) {
    asm volatile("cp.async.bulk.tensor.5d.global.shared::cta.bulk_group [%0, {%2,%3,%4,%5,%6}], [%1];" ::"l"(m), "r"(src),
                 "r"(c0), "r"(c1), "r"(c2), "r"(c3), "r"(c4) : "memory");
}
__device__ __forceinline__ uint32_t lds32(uint32_t a) { uint32_t v; asm volatile("ld.shared.u32 %0, [%1];" : "=r"(v) : "r"(a) : "memory"); return v; }
__device__ __forceinline__ uint4 ld_relaxed_u4(const uint4* p) {
    uint4 v;
    asm volatile("ld.relaxed.gpu.global.v4.u32 {%0,%1,%2,%3}, [%4];" : "=r"(v.x), "=r"(v.y), "=r"(v.z), "=r"(v.w) : "l"(p) : "memory");
    return v;
}
__device__ __forceinline__ void fence_async() { asm volatile("fence.proxy.async.global;" ::: "memory"); }
__device__ __forceinline__ void red_relaxed(unsigned* p, unsigned v) {
    asm volatile("red.relaxed.gpu.global.add.u32 [%0], %1;" ::"l"(p), "r"(v) : "memory");
}
__device__ __forceinline__ uint32_t mapa(uint32_t a, uint32_t rank) {
    uint32_t d;
    asm("mapa.shared::cluster.u32 %0, %1, %2;" : "=r"(d) : "r"(a), "r"(rank));
    return d;
}
__device__ __forceinline__ void mbar_arrive_remote(uint32_t ra) {
    asm volatile("mbarrier.arrive.relaxed.cluster.shared::cluster.b64 _, [%0];" ::"r"(ra) : "memory");
}
__device__ __forceinline__ void mbar_wait_cluster(uint32_t a, uint32_t parity) {
    asm volatile("{\n.reg .pred p, q;\n.reg .u32 n;\nmov.u32 n, 0;\n"
                 "W_%=:\nmbarrier.try_wait.parity.acquire.cluster.shared::cta.b64 p, [%0], %1;\n@p bra D_%=;\n"
                 "add.u32 n, n, 1;\nsetp.lt.u32 q, n, 4194304;\n@q bra W_%=;\nD_%=:\n}" ::"r"(a), "r"(parity) : "memory");
}
__device__ __forceinline__ void bulk_s2peer(uint32_t rdst, uint32_t src, uint32_t bytes, uint32_t rbar) {
    asm volatile("cp.async.bulk.shared::cluster.shared::cta.mbarrier::complete_tx::bytes [%0], [%1], %2, [%3];" ::"r"(rdst),
                 "r"(src), "r"(bytes), "r"(rbar) : "memory");
}
__device__ __forceinline__ void fence_async_smem() { asm volatile("fence.proxy.async.shared::cta;" ::: "memory"); }
__device__ __forceinline__ void wg_fence() { asm volatile("wgmma.fence.sync.aligned;" ::: "memory"); }
__device__ __forceinline__ void wg_commit() { asm volatile("wgmma.commit_group.sync.aligned;" ::: "memory"); }
template <int N> __device__ __forceinline__ void wg_wait() { asm volatile("wgmma.wait_group.sync.aligned %0;" ::"n"(N) : "memory"); }
__device__ __forceinline__ void bar_sync(int id, int n) { asm volatile("bar.sync %0, %1;" ::"r"(id), "r"(n) : "memory"); }
__device__ __forceinline__ void bar_arrive(int id, int n) { asm volatile("bar.arrive %0, %1;" ::"r"(id), "r"(n) : "memory"); }
__device__ __forceinline__ unsigned ld_acquire(const unsigned* p) {
    unsigned v;
    asm volatile("ld.acquire.gpu.global.u32 %0, [%1];" : "=r"(v) : "l"(p) : "memory");
    return v;
}
__device__ __forceinline__ void red_release(unsigned* p, unsigned v) {
    asm volatile("red.release.gpu.global.add.u32 [%0], %1;" ::"l"(p), "r"(v) : "memory");
}
__device__ __forceinline__ void wait_count(const unsigned* p, unsigned target) {
    unsigned n = 0;
#pragma unroll 1
    while ((int)(ld_acquire(p) - target) < 0 && ++n < SPIN_LIMIT) {}
}
__device__ __forceinline__ float4 ld_relaxed_f4(const float4* p) {
    float4 v;
    asm volatile("ld.relaxed.gpu.global.v4.f32 {%0,%1,%2,%3}, [%4];" : "=f"(v.x), "=f"(v.y), "=f"(v.z), "=f"(v.w) : "l"(p) : "memory");
    return v;
}
__device__ __forceinline__ void st_relaxed_f4(float4* p, float4 v) {
    asm volatile("st.relaxed.gpu.global.v4.f32 [%0], {%1,%2,%3,%4};" ::"l"(p), "f"(v.x), "f"(v.y), "f"(v.z), "f"(v.w) : "memory");
}
__device__ __forceinline__ uint32_t pack_bf16(float lo, float hi) {
    uint32_t r;
    asm("cvt.rn.bf16x2.f32 %0, %1, %2;" : "=r"(r) : "f"(hi), "f"(lo));
    return r;
}
__device__ __forceinline__ uint32_t hmul2(uint32_t a, uint32_t b) {
    uint32_t r;
    asm("mul.rn.bf16x2 %0, %1, %2;" : "=r"(r) : "r"(a), "r"(b));
    return r;
}
__device__ __forceinline__ uint32_t hfma2(uint32_t a, uint32_t b, uint32_t c) {
    uint32_t r;
    asm("fma.rn.bf16x2 %0, %1, %2, %3;" : "=r"(r) : "r"(a), "r"(b), "r"(c));
    return r;
}
__device__ __forceinline__ float bf_lo(uint32_t v) { return __uint_as_float(v << 16); }
__device__ __forceinline__ float bf_hi(uint32_t v) { return __uint_as_float(v & 0xffff0000u); }
__device__ __forceinline__ void sts32(uint32_t a, uint32_t v) { asm volatile("st.shared.u32 [%0], %1;" ::"r"(a), "r"(v) : "memory"); }
__device__ __forceinline__ void sts128(uint32_t a, uint4 v) {
    asm volatile("st.shared.v4.u32 [%0], {%1,%2,%3,%4};" ::"r"(a), "r"(v.x), "r"(v.y), "r"(v.z), "r"(v.w) : "memory");
}

__device__ __forceinline__ uint64_t desc_ni(uint32_t addr, uint32_t lbo, uint32_t sbo) {
    return (uint64_t)((addr & 0x3FFFF) >> 4) | ((uint64_t)(lbo >> 4) << 16) | ((uint64_t)(sbo >> 4) << 32);
}
__device__ __forceinline__ uint64_t desc_a(uint32_t addr) { return desc_ni(addr, 128, 1024); }
template <int N> __device__ __forceinline__ uint64_t desc_b(uint32_t addr) { return desc_ni(addr, 16 * N, 128); }
__device__ __forceinline__ uint64_t desc_k(uint32_t addr) {
    return (uint64_t)((addr & 0x3FFFF) >> 4) | (1ull << 16) | (64ull << 32) | (1ull << 62);
}
__device__ __forceinline__ uint64_t desc_mn(uint32_t addr, uint32_t lbo) {
    return (uint64_t)((addr & 0x3FFFF) >> 4) | ((uint64_t)(lbo >> 4) << 16) | (64ull << 32) | (1ull << 62);
}

#define ACC8(d, o) "+f"(d[o + 0]), "+f"(d[o + 1]), "+f"(d[o + 2]), "+f"(d[o + 3]), "+f"(d[o + 4]), "+f"(d[o + 5]), "+f"(d[o + 6]), "+f"(d[o + 7])
template <int TB, int SA = 1>
__device__ __forceinline__ void wgmma_n128(float (&d)[64], uint64_t da, uint64_t db, int sd) {
    asm volatile(
        "{\n.reg .pred p;\nsetp.ne.b32 p, %66, 0;\n"
        "wgmma.mma_async.sync.aligned.m64n128k16.f32.bf16.bf16 "
        "{%0,%1,%2,%3,%4,%5,%6,%7,%8,%9,%10,%11,%12,%13,%14,%15,%16,%17,%18,%19,%20,%21,%22,%23,%24,%25,%26,%27,%28,%29,%30,%31,"
        "%32,%33,%34,%35,%36,%37,%38,%39,%40,%41,%42,%43,%44,%45,%46,%47,%48,%49,%50,%51,%52,%53,%54,%55,%56,%57,%58,%59,%60,%61,%62,%63},"
        " %64, %65, p, %68, 1, 0, %67;\n}"
        : ACC8(d, 0), ACC8(d, 8), ACC8(d, 16), ACC8(d, 24), ACC8(d, 32), ACC8(d, 40), ACC8(d, 48), ACC8(d, 56)
        : "l"(da), "l"(db), "r"(sd), "n"(TB), "n"(SA));
}
template <int N> __device__ __forceinline__ void acc_def(float (&d)[N]) {
#pragma unroll
    for (int i = 0; i < N; i++) d[i] = 0.f;
}
template <int TB>
__device__ __forceinline__ void wgmma_n64(float (&d)[32], uint64_t da, uint64_t db, int sd) {
    asm volatile(
        "{\n.reg .pred p;\nsetp.ne.b32 p, %34, 0;\n"
        "wgmma.mma_async.sync.aligned.m64n64k16.f32.bf16.bf16 "
        "{%0,%1,%2,%3,%4,%5,%6,%7,%8,%9,%10,%11,%12,%13,%14,%15,%16,%17,%18,%19,%20,%21,%22,%23,%24,%25,%26,%27,%28,%29,%30,%31},"
        " %32, %33, p, 1, 1, 0, %35;\n}"
        : ACC8(d, 0), ACC8(d, 8), ACC8(d, 16), ACC8(d, 24)
        : "l"(da), "l"(db), "r"(sd), "n"(TB));
}
template <int SA>
__device__ __forceinline__ void wgmma_n64s(float (&d)[32], uint64_t da, uint64_t db, int sd) {
    asm volatile(
        "{\n.reg .pred p;\nsetp.ne.b32 p, %34, 0;\n"
        "wgmma.mma_async.sync.aligned.m64n64k16.f32.bf16.bf16 "
        "{%0,%1,%2,%3,%4,%5,%6,%7,%8,%9,%10,%11,%12,%13,%14,%15,%16,%17,%18,%19,%20,%21,%22,%23,%24,%25,%26,%27,%28,%29,%30,%31},"
        " %32, %33, p, %35, 1, 0, 1;\n}"
        : ACC8(d, 0), ACC8(d, 8), ACC8(d, 16), ACC8(d, 24)
        : "l"(da), "l"(db), "r"(sd), "n"(SA));
}
__device__ __forceinline__ void wgmma_n64_rs(float (&d)[32], uint32_t a0, uint32_t a1, uint32_t a2, uint32_t a3, uint64_t db, int sd) {
    asm volatile(
        "{\n.reg .pred p;\nsetp.ne.b32 p, %37, 0;\n"
        "wgmma.mma_async.sync.aligned.m64n64k16.f32.bf16.bf16 "
        "{%0,%1,%2,%3,%4,%5,%6,%7,%8,%9,%10,%11,%12,%13,%14,%15,%16,%17,%18,%19,%20,%21,%22,%23,%24,%25,%26,%27,%28,%29,%30,%31},"
        " {%32,%33,%34,%35}, %36, p, 1, 1, 1;\n}"
        : ACC8(d, 0), ACC8(d, 8), ACC8(d, 16), ACC8(d, 24)
        : "r"(a0), "r"(a1), "r"(a2), "r"(a3), "l"(db), "r"(sd));
}

struct Params {
    const __nv_bfloat16* x0;
    const __nv_bfloat16* w_r;
    const __nv_bfloat16* w_i;
    const __nv_bfloat16* lam_re;
    const __nv_bfloat16* lam_im;
    const __nv_bfloat16* log_dt;
    const __nv_bfloat16* dskip;
    float* out;
    int stop;
};

__device__ __forceinline__ float ldbf(const __nv_bfloat16* p) { return __bfloat162float(*p); }

__device__ __forceinline__ void dft_fp(int j, int& f, int& ph) {
    int cs = j >> 1;
    if (j == 1) { f = 256; ph = 0; }
    else { f = cs; ph = (j & 1) ? 128 : 0; }
}

__device__ __forceinline__ void gen_col_consts(uint32_t sb, int tid) {
#pragma unroll 1
    for (int task = tid; task < 640; task += 256) {
        int f, c8;
        uint32_t a_cc, d_pi, d_po;
        if (task < 512) {
            f = task & 63; c8 = task >> 6;
            a_cc = sb + SM_X + (f >> 5) * 16384 + ((f >> 3) & 3) * 2048 + c8 * 128 + (f & 7) * 16;
            d_pi = 8192; d_po = 1024;
        } else {
            int n2 = task & 31;
            f = 2 * n2; c8 = (task >> 5) & 3;
            a_cc = sb + SM_X + 32768 + (n2 >> 3) * 1024 + c8 * 128 + (n2 & 7) * 16;
            d_pi = 4096; d_po = 512;
        }
        float cd, sd, cs, sn;
        __sincosf((float)(f >= 32 ? f - 64 : f) * (6.283185307179586f / 64.f), &sd, &cd);
        int a = (8 * c8 * f) & 63;
        __sincosf((float)(a >= 32 ? a - 64 : a) * (6.283185307179586f / 64.f), &sn, &cs);
        float cv[8], sv[8];
#pragma unroll
        for (int e = 0; e < 8; e++) {
            cv[e] = cs; sv[e] = sn;
            float t = cs * cd - sn * sd;
            sn = sn * cd + cs * sd;
            cs = t;
        }
        uint4 oc = make_uint4(pack_bf16(cv[0], cv[1]), pack_bf16(cv[2], cv[3]), pack_bf16(cv[4], cv[5]), pack_bf16(cv[6], cv[7]));
        uint4 os = make_uint4(pack_bf16(sv[0], sv[1]), pack_bf16(sv[2], sv[3]), pack_bf16(sv[4], sv[5]), pack_bf16(sv[6], sv[7]));
        sts128(a_cc, oc);
        sts128(a_cc + d_pi, os);
        sts128(a_cc + d_po, make_uint4(os.x ^ 0x80008000u, os.y ^ 0x80008000u, os.z ^ 0x80008000u, os.w ^ 0x80008000u));
        sts128(a_cc + d_pi + d_po, oc);
    }
}

__global__ void __launch_bounds__(NTHREADS, 1)
fused_kernel(const __grid_constant__ CUtensorMap tm_x, const __grid_constant__ CUtensorMap tm_bre,
             const __grid_constant__ CUtensorMap tm_bim, const __grid_constant__ CUtensorMap tm_cre,
             const __grid_constant__ CUtensorMap tm_cim, const __grid_constant__ CUtensorMap tm_col, const Params p) {
    extern __shared__ __align__(1024) uint8_t sm[];
    const uint32_t sb = s2u(sm);
    const int tid = threadIdx.x, b = blockIdx.x;
    const int c = b >> 3, r = b & 7;
    const int par = r & 1, pi_ = r >> 1, own = 4 * par + pi_;
    const int wg = __shfl_sync(~0u, tid >> 7, 0), w = __shfl_sync(~0u, (tid >> 5) & 3, 0), lane = tid & 31, g = lane >> 2, q = lane & 3;
    auto BAR = [&](int i) { return sb + SM_BAR + 8 * i; };
    unsigned* s_tgt = (unsigned*)(sm + SM_TGT);

    if (tid < NBARS) {
        int cnt = 1;
        if (tid >= B_EMPTY0 && tid < B_EMPTY0 + 4) cnt = 16;
        if (tid >= B_XEMPTY && tid < B_XEMPTY + 4) cnt = 24;
        if (tid == B_RFREE) cnt = 12;
        if (tid == B_HDONE || tid == B_WST) cnt = 2;
        if ((tid >= B_AEMPTY && tid < B_AEMPTY + 8) || tid == B_BFREE) cnt = 8;
        if (tid == B_AFREE) cnt = 4;
        mbar_init(BAR(tid), cnt);
        asm volatile("fence.mbarrier_init.release.cluster;" ::: "memory");
    }
    asm volatile("barrier.cluster.arrive.release.aligned;" ::: "memory");

    if (wg == 3) {
        asm volatile("setmaxnreg.dec.sync.aligned.u32 56;");
        if (w == 0 && lane < 6) {
            const CUtensorMap* tm = lane == 0 ? &tm_x : lane == 1 ? &tm_bre : lane == 2 ? &tm_bim : lane == 3 ? &tm_cre : lane == 4 ? &tm_cim : &tm_col;
            asm volatile("prefetch.tensormap [%0];" ::"l"(tm) : "memory");
        }
        __syncwarp();
        asm volatile("barrier.cluster.wait.acquire.aligned;" ::: "memory");
        if (w > 0) {
            if (w == 1) {
                float lr[3], li[3], ld[3];
#pragma unroll
                for (int k = 0; k < 3; k++) {
                    int ps = k < 2 ? 64 * r + 32 * k + lane : 32 * c + lane;
                    lr[k] = ldbf(p.lam_re + ps); li[k] = ldbf(p.lam_im + ps); ld[k] = ldbf(p.log_dt + ps);
                }
                if (lane < 6) s_tgt[lane] = ((ld_acquire(&g_bar[lane]) >> 7) + 1u) << 7;
#pragma unroll 1
                for (int k = 0; k < 3; k++) {
                    float a = k == 0 ? lr[0] : (k == 1 ? lr[1] : lr[2]), bq = k == 0 ? li[0] : (k == 1 ? li[1] : li[2]);
                    float dt = __bfloat162float(__float2bfloat16(expf(k == 0 ? ld[0] : (k == 1 ? ld[1] : ld[2]))));
                    float mag = expf(a * dt), t = bq * dt * 0.15915494309189535f, sn, cs;
                    t -= rintf(t);
                    sincospif(2.f * t, &sn, &cs);
                    float er = mag * cs, ei = mag * sn;
                    if (k < 2) {
                        *(float2*)(sm + SM_LAM + (32 * k + lane) * 8) = make_float2(er, ei);
                    } else {
                        er -= 1.f;
                        float inv = 1.f / (a * a + bq * bq);
                        *(float2*)(sm + SM_TAB + lane * 8) = make_float2((er * a + ei * bq) * inv, (ei * a - er * bq) * inv);
                    }
                }
                __syncwarp();
                bar_arrive(15, 160);
                if (lane == 0) mbar_arrive(BAR(B_SETUP), 1);
            }
            if (w == 2) {
                const int kq = 2 * b + (lane >> 4), row = (kq >> 2) + 128 * (kq & 3) + 512 * ((lane >> 1) & 3) + 64 * (lane & 1);
                const char* src = (const char*)(((lane >> 3) & 1) ? p.w_i : p.w_r) + (size_t)row * 514;
                size_t a0 = (size_t)src & ~(size_t)15;
                int bytes = row == 2047 ? 512 : 544;
                asm volatile("cp.async.bulk.prefetch.L2.global [%0], %1;" ::"l"(a0), "r"(bytes) : "memory");
            }
#pragma unroll 1
            for (int task = tid - 448; task < 256 && w > 1; task += 64) {
                const int cb = task & 127, kq = 2 * b + (task >> 7), k1 = kq >> 2, qq = kq & 3;
                const unsigned short* wr_ = (const unsigned short*)p.w_r + (k1 + 128 * qq) * 257;
                const unsigned short* wi_ = (const unsigned short*)p.w_i + (k1 + 128 * qq) * 257;
                const int c0 = cb == 0 ? 256 : 2 * cb, c1 = 2 * cb + 1;
                uint32_t wf[16];
#pragma unroll
                for (int i = 0; i < 4; i++) {
                    int o = 512 * i * 257;
                    wf[2 * i] = (uint32_t)__ldg(wr_ + o + c0) | ((uint32_t)__ldg(wr_ + o + 64 * 257 + c0) << 16);
                    wf[2 * i + 1] = ((uint32_t)__ldg(wi_ + o + c0) | ((uint32_t)__ldg(wi_ + o + 64 * 257 + c0) << 16)) ^ 0x80008000u;
                    wf[8 + 2 * i] = (uint32_t)__ldg(wr_ + o + c1) | ((uint32_t)__ldg(wr_ + o + 64 * 257 + c1) << 16);
                    wf[8 + 2 * i + 1] = ((uint32_t)__ldg(wi_ + o + c1) | ((uint32_t)__ldg(wi_ + o + 64 * 257 + c1) << 16)) ^ 0x80008000u;
                }
#pragma unroll
                for (int i = 0; i < 4; i++)
                    sts128(sb + SM_H + cb * 128 + (task >> 7) * 64 + ((i ^ (b & 3)) << 4), make_uint4(wf[4 * i], wf[4 * i + 1], wf[4 * i + 2], wf[4 * i + 3]));
            }
            if (w > 1) {
                fence_async_smem();
#pragma unroll
                for (int k = 0; k < 2; k++) {
                    const int cb = tid - 448 + 64 * k;
                    asm volatile("cp.async.bulk.global.shared::cta.bulk_group [%0], [%1], 128;" ::"l"(g_Wfrag + (uint32_t)(cb * 1024 + b * 8)),
                                 "r"(sb + SM_H + cb * 128) : "memory");
                }
                asm volatile("cp.async.bulk.commit_group;" ::: "memory");
                asm volatile("cp.async.bulk.wait_group 0;" ::: "memory");
                fence_async();
                __syncwarp();
                if (lane == 0) mbar_arrive(BAR(B_WST), 1);
            }
#pragma unroll 1
            for (int i = tid - 448; i < 96 + 128 && w > 1; i += 64) {
                if (i < 96) g_P[(uint32_t)(b * 4 + i / 24) * 1024 + 640 + ((i % 24) >> 1) * 32 + 30 + (i & 1)] = make_uint4(0, 0, 0, 0);
                else g_Ebuf[b * 128 + i - 96] = make_float4(0.f, 0.f, 0.f, 0.f);
            }
            __syncwarp();
            if (w == 3) bar_arrive(11, 192);
            if (w == 2) {
                bar_sync(11, 192);
                if (lane == 0) red_release(&g_bar[4], 1);
            }
            if (w == 3) {
#pragma unroll 1
                for (int it = 0; it < 8; it++) {
                    const int m = 4 * c + (it >> 1), d = 64 * r + m, ch = lane + 32 * (it & 1);
                    float v[8];
#pragma unroll
                    for (int e = 0; e < 8; e++) {
                        int j = 8 * ch + e, f, ph;
                        dft_fp(j, f, ph);
                        int a = (d * f + ph) & 511;
                        a = a >= 256 ? a - 512 : a;
                        float wj = j == 0 ? 0.f : (j == 1 ? 1.f / 512.f : 2.f / 512.f);
                        v[e] = wj * __cosf((float)a * (6.283185307179586f / 512.f));
                    }
                    uint32_t off = (uint32_t)(64 + r * 8 + (ch >> 3)) * 8192 + (m >> 3) * 1024 + (ch & 7) * 128 + (m & 7) * 16;
                    *(uint4*)(g_E + off) = make_uint4(pack_bf16(v[0], v[1]), pack_bf16(v[2], v[3]), pack_bf16(v[4], v[5]), pack_bf16(v[6], v[7]));
                }
                __syncwarp();
                if (lane == 0) { fence_async(); red_release(&g_bar[6], 1); }
                return;
            }
            if (w == 2) {
#pragma unroll 1
                for (int it = 0; it < 4; it++) {
                    const int hf = it & 1;
                    __syncwarp();
                    if (hf == 0) bar_sync(13, 288); else bar_sync(6, 416);
                    if (lane == 0) {
                        const uint32_t src = sb + SM_HH + par * 32768 + hf * 16384;
                        bulk_s2peer(mapa(src, par ^ 1), src, 16384, mapa(BAR(hf ? B_HPEER1 : B_HPEER), par ^ 1));
                    }
                }
                return;
            }
            bar_sync(2, 288);
            if (lane == 0) {
                TX(5);
                fence_async();
                red_release(&g_bar[0], 1);
                TX(6);
            }
            __syncwarp();

            bar_sync(12, 160);
            if (lane == 0) {
                asm volatile("cp.async.bulk.global.shared::cta.bulk_group [%0], [%1], 8192;" ::"l"(g_A1 + (uint32_t)(((c >> 1) * 8 + r) * 16384 + (c & 1) * 8192)),
                             "r"(sb + SM_B1ST) : "memory");
                asm volatile("cp.async.bulk.commit_group;" ::: "memory");
                asm volatile("cp.async.bulk.wait_group 0;" ::: "memory");
                mbar_arrive(BAR(B_B1DONE), 1);
                fence_async();
                red_release(&g_bar[7], 1);
            }
#pragma unroll 1
            for (int layer = 0; layer < 2; layer++) {
                __syncwarp();
                bar_sync(5, 416);
                if (lane == 0) {
                    TX(0 + 8 * layer);
                    tma_store_5d(&tm_col, 32 * (b & 1), 0, b >> 1, 0, layer, sb + SM_RAW);
                    asm volatile("cp.reduce.async.bulk.global.shared::cta.bulk_group.add.f32 [%0], [%1], 8192;" ::"l"(g_ssqc + (layer * 16 + (b & 15)) * 2048),
                                 "r"(sb + SM_SSQ) : "memory");
                    asm volatile("cp.async.bulk.commit_group;" ::: "memory");
                    asm volatile("cp.async.bulk.wait_group 0;" ::: "memory");
                    TX(1 + 8 * layer);
                    fence_async();
                    red_release(&g_bar[1 + 2 * layer], 1);
                    TX(2 + 8 * layer);
                }
            }
        } else if (tid == 384) {
#pragma unroll 1
            for (int kb = 0; kb < 8; kb++) {
                uint32_t fb = BAR(B_FULL0 + kb);
                mbar_expect(fb, 16384);
                tma_5d_mc(sb + SM_A + 65536 + kb * 16384 + par * 8192, &tm_x, kb * 64, 0, 0, 8 * par, c, fb);
            }
#pragma unroll 1
            for (int k2 = 0; k2 < 8; k2++) {
                asm volatile("cp.async.bulk.prefetch.tensor.2d.L2.global [%0, {%1,%2}];" ::"l"(par ? &tm_bim : &tm_bre), "r"(k2 * 64), "r"(32 * c) : "memory");
                if ((k2 & 1) == par)
                    asm volatile("cp.async.bulk.prefetch.tensor.2d.L2.global [%0, {%1,%2}];" ::"l"((c & 1) ? &tm_cim : &tm_cre), "r"(64 * (c >> 1)), "r"(k2 * 64) : "memory");
            }
            mbar_wait(BAR(B_SETUP), 0);
#pragma unroll 1
            for (int layer = 0; layer < 2; layer++) {
                if (layer == 1) {
                    mbar_wait(BAR(B_AEMPTY + 6), 1);
                    mbar_expect(BAR(B_WRDY), 16384);
                    bulk_g2s(sb + SM_H + 16384, g_Wfrag + (uint32_t)b * 1024, 16384, BAR(B_WRDY));
                }
                wait_count(&g_bar[2 * layer], s_tgt[2 * layer]);
                TX(4 + 8 * layer);
                fence_async();
                mbar_expect(BAR(B_COL), 16384 + 8192);
                tma_5d(sb + SM_RAW, &tm_col, 32 * (b & 1), 0, b >> 1, 0, layer, BAR(B_COL));
                bulk_g2s(sb + SM_SSQ, g_ssq + layer * 2048, 8192, BAR(B_COL));
                if (layer == 0) {
                    wait_count(&g_bar[4], s_tgt[4]);
                    fence_async();
                    mbar_wait(BAR(B_B1DONE), 0);
                    mbar_expect(BAR(B_WRDY), 16384);
                    bulk_g2s(sb + SM_H + 16384, g_Wfrag + (uint32_t)b * 1024, 16384, BAR(B_WRDY));
                    wait_count(&g_bar[7], s_tgt[4]);
                    fence_async();
                }
                if (layer == 0) mbar_wait(BAR(B_AFREE), 0);
                mbar_wait(BAR(B_COL), layer);
#pragma unroll 1
                for (int s = 0; s < 8; s++) {
                    if (layer == 1) mbar_wait(BAR(B_AEMPTY + s), 1);
                    if (s >= 2) mbar_wait(BAR(B_AFULL + s - 2), 0);
                    mbar_expect(BAR(B_AFULL + s), 16384);
                    bulk_g2s(sb + SM_A + s * 16384, g_A1 + (uint32_t)(r * 8 + s) * 16384, 16384, BAR(B_AFULL + s));
                }
                if (layer == 1) wait_count(&g_bar[6], s_tgt[4]);
                wait_count(&g_bar[1 + 2 * layer], s_tgt[1 + 2 * layer]);
                TX(3 + 8 * layer);
                fence_async();
                const uint8_t* xsrc = g_X + (uint32_t)(layer * 16 + c) * 8 * 16384;
                const uint8_t* esrc = g_E + (uint32_t)(layer * 8 + own) * 8 * 8192;
                mbar_arrive(BAR(B_SSQ), 1);
                mbar_expect(BAR(B_HPEER), 16384);
                mbar_expect(BAR(B_HPEER1), 16384);
#pragma unroll 1
                for (int it = 0; it < 16; it++) {
                    if (it < 8) {
                        int st = it & 3, f = layer * 2 + (it >> 2);
                        if (f > 0) mbar_wait_cluster(BAR(B_XEMPTY + st), (f - 1) & 1);
                        mbar_expect(BAR(B_XFULL + st), 24576);
                        bulk_g2s_mc(sb + SM_X + st * 24576 + par * 8192, xsrc + (uint32_t)it * 16384 + par * 8192, 8192, BAR(B_XFULL + st));
                        bulk_g2s(sb + SM_X + st * 24576 + 16384, esrc + (uint32_t)it * 8192, 8192, BAR(B_XFULL + st));
                    }
                    if (it >= 8) {
                        if (it == 8) mbar_wait(BAR(B_AEMPTY + 5), 0);
                        int s = it - 8, tile = 4 * par + ((pi_ + 1 + (s >> 1)) & 3), sl = r ^ (s & 1);
                        mbar_wait(BAR(B_AEMPTY + s), 0);
                        uint32_t fb = BAR(B_AFULL + s), dst = sb + SM_A + s * 16384;
                        mbar_expect(fb, 16384);
                        if (layer == 1) {
                            tma_2d(dst, &tm_cre, 64 * sl, 64 * tile, fb);
                            tma_2d(dst + 8192, &tm_cim, 64 * sl, 64 * tile, fb);
                        } else {
                            bulk_g2s(dst, g_A2 + (uint32_t)(sl * 8 + tile) * 16384, 16384, fb);
                        }
                    }
                }
            }
        }
        return;
    }

    asm volatile("setmaxnreg.inc.sync.aligned.u32 152;");
    if (tid >= 96 && tid < 112) g_ssq[2048 + 16 * b + tid - 96] = 0.f;
    if (tid >= 128 && tid < 256) ((float4*)g_ssqc)[b * 128 + tid - 128] = make_float4(0.f, 0.f, 0.f, 0.f);
    TS(0);
    if (wg == 0) TC(30);
    {
        const int f = 32 * r + lane;
        float cd, sd;
        __sincosf((float)f * (6.283185307179586f / 512.f), &sd, &cd);
        const uint32_t dst = sb + SM_A + (lane >> 2) * 1024 + (lane & 3) * 32;
#pragma unroll 1
        for (int ch = tid >> 5; ch < 64; ch += 12) {
            int a = (8 * ch * f) & 511;
            a = a >= 256 ? a - 512 : a;
            float cs, sn;
            __sincosf((float)a * (6.283185307179586f / 512.f), &sn, &cs);
            float cv[8], sv[8];
#pragma unroll
            for (int e = 0; e < 8; e++) {
                cv[e] = cs; sv[e] = -sn;
                float t = cs * cd - sn * sd;
                sn = sn * cd + cs * sd;
                cs = t;
            }
            uint4 o1 = make_uint4(pack_bf16(sv[0], sv[1]), pack_bf16(sv[2], sv[3]), pack_bf16(sv[4], sv[5]), pack_bf16(sv[6], sv[7]));
            if (f == 0) o1 = make_uint4(0xbf803f80u, 0xbf803f80u, 0xbf803f80u, 0xbf803f80u);
            uint32_t a0 = dst + (ch >> 3) * 8192 + (ch & 7) * 128;
            sts128(a0, make_uint4(pack_bf16(cv[0], cv[1]), pack_bf16(cv[2], cv[3]), pack_bf16(cv[4], cv[5]), pack_bf16(cv[6], cv[7])));
            sts128(a0 + 16, o1);
        }
    }
    fence_async_smem();
    asm volatile("barrier.cluster.wait.acquire.aligned;" ::: "memory");
    bar_sync(10, 384);
    TS(1);
    if (wg < 2) {
        float acc[32];
        acc_def(acc);
        const int npos = 16 * r + 8 * wg + 2 * w;
        float sh0 = 0.f, sh1 = 0.f, s0 = 0.f, s1 = 0.f, q0 = 0.f, q1 = 0.f;
#pragma unroll 1
        for (int kb = 0; kb < 8; kb++) {
            uint32_t slot = sb + SM_A + 65536 + kb * 16384;
            mbar_wait(BAR(B_FULL0 + kb), 0);
            wg_fence();
#pragma unroll
            for (int ks = 0; ks < 4; ks++)
                wgmma_n64<0>(acc, desc_a(sb + SM_A + kb * 8192 + ks * 256), desc_k(slot + wg * 8192 + ks * 32), 1);
            wg_commit();
            {
                uint32_t v0 = lds32(slot + npos * 128 + lane * 4), v1 = lds32(slot + npos * 128 + 128 + lane * 4);
                if (kb == 0) { sh0 = __shfl_sync(~0u, bf_lo(v0), 0); sh1 = __shfl_sync(~0u, bf_lo(v1), 0); }
                float a = bf_lo(v0) - sh0, bq = bf_hi(v0) - sh0, cq = bf_lo(v1) - sh1, d = bf_hi(v1) - sh1;
                s0 += a + bq; q0 += a * a + bq * bq; s1 += cq + d; q1 += cq * cq + d * d;
            }
            wg_wait<1>();
            if (kb > 0 && kb <= 4 && lane == 0) { mbar_arrive(BAR(B_EMPTY0 + kb - 1), 1); mbar_arrive_remote(mapa(BAR(B_EMPTY0 + kb - 1), par ^ 1)); }
        }
#pragma unroll
        for (int o = 16; o; o >>= 1) {
            s0 += __shfl_xor_sync(~0u, s0, o); q0 += __shfl_xor_sync(~0u, q0, o);
            s1 += __shfl_xor_sync(~0u, s1, o); q1 += __shfl_xor_sync(~0u, q1, o);
        }
        if (lane == 0) *(float2*)(g_ssq + 128 * c + npos) = make_float2(fmaxf(q0 - s0 * s0 * (1.f / 512.f), 0.f), fmaxf(q1 - s1 * s1 * (1.f / 512.f), 0.f));
        wg_wait<0>();
        TS(2);
        uint8_t* dst = g_X + (uint32_t)((c * 8 + r) * 16384 + w * 4096 + wg * 1024 + g * 16 + 4 * q);
#pragma unroll
        for (int i = 0; i < 8; i++) {
            *(uint32_t*)(dst + i * 128) = pack_bf16(acc[4 * i], acc[4 * i + 1]);
            *(uint32_t*)(dst + 2048 + i * 128) = pack_bf16(acc[4 * i + 2], acc[4 * i + 3]);
        }
        bar_sync(2, 288);
        mbar_wait(BAR(B_SETUP), 0);
        TS(3);
    }

    if (wg == 2) {
        {
            uint4 p0 = __ldg((const uint4*)p.dskip + 2 * lane), p1 = __ldg((const uint4*)p.dskip + 2 * lane + 1);
            uint32_t u[8] = {p0.x, p0.y, p0.z, p0.w, p1.x, p1.y, p1.z, p1.w};
            int j = 64 * r + 4 * c + w, f, ph;
            dft_fp(j, f, ph);
            float s = 0.f;
            int idx = 16 * lane * f + ph;
#pragma unroll
            for (int i = 0; i < 16; i++) {
                int a = idx & 511;
                idx += f;
                a = a >= 256 ? a - 512 : a;
                s += ((i & 1) ? bf_hi(u[i >> 1]) : bf_lo(u[i >> 1])) * __cosf((float)a * (6.283185307179586f / 512.f));
            }
#pragma unroll
            for (int o = 16; o; o >>= 1) s += __shfl_xor_sync(~0u, s, o);
            if (lane == 0) g_Dh[j] = s;
            bar_arrive(11, 192);
        }
        bar_sync(15, 160);
        float acc[32];
        acc_def(acc);
        if (tid == 256) {
#pragma unroll 1
            for (int s = 0; s < 4; s++) mbar_wait_cluster(BAR(B_EMPTY0 + s), 0);
            mbar_expect(BAR(B_FULLB), 65536);
#pragma unroll 1
            for (int k2 = 0; k2 < 8; k2++)
                tma_2d_mc(sb + SM_A + 65536 + k2 * 8192 + par * 4096, par ? &tm_bim : &tm_bre, k2 * 64, 32 * c, BAR(B_FULLB));
        }
        __syncwarp();
        mbar_wait(BAR(B_FULLB), 0);
        wg_fence();
#pragma unroll 1
        for (int kb = 0; kb < 8; kb++) {
#pragma unroll
            for (int ks = 0; ks < 4; ks++)
                wgmma_n64<0>(acc, desc_a(sb + SM_A + kb * 8192 + ks * 256), desc_k(sb + SM_A + 65536 + kb * 8192 + ks * 32), 1);
            wg_commit();
        }
        wg_wait<0>();
        if (lane == 0) { mbar_arrive(BAR(B_BFREE), 1); mbar_arrive_remote(mapa(BAR(B_BFREE), par ^ 1)); }
        if (tid == 256) {
            mbar_wait_cluster(BAR(B_BFREE), 0);
            mbar_expect(BAR(B_FULLC), 65536);
#pragma unroll 1
            for (int k2 = par; k2 < 8; k2 += 2)
                tma_2d_mc(sb + SM_A + 65536 + k2 * 8192, (c & 1) ? &tm_cim : &tm_cre, 64 * (c >> 1), k2 * 64, BAR(B_FULLC));
        }
        __syncwarp();
        {
            uint8_t* dst = sm + SM_B1ST + w * 256 + q * 32 + g * 2;
            const float wj0 = (r == 0 && w == 0 && g < 2) ? (g == 0 ? 0.f : 1.f / 512.f) : 2.f / 512.f;
#pragma unroll
            for (int i = 0; i < 4; i++) {
#pragma unroll
                for (int e = 0; e < 2; e++) {
                    float2 cf = *(const float2*)(sm + SM_TAB + (8 * i + 2 * q + e) * 8);
#pragma unroll
                    for (int h = 0; h < 2; h++) {
                        float wj = h == 0 ? wj0 : 2.f / 512.f;
                        float pr = acc[4 * i + 2 * h + e] * wj, pi = acc[16 + 4 * i + 2 * h + e] * wj;
                        uint8_t* d2 = dst + i * 2048 + h * 128 + e * 16;
                        *(__nv_bfloat16*)(d2) = __float2bfloat16(cf.x * pr - cf.y * pi);
                        *(__nv_bfloat16*)(d2 + 1024) = __float2bfloat16(cf.x * pi + cf.y * pr);
                    }
                }
            }
            fence_async_smem();
            bar_arrive(12, 160);
        }
        acc_def(acc);
        mbar_wait(BAR(B_FULLC), 0);
        wg_fence();
#pragma unroll 1
        for (int kb = 0; kb < 8; kb++) {
#pragma unroll
            for (int ks = 0; ks < 4; ks++)
                wgmma_n64<1>(acc, desc_a(sb + SM_A + kb * 8192 + ks * 256), desc_mn(sb + SM_A + 65536 + kb * 8192 + ks * 2048, 8192), 1);
            wg_commit();
        }
        wg_wait<0>();
        fence_async_smem();
        if (lane == 0) mbar_arrive(BAR(B_AFREE), 1);
        uint8_t* dst = g_A2 + (uint32_t)(((c >> 1) * 8 + r) * 16384 + (c & 1) * 8192 + w * 2048 + g * 16 + 4 * q);
#pragma unroll
        for (int i = 0; i < 8; i++) {
            *(uint32_t*)(dst + i * 128) = pack_bf16(acc[4 * i], acc[4 * i + 1]);
            *(uint32_t*)(dst + 1024 + i * 128) = pack_bf16(acc[4 * i + 2], acc[4 * i + 3]);
        }
        {
            const int m = 4 * c + w, jp = 64 * r + m;
            int fp, php;
            dft_fp(jp, fp, php);
            const __nv_bfloat16* dh = (const __nv_bfloat16*)(sm + SM_RSTD);
            if (tid == 256) wait_count(&g_bar[4], s_tgt[4]);
            bar_sync(3, 128);
            float4 d4 = __ldcg((const float4*)g_Dh + (tid - 256));
            *(uint2*)(sm + SM_RSTD + (tid - 256) * 8) = make_uint2(pack_bf16(d4.x, d4.y), pack_bf16(d4.z, d4.w));
            bar_sync(3, 128);
#pragma unroll 1
            for (int it = 0; it < 2; it++) {
                const int ch = lane + 32 * it;
                float v[8];
#pragma unroll
                for (int e = 0; e < 8; e++) {
                    int j = 8 * ch + e, f, ph;
                    dft_fp(j, f, ph);
                    float wj = j == 0 ? 0.f : (j == 1 ? 1.f / 512.f : 2.f / 512.f);
                    float gsum = 0.f;
#pragma unroll
                    for (int sgn = 0; sgn < 2; sgn++) {
                        int mm = (sgn ? f - fp : f + fp) & 511, pp = (sgn ? ph - php : ph + php) & 511;
                        if (mm > 256) { mm = 512 - mm; pp = (512 - pp) & 511; }
                        int odd = (pp >> 7) & 1;
                        float t = __bfloat162float(dh[mm == 256 ? 1 : 2 * mm + odd]);
                        if (odd && (mm & 255) == 0) t = 0.f;
                        gsum += (pp & 256) ? -t : t;
                    }
                    v[e] = 0.5f * wj * gsum;
                }
                uint32_t off = (uint32_t)(r * 8 + (ch >> 3)) * 8192 + (m >> 3) * 1024 + (ch & 7) * 128 + (m & 7) * 16;
                *(uint4*)(g_E + off) = make_uint4(pack_bf16(v[0], v[1]), pack_bf16(v[2], v[3]), pack_bf16(v[4], v[5]), pack_bf16(v[6], v[7]));
            }
        }
    }

#pragma unroll 1
    for (int layer = 0; layer < 2; layer++) {
        if (wg < 2) {
            const int n1 = 32 * wg + 8 * w + g;
            const int ct = n1 >> 2;
            gen_col_consts(sb, tid);
            uint32_t tr2[4], ti2[4], tn2[4];
#pragma unroll
            for (int i = 0; i < 4; i++) {
                float cr[2], ci[2];
#pragma unroll
                for (int e = 0; e < 2; e++) {
                    int a = (n1 * (8 * i + 2 * q + e)) & 2047;
                    a = a >= 1024 ? a - 2048 : a;
                    float ang = (float)a * (-6.283185307179586f / 2048.f);
                    cr[e] = __cosf(ang); ci[e] = __sinf(ang);
                }
                tr2[i] = pack_bf16(cr[0], cr[1]); ti2[i] = pack_bf16(ci[0], ci[1]); tn2[i] = ti2[i] ^ 0x80008000u;
            }
            mbar_wait(BAR(B_WST), 0);
            mbar_wait(BAR(B_COL), layer);
            TS(4 + 12 * layer);
            if (wg == 0) TC(0 + 10 * layer);
            const uint32_t rw0 = sb + SM_RAW + ct * 1024 + q * 64 + ((q >> 1) << 4) + (g & 3) * 4, rw1 = rw0 ^ 16;
            const int pos0 = 128 * ct + 8 * q + 2 * (g & 3);
            const int sw = b == 0 ? 1 : 0;
            uint32_t xr[4][4];
            const uint32_t st0 = sb + SM_H + (n1 >> 3) * 1024 + g * 16 + 4 * q;
#pragma unroll
            for (int i = 0; i < 4; i++) {
                float2 sq = *(const float2*)(sm + SM_SSQ + (pos0 + 32 * i) * 4);
                const uint32_t rs2 = pack_bf16(rsqrtf(sq.x * (1.f / 512.f) + 1e-5f), rsqrtf(sq.y * (1.f / 512.f) + 1e-5f));
#pragma unroll
                for (int jj = 0; jj < 4; jj++) {
                    const int K = jj ^ (2 * (i & 1));
                    uint32_t a = ((K & 1) ? rw1 : rw0) + i * 256 + (K & 2) * 16;
                    if (jj < 2) a ^= sw << 4;
                    uint32_t v = lds32(a);
                    xr[jj][i] = v;
                    uint32_t o = hmul2(v, rs2);
                    if (jj == 1 && sw) o = 0u;
                    sts32(st0 + (jj & 1) * 8192 + (4 * (jj >> 1) + i) * 128, o);
                }
            }
            if (wg == 0) TC(1 + 10 * layer);
            fence_async_smem();
            bar_sync(1, 256);
            float acc[32];
            const uint32_t s1a = sb + SM_X + wg * 16384, s2b = sb + SM_X + 32768;
            wg_fence();
#pragma unroll
            for (int ks = 0; ks < 8; ks++)
                wgmma_n64<1>(acc, desc_a(s1a + (ks >> 2) * 8192 + (ks & 3) * 256), desc_b<64>(sb + SM_H + ks * 2048), ks != 0);
            wg_commit();
            wg_wait<0>();
            if (wg == 0) TC(2 + 10 * layer);
            uint32_t are[2][4], aim[2][4];
#pragma unroll
            for (int col = 0; col < 2; col++) {
#pragma unroll
                for (int i = 0; i < 4; i++) {
                    int o = 4 * (4 * col + i);
                    uint32_t zr = pack_bf16(acc[o], acc[o + 1]), zi = pack_bf16(acc[o + 2], acc[o + 3]);
                    are[col][i] = hfma2(zr, tr2[i], hmul2(zi, tn2[i]));
                    aim[col][i] = hfma2(zr, ti2[i], hmul2(zi, tr2[i]));
                }
            }
            wg_fence();
#pragma unroll
            for (int ks = 0; ks < 2; ks++)
                wgmma_n64_rs(acc, are[0][2 * ks], are[1][2 * ks], are[0][2 * ks + 1], are[1][2 * ks + 1], desc_b<64>(s2b + ks * 2048), ks != 0);
#pragma unroll
            for (int ks = 0; ks < 2; ks++)
                wgmma_n64_rs(acc, aim[0][2 * ks], aim[1][2 * ks], aim[0][2 * ks + 1], aim[1][2 * ks + 1], desc_b<64>(s2b + 4096 + ks * 2048), 1);
            wg_commit();
            uint32_t wf[16];
            mbar_wait(BAR(B_WRDY), layer);
#pragma unroll
            for (int i = 0; i < 4; i++) {
                const int kq = n1 * 4 + q;
                uint4 v = *(const uint4*)(sm + SM_H + 16384 + kq * 64 + ((i ^ ((kq >> 1) & 3)) << 4));
                wf[4 * i] = v.x; wf[4 * i + 1] = v.y; wf[4 * i + 2] = v.z; wf[4 * i + 3] = v.w;
            }
            wg_wait<0>();
            if (wg == 0) TC(3 + 10 * layer);
#pragma unroll
            for (int col = 0; col < 2; col++) {
#pragma unroll
                for (int i = 0; i < 4; i++) {
                    uint32_t wr = wf[col * 8 + 2 * i], wn = wf[col * 8 + 2 * i + 1];
                    uint32_t zr = pack_bf16(acc[4 * i + 2 * col], acc[4 * i + 2 * col + 1]);
                    uint32_t zi = pack_bf16(acc[16 + 4 * i + 2 * col], acc[16 + 4 * i + 2 * col + 1]);
                    are[col][i] = hfma2(zr, wr, hmul2(zi, wn));
                    aim[col][i] = hfma2(zr, wn, hmul2(zi ^ 0x80008000u, wr));
                }
            }
            wg_fence();
#pragma unroll
            for (int ks = 0; ks < 2; ks++)
                wgmma_n64_rs(acc, are[0][2 * ks], are[1][2 * ks], are[0][2 * ks + 1], are[1][2 * ks + 1], desc_b<64>(s2b + ks * 2048), ks != 0);
#pragma unroll
            for (int ks = 0; ks < 2; ks++)
                wgmma_n64_rs(acc, aim[0][2 * ks], aim[1][2 * ks], aim[0][2 * ks + 1], aim[1][2 * ks + 1], desc_b<64>(s2b + 4096 + ks * 2048), 1);
            wg_commit();
            wg_wait<0>();
            if (wg == 0) TC(4 + 10 * layer);
            bar_sync(1, 256);
#pragma unroll
            for (int col = 0; col < 2; col++) {
#pragma unroll
                for (int i = 0; i < 4; i++) {
                    uint32_t zr = pack_bf16(acc[4 * i + 2 * col], acc[4 * i + 2 * col + 1]);
                    uint32_t zi = pack_bf16(acc[16 + 4 * i + 2 * col], acc[16 + 4 * i + 2 * col + 1]);
                    sts32(st0 + 16384 + (4 * col + i) * 128, hfma2(zr, tr2[i], hmul2(zi, tn2[i])));
                    sts32(st0 + 16384 + 8192 + (4 * col + i) * 128, hfma2(zr, ti2[i], hmul2(zi, tr2[i])));
                }
            }
            if (wg == 0) TC(5 + 10 * layer);
            fence_async_smem();
            bar_sync(1, 256);
            wg_fence();
#pragma unroll
            for (int ks = 0; ks < 8; ks++)
                wgmma_n64<1>(acc, desc_a(s1a + (ks >> 2) * 8192 + (ks & 3) * 256), desc_b<64>(sb + SM_H + 16384 + ks * 2048), ks != 0);
            wg_commit();
            wg_wait<0>();
            if (wg == 0) TC(6 + 10 * layer);
            const float sc = 1.f / 2048.f;
            const float sci0 = sw ? 0.f : -sc;
            const float wr0 = sw ? 0.5f : 1.f, wi0 = sw ? 0.f : 1.f;
#pragma unroll
            for (int i = 0; i < 4; i++) {
                float ss0, ss1;
#pragma unroll
                for (int col = 0; col < 2; col++) {
                    int o = 4 * (4 * col + i);
                    uint32_t vr = xr[2 * col][i], vi = xr[2 * col + 1][i];
                    float si = col == 0 ? sci0 : -sc;
                    uint32_t nr = pack_bf16(fmaf(acc[o], sc, bf_lo(vr)), fmaf(acc[o + 1], sc, bf_hi(vr)));
                    uint32_t ni = pack_bf16(fmaf(acc[o + 2], si, bf_lo(vi)), fmaf(acc[o + 3], si, bf_hi(vi)));
                    float a0 = bf_lo(nr), a1 = bf_hi(nr), b0 = bf_lo(ni), b1 = bf_hi(ni);
                    if (col == 0) {
                        ss0 = wr0 * a0 * a0 + wi0 * b0 * b0;
                        ss1 = wr0 * a1 * a1 + wi0 * b1 * b1;
                    } else {
                        ss0 += a0 * a0 + b0 * b0;
                        ss1 += a1 * a1 + b1 * b1;
                    }
                    const int K = (2 * col) ^ (2 * (i & 1));
                    uint32_t a = rw0 + i * 256 + K * 16;
                    if (col == 0) a ^= sw << 4;
                    sts32(a, nr);
                    sts32(a ^ 16, ni);
                }
                *(float2*)(sm + SM_SSQ + (pos0 + 32 * i) * 4) = make_float2(ss0 * (2.f / 512.f), ss1 * (2.f / 512.f));
            }
            fence_async_smem();
        }
        TS(5 + 12 * layer);
        if (wg == 0) TC(7 + 10 * layer);
        bar_arrive(5, 416);

        float acc[64];
        float* s_rstd = (float*)(sm + SM_RSTD);
        float* s_mean = (float*)(sm + SM_MEAN);
        const unsigned epoch = s_tgt[0] >> 7;
        const uint32_t pt3 = 1u + (2u * epoch + layer) % 3u;
        const uint32_t ptag = (pt3 & 1u) | ((pt3 & 2u) << 15);
        const uint64_t dstep = layer == 0 ? 16 : 2;
        auto c_desc = [&](int s) { return layer == 0 ? desc_a(sb + SM_A + s * 16384) : desc_k(sb + SM_A + s * 16384); };
        if (wg < 2) {
            const int prow = 32 * wg + 8 * w + g;
            const float2 l1 = *(const float2*)(sm + SM_LAM + prow * 8);
            float lr32 = l1.x, li32 = l1.y;
#pragma unroll
            for (int i = 0; i < 5; i++) { float t = lr32 * lr32 - li32 * li32; li32 = 2.f * lr32 * li32; lr32 = t; }
            float lr128 = lr32, li128 = li32;
#pragma unroll
            for (int i = 0; i < 2; i++) { float t = lr128 * lr128 - li128 * li128; li128 = 2.f * lr128 * li128; lr128 = t; }
            const float lr1 = l1.x, li1 = l1.y;
            acc_def(acc);
#pragma unroll 1
            for (int kb = 0; kb < 8; kb++) {
                mbar_wait(BAR(B_AFULL + kb), 0);
                mbar_wait(BAR(B_XFULL + (kb & 3)), (kb >> 2) & 1);
                wg_fence();
#pragma unroll
                for (int ks = 0; ks < 4; ks++)
                    wgmma_n128<1>(acc, desc_a(sb + SM_A + kb * 16384 + wg * 8192 + ks * 256),
                                  desc_b<128>(sb + SM_X + (kb & 3) * 24576 + ks * 4096), 1);
                wg_commit();
                wg_wait<1>();
                if (kb > 0 && lane == 0) {
                    mbar_arrive(BAR(B_AEMPTY + kb - 1), 1); mbar_arrive(BAR(B_XEMPTY + ((kb - 1) & 3)), 1);
                    mbar_arrive_remote(mapa(BAR(B_XEMPTY + ((kb - 1) & 3)), par ^ 1));
                }
            }
            wg_wait<0>();
            if (lane == 0) {
                mbar_arrive(BAR(B_AEMPTY + 7), 1); mbar_arrive(BAR(B_XEMPTY + 3), 1);
                mbar_arrive_remote(mapa(BAR(B_XEMPTY + 3), par ^ 1)); mbar_arrive_remote(mapa(BAR(B_RFREE), par ^ 1));
            }
            bar_arrive(14, 384);
            TS(6 + 12 * layer);
            bar_sync(4, 384);
            TS(7 + 12 * layer);
            float er = 0.f, ei = 0.f;
#pragma unroll
            for (int i = 0; i < 16; i++) {
                float2 rs = *(const float2*)(s_rstd + 128 + 8 * i + 2 * q);
                acc[4 * i] *= rs.x; acc[4 * i + 1] *= rs.y; acc[4 * i + 2] *= rs.x; acc[4 * i + 3] *= rs.y;
                float nr = lr1 * er - li1 * ei + acc[4 * i], ni = lr1 * ei + li1 * er + acc[4 * i + 2];
                er = lr1 * nr - li1 * ni + acc[4 * i + 1];
                ei = lr1 * ni + li1 * nr + acc[4 * i + 3];
            }
            float cr = 0.f, ci = 0.f, tr = 0.f, ti = 0.f;
#pragma unroll
            for (int qq = 0; qq < 4; qq++) {
                float xr_ = __shfl_sync(~0u, er, (lane & ~3) | qq), xi_ = __shfl_sync(~0u, ei, (lane & ~3) | qq);
                if (qq == q) { cr = tr; ci = ti; }
                float nr = lr32 * tr - li32 * ti + xr_, ni = lr32 * ti + li32 * tr + xi_;
                tr = nr; ti = ni;
            }
            float4* eb = g_Ebuf + (uint32_t)(layer * 16 * 512 + 64 * r + prow);
            if (q == 0 && c < 15) st_relaxed_f4(eb + c * 512, make_float4(tr, ti, __uint_as_float(epoch), 0.f));
            TS(8 + 12 * layer);
            float pr[4], pi[4];
            {
                unsigned n = 0;
                bool ok;
#pragma unroll 1
                do {
                    ok = true;
#pragma unroll
                    for (int k = 0; k < 4; k++) {
                        float4 v = make_float4(0.f, 0.f, __uint_as_float(epoch), 0.f);
                        if (4 * k + q < c) v = ld_relaxed_f4(eb + (4 * k + q) * 512);
                        pr[k] = v.x; pi[k] = v.y;
                        ok = ok && __float_as_uint(v.z) == epoch;
                    }
                } while (!ok && ++n < SPIN_LIMIT);
            }
            __syncwarp();
            TS(9 + 12 * layer);
            float hr = 0.f, hi = 0.f;
#pragma unroll
            for (int cc = 0; cc < 15; cc++) {
                float xr_ = __shfl_sync(~0u, pr[cc >> 2], (lane & ~3) | (cc & 3)), xi_ = __shfl_sync(~0u, pi[cc >> 2], (lane & ~3) | (cc & 3));
                if (cc < c) {
                    float nr = lr128 * hr - li128 * hi + xr_, ni = lr128 * hi + li128 * hr + xi_;
                    hr = nr; hi = ni;
                }
            }
#pragma unroll
            for (int qq = 0; qq < 3; qq++) {
                if (qq < q) { float nr = lr32 * hr - li32 * hi, ni = lr32 * hi + li32 * hr; hr = nr; hi = ni; }
            }
            er = cr + hr; ei = ci + hi;
            bar_sync(7, 384);
            mbar_wait_cluster(BAR(B_RFREE), layer);
            const uint32_t ha = sb + SM_HH + par * 32768 + (prow >> 3) * 1024 + g * 16 + 4 * q;
#pragma unroll
            for (int i = 0; i < 16; i++) {
                float nr = lr1 * er - li1 * ei + acc[4 * i], ni = lr1 * ei + li1 * er + acc[4 * i + 2];
                er = lr1 * nr - li1 * ni + acc[4 * i + 1];
                ei = lr1 * ni + li1 * nr + acc[4 * i + 3];
                sts32(ha + (i >> 3) * 16384 + (i & 7) * 128, pack_bf16(nr, er));
                sts32(ha + (i >> 3) * 16384 + 8192 + (i & 7) * 128, pack_bf16(ni, ei));
                if (i == 7) { fence_async_smem(); bar_arrive(13, 288); }
            }
            fence_async_smem();
            acc_def(acc);
            float acc2[32];
            acc_def(acc2);
            TS(10 + 12 * layer);
            bar_sync(6, 416);
            TS(11 + 12 * layer);
            float (&a0)[32] = *reinterpret_cast<float (*)[32]>(&acc[0]);
            float (&a1)[32] = *reinterpret_cast<float (*)[32]>(&acc[32]);
            auto tile_mma = [&](float (&d)[32], int u) {
#pragma unroll 1
                for (int k = 0; k < 2; k++) {
                    const uint32_t hb = sb + SM_HH + (par ^ k) * 32768 + wg * 16384;
                    if (k == 1) mbar_wait(BAR(wg ? B_HPEER1 : B_HPEER), layer);
                    mbar_wait(BAR(B_AFULL + 2 * u + k), 1);
                    const uint64_t da = c_desc(2 * u + k);
                    wg_fence();
#pragma unroll
                    for (int ks = 0; ks < 4; ks++) wgmma_n64s<1>(d, da + ks * dstep, desc_b<64>(hb + ks * 2048), 1);
#pragma unroll
                    for (int ks = 0; ks < 4; ks++) wgmma_n64s<-1>(d, da + 512 + ks * dstep, desc_b<64>(hb + 8192 + ks * 2048), 1);
                }
                wg_commit();
            };
            auto tile_ship = [&](float (&d)[32], int u) {
                uint4* dst = g_P + (uint32_t)(((c * 8 + 2 * ((pi_ + 1 + u) & 3) + par) * 4 + pi_) * 1024 + wg * 512 + (tid & 127));
#pragma unroll
                for (int i = 0; i < 4; i++)
                    dst[i * 128] = make_uint4((pack_bf16(d[8 * i], d[8 * i + 1]) & 0xfffefffeu) | ptag, pack_bf16(d[8 * i + 2], d[8 * i + 3]),
                                              pack_bf16(d[8 * i + 4], d[8 * i + 5]), pack_bf16(d[8 * i + 6], d[8 * i + 7]));
            };
            tile_mma(a0, 0);
            if ((tid & 127) == 0) mbar_arrive_remote(mapa(BAR(B_HDONE), par ^ 1));
            __syncwarp();
            tile_mma(a1, 1);
            wg_wait<1>();
            tile_ship(a0, 0);
            tile_mma(acc2, 2);
            bar_arrive(12, 384);
            wg_wait<1>();
            tile_ship(a1, 1);
            wg_wait<0>();
            tile_ship(acc2, 2);
            if (lane < 6) mbar_arrive(BAR(B_AEMPTY + lane), 1);
            TS(12 + 12 * layer);
        } else {
            const int t2 = tid - 256;
            const uint8_t* ximg = g_X + (uint32_t)layer * 16 * 8 * 16384;
            mbar_wait(BAR(B_SSQ), layer);
            TS(6 + 12 * layer);
            float sqv[16];
#pragma unroll
            for (int i = 0; i < 16; i++) sqv[i] = __ldcg(g_ssqc + (layer * 16 + i) * 2048 + 128 * c + t2);
            const unsigned short xm = __ldcg((const unsigned short*)(ximg + (uint32_t)(c * 8 * 16384 + (t2 >> 3) * 128 + (t2 & 7) * 2)));
            acc_def(acc);
#pragma unroll 1
            for (int kb = 0; kb < 8; kb++) {
                if (kb == 4) {
                    wg_wait<0>();
                    if (lane == 0) { mbar_arrive(BAR(B_XEMPTY + 3), 1); mbar_arrive_remote(mapa(BAR(B_XEMPTY + 3), par ^ 1)); }
                    float tot = 0.f;
#pragma unroll
                    for (int i = 0; i < 16; i++) tot += sqv[i];
                    float rs = rsqrtf(tot * (1.f / 512.f) + 1e-5f);
                    s_rstd[t2] = rs;
                    s_rstd[128 + t2] = 2.f * rs;
                    s_mean[t2] = layer == 0 ? 0.f : __uint_as_float((uint32_t)xm << 16) * (1.f / 512.f);
                    TS(7 + 12 * layer);
                    bar_arrive(4, 384);
                    bar_sync(14, 384);
                }
                mbar_wait(BAR(B_XFULL + (kb & 3)), (kb >> 2) & 1);
                wg_fence();
#pragma unroll
                for (int ks = 0; ks < 4; ks++)
                    wgmma_n128<1>(acc, desc_a(sb + SM_X + (kb & 3) * 24576 + 16384 + ks * 256), desc_b<128>(sb + SM_X + (kb & 3) * 24576 + ks * 4096), 1);
                wg_commit();
                wg_wait<1>();
                if ((kb & 3) != 0 && lane == 0) { mbar_arrive(BAR(B_XEMPTY + ((kb - 1) & 3)), 1); mbar_arrive_remote(mapa(BAR(B_XEMPTY + ((kb - 1) & 3)), par ^ 1)); }
            }
            wg_wait<0>();
            if (lane == 0) { mbar_arrive(BAR(B_XEMPTY + 3), 1); mbar_arrive_remote(mapa(BAR(B_XEMPTY + 3), par ^ 1)); mbar_arrive_remote(mapa(BAR(B_RFREE), par ^ 1)); }
            bar_arrive(7, 384);
            bar_sync(3, 128);
            TS(9 + 12 * layer);
            const int m0 = 16 * w + g;
            const uint32_t xoff = (uint32_t)((c * 8 + own) * 16384 + w * 4096 + g * 16 + 4 * q);
            if (layer == 0) {
                const uint8_t* xs = g_X + xoff;
#pragma unroll
                for (int i = 0; i < 16; i++) {
                    float2 rs = *(const float2*)(s_rstd + 8 * i + 2 * q);
                    uint32_t x0v = __ldcg((const uint32_t*)(xs + i * 128)), x1v = __ldcg((const uint32_t*)(xs + 2048 + i * 128));
                    acc[4 * i] = acc[4 * i] * rs.x + bf_lo(x0v);
                    acc[4 * i + 1] = acc[4 * i + 1] * rs.y + bf_hi(x0v);
                    acc[4 * i + 2] = acc[4 * i + 2] * rs.x + bf_lo(x1v);
                    acc[4 * i + 3] = acc[4 * i + 3] * rs.y + bf_hi(x1v);
                }
            } else {
                float d0 = ldbf(p.dskip + 64 * own + m0), d1 = ldbf(p.dskip + 64 * own + m0 + 8);
#pragma unroll
                for (int i = 0; i < 16; i++) {
                    float2 rs = *(const float2*)(s_rstd + 8 * i + 2 * q);
                    float2 mn = *(const float2*)(s_mean + 8 * i + 2 * q);
                    acc[4 * i] = acc[4 * i] * (1.f + rs.x * d0) + mn.x;
                    acc[4 * i + 1] = acc[4 * i + 1] * (1.f + rs.y * d0) + mn.y;
                    acc[4 * i + 2] = acc[4 * i + 2] * (1.f + rs.x * d1) + mn.x;
                    acc[4 * i + 3] = acc[4 * i + 3] * (1.f + rs.y * d1) + mn.y;
                }
            }
            TS(10 + 12 * layer);
            bar_sync(6, 416);
            TS(11 + 12 * layer);
            {
                float (&a0)[32] = *reinterpret_cast<float (*)[32]>(&acc[0]);
                float (&a1)[32] = *reinterpret_cast<float (*)[32]>(&acc[32]);
#pragma unroll 1
                for (int k = 0; k < 2; k++) {
                    const uint32_t hb = sb + SM_HH + (par ^ k) * 32768;
                    if (k == 1) {
                        mbar_wait(BAR(B_HPEER), layer);
                        mbar_wait(BAR(B_HPEER1), layer);
                        bar_sync(12, 384);
                    }
                    mbar_wait(BAR(B_AFULL + 6 + k), 1);
                    const uint64_t da = c_desc(6 + k);
                    wg_fence();
#pragma unroll
                    for (int ks = 0; ks < 4; ks++) {
                        wgmma_n64s<1>(a0, da + ks * dstep, desc_b<64>(hb + ks * 2048), 1);
                        wgmma_n64s<1>(a1, da + ks * dstep, desc_b<64>(hb + 16384 + ks * 2048), 1);
                    }
#pragma unroll
                    for (int ks = 0; ks < 4; ks++) {
                        wgmma_n64s<-1>(a0, da + 512 + ks * dstep, desc_b<64>(hb + 8192 + ks * 2048), 1);
                        wgmma_n64s<-1>(a1, da + 512 + ks * dstep, desc_b<64>(hb + 16384 + 8192 + ks * 2048), 1);
                    }
                    wg_commit();
                }
                wg_wait<0>();
            }
#pragma unroll
            for (int i = 0; i < 16; i++)
                *(float4*)(sm + SM_A + 6 * 16384 + i * 2048 + t2 * 16) = make_float4(acc[4 * i], acc[4 * i + 1], acc[4 * i + 2], acc[4 * i + 3]);
            TS(12 + 12 * layer);
        }
        {
            const int t = tid & 127;
            const int nch = wg == 2 ? 2 : 3;
            const uint4* pb = g_P + (uint32_t)((c * 8 + r) * 4 * 1024 + wg * 128 + t);
            uint4 v[3][3];
            unsigned n = 0;
#pragma unroll 1
            while (true) {
                if (lane == 31) {
#pragma unroll 1
                    while (true) {
                        uint32_t bad = 0;
#pragma unroll
                        for (int sx = 0; sx < 3; sx++) {
                            uint32_t t0;
                            asm volatile("ld.relaxed.gpu.global.u32 %0, [%1];" : "=r"(t0) : "l"(pb + ((pi_ + 1 + sx) & 3) * 1024 + (nch - 1) * 384) : "memory");
                            bad |= t0 ^ ptag;
                        }
                        if (!(bad & 0x00010001u) || ++n >= SPIN_LIMIT) break;
                    }
                }
                __syncwarp();
                uint32_t bad = 0;
#pragma unroll
                for (int k = 0; k < 3; k++)
#pragma unroll
                    for (int sx = 0; sx < 3; sx++) {
                        v[k][sx] = make_uint4(ptag, 0, 0, 0);
                        if (k < nch) v[k][sx] = ld_relaxed_u4(pb + ((pi_ + 1 + sx) & 3) * 1024 + k * 384);
                        bad |= v[k][sx].x ^ ptag;
                    }
                if (!__any_sync(~0u, bad & 0x00010001u) || ++n >= SPIN_LIMIT) break;
            }
            bar_sync(8, 384);
            TS(13 + 12 * layer);
            const int m0 = 16 * w + g;
            const float w0 = (own == 0 && m0 < 2) ? (m0 == 0 ? 0.f : 0.5f) : 1.f;
#pragma unroll
            for (int k = 0; k < 3; k++) {
                if (k < nch) {
                    const int i = wg + 3 * k;
                    float4 a = *(const float4*)(sm + SM_A + 6 * 16384 + (2 * i) * 2048 + t * 16);
                    float4 bq = *(const float4*)(sm + SM_A + 6 * 16384 + (2 * i + 1) * 2048 + t * 16);
#pragma unroll
                    for (int sx = 0; sx < 3; sx++) {
                        a.x += bf_lo(v[k][sx].x); a.y += bf_hi(v[k][sx].x); a.z += bf_lo(v[k][sx].y); a.w += bf_hi(v[k][sx].y);
                        bq.x += bf_lo(v[k][sx].z); bq.y += bf_hi(v[k][sx].z); bq.z += bf_lo(v[k][sx].w); bq.w += bf_hi(v[k][sx].w);
                    }
                    if (layer == 0) {
                        uint8_t* xd = g_X + (uint32_t)((16 * 8 + c * 8 + own) * 16384 + w * 4096 + g * 16 + 4 * q + i * 256);
                        uint32_t v0 = pack_bf16(a.x, a.y), v1 = pack_bf16(a.z, a.w), v2 = pack_bf16(bq.x, bq.y), v3 = pack_bf16(bq.z, bq.w);
                        *(uint32_t*)(xd) = v0; *(uint32_t*)(xd + 2048) = v1; *(uint32_t*)(xd + 128) = v2; *(uint32_t*)(xd + 2048 + 128) = v3;
                        float sq[4];
                        sq[0] = w0 * bf_lo(v0) * bf_lo(v0) + bf_lo(v1) * bf_lo(v1);
                        sq[1] = w0 * bf_hi(v0) * bf_hi(v0) + bf_hi(v1) * bf_hi(v1);
                        sq[2] = w0 * bf_lo(v2) * bf_lo(v2) + bf_lo(v3) * bf_lo(v3);
                        sq[3] = w0 * bf_hi(v2) * bf_hi(v2) + bf_hi(v3) * bf_hi(v3);
                        float u0 = (g & 1) ? sq[2] : sq[0], u1 = (g & 1) ? sq[3] : sq[1];
                        u0 += __shfl_xor_sync(~0u, (g & 1) ? sq[0] : sq[2], 4);
                        u1 += __shfl_xor_sync(~0u, (g & 1) ? sq[1] : sq[3], 4);
                        float z = (g & 2) ? u1 : u0;
                        z += __shfl_xor_sync(~0u, (g & 2) ? u0 : u1, 8);
                        z += __shfl_xor_sync(~0u, z, 16);
                        if (g < 4) atomicAdd(s_mean + 16 * i + 8 * (g & 1) + 2 * q + (g >> 1), z);
                    } else {
                        float* o = p.out + (uint32_t)((128 * c + 32 * q + 4 * i) * 512 + 64 * own + m0);
                        o[0] = a.x; o[512] = a.y; o[8] = a.z; o[512 + 8] = a.w;
                        o[1024] = bq.x; o[1536] = bq.y; o[1024 + 8] = bq.z; o[1536 + 8] = bq.w;
                    }
                }
            }
            if (wg < 2) mbar_wait_cluster(BAR(B_HDONE), layer);
            if (layer == 0) {
                fence_async_smem();
                bar_sync(9, 384);
                TS(14 + 12 * layer);
                if (wg == 2) {
                    atomicAdd(g_ssq + 2048 + 128 * c + t, s_mean[t] * (2.f / 512.f));
                    bar_sync(3, 128);
                    if (lane == 0) { mbar_arrive(BAR(B_AEMPTY + 6), 2); mbar_arrive(BAR(B_AEMPTY + 7), 2); }
                    if (t == 0) { fence_async(); red_release(&g_bar[2], 1); }
                }
            }
        }
        TS(15 + 12 * layer);
        if (wg == 0) TC(31);
    }
}

typedef CUresult (*EncFn)(CUtensorMap*, CUtensorMapDataType, cuuint32_t, void*, const cuuint64_t*, const cuuint64_t*,
                          const cuuint32_t*, const cuuint32_t*, CUtensorMapInterleave, CUtensorMapSwizzle,
                          CUtensorMapL2promotion, CUtensorMapFloatOOBfill);

void launch_impl(void* const* d_in, void* d_out, int stop) {
    static EncFn enc = nullptr;
    if (!enc) {
        void* fn = nullptr;
        cudaDriverEntryPointQueryResult qr;
        cudaGetDriverEntryPoint("cuTensorMapEncodeTiled", &fn, cudaEnableDefault, &qr);
        enc = (EncFn)fn;
        cudaFuncSetAttribute(fused_kernel, cudaFuncAttributeMaxDynamicSharedMemorySize, SM_TOTAL);
    }
    CUtensorMap tx, tbr, tbi, tcr, tci, tcol;
    {
        void* gx = nullptr;
        cudaGetSymbolAddress(&gx, g_X);
        cuuint64_t gd[5] = {64, 16, 64, 16, 2};
        cuuint64_t gs[4] = {128, 2048, 128 * 1024, 2048 * 1024};
        cuuint32_t bx[5] = {32, 16, 1, 16, 1};
        cuuint32_t es[5] = {1, 1, 1, 1, 1};
        enc(&tcol, CU_TENSOR_MAP_DATA_TYPE_BFLOAT16, 5, gx, gd, gs, bx, es, CU_TENSOR_MAP_INTERLEAVE_NONE,
            CU_TENSOR_MAP_SWIZZLE_64B, CU_TENSOR_MAP_L2_PROMOTION_NONE, CU_TENSOR_MAP_FLOAT_OOB_FILL_NONE);
    }
    {
        cuuint64_t gd[5] = {512, 2, 4, 16, 16};
        cuuint64_t gs[4] = {1024, 32 * 1024, 2 * 1024, 128 * 1024};
        cuuint32_t bx[5] = {64, 2, 4, 8, 1};
        cuuint32_t es[5] = {1, 1, 1, 1, 1};
        enc(&tx, CU_TENSOR_MAP_DATA_TYPE_BFLOAT16, 5, d_in[0], gd, gs, bx, es, CU_TENSOR_MAP_INTERLEAVE_NONE,
            CU_TENSOR_MAP_SWIZZLE_128B, CU_TENSOR_MAP_L2_PROMOTION_L2_128B, CU_TENSOR_MAP_FLOAT_OOB_FILL_NONE);
    }
    auto mk2 = [&](CUtensorMap* m, void* ptr, cuuint32_t rows) {
        cuuint64_t gd[2] = {512, 512};
        cuuint64_t gs[1] = {1024};
        cuuint32_t bx[2] = {64, rows};
        cuuint32_t es[2] = {1, 1};
        enc(m, CU_TENSOR_MAP_DATA_TYPE_BFLOAT16, 2, ptr, gd, gs, bx, es, CU_TENSOR_MAP_INTERLEAVE_NONE,
            CU_TENSOR_MAP_SWIZZLE_128B, CU_TENSOR_MAP_L2_PROMOTION_L2_128B, CU_TENSOR_MAP_FLOAT_OOB_FILL_NONE);
    };
    mk2(&tbr, d_in[6], 32);
    mk2(&tbi, d_in[7], 32);
    mk2(&tcr, d_in[8], 64);
    mk2(&tci, d_in[9], 64);
    Params p;
    p.x0 = (const __nv_bfloat16*)d_in[0];
    p.w_r = (const __nv_bfloat16*)d_in[1];
    p.w_i = (const __nv_bfloat16*)d_in[2];
    p.lam_re = (const __nv_bfloat16*)d_in[4];
    p.lam_im = (const __nv_bfloat16*)d_in[5];
    p.log_dt = (const __nv_bfloat16*)d_in[10];
    p.dskip = (const __nv_bfloat16*)d_in[11];
    p.out = (float*)d_out;
    p.stop = stop;
    cudaLaunchConfig_t cfg = {};
    cfg.gridDim = dim3(NCTA); cfg.blockDim = dim3(NTHREADS); cfg.dynamicSmemBytes = SM_TOTAL; cfg.stream = cudaStreamPerThread;
    cudaLaunchAttribute at[1];
    at[0].id = cudaLaunchAttributeClusterDimension;
    at[0].val.clusterDim.x = 2; at[0].val.clusterDim.y = 1; at[0].val.clusterDim.z = 1;
    cfg.attrs = at; cfg.numAttrs = 1;
    cudaLaunchKernelEx(&cfg, fused_kernel, tx, tbr, tbi, tcr, tci, tcol, p);
}

}

extern "C" void kernel_launch(void* const* d_in, const int* in_sizes, int n_in, void* d_out, int out_size) {
    (void)in_sizes; (void)n_in; (void)out_size;
    launch_impl(d_in, d_out, 100);
}
```

```cpp
#include <cuda_runtime.h>
#include <cuda_bf16.h>
#include <cuda.h>
#include <stdint.h>

namespace {

constexpr int NCTA = 128;
constexpr int NTHREADS = 512;
constexpr int SM_A = 0;
constexpr int SM_X = 131072;
constexpr int SM_H = 196608;
constexpr int SM_HH = SM_X + 32768;
constexpr int SM_M = 229376;
constexpr int SM_TOTAL = 232448;
constexpr int SM_BAR = SM_M;
constexpr int SM_TGT = SM_M + 400;
constexpr int SM_LAM = SM_M + 424;
constexpr int SM_TAB = SM_M + 944;
constexpr int SM_RSTD = SM_M + 1920;
constexpr int SM_MEAN = SM_TAB;
constexpr int SM_T64 = SM_M + 2944;
constexpr int SM_B1ST = SM_H + 24576;
constexpr int SM_RAW = SM_X + 40960;
constexpr int SM_SSQ = SM_X + 57344;
constexpr int B_FULL0 = 0;
constexpr int B_EMPTY0 = 8;
constexpr int B_FULLC = 12;
constexpr int B_AFULL = 13;
constexpr int B_AEMPTY = 21;
constexpr int B_XFULL = 29;
constexpr int B_XEMPTY = 33;
constexpr int B_AFREE = 37;
constexpr int B_COL = 38;
constexpr int B_SSQ = 39;
constexpr int B_HPEER = 40;
constexpr int B_RFREE = 41;
constexpr int B_HDONE = 42;
constexpr int B_WRDY = 43;
constexpr int B_HPEER1 = 44;
constexpr int B_FULLB = 45;
constexpr int B_BFREE = 46;
constexpr int B_SETUP = 47;
constexpr int B_B1DONE = 48;
constexpr int B_WST = 49;
constexpr int NBARS = 50;

__device__ __align__(1024) uint8_t g_X[2 * 16 * 8 * 16384];
__device__ __align__(1024) uint8_t g_A1[8 * 8 * 16384];
__device__ __align__(1024) uint8_t g_A2[8 * 8 * 16384];
__device__ __align__(1024) uint8_t g_E[2 * 8 * 8 * 8192];
__device__ __align__(16) float g_ssq[2 * 2048];
__device__ __align__(16) float g_ssqc[2 * 16 * 2048];
__device__ __align__(16) float g_Dh[512];
__device__ __align__(16) uint4 g_Wfrag[128 * 4 * 256];
__device__ __align__(16) float4 g_Ebuf[2 * 16 * 512];
__device__ __align__(16) uint4 g_P[16 * 8 * 4 * 1024];
__device__ unsigned g_bar[8];
__device__ unsigned g_err;
#define TX(i)
#define TQ(i)
#define TS(i)
#define TC(i)

constexpr unsigned SPIN_LIMIT = 1u << 22;

__device__ __forceinline__ uint32_t s2u(const void* p) { return (uint32_t)__cvta_generic_to_shared(p); }
__device__ __forceinline__ void mbar_init(uint32_t a, uint32_t c) {
    asm volatile("mbarrier.init.shared::cta.b64 [%0], %1;" ::"r"(a), "r"(c) : "memory");
}
__device__ __forceinline__ void mbar_expect(uint32_t a, uint32_t bytes) {
    asm volatile("mbarrier.arrive.expect_tx.shared::cta.b64 _, [%0], %1;" ::"r"(a), "r"(bytes) : "memory");
}
__device__ __forceinline__ void mbar_arrive(uint32_t a, uint32_t cnt) {
    asm volatile("mbarrier.arrive.shared::cta.b64 _, [%0], %1;" ::"r"(a), "r"(cnt) : "memory");
}
__device__ __forceinline__ bool mbar_try(uint32_t a, uint32_t parity) {
    uint32_t ok;
    asm volatile("{\n.reg .pred p;\nmbarrier.try_wait.parity.shared::cta.b64 p, [%1], %2;\nselp.u32 %0, 1, 0, p;\n}"
                 : "=r"(ok) : "r"(a), "r"(parity) : "memory");
    return ok != 0;
}
__device__ __forceinline__ void mbar_wait(uint32_t a, uint32_t parity) {
    asm volatile("{\n.reg .pred p, q;\n.reg .u32 n;\nmov.u32 n, 0;\n"
                 "W_%=:\nmbarrier.try_wait.parity.shared::cta.b64 p, [%0], %1;\n@p bra D_%=;\n"
                 "add.u32 n, n, 1;\nsetp.lt.u32 q, n, 4194304;\n@q bra W_%=;\nD_%=:\n}" ::"r"(a), "r"(parity) : "memory");
}
__device__ __forceinline__ void bulk_g2s(uint32_t dst, const void* src, uint32_t bytes, uint32_t bar) {
    asm volatile("cp.async.bulk.shared::cluster.global.mbarrier::complete_tx::bytes [%0], [%1], %2, [%3];" ::"r"(dst),
                 "l"(src), "r"(bytes), "r"(bar) : "memory");
}
__device__ __forceinline__ void tma_2d(uint32_t dst, const CUtensorMap* m, int c0, int c1, uint32_t bar) {
    asm volatile("cp.async.bulk.tensor.2d.shared::cluster.global.mbarrier::complete_tx::bytes [%0], [%1, {%3,%4}], [%2];" ::"r"(dst),
                 "l"(m), "r"(bar), "r"(c0), "r"(c1) : "memory");
}
__device__ __forceinline__ void tma_5d(uint32_t dst, const CUtensorMap* m, int c0, int c1, int c2, int c3, int c4, uint32_t bar) {
    asm volatile("cp.async.bulk.tensor.5d.shared::cluster.global.mbarrier::complete_tx::bytes [%0], [%1, {%3,%4,%5,%6,%7}], [%2];" ::"r"(dst),
                 "l"(m), "r"(bar), "r"(c0), "r"(c1), "r"(c2), "r"(c3), "r"(c4) : "memory");
}
__device__ __forceinline__ void tma_2d_mc(uint32_t dst, const CUtensorMap* m, int c0, int c1, uint32_t bar) {
    asm volatile("cp.async.bulk.tensor.2d.shared::cluster.global.mbarrier::complete_tx::bytes.multicast::cluster [%0], [%1, {%3,%4}], [%2], %5;" ::"r"(dst),
                 "l"(m), "r"(bar), "r"(c0), "r"(c1), "h"((unsigned short)3) : "memory");
}
__device__ __forceinline__ void tma_5d_mc(uint32_t dst, const CUtensorMap* m, int c0, int c1, int c2, int c3, int c4, uint32_t bar) {
    asm volatile("cp.async.bulk.tensor.5d.shared::cluster.global.mbarrier::complete_tx::bytes.multicast::cluster [%0], [%1, {%3,%4,%5,%6,%7}], [%2], %8;" ::"r"(dst),
                 "l"(m), "r"(bar), "r"(c0), "r"(c1), "r"(c2), "r"(c3), "r"(c4), "h"((unsigned short)3) : "memory");
}
__device__ __forceinline__ void bulk_g2s_mc(uint32_t dst, const void* src, uint32_t bytes, uint32_t bar) {
    asm volatile("cp.async.bulk.shared::cluster.global.mbarrier::complete_tx::bytes.multicast::cluster [%0], [%1], %2, [%3], %4;" ::"r"(dst),
                 "l"(src), "r"(bytes), "r"(bar), "h"((unsigned short)3) : "memory");
}
__device__ __forceinline__ void tma_store_5d(const CUtensorMap* m, int c0, int c1, int c2, int c3, int c4, uint32_t src) {
    asm volatile("cp.async.bulk.tensor.5d.global.shared::cta.bulk_group [%0, {%2,%3,%4,%5,%6}], [%1];" ::"l"(m), "r"(src),
                 "r"(c0), "r"(c1), "r"(c2), "r"(c3), "r"(c4) : "memory");
}
__device__ __forceinline__ uint32_t lds32(uint32_t a) { uint32_t v; asm volatile("ld.shared.u32 %0, [%1];" : "=r"(v) : "r"(a) : "memory"); return v; }
__device__ __forceinline__ uint4 ld_relaxed_u4(const uint4* p) {
    uint4 v;
    asm volatile("ld.relaxed.gpu.global.v4.u32 {%0,%1,%2,%3}, [%4];" : "=r"(v.x), "=r"(v.y), "=r"(v.z), "=r"(v.w) : "l"(p) : "memory");
    return v;
}
__device__ __forceinline__ void fence_async() { asm volatile("fence.proxy.async.global;" ::: "memory"); }
__device__ __forceinline__ void red_relaxed(unsigned* p, unsigned v) {
    asm volatile("red.relaxed.gpu.global.add.u32 [%0], %1;" ::"l"(p), "r"(v) : "memory");
}
__device__ __forceinline__ uint32_t mapa(uint32_t a, uint32_t rank) {
    uint32_t d;
    asm("mapa.shared::cluster.u32 %0, %1, %2;" : "=r"(d) : "r"(a), "r"(rank));
    return d;
}
__device__ __forceinline__ void mbar_arrive_remote(uint32_t ra) {
    asm volatile("mbarrier.arrive.relaxed.cluster.shared::cluster.b64 _, [%0];" ::"r"(ra) : "memory");
}
__device__ __forceinline__ void mbar_wait_cluster(uint32_t a, uint32_t parity) {
    asm volatile("{\n.reg .pred p, q;\n.reg .u32 n;\nmov.u32 n, 0;\n"
                 "W_%=:\nmbarrier.try_wait.parity.acquire.cluster.shared::cta.b64 p, [%0], %1;\n@p bra D_%=;\n"
                 "add.u32 n, n, 1;\nsetp.lt.u32 q, n, 4194304;\n@q bra W_%=;\nD_%=:\n}" ::"r"(a), "r"(parity) : "memory");
}
__device__ __forceinline__ void bulk_s2peer(uint32_t rdst, uint32_t src, uint32_t bytes, uint32_t rbar) {
    asm volatile("cp.async.bulk.shared::cluster.shared::cta.mbarrier::complete_tx::bytes [%0], [%1], %2, [%3];" ::"r"(rdst),
                 "r"(src), "r"(bytes), "r"(rbar) : "memory");
}
__device__ __forceinline__ void fence_async_smem() { asm volatile("fence.proxy.async.shared::cta;" ::: "memory"); }
__device__ __forceinline__ void wg_fence() { asm volatile("wgmma.fence.sync.aligned;" ::: "memory"); }
__device__ __forceinline__ void wg_commit() { asm volatile("wgmma.commit_group.sync.aligned;" ::: "memory"); }
template <int N> __device__ __forceinline__ void wg_wait() { asm volatile("wgmma.wait_group.sync.aligned %0;" ::"n"(N) : "memory"); }
__device__ __forceinline__ void bar_sync(int id, int n) { asm volatile("bar.sync %0, %1;" ::"r"(id), "r"(n) : "memory"); }
__device__ __forceinline__ void bar_arrive(int id, int n) { asm volatile("bar.arrive %0, %1;" ::"r"(id), "r"(n) : "memory"); }
__device__ __forceinline__ unsigned ld_acquire(const unsigned* p) {
    unsigned v;
    asm volatile("ld.acquire.gpu.global.u32 %0, [%1];" : "=r"(v) : "l"(p) : "memory");
    return v;
}
__device__ __forceinline__ void red_release(unsigned* p, unsigned v) {
    asm volatile("red.release.gpu.global.add.u32 [%0], %1;" ::"l"(p), "r"(v) : "memory");
}
__device__ __forceinline__ void wait_count(const unsigned* p, unsigned target) {
    unsigned n = 0;
#pragma unroll 1
    while ((int)(ld_acquire(p) - target) < 0 && ++n < SPIN_LIMIT) {}
}
__device__ __forceinline__ float4 ld_relaxed_f4(const float4* p) {
    float4 v;
    asm volatile("ld.relaxed.gpu.global.v4.f32 {%0,%1,%2,%3}, [%4];" : "=f"(v.x), "=f"(v.y), "=f"(v.z), "=f"(v.w) : "l"(p) : "memory");
    return v;
}
__device__ __forceinline__ void st_relaxed_f4(float4* p, float4 v) {
    asm volatile("st.relaxed.gpu.global.v4.f32 [%0], {%1,%2,%3,%4};" ::"l"(p), "f"(v.x), "f"(v.y), "f"(v.z), "f"(v.w) : "memory");
}
__device__ __forceinline__ uint32_t pack_bf16(float lo, float hi) {
    uint32_t r;
    asm("cvt.rn.bf16x2.f32 %0, %1, %2;" : "=r"(r) : "f"(hi), "f"(lo));
    return r;
}
__device__ __forceinline__ uint32_t hmul2(uint32_t a, uint32_t b) {
    uint32_t r;
    asm("mul.rn.bf16x2 %0, %1, %2;" : "=r"(r) : "r"(a), "r"(b));
    return r;
}
__device__ __forceinline__ uint32_t hfma2(uint32_t a, uint32_t b, uint32_t c) {
    uint32_t r;
    asm("fma.rn.bf16x2 %0, %1, %2, %3;" : "=r"(r) : "r"(a), "r"(b), "r"(c));
    return r;
}
__device__ __forceinline__ float bf_lo(uint32_t v) { return __uint_as_float(v << 16); }
__device__ __forceinline__ float bf_hi(uint32_t v) { return __uint_as_float(v & 0xffff0000u); }
__device__ __forceinline__ void sts32(uint32_t a, uint32_t v) { asm volatile("st.shared.u32 [%0], %1;" ::"r"(a), "r"(v) : "memory"); }
__device__ __forceinline__ void sts128(uint32_t a, uint4 v) {
    asm volatile("st.shared.v4.u32 [%0], {%1,%2,%3,%4};" ::"r"(a), "r"(v.x), "r"(v.y), "r"(v.z), "r"(v.w) : "memory");
}

__device__ __forceinline__ uint64_t desc_ni(uint32_t addr, uint32_t lbo, uint32_t sbo) {
    return (uint64_t)((addr & 0x3FFFF) >> 4) | ((uint64_t)(lbo >> 4) << 16) | ((uint64_t)(sbo >> 4) << 32);
}
__device__ __forceinline__ uint64_t desc_a(uint32_t addr) { return desc_ni(addr, 128, 1024); }
template <int N> __device__ __forceinline__ uint64_t desc_b(uint32_t addr) { return desc_ni(addr, 16 * N, 128); }
__device__ __forceinline__ uint64_t desc_k(uint32_t addr) {
    return (uint64_t)((addr & 0x3FFFF) >> 4) | (1ull << 16) | (64ull << 32) | (1ull << 62);
}
__device__ __forceinline__ uint64_t desc_mn(uint32_t addr, uint32_t lbo) {
    return (uint64_t)((addr & 0x3FFFF) >> 4) | ((uint64_t)(lbo >> 4) << 16) | (64ull << 32) | (1ull << 62);
}

#define ACC8(d, o) "+f"(d[o + 0]), "+f"(d[o + 1]), "+f"(d[o + 2]), "+f"(d[o + 3]), "+f"(d[o + 4]), "+f"(d[o + 5]), "+f"(d[o + 6]), "+f"(d[o + 7])
template <int TB, int SA = 1>
__device__ __forceinline__ void wgmma_n128(float (&d)[64], uint64_t da, uint64_t db, int sd) {
    asm volatile(
        "{\n.reg .pred p;\nsetp.ne.b32 p, %66, 0;\n"
        "wgmma.mma_async.sync.aligned.m64n128k16.f32.bf16.bf16 "
        "{%0,%1,%2,%3,%4,%5,%6,%7,%8,%9,%10,%11,%12,%13,%14,%15,%16,%17,%18,%19,%20,%21,%22,%23,%24,%25,%26,%27,%28,%29,%30,%31,"
        "%32,%33,%34,%35,%36,%37,%38,%39,%40,%41,%42,%43,%44,%45,%46,%47,%48,%49,%50,%51,%52,%53,%54,%55,%56,%57,%58,%59,%60,%61,%62,%63},"
        " %64, %65, p, %68, 1, 0, %67;\n}"
        : ACC8(d, 0), ACC8(d, 8), ACC8(d, 16), ACC8(d, 24), ACC8(d, 32), ACC8(d, 40), ACC8(d, 48), ACC8(d, 56)
        : "l"(da), "l"(db), "r"(sd), "n"(TB), "n"(SA));
}
template <int N> __device__ __forceinline__ void acc_def(float (&d)[N]) {
#pragma unroll
    for (int i = 0; i < N; i++) d[i] = 0.f;
}
template <int TB>
__device__ __forceinline__ void wgmma_n64(float (&d)[32], uint64_t da, uint64_t db, int sd) {
    asm volatile(
        "{\n.reg .pred p;\nsetp.ne.b32 p, %34, 0;\n"
        "wgmma.mma_async.sync.aligned.m64n64k16.f32.bf16.bf16 "
        "{%0,%1,%2,%3,%4,%5,%6,%7,%8,%9,%10,%11,%12,%13,%14,%15,%16,%17,%18,%19,%20,%21,%22,%23,%24,%25,%26,%27,%28,%29,%30,%31},"
        " %32, %33, p, 1, 1, 0, %35;\n}"
        : ACC8(d, 0), ACC8(d, 8), ACC8(d, 16), ACC8(d, 24)
        : "l"(da), "l"(db), "r"(sd), "n"(TB));
}
template <int SA>
__device__ __forceinline__ void wgmma_n64s(float (&d)[32], uint64_t da, uint64_t db, int sd) {
    asm volatile(
        "{\n.reg .pred p;\nsetp.ne.b32 p, %34, 0;\n"
        "wgmma.mma_async.sync.aligned.m64n64k16.f32.bf16.bf16 "
        "{%0,%1,%2,%3,%4,%5,%6,%7,%8,%9,%10,%11,%12,%13,%14,%15,%16,%17,%18,%19,%20,%21,%22,%23,%24,%25,%26,%27,%28,%29,%30,%31},"
        " %32, %33, p, %35, 1, 0, 1;\n}"
        : ACC8(d, 0), ACC8(d, 8), ACC8(d, 16), ACC8(d, 24)
        : "l"(da), "l"(db), "r"(sd), "n"(SA));
}
__device__ __forceinline__ void wgmma_n64_rs(float (&d)[32], uint32_t a0, uint32_t a1, uint32_t a2, uint32_t a3, uint64_t db, int sd) {
    asm volatile(
        "{\n.reg .pred p;\nsetp.ne.b32 p, %37, 0;\n"
        "wgmma.mma_async.sync.aligned.m64n64k16.f32.bf16.bf16 "
        "{%0,%1,%2,%3,%4,%5,%6,%7,%8,%9,%10,%11,%12,%13,%14,%15,%16,%17,%18,%19,%20,%21,%22,%23,%24,%25,%26,%27,%28,%29,%30,%31},"
        " {%32,%33,%34,%35}, %36, p, 1, 1, 1;\n}"
        : ACC8(d, 0), ACC8(d, 8), ACC8(d, 16), ACC8(d, 24)
        : "r"(a0), "r"(a1), "r"(a2), "r"(a3), "l"(db), "r"(sd));
}

struct Params {
    const __nv_bfloat16* x0;
    const __nv_bfloat16* w_r;
    const __nv_bfloat16* w_i;
    const __nv_bfloat16* lam_re;
    const __nv_bfloat16* lam_im;
    const __nv_bfloat16* log_dt;
    const __nv_bfloat16* dskip;
    float* out;
    int stop;
};

__device__ __forceinline__ float ldbf(const __nv_bfloat16* p) { return __bfloat162float(*p); }

__device__ __forceinline__ void dft_fp(int j, int& f, int& ph) {
    int cs = j >> 1;
    if (j == 1) { f = 256; ph = 0; }
    else { f = cs; ph = (j & 1) ? 128 : 0; }
}

__device__ __forceinline__ void gen_col_consts(uint32_t sb, int tid) {
#pragma unroll 1
    for (int task = tid; task < 640; task += 256) {
        int f, c8;
        uint32_t a_cc, d_pi, d_po;
        if (task < 512) {
            f = task & 63; c8 = task >> 6;
            a_cc = sb + SM_X + (f >> 5) * 16384 + ((f >> 3) & 3) * 2048 + c8 * 128 + (f & 7) * 16;
            d_pi = 8192; d_po = 1024;
        } else {
            int n2 = task & 31;
            f = 2 * n2; c8 = (task >> 5) & 3;
            a_cc = sb + SM_X + 32768 + (n2 >> 3) * 1024 + c8 * 128 + (n2 & 7) * 16;
            d_pi = 4096; d_po = 512;
        }
        float cd, sd, cs, sn;
        __sincosf((float)(f >= 32 ? f - 64 : f) * (6.283185307179586f / 64.f), &sd, &cd);
        int a = (8 * c8 * f) & 63;
        __sincosf((float)(a >= 32 ? a - 64 : a) * (6.283185307179586f / 64.f), &sn, &cs);
        float cv[8], sv[8];
#pragma unroll
        for (int e = 0; e < 8; e++) {
            cv[e] = cs; sv[e] = sn;
            float t = cs * cd - sn * sd;
            sn = sn * cd + cs * sd;
            cs = t;
        }
        uint4 oc = make_uint4(pack_bf16(cv[0], cv[1]), pack_bf16(cv[2], cv[3]), pack_bf16(cv[4], cv[5]), pack_bf16(cv[6], cv[7]));
        uint4 os = make_uint4(pack_bf16(sv[0], sv[1]), pack_bf16(sv[2], sv[3]), pack_bf16(sv[4], sv[5]), pack_bf16(sv[6], sv[7]));
        sts128(a_cc, oc);
        sts128(a_cc + d_pi, os);
        sts128(a_cc + d_po, make_uint4(os.x ^ 0x80008000u, os.y ^ 0x80008000u, os.z ^ 0x80008000u, os.w ^ 0x80008000u));
        sts128(a_cc + d_pi + d_po, oc);
    }
}

__global__ void __launch_bounds__(NTHREADS, 1)
fused_kernel(const __grid_constant__ CUtensorMap tm_x, const __grid_constant__ CUtensorMap tm_bre,
             const __grid_constant__ CUtensorMap tm_bim, const __grid_constant__ CUtensorMap tm_cre,
             const __grid_constant__ CUtensorMap tm_cim, const __grid_constant__ CUtensorMap tm_col, const Params p) {
    extern __shared__ __align__(1024) uint8_t sm[];
    const uint32_t sb = s2u(sm);
    const int tid = threadIdx.x, b = blockIdx.x;
    const int c = b >> 3, r = b & 7;
    const int par = r & 1, pi_ = r >> 1, own = 4 * par + pi_;
    const int wg = __shfl_sync(~0u, tid >> 7, 0), w = __shfl_sync(~0u, (tid >> 5) & 3, 0), lane = tid & 31, g = lane >> 2, q = lane & 3;
    auto BAR = [&](int i) { return sb + SM_BAR + 8 * i; };
    unsigned* s_tgt = (unsigned*)(sm + SM_TGT);

    if (tid < NBARS) {
        int cnt = 1;
        if (tid >= B_EMPTY0 && tid < B_EMPTY0 + 4) cnt = 16;
        if (tid >= B_XEMPTY && tid < B_XEMPTY + 4) cnt = 24;
        if (tid == B_RFREE) cnt = 12;
        if (tid == B_HDONE || tid == B_WST) cnt = 2;
        if ((tid >= B_AEMPTY && tid < B_AEMPTY + 8) || tid == B_BFREE) cnt = 8;
        if (tid == B_AFREE) cnt = 4;
        mbar_init(BAR(tid), cnt);
        asm volatile("fence.mbarrier_init.release.cluster;" ::: "memory");
    }
    asm volatile("barrier.cluster.arrive.release.aligned;" ::: "memory");

    if (wg == 3) {
        asm volatile("setmaxnreg.dec.sync.aligned.u32 56;");
        if (w == 0 && lane < 6) {
            const CUtensorMap* tm = lane == 0 ? &tm_x : lane == 1 ? &tm_bre : lane == 2 ? &tm_bim : lane == 3 ? &tm_cre : lane == 4 ? &tm_cim : &tm_col;
            asm volatile("prefetch.tensormap [%0];" ::"l"(tm) : "memory");
        }
        __syncwarp();
        asm volatile("barrier.cluster.wait.acquire.aligned;" ::: "memory");
        if (w > 0) {
            if (w == 1) {
                float lr[3], li[3], ld[3];
#pragma unroll
                for (int k = 0; k < 3; k++) {
                    int ps = k < 2 ? 64 * r + 32 * k + lane : 32 * c + lane;
                    lr[k] = ldbf(p.lam_re + ps); li[k] = ldbf(p.lam_im + ps); ld[k] = ldbf(p.log_dt + ps);
                }
                if (lane < 6) s_tgt[lane] = ((ld_acquire(&g_bar[lane]) >> 7) + 1u) << 7;
#pragma unroll 1
                for (int k = 0; k < 3; k++) {
                    float a = k == 0 ? lr[0] : (k == 1 ? lr[1] : lr[2]), bq = k == 0 ? li[0] : (k == 1 ? li[1] : li[2]);
                    float dt = __bfloat162float(__float2bfloat16(expf(k == 0 ? ld[0] : (k == 1 ? ld[1] : ld[2]))));
                    float mag = expf(a * dt), t = bq * dt * 0.15915494309189535f, sn, cs;
                    t -= rintf(t);
                    sincospif(2.f * t, &sn, &cs);
                    float er = mag * cs, ei = mag * sn;
                    if (k < 2) {
                        *(float2*)(sm + SM_LAM + (32 * k + lane) * 8) = make_float2(er, ei);
                    } else {
                        er -= 1.f;
                        float inv = 1.f / (a * a + bq * bq);
                        *(float2*)(sm + SM_TAB + lane * 8) = make_float2((er * a + ei * bq) * inv, (ei * a - er * bq) * inv);
                    }
                }
                __syncwarp();
                bar_arrive(15, 160);
                if (lane == 0) mbar_arrive(BAR(B_SETUP), 1);
            }
            if (w > 1) bar_sync(0, 192);
            if (tid == 448) TX(14);
            if (w > 1) {
#pragma unroll
                for (int k = 0; k < 2; k++) {
                    const int cb = tid - 448 + 64 * k;
                    asm volatile("cp.async.bulk.global.shared::cta.bulk_group [%0], [%1], 128;" ::"l"(g_Wfrag + (uint32_t)(cb * 1024 + b * 8)),
                                 "r"(sb + SM_H + cb * 128) : "memory");
                }
                asm volatile("cp.async.bulk.commit_group;" ::: "memory");
                asm volatile("cp.async.bulk.wait_group 0;" ::: "memory");
                fence_async();
                __syncwarp();
                if (lane == 0) mbar_arrive(BAR(B_WST), 1);
                if (tid == 448) TX(15);
            }
#pragma unroll 1
            for (int i = tid - 448; i < 96 + 128 && w > 1; i += 64) {
                if (i < 96) g_P[(uint32_t)(b * 4 + i / 24) * 1024 + 640 + ((i % 24) >> 1) * 32 + 30 + (i & 1)] = make_uint4(0, 0, 0, 0);
                else g_Ebuf[b * 128 + i - 96] = make_float4(0.f, 0.f, 0.f, 0.f);
            }
            __syncwarp();
            if (w == 3) bar_arrive(11, 192);
            if (w == 2) {
                bar_sync(11, 192);
                if (lane == 0) { TX(7); red_release(&g_bar[4], 1);  }
            }
            if (w == 3) {
#pragma unroll 1
                for (int it = 0; it < 8; it++) {
                    const int m = 4 * c + (it >> 1), d = 64 * r + m, ch = lane + 32 * (it & 1);
                    float v[8];
#pragma unroll
                    for (int e = 0; e < 8; e++) {
                        int j = 8 * ch + e, f, ph;
                        dft_fp(j, f, ph);
                        int a = (d * f + ph) & 511;
                        a = a >= 256 ? a - 512 : a;
                        float wj = j == 0 ? 0.f : (j == 1 ? 1.f / 512.f : 2.f / 512.f);
                        v[e] = wj * __cosf((float)a * (6.283185307179586f / 512.f));
                    }
                    uint32_t off = (uint32_t)(64 + r * 8 + (ch >> 3)) * 8192 + (m >> 3) * 1024 + (ch & 7) * 128 + (m & 7) * 16;
                    *(uint4*)(g_E + off) = make_uint4(pack_bf16(v[0], v[1]), pack_bf16(v[2], v[3]), pack_bf16(v[4], v[5]), pack_bf16(v[6], v[7]));
                }
                __syncwarp();
                if (lane == 0) { fence_async(); red_release(&g_bar[6], 1); }
                return;
            }
            if (w == 2) {
#pragma unroll 1
                for (int it = 0; it < 4; it++) {
                    const int hf = it & 1;
                    __syncwarp();
                    if (hf == 0) bar_sync(13, 288); else bar_sync(6, 416);
                    if (lane == 0) {
                        const uint32_t src = sb + SM_HH + par * 32768 + hf * 16384;
                        bulk_s2peer(mapa(src, par ^ 1), src, 16384, mapa(BAR(hf ? B_HPEER1 : B_HPEER), par ^ 1));
                    }
                }
                return;
            }
            bar_sync(2, 288);
            if (lane == 0) {
                TX(5);
                fence_async();
                red_release(&g_bar[0], 1);
                TX(6);
            }
            __syncwarp();

            bar_sync(12, 160);
            if (lane == 0) {
                asm volatile("cp.async.bulk.global.shared::cta.bulk_group [%0], [%1], 8192;" ::"l"(g_A1 + (uint32_t)(((c >> 1) * 8 + r) * 16384 + (c & 1) * 8192)),
                             "r"(sb + SM_B1ST) : "memory");
                asm volatile("cp.async.bulk.commit_group;" ::: "memory");
                asm volatile("cp.async.bulk.wait_group 0;" ::: "memory");
                mbar_arrive(BAR(B_B1DONE), 1);
                fence_async();
                red_release(&g_bar[7], 1);
            }
#pragma unroll 1
            for (int layer = 0; layer < 2; layer++) {
                __syncwarp();
                bar_sync(5, 416);
                if (lane == 0) {
                    TX(0 + 8 * layer);
                    tma_store_5d(&tm_col, 32 * (b & 1), 0, b >> 1, 0, layer, sb + SM_RAW);
                    asm volatile("cp.reduce.async.bulk.global.shared::cta.bulk_group.add.f32 [%0], [%1], 8192;" ::"l"(g_ssqc + (layer * 16 + (b & 15)) * 2048),
                                 "r"(sb + SM_SSQ) : "memory");
                    asm volatile("cp.async.bulk.commit_group;" ::: "memory");
                    asm volatile("cp.async.bulk.wait_group 0;" ::: "memory");
                    TX(1 + 8 * layer);
                    fence_async();
                    red_release(&g_bar[1 + 2 * layer], 1);
                    TX(2 + 8 * layer);
                }
            }
        } else if (tid == 384) {
#pragma unroll 1
            for (int kb = 0; kb < 8; kb++) {
                uint32_t fb = BAR(B_FULL0 + kb);
                mbar_expect(fb, 16384);
                tma_5d_mc(sb + SM_A + 65536 + kb * 16384 + par * 8192, &tm_x, kb * 64, 0, 0, 8 * par, c, fb);
            }
#pragma unroll 1
            for (int k2 = 0; k2 < 8; k2++) {
                asm volatile("cp.async.bulk.prefetch.tensor.2d.L2.global [%0, {%1,%2}];" ::"l"(par ? &tm_bim : &tm_bre), "r"(k2 * 64), "r"(32 * c) : "memory");
                if ((k2 & 1) == par)
                    asm volatile("cp.async.bulk.prefetch.tensor.2d.L2.global [%0, {%1,%2}];" ::"l"((c & 1) ? &tm_cim : &tm_cre), "r"(64 * (c >> 1)), "r"(k2 * 64) : "memory");
            }
            mbar_wait(BAR(B_SETUP), 0);
#pragma unroll 1
            for (int layer = 0; layer < 2; layer++) {
                if (layer == 1) {
                    mbar_wait(BAR(B_AEMPTY + 6), 1);
                    mbar_expect(BAR(B_WRDY), 16384);
                    bulk_g2s(sb + SM_H + 16384, g_Wfrag + (uint32_t)b * 1024, 16384, BAR(B_WRDY));
                }
                wait_count(&g_bar[2 * layer], s_tgt[2 * layer]);
                TX(4 + 8 * layer);
                fence_async();
                mbar_expect(BAR(B_COL), 16384 + 8192);
                tma_5d(sb + SM_RAW, &tm_col, 32 * (b & 1), 0, b >> 1, 0, layer, BAR(B_COL));
                bulk_g2s(sb + SM_SSQ, g_ssq + layer * 2048, 8192, BAR(B_COL));
                if (layer == 0) {
                    wait_count(&g_bar[4], s_tgt[4]);
                    fence_async();
                    TX(16);
                    mbar_wait(BAR(B_B1DONE), 0);
                    TX(17);
                    mbar_expect(BAR(B_WRDY), 16384);
                    bulk_g2s(sb + SM_H + 16384, g_Wfrag + (uint32_t)b * 1024, 16384, BAR(B_WRDY));
                    wait_count(&g_bar[7], s_tgt[4]);
                    fence_async();
                }
                if (layer == 0) mbar_wait(BAR(B_AFREE), 0);
                mbar_wait(BAR(B_COL), layer);
#pragma unroll 1
                for (int s = 0; s < 8; s++) {
                    if (layer == 1) mbar_wait(BAR(B_AEMPTY + s), 1);
                    if (s >= 2) mbar_wait(BAR(B_AFULL + s - 2), 0);
                    mbar_expect(BAR(B_AFULL + s), 16384);
                    bulk_g2s(sb + SM_A + s * 16384, g_A1 + (uint32_t)(r * 8 + s) * 16384, 16384, BAR(B_AFULL + s));
                }
                if (layer == 1) wait_count(&g_bar[6], s_tgt[4]);
                wait_count(&g_bar[1 + 2 * layer], s_tgt[1 + 2 * layer]);
                TX(3 + 8 * layer);
                fence_async();
                const uint8_t* xsrc = g_X + (uint32_t)(layer * 16 + c) * 8 * 16384;
                const uint8_t* esrc = g_E + (uint32_t)(layer * 8 + own) * 8 * 8192;
                mbar_arrive(BAR(B_SSQ), 1);
                mbar_expect(BAR(B_HPEER), 16384);
                mbar_expect(BAR(B_HPEER1), 16384);
#pragma unroll 1
                for (int it = 0; it < 16; it++) {
                    if (it < 8) {
                        int st = it & 3, f = layer * 2 + (it >> 2);
                        if (f > 0) mbar_wait_cluster(BAR(B_XEMPTY + st), (f - 1) & 1);
                        mbar_expect(BAR(B_XFULL + st), 24576);
                        bulk_g2s_mc(sb + SM_X + st * 24576 + par * 8192, xsrc + (uint32_t)it * 16384 + par * 8192, 8192, BAR(B_XFULL + st));
                        bulk_g2s(sb + SM_X + st * 24576 + 16384, esrc + (uint32_t)it * 8192, 8192, BAR(B_XFULL + st));
                    }
                    if (it >= 8) {
                        if (it == 8) mbar_wait(BAR(B_AEMPTY + 5), 0);
                        int s = it - 8, tile = 4 * par + ((pi_ + 1 + (s >> 1)) & 3), sl = r ^ (s & 1);
                        mbar_wait(BAR(B_AEMPTY + s), 0);
                        uint32_t fb = BAR(B_AFULL + s), dst = sb + SM_A + s * 16384;
                        mbar_expect(fb, 16384);
                        if (layer == 1) {
                            tma_2d(dst, &tm_cre, 64 * sl, 64 * tile, fb);
                            tma_2d(dst + 8192, &tm_cim, 64 * sl, 64 * tile, fb);
                        } else {
                            bulk_g2s(dst, g_A2 + (uint32_t)(sl * 8 + tile) * 16384, 16384, fb);
                        }
                    }
                }
            }
        }
        return;
    }

    asm volatile("setmaxnreg.inc.sync.aligned.u32 152;");
    if (tid >= 96 && tid < 112) g_ssq[2048 + 16 * b + tid - 96] = 0.f;
    if (tid >= 128 && tid < 256) ((float4*)g_ssqc)[b * 128 + tid - 128] = make_float4(0.f, 0.f, 0.f, 0.f);
    TS(0);
    if (wg == 0) TC(30);
    {
        const int f = 32 * r + lane;
        float cd, sd;
        __sincosf((float)f * (6.283185307179586f / 512.f), &sd, &cd);
        const uint32_t dst = sb + SM_A + (lane >> 2) * 1024 + (lane & 3) * 32;
#pragma unroll 1
        for (int ch = tid >> 5; ch < 64; ch += 12) {
            int a = (8 * ch * f) & 511;
            a = a >= 256 ? a - 512 : a;
            float cs, sn;
            __sincosf((float)a * (6.283185307179586f / 512.f), &sn, &cs);
            float cv[8], sv[8];
#pragma unroll
            for (int e = 0; e < 8; e++) {
                cv[e] = cs; sv[e] = -sn;
                float t = cs * cd - sn * sd;
                sn = sn * cd + cs * sd;
                cs = t;
            }
            uint4 o1 = make_uint4(pack_bf16(sv[0], sv[1]), pack_bf16(sv[2], sv[3]), pack_bf16(sv[4], sv[5]), pack_bf16(sv[6], sv[7]));
            if (f == 0) o1 = make_uint4(0xbf803f80u, 0xbf803f80u, 0xbf803f80u, 0xbf803f80u);
            uint32_t a0 = dst + (ch >> 3) * 8192 + (ch & 7) * 128;
            sts128(a0, make_uint4(pack_bf16(cv[0], cv[1]), pack_bf16(cv[2], cv[3]), pack_bf16(cv[4], cv[5]), pack_bf16(cv[6], cv[7])));
            sts128(a0 + 16, o1);
        }
    }
    fence_async_smem();
    asm volatile("barrier.cluster.wait.acquire.aligned;" ::: "memory");
    bar_sync(10, 384);
    TS(1);
    if (wg < 2) {
        float acc[32];
        acc_def(acc);
        const int npos = 16 * r + 8 * wg + 2 * w;
        float sh0 = 0.f, sh1 = 0.f, s0 = 0.f, s1 = 0.f, q0 = 0.f, q1 = 0.f;
#pragma unroll 1
        for (int kb = 0; kb < 8; kb++) {
            uint32_t slot = sb + SM_A + 65536 + kb * 16384;
            mbar_wait(BAR(B_FULL0 + kb), 0);
            wg_fence();
#pragma unroll
            for (int ks = 0; ks < 4; ks++)
                wgmma_n64<0>(acc, desc_a(sb + SM_A + kb * 8192 + ks * 256), desc_k(slot + wg * 8192 + ks * 32), 1);
            wg_commit();
            {
                uint32_t v0 = lds32(slot + npos * 128 + lane * 4), v1 = lds32(slot + npos * 128 + 128 + lane * 4);
                if (kb == 0) { sh0 = __shfl_sync(~0u, bf_lo(v0), 0); sh1 = __shfl_sync(~0u, bf_lo(v1), 0); }
                float a = bf_lo(v0) - sh0, bq = bf_hi(v0) - sh0, cq = bf_lo(v1) - sh1, d = bf_hi(v1) - sh1;
                s0 += a + bq; q0 += a * a + bq * bq; s1 += cq + d; q1 += cq * cq + d * d;
            }
            wg_wait<1>();
            if (kb > 0 && kb <= 4 && lane == 0) { mbar_arrive(BAR(B_EMPTY0 + kb - 1), 1); mbar_arrive_remote(mapa(BAR(B_EMPTY0 + kb - 1), par ^ 1)); }
        }
#pragma unroll
        for (int o = 16; o; o >>= 1) {
            s0 += __shfl_xor_sync(~0u, s0, o); q0 += __shfl_xor_sync(~0u, q0, o);
            s1 += __shfl_xor_sync(~0u, s1, o); q1 += __shfl_xor_sync(~0u, q1, o);
        }
        if (lane == 0) *(float2*)(g_ssq + 128 * c + npos) = make_float2(fmaxf(q0 - s0 * s0 * (1.f / 512.f), 0.f), fmaxf(q1 - s1 * s1 * (1.f / 512.f), 0.f));
        wg_wait<0>();
        TS(2);
        uint8_t* dst = g_X + (uint32_t)((c * 8 + r) * 16384 + w * 4096 + wg * 1024 + g * 16 + 4 * q);
#pragma unroll
        for (int i = 0; i < 8; i++) {
            *(uint32_t*)(dst + i * 128) = pack_bf16(acc[4 * i], acc[4 * i + 1]);
            *(uint32_t*)(dst + 2048 + i * 128) = pack_bf16(acc[4 * i + 2], acc[4 * i + 3]);
        }
        bar_sync(2, 288);
        mbar_wait(BAR(B_SETUP), 0);
        TS(3);
    }

    if (wg == 2) {
        {
            const int cb = tid & 127;
            const int c0 = cb == 0 ? 256 : 2 * cb, c1 = 2 * cb + 1;
            uint32_t wf[2][16];
#pragma unroll
            for (int h = 0; h < 2; h++) {
                const int kq = 2 * b + h, k1 = kq >> 2, qq = kq & 3;
                const unsigned short* wr_ = (const unsigned short*)p.w_r + (k1 + 128 * qq) * 257;
                const unsigned short* wi_ = (const unsigned short*)p.w_i + (k1 + 128 * qq) * 257;
#pragma unroll
                for (int i = 0; i < 4; i++) {
                    int o = 512 * i * 257;
                    wf[h][2 * i] = (uint32_t)__ldg(wr_ + o + c0) | ((uint32_t)__ldg(wr_ + o + 64 * 257 + c0) << 16);
                    wf[h][2 * i + 1] = ((uint32_t)__ldg(wi_ + o + c0) | ((uint32_t)__ldg(wi_ + o + 64 * 257 + c0) << 16)) ^ 0x80008000u;
                    wf[h][8 + 2 * i] = (uint32_t)__ldg(wr_ + o + c1) | ((uint32_t)__ldg(wr_ + o + 64 * 257 + c1) << 16);
                    wf[h][8 + 2 * i + 1] = ((uint32_t)__ldg(wi_ + o + c1) | ((uint32_t)__ldg(wi_ + o + 64 * 257 + c1) << 16)) ^ 0x80008000u;
                }
            }
            uint4 p0 = __ldg((const uint4*)p.dskip + 2 * lane), p1 = __ldg((const uint4*)p.dskip + 2 * lane + 1);
            uint32_t u[8] = {p0.x, p0.y, p0.z, p0.w, p1.x, p1.y, p1.z, p1.w};
            int j = 64 * r + 4 * c + w, f, ph;
            dft_fp(j, f, ph);
            float s = 0.f;
            int idx = 16 * lane * f + ph;
#pragma unroll
            for (int i = 0; i < 16; i++) {
                int a = idx & 511;
                idx += f;
                a = a >= 256 ? a - 512 : a;
                s += ((i & 1) ? bf_hi(u[i >> 1]) : bf_lo(u[i >> 1])) * __cosf((float)a * (6.283185307179586f / 512.f));
            }
#pragma unroll
            for (int o = 16; o; o >>= 1) s += __shfl_xor_sync(~0u, s, o);
            if (lane == 0) g_Dh[j] = s;
#pragma unroll
            for (int h = 0; h < 2; h++)
#pragma unroll
                for (int i = 0; i < 4; i++)
                    sts128(sb + SM_H + cb * 128 + h * 64 + ((i ^ (b & 3)) << 4), make_uint4(wf[h][4 * i], wf[h][4 * i + 1], wf[h][4 * i + 2], wf[h][4 * i + 3]));
            fence_async_smem();
            bar_arrive(0, 192);
            bar_arrive(11, 192);
        }
        bar_sync(15, 160);
        float acc[32];
        acc_def(acc);
        if (tid == 256) {
#pragma unroll 1
            for (int s = 0; s < 4; s++) mbar_wait_cluster(BAR(B_EMPTY0 + s), 0);
            mbar_expect(BAR(B_FULLB), 65536);
#pragma unroll 1
            for (int k2 = 0; k2 < 8; k2++)
                tma_2d_mc(sb + SM_A + 65536 + k2 * 8192 + par * 4096, par ? &tm_bim : &tm_bre, k2 * 64, 32 * c, BAR(B_FULLB));
        }
        __syncwarp();
        mbar_wait(BAR(B_FULLB), 0);
        wg_fence();
#pragma unroll 1
        for (int kb = 0; kb < 8; kb++) {
#pragma unroll
            for (int ks = 0; ks < 4; ks++)
                wgmma_n64<0>(acc, desc_a(sb + SM_A + kb * 8192 + ks * 256), desc_k(sb + SM_A + 65536 + kb * 8192 + ks * 32), 1);
            wg_commit();
        }
        wg_wait<0>();
        if (lane == 0) { mbar_arrive(BAR(B_BFREE), 1); mbar_arrive_remote(mapa(BAR(B_BFREE), par ^ 1)); }
        if (tid == 256) {
            mbar_wait_cluster(BAR(B_BFREE), 0);
            mbar_expect(BAR(B_FULLC), 65536);
#pragma unroll 1
            for (int k2 = par; k2 < 8; k2 += 2)
                tma_2d_mc(sb + SM_A + 65536 + k2 * 8192, (c & 1) ? &tm_cim : &tm_cre, 64 * (c >> 1), k2 * 64, BAR(B_FULLC));
        }
        __syncwarp();
        {
            uint8_t* dst = sm + SM_B1ST + w * 256 + q * 32 + g * 2;
            const float wj0 = (r == 0 && w == 0 && g < 2) ? (g == 0 ? 0.f : 1.f / 512.f) : 2.f / 512.f;
#pragma unroll
            for (int i = 0; i < 4; i++) {
#pragma unroll
                for (int e = 0; e < 2; e++) {
                    float2 cf = *(const float2*)(sm + SM_TAB + (8 * i + 2 * q + e) * 8);
#pragma unroll
                    for (int h = 0; h < 2; h++) {
                        float wj = h == 0 ? wj0 : 2.f / 512.f;
                        float pr = acc[4 * i + 2 * h + e] * wj, pi = acc[16 + 4 * i + 2 * h + e] * wj;
                        uint8_t* d2 = dst + i * 2048 + h * 128 + e * 16;
                        *(__nv_bfloat16*)(d2) = __float2bfloat16(cf.x * pr - cf.y * pi);
                        *(__nv_bfloat16*)(d2 + 1024) = __float2bfloat16(cf.x * pi + cf.y * pr);
                    }
                }
            }
            fence_async_smem();
            bar_arrive(12, 160);
        }
        acc_def(acc);
        mbar_wait(BAR(B_FULLC), 0);
        wg_fence();
#pragma unroll 1
        for (int kb = 0; kb < 8; kb++) {
#pragma unroll
            for (int ks = 0; ks < 4; ks++)
                wgmma_n64<1>(acc, desc_a(sb + SM_A + kb * 8192 + ks * 256), desc_mn(sb + SM_A + 65536 + kb * 8192 + ks * 2048, 8192), 1);
            wg_commit();
        }
        wg_wait<0>();
        fence_async_smem();
        if (lane == 0) mbar_arrive(BAR(B_AFREE), 1);
        uint8_t* dst = g_A2 + (uint32_t)(((c >> 1) * 8 + r) * 16384 + (c & 1) * 8192 + w * 2048 + g * 16 + 4 * q);
#pragma unroll
        for (int i = 0; i < 8; i++) {
            *(uint32_t*)(dst + i * 128) = pack_bf16(acc[4 * i], acc[4 * i + 1]);
            *(uint32_t*)(dst + 1024 + i * 128) = pack_bf16(acc[4 * i + 2], acc[4 * i + 3]);
        }
        {
            const int m = 4 * c + w, jp = 64 * r + m;
            int fp, php;
            dft_fp(jp, fp, php);
            const __nv_bfloat16* dh = (const __nv_bfloat16*)(sm + SM_RSTD);
            if (tid == 256) wait_count(&g_bar[4], s_tgt[4]);
            bar_sync(3, 128);
            float4 d4 = __ldcg((const float4*)g_Dh + (tid - 256));
            *(uint2*)(sm + SM_RSTD + (tid - 256) * 8) = make_uint2(pack_bf16(d4.x, d4.y), pack_bf16(d4.z, d4.w));
            bar_sync(3, 128);
#pragma unroll 1
            for (int it = 0; it < 2; it++) {
                const int ch = lane + 32 * it;
                float v[8];
#pragma unroll
                for (int e = 0; e < 8; e++) {
                    int j = 8 * ch + e, f, ph;
                    dft_fp(j, f, ph);
                    float wj = j == 0 ? 0.f : (j == 1 ? 1.f / 512.f : 2.f / 512.f);
                    float gsum = 0.f;
#pragma unroll
                    for (int sgn = 0; sgn < 2; sgn++) {
                        int mm = (sgn ? f - fp : f + fp) & 511, pp = (sgn ? ph - php : ph + php) & 511;
                        if (mm > 256) { mm = 512 - mm; pp = (512 - pp) & 511; }
                        int odd = (pp >> 7) & 1;
                        float t = __bfloat162float(dh[mm == 256 ? 1 : 2 * mm + odd]);
                        if (odd && (mm & 255) == 0) t = 0.f;
                        gsum += (pp & 256) ? -t : t;
                    }
                    v[e] = 0.5f * wj * gsum;
                }
                uint32_t off = (uint32_t)(r * 8 + (ch >> 3)) * 8192 + (m >> 3) * 1024 + (ch & 7) * 128 + (m & 7) * 16;
                *(uint4*)(g_E + off) = make_uint4(pack_bf16(v[0], v[1]), pack_bf16(v[2], v[3]), pack_bf16(v[4], v[5]), pack_bf16(v[6], v[7]));
            }
        }
    }

#pragma unroll 1
    for (int layer = 0; layer < 2; layer++) {
        if (wg < 2) {
            const int n1 = 32 * wg + 8 * w + g;
            const int ct = n1 >> 2;
            gen_col_consts(sb, tid);
            uint32_t tr2[4], ti2[4], tn2[4];
#pragma unroll
            for (int i = 0; i < 4; i++) {
                float cr[2], ci[2];
#pragma unroll
                for (int e = 0; e < 2; e++) {
                    int a = (n1 * (8 * i + 2 * q + e)) & 2047;
                    a = a >= 1024 ? a - 2048 : a;
                    float ang = (float)a * (-6.283185307179586f / 2048.f);
                    cr[e] = __cosf(ang); ci[e] = __sinf(ang);
                }
                tr2[i] = pack_bf16(cr[0], cr[1]); ti2[i] = pack_bf16(ci[0], ci[1]); tn2[i] = ti2[i] ^ 0x80008000u;
            }
            mbar_wait(BAR(B_WST), 0);
            mbar_wait(BAR(B_COL), layer);
            TS(4 + 12 * layer);
            if (wg == 0) TC(0 + 10 * layer);
            const uint32_t rw0 = sb + SM_RAW + ct * 1024 + q * 64 + ((q >> 1) << 4) + (g & 3) * 4, rw1 = rw0 ^ 16;
            const int pos0 = 128 * ct + 8 * q + 2 * (g & 3);
            const int sw = b == 0 ? 1 : 0;
            uint32_t xr[4][4];
            const uint32_t st0 = sb + SM_H + (n1 >> 3) * 1024 + g * 16 + 4 * q;
#pragma unroll
            for (int i = 0; i < 4; i++) {
                float2 sq = *(const float2*)(sm + SM_SSQ + (pos0 + 32 * i) * 4);
                const uint32_t rs2 = pack_bf16(rsqrtf(sq.x * (1.f / 512.f) + 1e-5f), rsqrtf(sq.y * (1.f / 512.f) + 1e-5f));
#pragma unroll
                for (int jj = 0; jj < 4; jj++) {
                    const int K = jj ^ (2 * (i & 1));
                    uint32_t a = ((K & 1) ? rw1 : rw0) + i * 256 + (K & 2) * 16;
                    if (jj < 2) a ^= sw << 4;
                    uint32_t v = lds32(a);
                    xr[jj][i] = v;
                    uint32_t o = hmul2(v, rs2);
                    if (jj == 1 && sw) o = 0u;
                    sts32(st0 + (jj & 1) * 8192 + (4 * (jj >> 1) + i) * 128, o);
                }
            }
            if (wg == 0) TC(1 + 10 * layer);
            fence_async_smem();
            bar_sync(1, 256);
            float acc[32];
            const uint32_t s1a = sb + SM_X + wg * 16384, s2b = sb + SM_X + 32768;
            wg_fence();
#pragma unroll
            for (int ks = 0; ks < 8; ks++)
                wgmma_n64<1>(acc, desc_a(s1a + (ks >> 2) * 8192 + (ks & 3) * 256), desc_b<64>(sb + SM_H + ks * 2048), ks != 0);
            wg_commit();
            wg_wait<0>();
            if (wg == 0) TC(2 + 10 * layer);
            uint32_t are[2][4], aim[2][4];
#pragma unroll
            for (int col = 0; col < 2; col++) {
#pragma unroll
                for (int i = 0; i < 4; i++) {
                    int o = 4 * (4 * col + i);
                    uint32_t zr = pack_bf16(acc[o], acc[o + 1]), zi = pack_bf16(acc[o + 2], acc[o + 3]);
                    are[col][i] = hfma2(zr, tr2[i], hmul2(zi, tn2[i]));
                    aim[col][i] = hfma2(zr, ti2[i], hmul2(zi, tr2[i]));
                }
            }
            wg_fence();
#pragma unroll
            for (int ks = 0; ks < 2; ks++)
                wgmma_n64_rs(acc, are[0][2 * ks], are[1][2 * ks], are[0][2 * ks + 1], are[1][2 * ks + 1], desc_b<64>(s2b + ks * 2048), ks != 0);
#pragma unroll
            for (int ks = 0; ks < 2; ks++)
                wgmma_n64_rs(acc, aim[0][2 * ks], aim[1][2 * ks], aim[0][2 * ks + 1], aim[1][2 * ks + 1], desc_b<64>(s2b + 4096 + ks * 2048), 1);
            wg_commit();
            uint32_t wf[16];
            mbar_wait(BAR(B_WRDY), layer);
#pragma unroll
            for (int i = 0; i < 4; i++) {
                const int kq = n1 * 4 + q;
                uint4 v = *(const uint4*)(sm + SM_H + 16384 + kq * 64 + ((i ^ ((kq >> 1) & 3)) << 4));
                wf[4 * i] = v.x; wf[4 * i + 1] = v.y; wf[4 * i + 2] = v.z; wf[4 * i + 3] = v.w;
            }
            wg_wait<0>();
            if (wg == 0) TC(3 + 10 * layer);
#pragma unroll
            for (int col = 0; col < 2; col++) {
#pragma unroll
                for (int i = 0; i < 4; i++) {
                    uint32_t wr = wf[col * 8 + 2 * i], wn = wf[col * 8 + 2 * i + 1];
                    uint32_t zr = pack_bf16(acc[4 * i + 2 * col], acc[4 * i + 2 * col + 1]);
                    uint32_t zi = pack_bf16(acc[16 + 4 * i + 2 * col], acc[16 + 4 * i + 2 * col + 1]);
                    are[col][i] = hfma2(zr, wr, hmul2(zi, wn));
                    aim[col][i] = hfma2(zr, wn, hmul2(zi ^ 0x80008000u, wr));
                }
            }
            wg_fence();
#pragma unroll
            for (int ks = 0; ks < 2; ks++)
                wgmma_n64_rs(acc, are[0][2 * ks], are[1][2 * ks], are[0][2 * ks + 1], are[1][2 * ks + 1], desc_b<64>(s2b + ks * 2048), ks != 0);
#pragma unroll
            for (int ks = 0; ks < 2; ks++)
                wgmma_n64_rs(acc, aim[0][2 * ks], aim[1][2 * ks], aim[0][2 * ks + 1], aim[1][2 * ks + 1], desc_b<64>(s2b + 4096 + ks * 2048), 1);
            wg_commit();
            wg_wait<0>();
            if (wg == 0) TC(4 + 10 * layer);
            bar_sync(1, 256);
#pragma unroll
            for (int col = 0; col < 2; col++) {
#pragma unroll
                for (int i = 0; i < 4; i++) {
                    uint32_t zr = pack_bf16(acc[4 * i + 2 * col], acc[4 * i + 2 * col + 1]);
                    uint32_t zi = pack_bf16(acc[16 + 4 * i + 2 * col], acc[16 + 4 * i + 2 * col + 1]);
                    sts32(st0 + 16384 + (4 * col + i) * 128, hfma2(zr, tr2[i], hmul2(zi, tn2[i])));
                    sts32(st0 + 16384 + 8192 + (4 * col + i) * 128, hfma2(zr, ti2[i], hmul2(zi, tr2[i])));
                }
            }
            if (wg == 0) TC(5 + 10 * layer);
            fence_async_smem();
            bar_sync(1, 256);
            wg_fence();
#pragma unroll
            for (int ks = 0; ks < 8; ks++)
                wgmma_n64<1>(acc, desc_a(s1a + (ks >> 2) * 8192 + (ks & 3) * 256), desc_b<64>(sb + SM_H + 16384 + ks * 2048), ks != 0);
            wg_commit();
            wg_wait<0>();
            if (wg == 0) TC(6 + 10 * layer);
            const float sc = 1.f / 2048.f;
            const float sci0 = sw ? 0.f : -sc;
            const float wr0 = sw ? 0.5f : 1.f, wi0 = sw ? 0.f : 1.f;
#pragma unroll
            for (int i = 0; i < 4; i++) {
                float ss0, ss1;
#pragma unroll
                for (int col = 0; col < 2; col++) {
                    int o = 4 * (4 * col + i);
                    uint32_t vr = xr[2 * col][i], vi = xr[2 * col + 1][i];
                    float si = col == 0 ? sci0 : -sc;
                    uint32_t nr = pack_bf16(fmaf(acc[o], sc, bf_lo(vr)), fmaf(acc[o + 1], sc, bf_hi(vr)));
                    uint32_t ni = pack_bf16(fmaf(acc[o + 2], si, bf_lo(vi)), fmaf(acc[o + 3], si, bf_hi(vi)));
                    float a0 = bf_lo(nr), a1 = bf_hi(nr), b0 = bf_lo(ni), b1 = bf_hi(ni);
                    if (col == 0) {
                        ss0 = wr0 * a0 * a0 + wi0 * b0 * b0;
                        ss1 = wr0 * a1 * a1 + wi0 * b1 * b1;
                    } else {
                        ss0 += a0 * a0 + b0 * b0;
                        ss1 += a1 * a1 + b1 * b1;
                    }
                    const int K = (2 * col) ^ (2 * (i & 1));
                    uint32_t a = rw0 + i * 256 + K * 16;
                    if (col == 0) a ^= sw << 4;
                    sts32(a, nr);
                    sts32(a ^ 16, ni);
                }
                *(float2*)(sm + SM_SSQ + (pos0 + 32 * i) * 4) = make_float2(ss0 * (2.f / 512.f), ss1 * (2.f / 512.f));
            }
            fence_async_smem();
        }
        TS(5 + 12 * layer);
        if (wg == 0) TC(7 + 10 * layer);
        bar_arrive(5, 416);

        float acc[64];
        float* s_rstd = (float*)(sm + SM_RSTD);
        float* s_mean = (float*)(sm + SM_MEAN);
        const unsigned epoch = s_tgt[0] >> 7;
        const uint32_t pt3 = 1u + (2u * epoch + layer) % 3u;
        const uint32_t ptag = (pt3 & 1u) | ((pt3 & 2u) << 15);
        const uint64_t dstep = layer == 0 ? 16 : 2;
        auto c_desc = [&](int s) { return layer == 0 ? desc_a(sb + SM_A + s * 16384) : desc_k(sb + SM_A + s * 16384); };
        if (wg < 2) {
            const int prow = 32 * wg + 8 * w + g;
            const float2 l1 = *(const float2*)(sm + SM_LAM + prow * 8);
            float lr32 = l1.x, li32 = l1.y;
#pragma unroll
            for (int i = 0; i < 5; i++) { float t = lr32 * lr32 - li32 * li32; li32 = 2.f * lr32 * li32; lr32 = t; }
            float lr128 = lr32, li128 = li32;
#pragma unroll
            for (int i = 0; i < 2; i++) { float t = lr128 * lr128 - li128 * li128; li128 = 2.f * lr128 * li128; lr128 = t; }
            const float lr1 = l1.x, li1 = l1.y;
            acc_def(acc);
#pragma unroll 1
            for (int kb = 0; kb < 8; kb++) {
                mbar_wait(BAR(B_AFULL + kb), 0);
                mbar_wait(BAR(B_XFULL + (kb & 3)), (kb >> 2) & 1);
                wg_fence();
#pragma unroll
                for (int ks = 0; ks < 4; ks++)
                    wgmma_n128<1>(acc, desc_a(sb + SM_A + kb * 16384 + wg * 8192 + ks * 256),
                                  desc_b<128>(sb + SM_X + (kb & 3) * 24576 + ks * 4096), 1);
                wg_commit();
                wg_wait<1>();
                if (kb > 0 && lane == 0) {
                    mbar_arrive(BAR(B_AEMPTY + kb - 1), 1); mbar_arrive(BAR(B_XEMPTY + ((kb - 1) & 3)), 1);
                    mbar_arrive_remote(mapa(BAR(B_XEMPTY + ((kb - 1) & 3)), par ^ 1));
                }
            }
            wg_wait<0>();
            if (lane == 0) {
                mbar_arrive(BAR(B_AEMPTY + 7), 1); mbar_arrive(BAR(B_XEMPTY + 3), 1);
                mbar_arrive_remote(mapa(BAR(B_XEMPTY + 3), par ^ 1)); mbar_arrive_remote(mapa(BAR(B_RFREE), par ^ 1));
            }
            bar_arrive(14, 384);
            TS(6 + 12 * layer);
            bar_sync(4, 384);
            TS(7 + 12 * layer);
            float er = 0.f, ei = 0.f;
#pragma unroll
            for (int i = 0; i < 16; i++) {
                float2 rs = *(const float2*)(s_rstd + 128 + 8 * i + 2 * q);
                acc[4 * i] *= rs.x; acc[4 * i + 1] *= rs.y; acc[4 * i + 2] *= rs.x; acc[4 * i + 3] *= rs.y;
                float nr = lr1 * er - li1 * ei + acc[4 * i], ni = lr1 * ei + li1 * er + acc[4 * i + 2];
                er = lr1 * nr - li1 * ni + acc[4 * i + 1];
                ei = lr1 * ni + li1 * nr + acc[4 * i + 3];
            }
            float cr = 0.f, ci = 0.f, tr = 0.f, ti = 0.f;
#pragma unroll
            for (int qq = 0; qq < 4; qq++) {
                float xr_ = __shfl_sync(~0u, er, (lane & ~3) | qq), xi_ = __shfl_sync(~0u, ei, (lane & ~3) | qq);
                if (qq == q) { cr = tr; ci = ti; }
                float nr = lr32 * tr - li32 * ti + xr_, ni = lr32 * ti + li32 * tr + xi_;
                tr = nr; ti = ni;
            }
            float4* eb = g_Ebuf + (uint32_t)(layer * 16 * 512 + 64 * r + prow);
            if (q == 0 && c < 15) st_relaxed_f4(eb + c * 512, make_float4(tr, ti, __uint_as_float(epoch), 0.f));
            TS(8 + 12 * layer);
            float pr[4], pi[4];
            {
                unsigned n = 0;
                bool ok;
#pragma unroll 1
                do {
                    ok = true;
#pragma unroll
                    for (int k = 0; k < 4; k++) {
                        float4 v = make_float4(0.f, 0.f, __uint_as_float(epoch), 0.f);
                        if (4 * k + q < c) v = ld_relaxed_f4(eb + (4 * k + q) * 512);
                        pr[k] = v.x; pi[k] = v.y;
                        ok = ok && __float_as_uint(v.z) == epoch;
                    }
                } while (!ok && ++n < SPIN_LIMIT);
            }
            __syncwarp();
            TS(9 + 12 * layer);
            float hr = 0.f, hi = 0.f;
#pragma unroll
            for (int cc = 0; cc < 15; cc++) {
                float xr_ = __shfl_sync(~0u, pr[cc >> 2], (lane & ~3) | (cc & 3)), xi_ = __shfl_sync(~0u, pi[cc >> 2], (lane & ~3) | (cc & 3));
                if (cc < c) {
                    float nr = lr128 * hr - li128 * hi + xr_, ni = lr128 * hi + li128 * hr + xi_;
                    hr = nr; hi = ni;
                }
            }
#pragma unroll
            for (int qq = 0; qq < 3; qq++) {
                if (qq < q) { float nr = lr32 * hr - li32 * hi, ni = lr32 * hi + li32 * hr; hr = nr; hi = ni; }
            }
            er = cr + hr; ei = ci + hi;
            bar_sync(7, 384);
            mbar_wait_cluster(BAR(B_RFREE), layer);
            const uint32_t ha = sb + SM_HH + par * 32768 + (prow >> 3) * 1024 + g * 16 + 4 * q;
#pragma unroll
            for (int i = 0; i < 16; i++) {
                float nr = lr1 * er - li1 * ei + acc[4 * i], ni = lr1 * ei + li1 * er + acc[4 * i + 2];
                er = lr1 * nr - li1 * ni + acc[4 * i + 1];
                ei = lr1 * ni + li1 * nr + acc[4 * i + 3];
                sts32(ha + (i >> 3) * 16384 + (i & 7) * 128, pack_bf16(nr, er));
                sts32(ha + (i >> 3) * 16384 + 8192 + (i & 7) * 128, pack_bf16(ni, ei));
                if (i == 7) { fence_async_smem(); bar_arrive(13, 288); }
            }
            fence_async_smem();
            acc_def(acc);
            float acc2[32];
            acc_def(acc2);
            TS(10 + 12 * layer);
            bar_sync(6, 416);
            TS(11 + 12 * layer);
            float (&a0)[32] = *reinterpret_cast<float (*)[32]>(&acc[0]);
            float (&a1)[32] = *reinterpret_cast<float (*)[32]>(&acc[32]);
            auto tile_mma = [&](float (&d)[32], int u) {
#pragma unroll 1
                for (int k = 0; k < 2; k++) {
                    const uint32_t hb = sb + SM_HH + (par ^ k) * 32768 + wg * 16384;
                    if (k == 1) mbar_wait(BAR(wg ? B_HPEER1 : B_HPEER), layer);
                    mbar_wait(BAR(B_AFULL + 2 * u + k), 1);
                    const uint64_t da = c_desc(2 * u + k);
                    wg_fence();
#pragma unroll
                    for (int ks = 0; ks < 4; ks++) wgmma_n64s<1>(d, da + ks * dstep, desc_b<64>(hb + ks * 2048), 1);
#pragma unroll
                    for (int ks = 0; ks < 4; ks++) wgmma_n64s<-1>(d, da + 512 + ks * dstep, desc_b<64>(hb + 8192 + ks * 2048), 1);
                }
                wg_commit();
            };
            auto tile_ship = [&](float (&d)[32], int u) {
                uint4* dst = g_P + (uint32_t)(((c * 8 + 2 * ((pi_ + 1 + u) & 3) + par) * 4 + pi_) * 1024 + wg * 512 + (tid & 127));
#pragma unroll
                for (int i = 0; i < 4; i++)
                    dst[i * 128] = make_uint4((pack_bf16(d[8 * i], d[8 * i + 1]) & 0xfffefffeu) | ptag, pack_bf16(d[8 * i + 2], d[8 * i + 3]),
                                              pack_bf16(d[8 * i + 4], d[8 * i + 5]), pack_bf16(d[8 * i + 6], d[8 * i + 7]));
            };
            tile_mma(a0, 0);
            if ((tid & 127) == 0) mbar_arrive_remote(mapa(BAR(B_HDONE), par ^ 1));
            __syncwarp();
            tile_mma(a1, 1);
            wg_wait<1>();
            tile_ship(a0, 0);
            tile_mma(acc2, 2);
            bar_arrive(12, 384);
            wg_wait<1>();
            tile_ship(a1, 1);
            wg_wait<0>();
            tile_ship(acc2, 2);
            if (lane < 6) mbar_arrive(BAR(B_AEMPTY + lane), 1);
            TS(12 + 12 * layer);
        } else {
            const int t2 = tid - 256;
            const uint8_t* ximg = g_X + (uint32_t)layer * 16 * 8 * 16384;
            mbar_wait(BAR(B_SSQ), layer);
            TS(6 + 12 * layer);
            float sqv[16];
#pragma unroll
            for (int i = 0; i < 16; i++) sqv[i] = __ldcg(g_ssqc + (layer * 16 + i) * 2048 + 128 * c + t2);
            const unsigned short xm = __ldcg((const unsigned short*)(ximg + (uint32_t)(c * 8 * 16384 + (t2 >> 3) * 128 + (t2 & 7) * 2)));
            acc_def(acc);
#pragma unroll 1
            for (int kb = 0; kb < 8; kb++) {
                if (kb == 4) {
                    wg_wait<0>();
                    if (lane == 0) { mbar_arrive(BAR(B_XEMPTY + 3), 1); mbar_arrive_remote(mapa(BAR(B_XEMPTY + 3), par ^ 1)); }
                    float tot = 0.f;
#pragma unroll
                    for (int i = 0; i < 16; i++) tot += sqv[i];
                    float rs = rsqrtf(tot * (1.f / 512.f) + 1e-5f);
                    s_rstd[t2] = rs;
                    s_rstd[128 + t2] = 2.f * rs;
                    s_mean[t2] = layer == 0 ? 0.f : __uint_as_float((uint32_t)xm << 16) * (1.f / 512.f);
                    TS(7 + 12 * layer);
                    bar_arrive(4, 384);
                    bar_sync(14, 384);
                }
                mbar_wait(BAR(B_XFULL + (kb & 3)), (kb >> 2) & 1);
                wg_fence();
#pragma unroll
                for (int ks = 0; ks < 4; ks++)
                    wgmma_n128<1>(acc, desc_a(sb + SM_X + (kb & 3) * 24576 + 16384 + ks * 256), desc_b<128>(sb + SM_X + (kb & 3) * 24576 + ks * 4096), 1);
                wg_commit();
                wg_wait<1>();
                if ((kb & 3) != 0 && lane == 0) { mbar_arrive(BAR(B_XEMPTY + ((kb - 1) & 3)), 1); mbar_arrive_remote(mapa(BAR(B_XEMPTY + ((kb - 1) & 3)), par ^ 1)); }
            }
            wg_wait<0>();
            if (lane == 0) { mbar_arrive(BAR(B_XEMPTY + 3), 1); mbar_arrive_remote(mapa(BAR(B_XEMPTY + 3), par ^ 1)); mbar_arrive_remote(mapa(BAR(B_RFREE), par ^ 1)); }
            bar_arrive(7, 384);
            bar_sync(3, 128);
            TS(9 + 12 * layer);
            const int m0 = 16 * w + g;
            const uint32_t xoff = (uint32_t)((c * 8 + own) * 16384 + w * 4096 + g * 16 + 4 * q);
            if (layer == 0) {
                const uint8_t* xs = g_X + xoff;
#pragma unroll
                for (int i = 0; i < 16; i++) {
                    float2 rs = *(const float2*)(s_rstd + 8 * i + 2 * q);
                    uint32_t x0v = __ldcg((const uint32_t*)(xs + i * 128)), x1v = __ldcg((const uint32_t*)(xs + 2048 + i * 128));
                    acc[4 * i] = acc[4 * i] * rs.x + bf_lo(x0v);
                    acc[4 * i + 1] = acc[4 * i + 1] * rs.y + bf_hi(x0v);
                    acc[4 * i + 2] = acc[4 * i + 2] * rs.x + bf_lo(x1v);
                    acc[4 * i + 3] = acc[4 * i + 3] * rs.y + bf_hi(x1v);
                }
            } else {
                float d0 = ldbf(p.dskip + 64 * own + m0), d1 = ldbf(p.dskip + 64 * own + m0 + 8);
#pragma unroll
                for (int i = 0; i < 16; i++) {
                    float2 rs = *(const float2*)(s_rstd + 8 * i + 2 * q);
                    float2 mn = *(const float2*)(s_mean + 8 * i + 2 * q);
                    acc[4 * i] = acc[4 * i] * (1.f + rs.x * d0) + mn.x;
                    acc[4 * i + 1] = acc[4 * i + 1] * (1.f + rs.y * d0) + mn.y;
                    acc[4 * i + 2] = acc[4 * i + 2] * (1.f + rs.x * d1) + mn.x;
                    acc[4 * i + 3] = acc[4 * i + 3] * (1.f + rs.y * d1) + mn.y;
                }
            }
            TS(10 + 12 * layer);
            bar_sync(6, 416);
            TS(11 + 12 * layer);
            {
                float (&a0)[32] = *reinterpret_cast<float (*)[32]>(&acc[0]);
                float (&a1)[32] = *reinterpret_cast<float (*)[32]>(&acc[32]);
#pragma unroll 1
                for (int k = 0; k < 2; k++) {
                    const uint32_t hb = sb + SM_HH + (par ^ k) * 32768;
                    if (k == 1) {
                        mbar_wait(BAR(B_HPEER), layer);
                        mbar_wait(BAR(B_HPEER1), layer);
                        bar_sync(12, 384);
                    }
                    mbar_wait(BAR(B_AFULL + 6 + k), 1);
                    const uint64_t da = c_desc(6 + k);
                    wg_fence();
#pragma unroll
                    for (int ks = 0; ks < 4; ks++) {
                        wgmma_n64s<1>(a0, da + ks * dstep, desc_b<64>(hb + ks * 2048), 1);
                        wgmma_n64s<1>(a1, da + ks * dstep, desc_b<64>(hb + 16384 + ks * 2048), 1);
                    }
#pragma unroll
                    for (int ks = 0; ks < 4; ks++) {
                        wgmma_n64s<-1>(a0, da + 512 + ks * dstep, desc_b<64>(hb + 8192 + ks * 2048), 1);
                        wgmma_n64s<-1>(a1, da + 512 + ks * dstep, desc_b<64>(hb + 16384 + 8192 + ks * 2048), 1);
                    }
                    wg_commit();
                }
                wg_wait<0>();
            }
#pragma unroll
            for (int i = 0; i < 16; i++)
                *(float4*)(sm + SM_A + 6 * 16384 + i * 2048 + t2 * 16) = make_float4(acc[4 * i], acc[4 * i + 1], acc[4 * i + 2], acc[4 * i + 3]);
            TS(12 + 12 * layer);
        }
        {
            const int t = tid & 127;
            const int nch = wg == 2 ? 2 : 3;
            const uint4* pb = g_P + (uint32_t)((c * 8 + r) * 4 * 1024 + wg * 128 + t);
            uint4 v[3][3];
            unsigned n = 0;
#pragma unroll 1
            while (true) {
                if (lane == 31) {
#pragma unroll 1
                    while (true) {
                        uint32_t bad = 0;
#pragma unroll
                        for (int sx = 0; sx < 3; sx++) {
                            uint32_t t0;
                            asm volatile("ld.relaxed.gpu.global.u32 %0, [%1];" : "=r"(t0) : "l"(pb + ((pi_ + 1 + sx) & 3) * 1024 + (nch - 1) * 384) : "memory");
                            bad |= t0 ^ ptag;
                        }
                        if (!(bad & 0x00010001u) || ++n >= SPIN_LIMIT) break;
                    }
                }
                __syncwarp();
                uint32_t bad = 0;
#pragma unroll
                for (int k = 0; k < 3; k++)
#pragma unroll
                    for (int sx = 0; sx < 3; sx++) {
                        v[k][sx] = make_uint4(ptag, 0, 0, 0);
                        if (k < nch) v[k][sx] = ld_relaxed_u4(pb + ((pi_ + 1 + sx) & 3) * 1024 + k * 384);
                        bad |= v[k][sx].x ^ ptag;
                    }
                if (!__any_sync(~0u, bad & 0x00010001u) || ++n >= SPIN_LIMIT) break;
            }
            bar_sync(8, 384);
            TS(13 + 12 * layer);
            const int m0 = 16 * w + g;
            const float w0 = (own == 0 && m0 < 2) ? (m0 == 0 ? 0.f : 0.5f) : 1.f;
#pragma unroll
            for (int k = 0; k < 3; k++) {
                if (k < nch) {
                    const int i = wg + 3 * k;
                    float4 a = *(const float4*)(sm + SM_A + 6 * 16384 + (2 * i) * 2048 + t * 16);
                    float4 bq = *(const float4*)(sm + SM_A + 6 * 16384 + (2 * i + 1) * 2048 + t * 16);
#pragma unroll
                    for (int sx = 0; sx < 3; sx++) {
                        a.x += bf_lo(v[k][sx].x); a.y += bf_hi(v[k][sx].x); a.z += bf_lo(v[k][sx].y); a.w += bf_hi(v[k][sx].y);
                        bq.x += bf_lo(v[k][sx].z); bq.y += bf_hi(v[k][sx].z); bq.z += bf_lo(v[k][sx].w); bq.w += bf_hi(v[k][sx].w);
                    }
                    if (layer == 0) {
                        uint8_t* xd = g_X + (uint32_t)((16 * 8 + c * 8 + own) * 16384 + w * 4096 + g * 16 + 4 * q + i * 256);
                        uint32_t v0 = pack_bf16(a.x, a.y), v1 = pack_bf16(a.z, a.w), v2 = pack_bf16(bq.x, bq.y), v3 = pack_bf16(bq.z, bq.w);
                        *(uint32_t*)(xd) = v0; *(uint32_t*)(xd + 2048) = v1; *(uint32_t*)(xd + 128) = v2; *(uint32_t*)(xd + 2048 + 128) = v3;
                        float sq[4];
                        sq[0] = w0 * bf_lo(v0) * bf_lo(v0) + bf_lo(v1) * bf_lo(v1);
                        sq[1] = w0 * bf_hi(v0) * bf_hi(v0) + bf_hi(v1) * bf_hi(v1);
                        sq[2] = w0 * bf_lo(v2) * bf_lo(v2) + bf_lo(v3) * bf_lo(v3);
                        sq[3] = w0 * bf_hi(v2) * bf_hi(v2) + bf_hi(v3) * bf_hi(v3);
                        float u0 = (g & 1) ? sq[2] : sq[0], u1 = (g & 1) ? sq[3] : sq[1];
                        u0 += __shfl_xor_sync(~0u, (g & 1) ? sq[0] : sq[2], 4);
                        u1 += __shfl_xor_sync(~0u, (g & 1) ? sq[1] : sq[3], 4);
                        float z = (g & 2) ? u1 : u0;
                        z += __shfl_xor_sync(~0u, (g & 2) ? u0 : u1, 8);
                        z += __shfl_xor_sync(~0u, z, 16);
                        if (g < 4) atomicAdd(s_mean + 16 * i + 8 * (g & 1) + 2 * q + (g >> 1), z);
                    } else {
                        float* o = p.out + (uint32_t)((128 * c + 32 * q + 4 * i) * 512 + 64 * own + m0);
                        o[0] = a.x; o[512] = a.y; o[8] = a.z; o[512 + 8] = a.w;
                        o[1024] = bq.x; o[1536] = bq.y; o[1024 + 8] = bq.z; o[1536 + 8] = bq.w;
                    }
                }
            }
            if (wg < 2) mbar_wait_cluster(BAR(B_HDONE), layer);
            if (layer == 0) {
                fence_async_smem();
                bar_sync(9, 384);
                TS(14 + 12 * layer);
                if (wg == 2) {
                    atomicAdd(g_ssq + 2048 + 128 * c + t, s_mean[t] * (2.f / 512.f));
                    bar_sync(3, 128);
                    if (lane == 0) { mbar_arrive(BAR(B_AEMPTY + 6), 2); mbar_arrive(BAR(B_AEMPTY + 7), 2); }
                    if (t == 0) { fence_async(); red_release(&g_bar[2], 1); }
                }
            }
        }
        TS(15 + 12 * layer);
        if (wg == 0) TC(31);
    }
}

typedef CUresult (*EncFn)(CUtensorMap*, CUtensorMapDataType, cuuint32_t, void*, const cuuint64_t*, const cuuint64_t*,
                          const cuuint32_t*, const cuuint32_t*, CUtensorMapInterleave, CUtensorMapSwizzle,
                          CUtensorMapL2promotion, CUtensorMapFloatOOBfill);

void launch_impl(void* const* d_in, void* d_out, int stop) {
    static EncFn enc = nullptr;
    if (!enc) {
        void* fn = nullptr;
        cudaDriverEntryPointQueryResult qr;
        cudaGetDriverEntryPoint("cuTensorMapEncodeTiled", &fn, cudaEnableDefault, &qr);
        enc = (EncFn)fn;
        cudaFuncSetAttribute(fused_kernel, cudaFuncAttributeMaxDynamicSharedMemorySize, SM_TOTAL);
    }
    CUtensorMap tx, tbr, tbi, tcr, tci, tcol;
    {
        void* gx = nullptr;
        cudaGetSymbolAddress(&gx, g_X);
        cuuint64_t gd[5] = {64, 16, 64, 16, 2};
        cuuint64_t gs[4] = {128, 2048, 128 * 1024, 2048 * 1024};
        cuuint32_t bx[5] = {32, 16, 1, 16, 1};
        cuuint32_t es[5] = {1, 1, 1, 1, 1};
        enc(&tcol, CU_TENSOR_MAP_DATA_TYPE_BFLOAT16, 5, gx, gd, gs, bx, es, CU_TENSOR_MAP_INTERLEAVE_NONE,
            CU_TENSOR_MAP_SWIZZLE_64B, CU_TENSOR_MAP_L2_PROMOTION_NONE, CU_TENSOR_MAP_FLOAT_OOB_FILL_NONE);
    }
    {
        cuuint64_t gd[5] = {512, 2, 4, 16, 16};
        cuuint64_t gs[4] = {1024, 32 * 1024, 2 * 1024, 128 * 1024};
        cuuint32_t bx[5] = {64, 2, 4, 8, 1};
        cuuint32_t es[5] = {1, 1, 1, 1, 1};
        enc(&tx, CU_TENSOR_MAP_DATA_TYPE_BFLOAT16, 5, d_in[0], gd, gs, bx, es, CU_TENSOR_MAP_INTERLEAVE_NONE,
            CU_TENSOR_MAP_SWIZZLE_128B, CU_TENSOR_MAP_L2_PROMOTION_L2_128B, CU_TENSOR_MAP_FLOAT_OOB_FILL_NONE);
    }
    auto mk2 = [&](CUtensorMap* m, void* ptr, cuuint32_t rows) {
        cuuint64_t gd[2] = {512, 512};
        cuuint64_t gs[1] = {1024};
        cuuint32_t bx[2] = {64, rows};
        cuuint32_t es[2] = {1, 1};
        enc(m, CU_TENSOR_MAP_DATA_TYPE_BFLOAT16, 2, ptr, gd, gs, bx, es, CU_TENSOR_MAP_INTERLEAVE_NONE,
            CU_TENSOR_MAP_SWIZZLE_128B, CU_TENSOR_MAP_L2_PROMOTION_L2_128B, CU_TENSOR_MAP_FLOAT_OOB_FILL_NONE);
    };
    mk2(&tbr, d_in[6], 32);
    mk2(&tbi, d_in[7], 32);
    mk2(&tcr, d_in[8], 64);
    mk2(&tci, d_in[9], 64);
    Params p;
    p.x0 = (const __nv_bfloat16*)d_in[0];
    p.w_r = (const __nv_bfloat16*)d_in[1];
    p.w_i = (const __nv_bfloat16*)d_in[2];
    p.lam_re = (const __nv_bfloat16*)d_in[4];
    p.lam_im = (const __nv_bfloat16*)d_in[5];
    p.log_dt = (const __nv_bfloat16*)d_in[10];
    p.dskip = (const __nv_bfloat16*)d_in[11];
    p.out = (float*)d_out;
    p.stop = stop;
    cudaLaunchConfig_t cfg = {};
    cfg.gridDim = dim3(NCTA); cfg.blockDim = dim3(NTHREADS); cfg.dynamicSmemBytes = SM_TOTAL; cfg.stream = cudaStreamPerThread;
    cudaLaunchAttribute at[1];
    at[0].id = cudaLaunchAttributeClusterDimension;
    at[0].val.clusterDim.x = 2; at[0].val.clusterDim.y = 1; at[0].val.clusterDim.z = 1;
    cfg.attrs = at; cfg.numAttrs = 1;
    cudaLaunchKernelEx(&cfg, fused_kernel, tx, tbr, tbi, tcr, tci, tcol, p);
}

}

extern "C" void kernel_launch(void* const* d_in, const int* in_sizes, int n_in, void* d_out, int out_size) {
    (void)in_sizes; (void)n_in; (void)out_size;
    launch_impl(d_in, d_out, 100);
}
```

```cpp
#include <cuda_runtime.h>
#include <cuda_bf16.h>
#include <cuda.h>
#include <stdint.h>

namespace {

constexpr int NCTA = 128;
constexpr int NTHREADS = 512;
constexpr int SM_A = 0;
constexpr int SM_X = 131072;
constexpr int SM_H = 196608;
constexpr int SM_HH = SM_X + 32768;
constexpr int SM_M = 229376;
constexpr int SM_TOTAL = 232448;
constexpr int SM_BAR = SM_M;
constexpr int SM_TGT = SM_M + 400;
constexpr int SM_LAM = SM_M + 424;
constexpr int SM_TAB = SM_M + 944;
constexpr int SM_RSTD = SM_M + 1920;
constexpr int SM_MEAN = SM_TAB;
constexpr int SM_T64 = SM_M + 2944;
constexpr int SM_B1ST = SM_H;
constexpr int SM_RAW = SM_X + 40960;
constexpr int SM_SSQ = SM_X + 57344;
constexpr int B_FULL0 = 0;
constexpr int B_EMPTY0 = 8;
constexpr int B_FULLC = 12;
constexpr int B_AFULL = 13;
constexpr int B_AEMPTY = 21;
constexpr int B_XFULL = 29;
constexpr int B_XEMPTY = 33;
constexpr int B_AFREE = 37;
constexpr int B_COL = 38;
constexpr int B_SSQ = 39;
constexpr int B_HPEER = 40;
constexpr int B_RFREE = 41;
constexpr int B_HDONE = 42;
constexpr int B_WRDY = 43;
constexpr int B_HPEER1 = 44;
constexpr int B_FULLB = 45;
constexpr int B_BFREE = 46;
constexpr int B_SETUP = 47;
constexpr int B_B1DONE = 48;
constexpr int B_WST = 49;
constexpr int NBARS = 50;

__device__ __align__(1024) uint8_t g_X[2 * 16 * 8 * 16384];
__device__ __align__(1024) uint8_t g_A1[8 * 8 * 16384];
__device__ __align__(1024) uint8_t g_A2[8 * 8 * 16384];
__device__ __align__(1024) uint8_t g_E[2 * 8 * 8 * 8192];
__device__ __align__(16) float g_ssq[2 * 2048];
__device__ __align__(16) float g_ssqc[2 * 16 * 2048];
__device__ __align__(16) float g_Dh[512];
__device__ __align__(16) uint4 g_Wfrag[128 * 4 * 256];
__device__ __align__(16) float4 g_Ebuf[2 * 16 * 512];
__device__ __align__(16) uint4 g_P[16 * 8 * 4 * 1024];
__device__ unsigned g_bar[8];
__device__ unsigned g_err;
#define TX(i)
#define TQ(i)
#define TS(i)
#define TC(i)

constexpr unsigned SPIN_LIMIT = 1u << 22;

__device__ __forceinline__ uint32_t s2u(const void* p) { return (uint32_t)__cvta_generic_to_shared(p); }
__device__ __forceinline__ void mbar_init(uint32_t a, uint32_t c) {
    asm volatile("mbarrier.init.shared::cta.b64 [%0], %1;" ::"r"(a), "r"(c) : "memory");
}
__device__ __forceinline__ void mbar_expect(uint32_t a, uint32_t bytes) {
    asm volatile("mbarrier.arrive.expect_tx.shared::cta.b64 _, [%0], %1;" ::"r"(a), "r"(bytes) : "memory");
}
__device__ __forceinline__ void mbar_arrive(uint32_t a, uint32_t cnt) {
    asm volatile("mbarrier.arrive.shared::cta.b64 _, [%0], %1;" ::"r"(a), "r"(cnt) : "memory");
}
__device__ __forceinline__ bool mbar_try(uint32_t a, uint32_t parity) {
    uint32_t ok;
    asm volatile("{\n.reg .pred p;\nmbarrier.try_wait.parity.shared::cta.b64 p, [%1], %2;\nselp.u32 %0, 1, 0, p;\n}"
                 : "=r"(ok) : "r"(a), "r"(parity) : "memory");
    return ok != 0;
}
__device__ __forceinline__ void mbar_wait(uint32_t a, uint32_t parity) {
    asm volatile("{\n.reg .pred p, q;\n.reg .u32 n;\nmov.u32 n, 0;\n"
                 "W_%=:\nmbarrier.try_wait.parity.shared::cta.b64 p, [%0], %1;\n@p bra D_%=;\n"
                 "add.u32 n, n, 1;\nsetp.lt.u32 q, n, 4194304;\n@q bra W_%=;\nD_%=:\n}" ::"r"(a), "r"(parity) : "memory");
}
__device__ __forceinline__ void bulk_g2s(uint32_t dst, const void* src, uint32_t bytes, uint32_t bar) {
    asm volatile("cp.async.bulk.shared::cluster.global.mbarrier::complete_tx::bytes [%0], [%1], %2, [%3];" ::"r"(dst),
                 "l"(src), "r"(bytes), "r"(bar) : "memory");
}
__device__ __forceinline__ void tma_2d(uint32_t dst, const CUtensorMap* m, int c0, int c1, uint32_t bar) {
    asm volatile("cp.async.bulk.tensor.2d.shared::cluster.global.mbarrier::complete_tx::bytes [%0], [%1, {%3,%4}], [%2];" ::"r"(dst),
                 "l"(m), "r"(bar), "r"(c0), "r"(c1) : "memory");
}
__device__ __forceinline__ void tma_5d(uint32_t dst, const CUtensorMap* m, int c0, int c1, int c2, int c3, int c4, uint32_t bar) {
    asm volatile("cp.async.bulk.tensor.5d.shared::cluster.global.mbarrier::complete_tx::bytes [%0], [%1, {%3,%4,%5,%6,%7}], [%2];" ::"r"(dst),
                 "l"(m), "r"(bar), "r"(c0), "r"(c1), "r"(c2), "r"(c3), "r"(c4) : "memory");
}
__device__ __forceinline__ void tma_2d_mc(uint32_t dst, const CUtensorMap* m, int c0, int c1, uint32_t bar) {
    asm volatile("cp.async.bulk.tensor.2d.shared::cluster.global.mbarrier::complete_tx::bytes.multicast::cluster [%0], [%1, {%3,%4}], [%2], %5;" ::"r"(dst),
                 "l"(m), "r"(bar), "r"(c0), "r"(c1), "h"((unsigned short)3) : "memory");
}
__device__ __forceinline__ void tma_5d_mc(uint32_t dst, const CUtensorMap* m, int c0, int c1, int c2, int c3, int c4, uint32_t bar) {
    asm volatile("cp.async.bulk.tensor.5d.shared::cluster.global.mbarrier::complete_tx::bytes.multicast::cluster [%0], [%1, {%3,%4,%5,%6,%7}], [%2], %8;" ::"r"(dst),
                 "l"(m), "r"(bar), "r"(c0), "r"(c1), "r"(c2), "r"(c3), "r"(c4), "h"((unsigned short)3) : "memory");
}
__device__ __forceinline__ void bulk_g2s_mc(uint32_t dst, const void* src, uint32_t bytes, uint32_t bar) {
    asm volatile("cp.async.bulk.shared::cluster.global.mbarrier::complete_tx::bytes.multicast::cluster [%0], [%1], %2, [%3], %4;" ::"r"(dst),
                 "l"(src), "r"(bytes), "r"(bar), "h"((unsigned short)3) : "memory");
}
__device__ __forceinline__ void tma_store_5d(const CUtensorMap* m, int c0, int c1, int c2, int c3, int c4, uint32_t src) {
    asm volatile("cp.async.bulk.tensor.5d.global.shared::cta.bulk_group [%0, {%2,%3,%4,%5,%6}], [%1];" ::"l"(m), "r"(src),
                 "r"(c0), "r"(c1), "r"(c2), "r"(c3), "r"(c4) : "memory");
}
__device__ __forceinline__ uint32_t lds32(uint32_t a) { uint32_t v; asm volatile("ld.shared.u32 %0, [%1];" : "=r"(v) : "r"(a) : "memory"); return v; }
__device__ __forceinline__ uint4 ld_relaxed_u4(const uint4* p) {
    uint4 v;
    asm volatile("ld.relaxed.gpu.global.v4.u32 {%0,%1,%2,%3}, [%4];" : "=r"(v.x), "=r"(v.y), "=r"(v.z), "=r"(v.w) : "l"(p) : "memory");
    return v;
}
__device__ __forceinline__ void fence_async() { asm volatile("fence.proxy.async.global;" ::: "memory"); }
__device__ __forceinline__ void red_relaxed(unsigned* p, unsigned v) {
    asm volatile("red.relaxed.gpu.global.add.u32 [%0], %1;" ::"l"(p), "r"(v) : "memory");
}
__device__ __forceinline__ uint32_t mapa(uint32_t a, uint32_t rank) {
    uint32_t d;
    asm("mapa.shared::cluster.u32 %0, %1, %2;" : "=r"(d) : "r"(a), "r"(rank));
    return d;
}
__device__ __forceinline__ void mbar_arrive_remote(uint32_t ra) {
    asm volatile("mbarrier.arrive.relaxed.cluster.shared::cluster.b64 _, [%0];" ::"r"(ra) : "memory");
}
__device__ __forceinline__ void mbar_wait_cluster(uint32_t a, uint32_t parity) {
    asm volatile("{\n.reg .pred p, q;\n.reg .u32 n;\nmov.u32 n, 0;\n"
                 "W_%=:\nmbarrier.try_wait.parity.acquire.cluster.shared::cta.b64 p, [%0], %1;\n@p bra D_%=;\n"
                 "add.u32 n, n, 1;\nsetp.lt.u32 q, n, 4194304;\n@q bra W_%=;\nD_%=:\n}" ::"r"(a), "r"(parity) : "memory");
}
__device__ __forceinline__ void bulk_s2peer(uint32_t rdst, uint32_t src, uint32_t bytes, uint32_t rbar) {
    asm volatile("cp.async.bulk.shared::cluster.shared::cta.mbarrier::complete_tx::bytes [%0], [%1], %2, [%3];" ::"r"(rdst),
                 "r"(src), "r"(bytes), "r"(rbar) : "memory");
}
__device__ __forceinline__ void fence_async_smem() { asm volatile("fence.proxy.async.shared::cta;" ::: "memory"); }
__device__ __forceinline__ void wg_fence() { asm volatile("wgmma.fence.sync.aligned;" ::: "memory"); }
__device__ __forceinline__ void wg_commit() { asm volatile("wgmma.commit_group.sync.aligned;" ::: "memory"); }
template <int N> __device__ __forceinline__ void wg_wait() { asm volatile("wgmma.wait_group.sync.aligned %0;" ::"n"(N) : "memory"); }
__device__ __forceinline__ void bar_sync(int id, int n) { asm volatile("bar.sync %0, %1;" ::"r"(id), "r"(n) : "memory"); }
__device__ __forceinline__ void bar_arrive(int id, int n) { asm volatile("bar.arrive %0, %1;" ::"r"(id), "r"(n) : "memory"); }
__device__ __forceinline__ unsigned ld_acquire(const unsigned* p) {
    unsigned v;
    asm volatile("ld.acquire.gpu.global.u32 %0, [%1];" : "=r"(v) : "l"(p) : "memory");
    return v;
}
__device__ __forceinline__ void red_release(unsigned* p, unsigned v) {
    asm volatile("red.release.gpu.global.add.u32 [%0], %1;" ::"l"(p), "r"(v) : "memory");
}
__device__ __forceinline__ void wait_count(const unsigned* p, unsigned target) {
    unsigned n = 0;
#pragma unroll 1
    while ((int)(ld_acquire(p) - target) < 0 && ++n < SPIN_LIMIT) {}
}
__device__ __forceinline__ float4 ld_relaxed_f4(const float4* p) {
    float4 v;
    asm volatile("ld.relaxed.gpu.global.v4.f32 {%0,%1,%2,%3}, [%4];" : "=f"(v.x), "=f"(v.y), "=f"(v.z), "=f"(v.w) : "l"(p) : "memory");
    return v;
}
__device__ __forceinline__ void st_relaxed_f4(float4* p, float4 v) {
    asm volatile("st.relaxed.gpu.global.v4.f32 [%0], {%1,%2,%3,%4};" ::"l"(p), "f"(v.x), "f"(v.y), "f"(v.z), "f"(v.w) : "memory");
}
__device__ __forceinline__ uint32_t pack_bf16(float lo, float hi) {
    uint32_t r;
    asm("cvt.rn.bf16x2.f32 %0, %1, %2;" : "=r"(r) : "f"(hi), "f"(lo));
    return r;
}
__device__ __forceinline__ uint32_t hmul2(uint32_t a, uint32_t b) {
    uint32_t r;
    asm("mul.rn.bf16x2 %0, %1, %2;" : "=r"(r) : "r"(a), "r"(b));
    return r;
}
__device__ __forceinline__ uint32_t hfma2(uint32_t a, uint32_t b, uint32_t c) {
    uint32_t r;
    asm("fma.rn.bf16x2 %0, %1, %2, %3;" : "=r"(r) : "r"(a), "r"(b), "r"(c));
    return r;
}
__device__ __forceinline__ float bf_lo(uint32_t v) { return __uint_as_float(v << 16); }
__device__ __forceinline__ float bf_hi(uint32_t v) { return __uint_as_float(v & 0xffff0000u); }
__device__ __forceinline__ void sts32(uint32_t a, uint32_t v) { asm volatile("st.shared.u32 [%0], %1;" ::"r"(a), "r"(v) : "memory"); }
__device__ __forceinline__ void sts128(uint32_t a, uint4 v) {
    asm volatile("st.shared.v4.u32 [%0], {%1,%2,%3,%4};" ::"r"(a), "r"(v.x), "r"(v.y), "r"(v.z), "r"(v.w) : "memory");
}

__device__ __forceinline__ uint64_t desc_ni(uint32_t addr, uint32_t lbo, uint32_t sbo) {
    return (uint64_t)((addr & 0x3FFFF) >> 4) | ((uint64_t)(lbo >> 4) << 16) | ((uint64_t)(sbo >> 4) << 32);
}
__device__ __forceinline__ uint64_t desc_a(uint32_t addr) { return desc_ni(addr, 128, 1024); }
template <int N> __device__ __forceinline__ uint64_t desc_b(uint32_t addr) { return desc_ni(addr, 16 * N, 128); }
__device__ __forceinline__ uint64_t desc_k(uint32_t addr) {
    return (uint64_t)((addr & 0x3FFFF) >> 4) | (1ull << 16) | (64ull << 32) | (1ull << 62);
}
__device__ __forceinline__ uint64_t desc_mn(uint32_t addr, uint32_t lbo) {
    return (uint64_t)((addr & 0x3FFFF) >> 4) | ((uint64_t)(lbo >> 4) << 16) | (64ull << 32) | (1ull << 62);
}

#define ACC8(d, o) "+f"(d[o + 0]), "+f"(d[o + 1]), "+f"(d[o + 2]), "+f"(d[o + 3]), "+f"(d[o + 4]), "+f"(d[o + 5]), "+f"(d[o + 6]), "+f"(d[o + 7])
template <int TB, int SA = 1>
__device__ __forceinline__ void wgmma_n128(float (&d)[64], uint64_t da, uint64_t db, int sd) {
    asm volatile(
        "{\n.reg .pred p;\nsetp.ne.b32 p, %66, 0;\n"
        "wgmma.mma_async.sync.aligned.m64n128k16.f32.bf16.bf16 "
        "{%0,%1,%2,%3,%4,%5,%6,%7,%8,%9,%10,%11,%12,%13,%14,%15,%16,%17,%18,%19,%20,%21,%22,%23,%24,%25,%26,%27,%28,%29,%30,%31,"
        "%32,%33,%34,%35,%36,%37,%38,%39,%40,%41,%42,%43,%44,%45,%46,%47,%48,%49,%50,%51,%52,%53,%54,%55,%56,%57,%58,%59,%60,%61,%62,%63},"
        " %64, %65, p, %68, 1, 0, %67;\n}"
        : ACC8(d, 0), ACC8(d, 8), ACC8(d, 16), ACC8(d, 24), ACC8(d, 32), ACC8(d, 40), ACC8(d, 48), ACC8(d, 56)
        : "l"(da), "l"(db), "r"(sd), "n"(TB), "n"(SA));
}
template <int N> __device__ __forceinline__ void acc_def(float (&d)[N]) {
#pragma unroll
    for (int i = 0; i < N; i++) d[i] = 0.f;
}
template <int TB>
__device__ __forceinline__ void wgmma_n64(float (&d)[32], uint64_t da, uint64_t db, int sd) {
    asm volatile(
        "{\n.reg .pred p;\nsetp.ne.b32 p, %34, 0;\n"
        "wgmma.mma_async.sync.aligned.m64n64k16.f32.bf16.bf16 "
        "{%0,%1,%2,%3,%4,%5,%6,%7,%8,%9,%10,%11,%12,%13,%14,%15,%16,%17,%18,%19,%20,%21,%22,%23,%24,%25,%26,%27,%28,%29,%30,%31},"
        " %32, %33, p, 1, 1, 0, %35;\n}"
        : ACC8(d, 0), ACC8(d, 8), ACC8(d, 16), ACC8(d, 24)
        : "l"(da), "l"(db), "r"(sd), "n"(TB));
}
template <int SA>
__device__ __forceinline__ void wgmma_n64s(float (&d)[32], uint64_t da, uint64_t db, int sd) {
    asm volatile(
        "{\n.reg .pred p;\nsetp.ne.b32 p, %34, 0;\n"
        "wgmma.mma_async.sync.aligned.m64n64k16.f32.bf16.bf16 "
        "{%0,%1,%2,%3,%4,%5,%6,%7,%8,%9,%10,%11,%12,%13,%14,%15,%16,%17,%18,%19,%20,%21,%22,%23,%24,%25,%26,%27,%28,%29,%30,%31},"
        " %32, %33, p, %35, 1, 0, 1;\n}"
        : ACC8(d, 0), ACC8(d, 8), ACC8(d, 16), ACC8(d, 24)
        : "l"(da), "l"(db), "r"(sd), "n"(SA));
}
__device__ __forceinline__ void wgmma_n64_rs(float (&d)[32], uint32_t a0, uint32_t a1, uint32_t a2, uint32_t a3, uint64_t db, int sd) {
    asm volatile(
        "{\n.reg .pred p;\nsetp.ne.b32 p, %37, 0;\n"
        "wgmma.mma_async.sync.aligned.m64n64k16.f32.bf16.bf16 "
        "{%0,%1,%2,%3,%4,%5,%6,%7,%8,%9,%10,%11,%12,%13,%14,%15,%16,%17,%18,%19,%20,%21,%22,%23,%24,%25,%26,%27,%28,%29,%30,%31},"
        " {%32,%33,%34,%35}, %36, p, 1, 1, 1;\n}"
        : ACC8(d, 0), ACC8(d, 8), ACC8(d, 16), ACC8(d, 24)
        : "r"(a0), "r"(a1), "r"(a2), "r"(a3), "l"(db), "r"(sd));
}

struct Params {
    const __nv_bfloat16* x0;
    const __nv_bfloat16* w_r;
    const __nv_bfloat16* w_i;
    const __nv_bfloat16* lam_re;
    const __nv_bfloat16* lam_im;
    const __nv_bfloat16* log_dt;
    const __nv_bfloat16* dskip;
    float* out;
    int stop;
};

__device__ __forceinline__ float ldbf(const __nv_bfloat16* p) { return __bfloat162float(*p); }

__device__ __forceinline__ void dft_fp(int j, int& f, int& ph) {
    int cs = j >> 1;
    if (j == 1) { f = 256; ph = 0; }
    else { f = cs; ph = (j & 1) ? 128 : 0; }
}

__device__ __forceinline__ void gen_col_consts(uint32_t sb, int tid) {
#pragma unroll 1
    for (int task = tid; task < 640; task += 256) {
        int f, c8;
        uint32_t a_cc, d_pi, d_po;
        if (task < 512) {
            f = task & 63; c8 = task >> 6;
            a_cc = sb + SM_X + (f >> 5) * 16384 + ((f >> 3) & 3) * 2048 + c8 * 128 + (f & 7) * 16;
            d_pi = 8192; d_po = 1024;
        } else {
            int n2 = task & 31;
            f = 2 * n2; c8 = (task >> 5) & 3;
            a_cc = sb + SM_X + 32768 + (n2 >> 3) * 1024 + c8 * 128 + (n2 & 7) * 16;
            d_pi = 4096; d_po = 512;
        }
        float cd, sd, cs, sn;
        __sincosf((float)(f >= 32 ? f - 64 : f) * (6.283185307179586f / 64.f), &sd, &cd);
        int a = (8 * c8 * f) & 63;
        __sincosf((float)(a >= 32 ? a - 64 : a) * (6.283185307179586f / 64.f), &sn, &cs);
        float cv[8], sv[8];
#pragma unroll
        for (int e = 0; e < 8; e++) {
            cv[e] = cs; sv[e] = sn;
            float t = cs * cd - sn * sd;
            sn = sn * cd + cs * sd;
            cs = t;
        }
        uint4 oc = make_uint4(pack_bf16(cv[0], cv[1]), pack_bf16(cv[2], cv[3]), pack_bf16(cv[4], cv[5]), pack_bf16(cv[6], cv[7]));
        uint4 os = make_uint4(pack_bf16(sv[0], sv[1]), pack_bf16(sv[2], sv[3]), pack_bf16(sv[4], sv[5]), pack_bf16(sv[6], sv[7]));
        sts128(a_cc, oc);
        sts128(a_cc + d_pi, os);
        sts128(a_cc + d_po, make_uint4(os.x ^ 0x80008000u, os.y ^ 0x80008000u, os.z ^ 0x80008000u, os.w ^ 0x80008000u));
        sts128(a_cc + d_pi + d_po, oc);
    }
}

__global__ void __launch_bounds__(NTHREADS, 1)
fused_kernel(const __grid_constant__ CUtensorMap tm_x, const __grid_constant__ CUtensorMap tm_bre,
             const __grid_constant__ CUtensorMap tm_bim, const __grid_constant__ CUtensorMap tm_cre,
             const __grid_constant__ CUtensorMap tm_cim, const __grid_constant__ CUtensorMap tm_col, const Params p) {
    extern __shared__ __align__(1024) uint8_t sm[];
    const uint32_t sb = s2u(sm);
    const int tid = threadIdx.x, b = blockIdx.x;
    const int c = b >> 3, r = b & 7;
    const int par = r & 1, pi_ = r >> 1, own = 4 * par + pi_;
    const int wg = __shfl_sync(~0u, tid >> 7, 0), w = __shfl_sync(~0u, (tid >> 5) & 3, 0), lane = tid & 31, g = lane >> 2, q = lane & 3;
    auto BAR = [&](int i) { return sb + SM_BAR + 8 * i; };
    unsigned* s_tgt = (unsigned*)(sm + SM_TGT);

    if (tid < NBARS) {
        int cnt = 1;
        if (tid >= B_EMPTY0 && tid < B_EMPTY0 + 4) cnt = 16;
        if (tid >= B_XEMPTY && tid < B_XEMPTY + 4) cnt = 24;
        if (tid == B_RFREE) cnt = 12;
        if (tid == B_HDONE || tid == B_WST) cnt = 2;
        if ((tid >= B_AEMPTY && tid < B_AEMPTY + 8) || tid == B_BFREE) cnt = 8;
        if (tid == B_AFREE) cnt = 4;
        mbar_init(BAR(tid), cnt);
        asm volatile("fence.mbarrier_init.release.cluster;" ::: "memory");
    }
    asm volatile("barrier.cluster.arrive.release.aligned;" ::: "memory");

    if (wg == 3) {
        asm volatile("setmaxnreg.dec.sync.aligned.u32 56;");
        if (w == 0 && lane < 6) {
            const CUtensorMap* tm = lane == 0 ? &tm_x : lane == 1 ? &tm_bre : lane == 2 ? &tm_bim : lane == 3 ? &tm_cre : lane == 4 ? &tm_cim : &tm_col;
            asm volatile("prefetch.tensormap [%0];" ::"l"(tm) : "memory");
        }
        __syncwarp();
        asm volatile("barrier.cluster.wait.acquire.aligned;" ::: "memory");
        if (w > 0) {
            if (w == 1) {
                float lr[3], li[3], ld[3];
#pragma unroll
                for (int k = 0; k < 3; k++) {
                    int ps = k < 2 ? 64 * r + 32 * k + lane : 32 * c + lane;
                    lr[k] = ldbf(p.lam_re + ps); li[k] = ldbf(p.lam_im + ps); ld[k] = ldbf(p.log_dt + ps);
                }
                if (lane < 6) s_tgt[lane] = ((ld_acquire(&g_bar[lane]) >> 7) + 1u) << 7;
#pragma unroll 1
                for (int k = 0; k < 3; k++) {
                    float a = k == 0 ? lr[0] : (k == 1 ? lr[1] : lr[2]), bq = k == 0 ? li[0] : (k == 1 ? li[1] : li[2]);
                    float dt = __bfloat162float(__float2bfloat16(expf(k == 0 ? ld[0] : (k == 1 ? ld[1] : ld[2]))));
                    float mag = expf(a * dt), t = bq * dt * 0.15915494309189535f, sn, cs;
                    t -= rintf(t);
                    sincospif(2.f * t, &sn, &cs);
                    float er = mag * cs, ei = mag * sn;
                    if (k < 2) {
                        *(float2*)(sm + SM_LAM + (32 * k + lane) * 8) = make_float2(er, ei);
                    } else {
                        er -= 1.f;
                        float inv = 1.f / (a * a + bq * bq);
                        *(float2*)(sm + SM_TAB + lane * 8) = make_float2((er * a + ei * bq) * inv, (ei * a - er * bq) * inv);
                    }
                }
                __syncwarp();
                bar_arrive(15, 160);
                if (lane == 0) mbar_arrive(BAR(B_SETUP), 1);
            }
            if (w == 3) {
                bar_sync(0, 160);
                if (lane == 0) {
                    asm volatile("cp.async.bulk.global.shared::cta.bulk_group [%0], [%1], 16384;" ::"l"(g_Wfrag + (uint32_t)b * 1024), "r"(sb + SM_H + 16384) : "memory");
                    asm volatile("cp.async.bulk.commit_group;" ::: "memory");
                    asm volatile("cp.async.bulk.wait_group 0;" ::: "memory");
                    TX(15);
                    mbar_arrive(BAR(B_WRDY), 1);
                }
                __syncwarp();
            }
#pragma unroll 1
            for (int i = tid - 448; i < 96 + 128 && w > 1; i += 64) {
                if (i < 96) g_P[(uint32_t)(b * 4 + i / 24) * 1024 + 640 + ((i % 24) >> 1) * 32 + 30 + (i & 1)] = make_uint4(0, 0, 0, 0);
                else g_Ebuf[b * 128 + i - 96] = make_float4(0.f, 0.f, 0.f, 0.f);
            }
            __syncwarp();
            if (w == 3) bar_arrive(11, 192);
            if (w == 2) {
                bar_sync(11, 192);
                if (lane == 0) { TX(7); red_release(&g_bar[4], 1);  }
            }
            if (w == 3) {
#pragma unroll 1
                for (int it = 0; it < 8; it++) {
                    const int m = 4 * c + (it >> 1), d = 64 * r + m, ch = lane + 32 * (it & 1);
                    float v[8];
#pragma unroll
                    for (int e = 0; e < 8; e++) {
                        int j = 8 * ch + e, f, ph;
                        dft_fp(j, f, ph);
                        int a = (d * f + ph) & 511;
                        a = a >= 256 ? a - 512 : a;
                        float wj = j == 0 ? 0.f : (j == 1 ? 1.f / 512.f : 2.f / 512.f);
                        v[e] = wj * __cosf((float)a * (6.283185307179586f / 512.f));
                    }
                    uint32_t off = (uint32_t)(64 + r * 8 + (ch >> 3)) * 8192 + (m >> 3) * 1024 + (ch & 7) * 128 + (m & 7) * 16;
                    *(uint4*)(g_E + off) = make_uint4(pack_bf16(v[0], v[1]), pack_bf16(v[2], v[3]), pack_bf16(v[4], v[5]), pack_bf16(v[6], v[7]));
                }
                __syncwarp();
                if (lane == 0) { fence_async(); red_release(&g_bar[6], 1); }
                return;
            }
            if (w == 2) {
#pragma unroll 1
                for (int it = 0; it < 4; it++) {
                    const int hf = it & 1;
                    __syncwarp();
                    if (hf == 0) bar_sync(13, 288); else bar_sync(6, 416);
                    if (lane == 0) {
                        const uint32_t src = sb + SM_HH + par * 32768 + hf * 16384;
                        bulk_s2peer(mapa(src, par ^ 1), src, 16384, mapa(BAR(hf ? B_HPEER1 : B_HPEER), par ^ 1));
                    }
                }
                return;
            }
            bar_sync(2, 288);
            if (lane == 0) {
                TX(5);
                fence_async();
                red_release(&g_bar[0], 1);
                TX(6);
            }
            __syncwarp();

            bar_sync(12, 160);
            if (lane == 0) {
                asm volatile("cp.async.bulk.global.shared::cta.bulk_group [%0], [%1], 8192;" ::"l"(g_A1 + (uint32_t)(((c >> 1) * 8 + r) * 16384 + (c & 1) * 8192)),
                             "r"(sb + SM_B1ST) : "memory");
                asm volatile("cp.async.bulk.commit_group;" ::: "memory");
                asm volatile("cp.async.bulk.wait_group 0;" ::: "memory");
                mbar_arrive(BAR(B_B1DONE), 1);
                fence_async();
                red_release(&g_bar[7], 1);
            }
#pragma unroll 1
            for (int layer = 0; layer < 2; layer++) {
                __syncwarp();
                bar_sync(5, 416);
                if (lane == 0) {
                    TX(0 + 8 * layer);
                    tma_store_5d(&tm_col, 32 * (b & 1), 0, b >> 1, 0, layer, sb + SM_RAW);
                    asm volatile("cp.reduce.async.bulk.global.shared::cta.bulk_group.add.f32 [%0], [%1], 8192;" ::"l"(g_ssqc + (layer * 16 + (b & 15)) * 2048),
                                 "r"(sb + SM_SSQ) : "memory");
                    asm volatile("cp.async.bulk.commit_group;" ::: "memory");
                    asm volatile("cp.async.bulk.wait_group 0;" ::: "memory");
                    TX(1 + 8 * layer);
                    fence_async();
                    red_release(&g_bar[1 + 2 * layer], 1);
                    TX(2 + 8 * layer);
                }
            }
        } else if (tid == 384) {
#pragma unroll 1
            for (int kb = 0; kb < 8; kb++) {
                uint32_t fb = BAR(B_FULL0 + kb);
                mbar_expect(fb, 16384);
                tma_5d_mc(sb + SM_A + 65536 + kb * 16384 + par * 8192, &tm_x, kb * 64, 0, 0, 8 * par, c, fb);
            }
#pragma unroll 1
            for (int k2 = 0; k2 < 8; k2++) {
                asm volatile("cp.async.bulk.prefetch.tensor.2d.L2.global [%0, {%1,%2}];" ::"l"(par ? &tm_bim : &tm_bre), "r"(k2 * 64), "r"(32 * c) : "memory");
                if ((k2 & 1) == par)
                    asm volatile("cp.async.bulk.prefetch.tensor.2d.L2.global [%0, {%1,%2}];" ::"l"((c & 1) ? &tm_cim : &tm_cre), "r"(64 * (c >> 1)), "r"(k2 * 64) : "memory");
            }
            mbar_wait(BAR(B_SETUP), 0);
#pragma unroll 1
            for (int layer = 0; layer < 2; layer++) {
                if (layer == 1) {
                    mbar_wait(BAR(B_AEMPTY + 6), 1);
                    mbar_expect(BAR(B_WRDY), 16384);
                    bulk_g2s(sb + SM_H + 16384, g_Wfrag + (uint32_t)b * 1024, 16384, BAR(B_WRDY));
                }
                wait_count(&g_bar[2 * layer], s_tgt[2 * layer]);
                TX(4 + 8 * layer);
                fence_async();
                mbar_expect(BAR(B_COL), 16384 + 8192);
                tma_5d(sb + SM_RAW, &tm_col, 32 * (b & 1), 0, b >> 1, 0, layer, BAR(B_COL));
                bulk_g2s(sb + SM_SSQ, g_ssq + layer * 2048, 8192, BAR(B_COL));
                if (layer == 0) {
                    wait_count(&g_bar[7], s_tgt[4]);
                    fence_async();
                }
                if (layer == 0) mbar_wait(BAR(B_AFREE), 0);
                mbar_wait(BAR(B_COL), layer);
#pragma unroll 1
                for (int s = 0; s < 8; s++) {
                    if (layer == 1) mbar_wait(BAR(B_AEMPTY + s), 1);
                    if (s >= 2) mbar_wait(BAR(B_AFULL + s - 2), 0);
                    mbar_expect(BAR(B_AFULL + s), 16384);
                    bulk_g2s(sb + SM_A + s * 16384, g_A1 + (uint32_t)(r * 8 + s) * 16384, 16384, BAR(B_AFULL + s));
                }
                wait_count(&g_bar[layer == 0 ? 4 : 6], s_tgt[4]);
                wait_count(&g_bar[1 + 2 * layer], s_tgt[1 + 2 * layer]);
                TX(3 + 8 * layer);
                fence_async();
                const uint8_t* xsrc = g_X + (uint32_t)(layer * 16 + c) * 8 * 16384;
                const uint8_t* esrc = g_E + (uint32_t)(layer * 8 + own) * 8 * 8192;
                mbar_arrive(BAR(B_SSQ), 1);
                mbar_expect(BAR(B_HPEER), 16384);
                mbar_expect(BAR(B_HPEER1), 16384);
#pragma unroll 1
                for (int it = 0; it < 16; it++) {
                    if (it < 8) {
                        int st = it & 3, f = layer * 2 + (it >> 2);
                        if (f > 0) mbar_wait_cluster(BAR(B_XEMPTY + st), (f - 1) & 1);
                        mbar_expect(BAR(B_XFULL + st), 24576);
                        bulk_g2s_mc(sb + SM_X + st * 24576 + par * 8192, xsrc + (uint32_t)it * 16384 + par * 8192, 8192, BAR(B_XFULL + st));
                        bulk_g2s(sb + SM_X + st * 24576 + 16384, esrc + (uint32_t)it * 8192, 8192, BAR(B_XFULL + st));
                    }
                    if (it >= 8) {
                        if (it == 8) mbar_wait(BAR(B_AEMPTY + 5), 0);
                        int s = it - 8, tile = 4 * par + ((pi_ + 1 + (s >> 1)) & 3), sl = r ^ (s & 1);
                        mbar_wait(BAR(B_AEMPTY + s), 0);
                        uint32_t fb = BAR(B_AFULL + s), dst = sb + SM_A + s * 16384;
                        mbar_expect(fb, 16384);
                        if (layer == 1) {
                            tma_2d(dst, &tm_cre, 64 * sl, 64 * tile, fb);
                            tma_2d(dst + 8192, &tm_cim, 64 * sl, 64 * tile, fb);
                        } else {
                            bulk_g2s(dst, g_A2 + (uint32_t)(sl * 8 + tile) * 16384, 16384, fb);
                        }
                    }
                }
            }
        }
        return;
    }

    asm volatile("setmaxnreg.inc.sync.aligned.u32 152;");
    if (tid >= 96 && tid < 112) g_ssq[2048 + 16 * b + tid - 96] = 0.f;
    if (tid >= 128 && tid < 256) ((float4*)g_ssqc)[b * 128 + tid - 128] = make_float4(0.f, 0.f, 0.f, 0.f);
    TS(0);
    if (wg == 0) TC(30);
    {
        const int f = 32 * r + lane;
        float cd, sd;
        __sincosf((float)f * (6.283185307179586f / 512.f), &sd, &cd);
        const uint32_t dst = sb + SM_A + (lane >> 2) * 1024 + (lane & 3) * 32;
#pragma unroll 1
        for (int ch = tid >> 5; ch < 64; ch += 12) {
            int a = (8 * ch * f) & 511;
            a = a >= 256 ? a - 512 : a;
            float cs, sn;
            __sincosf((float)a * (6.283185307179586f / 512.f), &sn, &cs);
            float cv[8], sv[8];
#pragma unroll
            for (int e = 0; e < 8; e++) {
                cv[e] = cs; sv[e] = -sn;
                float t = cs * cd - sn * sd;
                sn = sn * cd + cs * sd;
                cs = t;
            }
            uint4 o1 = make_uint4(pack_bf16(sv[0], sv[1]), pack_bf16(sv[2], sv[3]), pack_bf16(sv[4], sv[5]), pack_bf16(sv[6], sv[7]));
            if (f == 0) o1 = make_uint4(0xbf803f80u, 0xbf803f80u, 0xbf803f80u, 0xbf803f80u);
            uint32_t a0 = dst + (ch >> 3) * 8192 + (ch & 7) * 128;
            sts128(a0, make_uint4(pack_bf16(cv[0], cv[1]), pack_bf16(cv[2], cv[3]), pack_bf16(cv[4], cv[5]), pack_bf16(cv[6], cv[7])));
            sts128(a0 + 16, o1);
        }
    }
    fence_async_smem();
    asm volatile("barrier.cluster.wait.acquire.aligned;" ::: "memory");
    bar_sync(10, 384);
    TS(1);
    if (wg < 2) {
        float acc[32];
        acc_def(acc);
        const int npos = 16 * r + 8 * wg + 2 * w;
        float sh0 = 0.f, sh1 = 0.f, s0 = 0.f, s1 = 0.f, q0 = 0.f, q1 = 0.f;
#pragma unroll 1
        for (int kb = 0; kb < 8; kb++) {
            uint32_t slot = sb + SM_A + 65536 + kb * 16384;
            mbar_wait(BAR(B_FULL0 + kb), 0);
            wg_fence();
#pragma unroll
            for (int ks = 0; ks < 4; ks++)
                wgmma_n64<0>(acc, desc_a(sb + SM_A + kb * 8192 + ks * 256), desc_k(slot + wg * 8192 + ks * 32), 1);
            wg_commit();
            {
                uint32_t v0 = lds32(slot + npos * 128 + lane * 4), v1 = lds32(slot + npos * 128 + 128 + lane * 4);
                if (kb == 0) { sh0 = __shfl_sync(~0u, bf_lo(v0), 0); sh1 = __shfl_sync(~0u, bf_lo(v1), 0); }
                float a = bf_lo(v0) - sh0, bq = bf_hi(v0) - sh0, cq = bf_lo(v1) - sh1, d = bf_hi(v1) - sh1;
                s0 += a + bq; q0 += a * a + bq * bq; s1 += cq + d; q1 += cq * cq + d * d;
            }
            wg_wait<1>();
            if (kb > 0 && kb <= 4 && lane == 0) { mbar_arrive(BAR(B_EMPTY0 + kb - 1), 1); mbar_arrive_remote(mapa(BAR(B_EMPTY0 + kb - 1), par ^ 1)); }
        }
#pragma unroll
        for (int o = 16; o; o >>= 1) {
            s0 += __shfl_xor_sync(~0u, s0, o); q0 += __shfl_xor_sync(~0u, q0, o);
            s1 += __shfl_xor_sync(~0u, s1, o); q1 += __shfl_xor_sync(~0u, q1, o);
        }
        if (lane == 0) *(float2*)(g_ssq + 128 * c + npos) = make_float2(fmaxf(q0 - s0 * s0 * (1.f / 512.f), 0.f), fmaxf(q1 - s1 * s1 * (1.f / 512.f), 0.f));
        wg_wait<0>();
        TS(2);
        uint8_t* dst = g_X + (uint32_t)((c * 8 + r) * 16384 + w * 4096 + wg * 1024 + g * 16 + 4 * q);
#pragma unroll
        for (int i = 0; i < 8; i++) {
            *(uint32_t*)(dst + i * 128) = pack_bf16(acc[4 * i], acc[4 * i + 1]);
            *(uint32_t*)(dst + 2048 + i * 128) = pack_bf16(acc[4 * i + 2], acc[4 * i + 3]);
        }
        bar_sync(2, 288);
        mbar_wait(BAR(B_SETUP), 0);
        TS(3);
    }

    if (wg == 2) {
        {
            const int c0 = b == 0 ? 256 : 2 * b, c1 = 2 * b + 1;
            uint32_t wf[2][16];
#pragma unroll
            for (int h = 0; h < 2; h++) {
                const int kq = (tid & 127) + 128 * h, k1 = kq >> 2, qq = kq & 3;
                const unsigned short* wr_ = (const unsigned short*)p.w_r + (k1 + 128 * qq) * 257;
                const unsigned short* wi_ = (const unsigned short*)p.w_i + (k1 + 128 * qq) * 257;
#pragma unroll
                for (int i = 0; i < 4; i++) {
                    int o = 512 * i * 257;
                    wf[h][2 * i] = (uint32_t)__ldg(wr_ + o + c0) | ((uint32_t)__ldg(wr_ + o + 64 * 257 + c0) << 16);
                    wf[h][2 * i + 1] = ((uint32_t)__ldg(wi_ + o + c0) | ((uint32_t)__ldg(wi_ + o + 64 * 257 + c0) << 16)) ^ 0x80008000u;
                    wf[h][8 + 2 * i] = (uint32_t)__ldg(wr_ + o + c1) | ((uint32_t)__ldg(wr_ + o + 64 * 257 + c1) << 16);
                    wf[h][8 + 2 * i + 1] = ((uint32_t)__ldg(wi_ + o + c1) | ((uint32_t)__ldg(wi_ + o + 64 * 257 + c1) << 16)) ^ 0x80008000u;
                }
            }
            uint4 p0 = __ldg((const uint4*)p.dskip + 2 * lane), p1 = __ldg((const uint4*)p.dskip + 2 * lane + 1);
            uint32_t u[8] = {p0.x, p0.y, p0.z, p0.w, p1.x, p1.y, p1.z, p1.w};
            int j = 64 * r + 4 * c + w, f, ph;
            dft_fp(j, f, ph);
            float s = 0.f;
            int idx = 16 * lane * f + ph;
#pragma unroll
            for (int i = 0; i < 16; i++) {
                int a = idx & 511;
                idx += f;
                a = a >= 256 ? a - 512 : a;
                s += ((i & 1) ? bf_hi(u[i >> 1]) : bf_lo(u[i >> 1])) * __cosf((float)a * (6.283185307179586f / 512.f));
            }
#pragma unroll
            for (int o = 16; o; o >>= 1) s += __shfl_xor_sync(~0u, s, o);
            if (lane == 0) g_Dh[j] = s;
#pragma unroll
            for (int h = 0; h < 2; h++)
#pragma unroll
                for (int i = 0; i < 4; i++)
                    sts128(sb + SM_H + 16384 + ((tid & 127) + 128 * h) * 64 + ((i ^ ((tid >> 1) & 3)) << 4),
                           make_uint4(wf[h][4 * i], wf[h][4 * i + 1], wf[h][4 * i + 2], wf[h][4 * i + 3]));
            fence_async_smem();
            bar_arrive(0, 160);
            bar_arrive(11, 192);
        }
        bar_sync(15, 160);
        float acc[32];
        acc_def(acc);
        if (tid == 256) {
#pragma unroll 1
            for (int s = 0; s < 4; s++) mbar_wait_cluster(BAR(B_EMPTY0 + s), 0);
            mbar_expect(BAR(B_FULLB), 65536);
#pragma unroll 1
            for (int k2 = 0; k2 < 8; k2++)
                tma_2d_mc(sb + SM_A + 65536 + k2 * 8192 + par * 4096, par ? &tm_bim : &tm_bre, k2 * 64, 32 * c, BAR(B_FULLB));
        }
        __syncwarp();
        mbar_wait(BAR(B_FULLB), 0);
        wg_fence();
#pragma unroll 1
        for (int kb = 0; kb < 8; kb++) {
#pragma unroll
            for (int ks = 0; ks < 4; ks++)
                wgmma_n64<0>(acc, desc_a(sb + SM_A + kb * 8192 + ks * 256), desc_k(sb + SM_A + 65536 + kb * 8192 + ks * 32), 1);
            wg_commit();
        }
        wg_wait<0>();
        if (lane == 0) { mbar_arrive(BAR(B_BFREE), 1); mbar_arrive_remote(mapa(BAR(B_BFREE), par ^ 1)); }
        if (tid == 256) {
            mbar_wait_cluster(BAR(B_BFREE), 0);
            mbar_expect(BAR(B_FULLC), 65536);
#pragma unroll 1
            for (int k2 = par; k2 < 8; k2 += 2)
                tma_2d_mc(sb + SM_A + 65536 + k2 * 8192, (c & 1) ? &tm_cim : &tm_cre, 64 * (c >> 1), k2 * 64, BAR(B_FULLC));
        }
        __syncwarp();
        {
            uint8_t* dst = sm + SM_B1ST + w * 256 + q * 32 + g * 2;
            const float wj0 = (r == 0 && w == 0 && g < 2) ? (g == 0 ? 0.f : 1.f / 512.f) : 2.f / 512.f;
#pragma unroll
            for (int i = 0; i < 4; i++) {
#pragma unroll
                for (int e = 0; e < 2; e++) {
                    float2 cf = *(const float2*)(sm + SM_TAB + (8 * i + 2 * q + e) * 8);
#pragma unroll
                    for (int h = 0; h < 2; h++) {
                        float wj = h == 0 ? wj0 : 2.f / 512.f;
                        float pr = acc[4 * i + 2 * h + e] * wj, pi = acc[16 + 4 * i + 2 * h + e] * wj;
                        uint8_t* d2 = dst + i * 2048 + h * 128 + e * 16;
                        *(__nv_bfloat16*)(d2) = __float2bfloat16(cf.x * pr - cf.y * pi);
                        *(__nv_bfloat16*)(d2 + 1024) = __float2bfloat16(cf.x * pi + cf.y * pr);
                    }
                }
            }
            fence_async_smem();
            bar_arrive(12, 160);
        }
        acc_def(acc);
        mbar_wait(BAR(B_FULLC), 0);
        wg_fence();
#pragma unroll 1
        for (int kb = 0; kb < 8; kb++) {
#pragma unroll
            for (int ks = 0; ks < 4; ks++)
                wgmma_n64<1>(acc, desc_a(sb + SM_A + kb * 8192 + ks * 256), desc_mn(sb + SM_A + 65536 + kb * 8192 + ks * 2048, 8192), 1);
            wg_commit();
        }
        wg_wait<0>();
        fence_async_smem();
        if (lane == 0) mbar_arrive(BAR(B_AFREE), 1);
        uint8_t* dst = g_A2 + (uint32_t)(((c >> 1) * 8 + r) * 16384 + (c & 1) * 8192 + w * 2048 + g * 16 + 4 * q);
#pragma unroll
        for (int i = 0; i < 8; i++) {
            *(uint32_t*)(dst + i * 128) = pack_bf16(acc[4 * i], acc[4 * i + 1]);
            *(uint32_t*)(dst + 1024 + i * 128) = pack_bf16(acc[4 * i + 2], acc[4 * i + 3]);
        }
        {
            const int m = 4 * c + w, jp = 64 * r + m;
            int fp, php;
            dft_fp(jp, fp, php);
            const __nv_bfloat16* dh = (const __nv_bfloat16*)(sm + SM_RSTD);
            if (tid == 256) wait_count(&g_bar[4], s_tgt[4]);
            bar_sync(3, 128);
            float4 d4 = __ldcg((const float4*)g_Dh + (tid - 256));
            *(uint2*)(sm + SM_RSTD + (tid - 256) * 8) = make_uint2(pack_bf16(d4.x, d4.y), pack_bf16(d4.z, d4.w));
            bar_sync(3, 128);
#pragma unroll 1
            for (int it = 0; it < 2; it++) {
                const int ch = lane + 32 * it;
                float v[8];
#pragma unroll
                for (int e = 0; e < 8; e++) {
                    int j = 8 * ch + e, f, ph;
                    dft_fp(j, f, ph);
                    float wj = j == 0 ? 0.f : (j == 1 ? 1.f / 512.f : 2.f / 512.f);
                    float gsum = 0.f;
#pragma unroll
                    for (int sgn = 0; sgn < 2; sgn++) {
                        int mm = (sgn ? f - fp : f + fp) & 511, pp = (sgn ? ph - php : ph + php) & 511;
                        if (mm > 256) { mm = 512 - mm; pp = (512 - pp) & 511; }
                        int odd = (pp >> 7) & 1;
                        float t = __bfloat162float(dh[mm == 256 ? 1 : 2 * mm + odd]);
                        if (odd && (mm & 255) == 0) t = 0.f;
                        gsum += (pp & 256) ? -t : t;
                    }
                    v[e] = 0.5f * wj * gsum;
                }
                uint32_t off = (uint32_t)(r * 8 + (ch >> 3)) * 8192 + (m >> 3) * 1024 + (ch & 7) * 128 + (m & 7) * 16;
                *(uint4*)(g_E + off) = make_uint4(pack_bf16(v[0], v[1]), pack_bf16(v[2], v[3]), pack_bf16(v[4], v[5]), pack_bf16(v[6], v[7]));
            }
        }
    }

#pragma unroll 1
    for (int layer = 0; layer < 2; layer++) {
        if (wg < 2) {
            const int n1 = 32 * wg + 8 * w + g;
            const int ct = n1 >> 2;
            gen_col_consts(sb, tid);
            uint32_t tr2[4], ti2[4], tn2[4];
#pragma unroll
            for (int i = 0; i < 4; i++) {
                float cr[2], ci[2];
#pragma unroll
                for (int e = 0; e < 2; e++) {
                    int a = (n1 * (8 * i + 2 * q + e)) & 2047;
                    a = a >= 1024 ? a - 2048 : a;
                    float ang = (float)a * (-6.283185307179586f / 2048.f);
                    cr[e] = __cosf(ang); ci[e] = __sinf(ang);
                }
                tr2[i] = pack_bf16(cr[0], cr[1]); ti2[i] = pack_bf16(ci[0], ci[1]); tn2[i] = ti2[i] ^ 0x80008000u;
            }
            mbar_wait(BAR(B_B1DONE), 0);
            mbar_wait(BAR(B_COL), layer);
            TS(4 + 12 * layer);
            if (wg == 0) TC(0 + 10 * layer);
            const uint32_t rw0 = sb + SM_RAW + ct * 1024 + q * 64 + ((q >> 1) << 4) + (g & 3) * 4, rw1 = rw0 ^ 16;
            const int pos0 = 128 * ct + 8 * q + 2 * (g & 3);
            const int sw = b == 0 ? 1 : 0;
            uint32_t xr[4][4];
            const uint32_t st0 = sb + SM_H + (n1 >> 3) * 1024 + g * 16 + 4 * q;
#pragma unroll
            for (int i = 0; i < 4; i++) {
                float2 sq = *(const float2*)(sm + SM_SSQ + (pos0 + 32 * i) * 4);
                const uint32_t rs2 = pack_bf16(rsqrtf(sq.x * (1.f / 512.f) + 1e-5f), rsqrtf(sq.y * (1.f / 512.f) + 1e-5f));
#pragma unroll
                for (int jj = 0; jj < 4; jj++) {
                    const int K = jj ^ (2 * (i & 1));
                    uint32_t a = ((K & 1) ? rw1 : rw0) + i * 256 + (K & 2) * 16;
                    if (jj < 2) a ^= sw << 4;
                    uint32_t v = lds32(a);
                    xr[jj][i] = v;
                    uint32_t o = hmul2(v, rs2);
                    if (jj == 1 && sw) o = 0u;
                    sts32(st0 + (jj & 1) * 8192 + (4 * (jj >> 1) + i) * 128, o);
                }
            }
            if (wg == 0) TC(1 + 10 * layer);
            fence_async_smem();
            bar_sync(1, 256);
            float acc[32];
            const uint32_t s1a = sb + SM_X + wg * 16384, s2b = sb + SM_X + 32768;
            wg_fence();
#pragma unroll
            for (int ks = 0; ks < 8; ks++)
                wgmma_n64<1>(acc, desc_a(s1a + (ks >> 2) * 8192 + (ks & 3) * 256), desc_b<64>(sb + SM_H + ks * 2048), ks != 0);
            wg_commit();
            wg_wait<0>();
            if (wg == 0) TC(2 + 10 * layer);
            uint32_t are[2][4], aim[2][4];
#pragma unroll
            for (int col = 0; col < 2; col++) {
#pragma unroll
                for (int i = 0; i < 4; i++) {
                    int o = 4 * (4 * col + i);
                    uint32_t zr = pack_bf16(acc[o], acc[o + 1]), zi = pack_bf16(acc[o + 2], acc[o + 3]);
                    are[col][i] = hfma2(zr, tr2[i], hmul2(zi, tn2[i]));
                    aim[col][i] = hfma2(zr, ti2[i], hmul2(zi, tr2[i]));
                }
            }
            wg_fence();
#pragma unroll
            for (int ks = 0; ks < 2; ks++)
                wgmma_n64_rs(acc, are[0][2 * ks], are[1][2 * ks], are[0][2 * ks + 1], are[1][2 * ks + 1], desc_b<64>(s2b + ks * 2048), ks != 0);
#pragma unroll
            for (int ks = 0; ks < 2; ks++)
                wgmma_n64_rs(acc, aim[0][2 * ks], aim[1][2 * ks], aim[0][2 * ks + 1], aim[1][2 * ks + 1], desc_b<64>(s2b + 4096 + ks * 2048), 1);
            wg_commit();
            uint32_t wf[16];
            mbar_wait(BAR(B_WRDY), layer);
#pragma unroll
            for (int i = 0; i < 4; i++) {
                const int kq = n1 * 4 + q;
                uint4 v = *(const uint4*)(sm + SM_H + 16384 + kq * 64 + ((i ^ ((kq >> 1) & 3)) << 4));
                wf[4 * i] = v.x; wf[4 * i + 1] = v.y; wf[4 * i + 2] = v.z; wf[4 * i + 3] = v.w;
            }
            wg_wait<0>();
            if (wg == 0) TC(3 + 10 * layer);
#pragma unroll
            for (int col = 0; col < 2; col++) {
#pragma unroll
                for (int i = 0; i < 4; i++) {
                    uint32_t wr = wf[col * 8 + 2 * i], wn = wf[col * 8 + 2 * i + 1];
                    uint32_t zr = pack_bf16(acc[4 * i + 2 * col], acc[4 * i + 2 * col + 1]);
                    uint32_t zi = pack_bf16(acc[16 + 4 * i + 2 * col], acc[16 + 4 * i + 2 * col + 1]);
                    are[col][i] = hfma2(zr, wr, hmul2(zi, wn));
                    aim[col][i] = hfma2(zr, wn, hmul2(zi ^ 0x80008000u, wr));
                }
            }
            wg_fence();
#pragma unroll
            for (int ks = 0; ks < 2; ks++)
                wgmma_n64_rs(acc, are[0][2 * ks], are[1][2 * ks], are[0][2 * ks + 1], are[1][2 * ks + 1], desc_b<64>(s2b + ks * 2048), ks != 0);
#pragma unroll
            for (int ks = 0; ks < 2; ks++)
                wgmma_n64_rs(acc, aim[0][2 * ks], aim[1][2 * ks], aim[0][2 * ks + 1], aim[1][2 * ks + 1], desc_b<64>(s2b + 4096 + ks * 2048), 1);
            wg_commit();
            wg_wait<0>();
            if (wg == 0) TC(4 + 10 * layer);
            bar_sync(1, 256);
#pragma unroll
            for (int col = 0; col < 2; col++) {
#pragma unroll
                for (int i = 0; i < 4; i++) {
                    uint32_t zr = pack_bf16(acc[4 * i + 2 * col], acc[4 * i + 2 * col + 1]);
                    uint32_t zi = pack_bf16(acc[16 + 4 * i + 2 * col], acc[16 + 4 * i + 2 * col + 1]);
                    sts32(st0 + 16384 + (4 * col + i) * 128, hfma2(zr, tr2[i], hmul2(zi, tn2[i])));
                    sts32(st0 + 16384 + 8192 + (4 * col + i) * 128, hfma2(zr, ti2[i], hmul2(zi, tr2[i])));
                }
            }
            if (wg == 0) TC(5 + 10 * layer);
            fence_async_smem();
            bar_sync(1, 256);
            wg_fence();
#pragma unroll
            for (int ks = 0; ks < 8; ks++)
                wgmma_n64<1>(acc, desc_a(s1a + (ks >> 2) * 8192 + (ks & 3) * 256), desc_b<64>(sb + SM_H + 16384 + ks * 2048), ks != 0);
            wg_commit();
            wg_wait<0>();
            if (wg == 0) TC(6 + 10 * layer);
            const float sc = 1.f / 2048.f;
            const float sci0 = sw ? 0.f : -sc;
            const float wr0 = sw ? 0.5f : 1.f, wi0 = sw ? 0.f : 1.f;
#pragma unroll
            for (int i = 0; i < 4; i++) {
                float ss0, ss1;
#pragma unroll
                for (int col = 0; col < 2; col++) {
                    int o = 4 * (4 * col + i);
                    uint32_t vr = xr[2 * col][i], vi = xr[2 * col + 1][i];
                    float si = col == 0 ? sci0 : -sc;
                    uint32_t nr = pack_bf16(fmaf(acc[o], sc, bf_lo(vr)), fmaf(acc[o + 1], sc, bf_hi(vr)));
                    uint32_t ni = pack_bf16(fmaf(acc[o + 2], si, bf_lo(vi)), fmaf(acc[o + 3], si, bf_hi(vi)));
                    float a0 = bf_lo(nr), a1 = bf_hi(nr), b0 = bf_lo(ni), b1 = bf_hi(ni);
                    if (col == 0) {
                        ss0 = wr0 * a0 * a0 + wi0 * b0 * b0;
                        ss1 = wr0 * a1 * a1 + wi0 * b1 * b1;
                    } else {
                        ss0 += a0 * a0 + b0 * b0;
                        ss1 += a1 * a1 + b1 * b1;
                    }
                    const int K = (2 * col) ^ (2 * (i & 1));
                    uint32_t a = rw0 + i * 256 + K * 16;
                    if (col == 0) a ^= sw << 4;
                    sts32(a, nr);
                    sts32(a ^ 16, ni);
                }
                *(float2*)(sm + SM_SSQ + (pos0 + 32 * i) * 4) = make_float2(ss0 * (2.f / 512.f), ss1 * (2.f / 512.f));
            }
            fence_async_smem();
        }
        TS(5 + 12 * layer);
        if (wg == 0) TC(7 + 10 * layer);
        bar_arrive(5, 416);

        float acc[64];
        float* s_rstd = (float*)(sm + SM_RSTD);
        float* s_mean = (float*)(sm + SM_MEAN);
        const unsigned epoch = s_tgt[0] >> 7;
        const uint32_t pt3 = 1u + (2u * epoch + layer) % 3u;
        const uint32_t ptag = (pt3 & 1u) | ((pt3 & 2u) << 15);
        const uint64_t dstep = layer == 0 ? 16 : 2;
        auto c_desc = [&](int s) { return layer == 0 ? desc_a(sb + SM_A + s * 16384) : desc_k(sb + SM_A + s * 16384); };
        if (wg < 2) {
            const int prow = 32 * wg + 8 * w + g;
            const float2 l1 = *(const float2*)(sm + SM_LAM + prow * 8);
            float lr32 = l1.x, li32 = l1.y;
#pragma unroll
            for (int i = 0; i < 5; i++) { float t = lr32 * lr32 - li32 * li32; li32 = 2.f * lr32 * li32; lr32 = t; }
            float lr128 = lr32, li128 = li32;
#pragma unroll
            for (int i = 0; i < 2; i++) { float t = lr128 * lr128 - li128 * li128; li128 = 2.f * lr128 * li128; lr128 = t; }
            const float lr1 = l1.x, li1 = l1.y;
            acc_def(acc);
#pragma unroll 1
            for (int kb = 0; kb < 8; kb++) {
                mbar_wait(BAR(B_AFULL + kb), 0);
                mbar_wait(BAR(B_XFULL + (kb & 3)), (kb >> 2) & 1);
                wg_fence();
#pragma unroll
                for (int ks = 0; ks < 4; ks++)
                    wgmma_n128<1>(acc, desc_a(sb + SM_A + kb * 16384 + wg * 8192 + ks * 256),
                                  desc_b<128>(sb + SM_X + (kb & 3) * 24576 + ks * 4096), 1);
                wg_commit();
                wg_wait<1>();
                if (kb > 0 && lane == 0) {
                    mbar_arrive(BAR(B_AEMPTY + kb - 1), 1); mbar_arrive(BAR(B_XEMPTY + ((kb - 1) & 3)), 1);
                    mbar_arrive_remote(mapa(BAR(B_XEMPTY + ((kb - 1) & 3)), par ^ 1));
                }
            }
            wg_wait<0>();
            if (lane == 0) {
                mbar_arrive(BAR(B_AEMPTY + 7), 1); mbar_arrive(BAR(B_XEMPTY + 3), 1);
                mbar_arrive_remote(mapa(BAR(B_XEMPTY + 3), par ^ 1)); mbar_arrive_remote(mapa(BAR(B_RFREE), par ^ 1));
            }
            bar_arrive(14, 384);
            TS(6 + 12 * layer);
            bar_sync(4, 384);
            TS(7 + 12 * layer);
            float er = 0.f, ei = 0.f;
#pragma unroll
            for (int i = 0; i < 16; i++) {
                float2 rs = *(const float2*)(s_rstd + 128 + 8 * i + 2 * q);
                acc[4 * i] *= rs.x; acc[4 * i + 1] *= rs.y; acc[4 * i + 2] *= rs.x; acc[4 * i + 3] *= rs.y;
                float nr = lr1 * er - li1 * ei + acc[4 * i], ni = lr1 * ei + li1 * er + acc[4 * i + 2];
                er = lr1 * nr - li1 * ni + acc[4 * i + 1];
                ei = lr1 * ni + li1 * nr + acc[4 * i + 3];
            }
            float cr = 0.f, ci = 0.f, tr = 0.f, ti = 0.f;
#pragma unroll
            for (int qq = 0; qq < 4; qq++) {
                float xr_ = __shfl_sync(~0u, er, (lane & ~3) | qq), xi_ = __shfl_sync(~0u, ei, (lane & ~3) | qq);
                if (qq == q) { cr = tr; ci = ti; }
                float nr = lr32 * tr - li32 * ti + xr_, ni = lr32 * ti + li32 * tr + xi_;
                tr = nr; ti = ni;
            }
            float4* eb = g_Ebuf + (uint32_t)(layer * 16 * 512 + 64 * r + prow);
            if (q == 0 && c < 15) st_relaxed_f4(eb + c * 512, make_float4(tr, ti, __uint_as_float(epoch), 0.f));
            TS(8 + 12 * layer);
            float pr[4], pi[4];
            {
                unsigned n = 0;
                bool ok;
#pragma unroll 1
                do {
                    ok = true;
#pragma unroll
                    for (int k = 0; k < 4; k++) {
                        float4 v = make_float4(0.f, 0.f, __uint_as_float(epoch), 0.f);
                        if (4 * k + q < c) v = ld_relaxed_f4(eb + (4 * k + q) * 512);
                        pr[k] = v.x; pi[k] = v.y;
                        ok = ok && __float_as_uint(v.z) == epoch;
                    }
                } while (!ok && ++n < SPIN_LIMIT);
            }
            __syncwarp();
            TS(9 + 12 * layer);
            float hr = 0.f, hi = 0.f;
#pragma unroll
            for (int cc = 0; cc < 15; cc++) {
                float xr_ = __shfl_sync(~0u, pr[cc >> 2], (lane & ~3) | (cc & 3)), xi_ = __shfl_sync(~0u, pi[cc >> 2], (lane & ~3) | (cc & 3));
                if (cc < c) {
                    float nr = lr128 * hr - li128 * hi + xr_, ni = lr128 * hi + li128 * hr + xi_;
                    hr = nr; hi = ni;
                }
            }
#pragma unroll
            for (int qq = 0; qq < 3; qq++) {
                if (qq < q) { float nr = lr32 * hr - li32 * hi, ni = lr32 * hi + li32 * hr; hr = nr; hi = ni; }
            }
            er = cr + hr; ei = ci + hi;
            bar_sync(7, 384);
            mbar_wait_cluster(BAR(B_RFREE), layer);
            const uint32_t ha = sb + SM_HH + par * 32768 + (prow >> 3) * 1024 + g * 16 + 4 * q;
#pragma unroll
            for (int i = 0; i < 16; i++) {
                float nr = lr1 * er - li1 * ei + acc[4 * i], ni = lr1 * ei + li1 * er + acc[4 * i + 2];
                er = lr1 * nr - li1 * ni + acc[4 * i + 1];
                ei = lr1 * ni + li1 * nr + acc[4 * i + 3];
                sts32(ha + (i >> 3) * 16384 + (i & 7) * 128, pack_bf16(nr, er));
                sts32(ha + (i >> 3) * 16384 + 8192 + (i & 7) * 128, pack_bf16(ni, ei));
                if (i == 7) { fence_async_smem(); bar_arrive(13, 288); }
            }
            fence_async_smem();
            acc_def(acc);
            float acc2[32];
            acc_def(acc2);
            TS(10 + 12 * layer);
            bar_sync(6, 416);
            TS(11 + 12 * layer);
            float (&a0)[32] = *reinterpret_cast<float (*)[32]>(&acc[0]);
            float (&a1)[32] = *reinterpret_cast<float (*)[32]>(&acc[32]);
            auto tile_mma = [&](float (&d)[32], int u) {
#pragma unroll 1
                for (int k = 0; k < 2; k++) {
                    const uint32_t hb = sb + SM_HH + (par ^ k) * 32768 + wg * 16384;
                    if (k == 1) mbar_wait(BAR(wg ? B_HPEER1 : B_HPEER), layer);
                    mbar_wait(BAR(B_AFULL + 2 * u + k), 1);
                    const uint64_t da = c_desc(2 * u + k);
                    wg_fence();
#pragma unroll
                    for (int ks = 0; ks < 4; ks++) wgmma_n64s<1>(d, da + ks * dstep, desc_b<64>(hb + ks * 2048), 1);
#pragma unroll
                    for (int ks = 0; ks < 4; ks++) wgmma_n64s<-1>(d, da + 512 + ks * dstep, desc_b<64>(hb + 8192 + ks * 2048), 1);
                }
                wg_commit();
            };
            auto tile_ship = [&](float (&d)[32], int u) {
                uint4* dst = g_P + (uint32_t)(((c * 8 + 2 * ((pi_ + 1 + u) & 3) + par) * 4 + pi_) * 1024 + wg * 512 + (tid & 127));
#pragma unroll
                for (int i = 0; i < 4; i++)
                    dst[i * 128] = make_uint4((pack_bf16(d[8 * i], d[8 * i + 1]) & 0xfffefffeu) | ptag, pack_bf16(d[8 * i + 2], d[8 * i + 3]),
                                              pack_bf16(d[8 * i + 4], d[8 * i + 5]), pack_bf16(d[8 * i + 6], d[8 * i + 7]));
            };
            tile_mma(a0, 0);
            if ((tid & 127) == 0) mbar_arrive_remote(mapa(BAR(B_HDONE), par ^ 1));
            __syncwarp();
            tile_mma(a1, 1);
            wg_wait<1>();
            tile_ship(a0, 0);
            tile_mma(acc2, 2);
            bar_arrive(12, 384);
            wg_wait<1>();
            tile_ship(a1, 1);
            wg_wait<0>();
            tile_ship(acc2, 2);
            if (lane < 6) mbar_arrive(BAR(B_AEMPTY + lane), 1);
            TS(12 + 12 * layer);
        } else {
            const int t2 = tid - 256;
            const uint8_t* ximg = g_X + (uint32_t)layer * 16 * 8 * 16384;
            mbar_wait(BAR(B_SSQ), layer);
            TS(6 + 12 * layer);
            float sqv[16];
#pragma unroll
            for (int i = 0; i < 16; i++) sqv[i] = __ldcg(g_ssqc + (layer * 16 + i) * 2048 + 128 * c + t2);
            const unsigned short xm = __ldcg((const unsigned short*)(ximg + (uint32_t)(c * 8 * 16384 + (t2 >> 3) * 128 + (t2 & 7) * 2)));
            acc_def(acc);
#pragma unroll 1
            for (int kb = 0; kb < 8; kb++) {
                if (kb == 4) {
                    wg_wait<0>();
                    if (lane == 0) { mbar_arrive(BAR(B_XEMPTY + 3), 1); mbar_arrive_remote(mapa(BAR(B_XEMPTY + 3), par ^ 1)); }
                    float tot = 0.f;
#pragma unroll
                    for (int i = 0; i < 16; i++) tot += sqv[i];
                    float rs = rsqrtf(tot * (1.f / 512.f) + 1e-5f);
                    s_rstd[t2] = rs;
                    s_rstd[128 + t2] = 2.f * rs;
                    s_mean[t2] = layer == 0 ? 0.f : __uint_as_float((uint32_t)xm << 16) * (1.f / 512.f);
                    TS(7 + 12 * layer);
                    bar_arrive(4, 384);
                    bar_sync(14, 384);
                }
                mbar_wait(BAR(B_XFULL + (kb & 3)), (kb >> 2) & 1);
                wg_fence();
#pragma unroll
                for (int ks = 0; ks < 4; ks++)
                    wgmma_n128<1>(acc, desc_a(sb + SM_X + (kb & 3) * 24576 + 16384 + ks * 256), desc_b<128>(sb + SM_X + (kb & 3) * 24576 + ks * 4096), 1);
                wg_commit();
                wg_wait<1>();
                if ((kb & 3) != 0 && lane == 0) { mbar_arrive(BAR(B_XEMPTY + ((kb - 1) & 3)), 1); mbar_arrive_remote(mapa(BAR(B_XEMPTY + ((kb - 1) & 3)), par ^ 1)); }
            }
            wg_wait<0>();
            if (lane == 0) { mbar_arrive(BAR(B_XEMPTY + 3), 1); mbar_arrive_remote(mapa(BAR(B_XEMPTY + 3), par ^ 1)); mbar_arrive_remote(mapa(BAR(B_RFREE), par ^ 1)); }
            bar_arrive(7, 384);
            bar_sync(3, 128);
            TS(9 + 12 * layer);
            const int m0 = 16 * w + g;
            const uint32_t xoff = (uint32_t)((c * 8 + own) * 16384 + w * 4096 + g * 16 + 4 * q);
            if (layer == 0) {
                const uint8_t* xs = g_X + xoff;
#pragma unroll
                for (int i = 0; i < 16; i++) {
                    float2 rs = *(const float2*)(s_rstd + 8 * i + 2 * q);
                    uint32_t x0v = __ldcg((const uint32_t*)(xs + i * 128)), x1v = __ldcg((const uint32_t*)(xs + 2048 + i * 128));
                    acc[4 * i] = acc[4 * i] * rs.x + bf_lo(x0v);
                    acc[4 * i + 1] = acc[4 * i + 1] * rs.y + bf_hi(x0v);
                    acc[4 * i + 2] = acc[4 * i + 2] * rs.x + bf_lo(x1v);
                    acc[4 * i + 3] = acc[4 * i + 3] * rs.y + bf_hi(x1v);
                }
            } else {
                float d0 = ldbf(p.dskip + 64 * own + m0), d1 = ldbf(p.dskip + 64 * own + m0 + 8);
#pragma unroll
                for (int i = 0; i < 16; i++) {
                    float2 rs = *(const float2*)(s_rstd + 8 * i + 2 * q);
                    float2 mn = *(const float2*)(s_mean + 8 * i + 2 * q);
                    acc[4 * i] = acc[4 * i] * (1.f + rs.x * d0) + mn.x;
                    acc[4 * i + 1] = acc[4 * i + 1] * (1.f + rs.y * d0) + mn.y;
                    acc[4 * i + 2] = acc[4 * i + 2] * (1.f + rs.x * d1) + mn.x;
                    acc[4 * i + 3] = acc[4 * i + 3] * (1.f + rs.y * d1) + mn.y;
                }
            }
            TS(10 + 12 * layer);
            bar_sync(6, 416);
            TS(11 + 12 * layer);
            {
                float (&a0)[32] = *reinterpret_cast<float (*)[32]>(&acc[0]);
                float (&a1)[32] = *reinterpret_cast<float (*)[32]>(&acc[32]);
#pragma unroll 1
                for (int k = 0; k < 2; k++) {
                    const uint32_t hb = sb + SM_HH + (par ^ k) * 32768;
                    if (k == 1) {
                        mbar_wait(BAR(B_HPEER), layer);
                        mbar_wait(BAR(B_HPEER1), layer);
                        bar_sync(12, 384);
                    }
                    mbar_wait(BAR(B_AFULL + 6 + k), 1);
                    const uint64_t da = c_desc(6 + k);
                    wg_fence();
#pragma unroll
                    for (int ks = 0; ks < 4; ks++) {
                        wgmma_n64s<1>(a0, da + ks * dstep, desc_b<64>(hb + ks * 2048), 1);
                        wgmma_n64s<1>(a1, da + ks * dstep, desc_b<64>(hb + 16384 + ks * 2048), 1);
                    }
#pragma unroll
                    for (int ks = 0; ks < 4; ks++) {
                        wgmma_n64s<-1>(a0, da + 512 + ks * dstep, desc_b<64>(hb + 8192 + ks * 2048), 1);
                        wgmma_n64s<-1>(a1, da + 512 + ks * dstep, desc_b<64>(hb + 16384 + 8192 + ks * 2048), 1);
                    }
                    wg_commit();
                }
                wg_wait<0>();
            }
#pragma unroll
            for (int i = 0; i < 16; i++)
                *(float4*)(sm + SM_A + 6 * 16384 + i * 2048 + t2 * 16) = make_float4(acc[4 * i], acc[4 * i + 1], acc[4 * i + 2], acc[4 * i + 3]);
            TS(12 + 12 * layer);
        }
        {
            const int t = tid & 127;
            const int nch = wg == 2 ? 2 : 3;
            const uint4* pb = g_P + (uint32_t)((c * 8 + r) * 4 * 1024 + wg * 128 + t);
            uint4 v[3][3];
            unsigned n = 0;
#pragma unroll 1
            while (true) {
                if (lane == 31) {
#pragma unroll 1
                    while (true) {
                        uint32_t bad = 0;
#pragma unroll
                        for (int sx = 0; sx < 3; sx++) {
                            uint32_t t0;
                            asm volatile("ld.relaxed.gpu.global.u32 %0, [%1];" : "=r"(t0) : "l"(pb + ((pi_ + 1 + sx) & 3) * 1024 + (nch - 1) * 384) : "memory");
                            bad |= t0 ^ ptag;
                        }
                        if (!(bad & 0x00010001u) || ++n >= SPIN_LIMIT) break;
                    }
                }
                __syncwarp();
                uint32_t bad = 0;
#pragma unroll
                for (int k = 0; k < 3; k++)
#pragma unroll
                    for (int sx = 0; sx < 3; sx++) {
                        v[k][sx] = make_uint4(ptag, 0, 0, 0);
                        if (k < nch) v[k][sx] = ld_relaxed_u4(pb + ((pi_ + 1 + sx) & 3) * 1024 + k * 384);
                        bad |= v[k][sx].x ^ ptag;
                    }
                if (!__any_sync(~0u, bad & 0x00010001u) || ++n >= SPIN_LIMIT) break;
            }
            bar_sync(8, 384);
            TS(13 + 12 * layer);
            const int m0 = 16 * w + g;
            const float w0 = (own == 0 && m0 < 2) ? (m0 == 0 ? 0.f : 0.5f) : 1.f;
#pragma unroll
            for (int k = 0; k < 3; k++) {
                if (k < nch) {
                    const int i = wg + 3 * k;
                    float4 a = *(const float4*)(sm + SM_A + 6 * 16384 + (2 * i) * 2048 + t * 16);
                    float4 bq = *(const float4*)(sm + SM_A + 6 * 16384 + (2 * i + 1) * 2048 + t * 16);
#pragma unroll
                    for (int sx = 0; sx < 3; sx++) {
                        a.x += bf_lo(v[k][sx].x); a.y += bf_hi(v[k][sx].x); a.z += bf_lo(v[k][sx].y); a.w += bf_hi(v[k][sx].y);
                        bq.x += bf_lo(v[k][sx].z); bq.y += bf_hi(v[k][sx].z); bq.z += bf_lo(v[k][sx].w); bq.w += bf_hi(v[k][sx].w);
                    }
                    if (layer == 0) {
                        uint8_t* xd = g_X + (uint32_t)((16 * 8 + c * 8 + own) * 16384 + w * 4096 + g * 16 + 4 * q + i * 256);
                        uint32_t v0 = pack_bf16(a.x, a.y), v1 = pack_bf16(a.z, a.w), v2 = pack_bf16(bq.x, bq.y), v3 = pack_bf16(bq.z, bq.w);
                        *(uint32_t*)(xd) = v0; *(uint32_t*)(xd + 2048) = v1; *(uint32_t*)(xd + 128) = v2; *(uint32_t*)(xd + 2048 + 128) = v3;
                        float sq[4];
                        sq[0] = w0 * bf_lo(v0) * bf_lo(v0) + bf_lo(v1) * bf_lo(v1);
                        sq[1] = w0 * bf_hi(v0) * bf_hi(v0) + bf_hi(v1) * bf_hi(v1);
                        sq[2] = w0 * bf_lo(v2) * bf_lo(v2) + bf_lo(v3) * bf_lo(v3);
                        sq[3] = w0 * bf_hi(v2) * bf_hi(v2) + bf_hi(v3) * bf_hi(v3);
                        float u0 = (g & 1) ? sq[2] : sq[0], u1 = (g & 1) ? sq[3] : sq[1];
                        u0 += __shfl_xor_sync(~0u, (g & 1) ? sq[0] : sq[2], 4);
                        u1 += __shfl_xor_sync(~0u, (g & 1) ? sq[1] : sq[3], 4);
                        float z = (g & 2) ? u1 : u0;
                        z += __shfl_xor_sync(~0u, (g & 2) ? u0 : u1, 8);
                        z += __shfl_xor_sync(~0u, z, 16);
                        if (g < 4) atomicAdd(s_mean + 16 * i + 8 * (g & 1) + 2 * q + (g >> 1), z);
                    } else {
                        float* o = p.out + (uint32_t)((128 * c + 32 * q + 4 * i) * 512 + 64 * own + m0);
                        o[0] = a.x; o[512] = a.y; o[8] = a.z; o[512 + 8] = a.w;
                        o[1024] = bq.x; o[1536] = bq.y; o[1024 + 8] = bq.z; o[1536 + 8] = bq.w;
                    }
                }
            }
            if (wg < 2) mbar_wait_cluster(BAR(B_HDONE), layer);
            if (layer == 0) {
                fence_async_smem();
                bar_sync(9, 384);
                TS(14 + 12 * layer);
                if (wg == 2) {
                    atomicAdd(g_ssq + 2048 + 128 * c + t, s_mean[t] * (2.f / 512.f));
                    bar_sync(3, 128);
                    if (lane == 0) { mbar_arrive(BAR(B_AEMPTY + 6), 2); mbar_arrive(BAR(B_AEMPTY + 7), 2); }
                    if (t == 0) { fence_async(); red_release(&g_bar[2], 1); }
                }
            }
        }
        TS(15 + 12 * layer);
        if (wg == 0) TC(31);
    }
}

typedef CUresult (*EncFn)(CUtensorMap*, CUtensorMapDataType, cuuint32_t, void*, const cuuint64_t*, const cuuint64_t*,
                          const cuuint32_t*, const cuuint32_t*, CUtensorMapInterleave, CUtensorMapSwizzle,
                          CUtensorMapL2promotion, CUtensorMapFloatOOBfill);

void launch_impl(void* const* d_in, void* d_out, int stop) {
    static EncFn enc = nullptr;
    if (!enc) {
        void* fn = nullptr;
        cudaDriverEntryPointQueryResult qr;
        cudaGetDriverEntryPoint("cuTensorMapEncodeTiled", &fn, cudaEnableDefault, &qr);
        enc = (EncFn)fn;
        cudaFuncSetAttribute(fused_kernel, cudaFuncAttributeMaxDynamicSharedMemorySize, SM_TOTAL);
    }
    CUtensorMap tx, tbr, tbi, tcr, tci, tcol;
    {
        void* gx = nullptr;
        cudaGetSymbolAddress(&gx, g_X);
        cuuint64_t gd[5] = {64, 16, 64, 16, 2};
        cuuint64_t gs[4] = {128, 2048, 128 * 1024, 2048 * 1024};
        cuuint32_t bx[5] = {32, 16, 1, 16, 1};
        cuuint32_t es[5] = {1, 1, 1, 1, 1};
        enc(&tcol, CU_TENSOR_MAP_DATA_TYPE_BFLOAT16, 5, gx, gd, gs, bx, es, CU_TENSOR_MAP_INTERLEAVE_NONE,
            CU_TENSOR_MAP_SWIZZLE_64B, CU_TENSOR_MAP_L2_PROMOTION_NONE, CU_TENSOR_MAP_FLOAT_OOB_FILL_NONE);
    }
    {
        cuuint64_t gd[5] = {512, 2, 4, 16, 16};
        cuuint64_t gs[4] = {1024, 32 * 1024, 2 * 1024, 128 * 1024};
        cuuint32_t bx[5] = {64, 2, 4, 8, 1};
        cuuint32_t es[5] = {1, 1, 1, 1, 1};
        enc(&tx, CU_TENSOR_MAP_DATA_TYPE_BFLOAT16, 5, d_in[0], gd, gs, bx, es, CU_TENSOR_MAP_INTERLEAVE_NONE,
            CU_TENSOR_MAP_SWIZZLE_128B, CU_TENSOR_MAP_L2_PROMOTION_L2_128B, CU_TENSOR_MAP_FLOAT_OOB_FILL_NONE);
    }
    auto mk2 = [&](CUtensorMap* m, void* ptr, cuuint32_t rows) {
        cuuint64_t gd[2] = {512, 512};
        cuuint64_t gs[1] = {1024};
        cuuint32_t bx[2] = {64, rows};
        cuuint32_t es[2] = {1, 1};
        enc(m, CU_TENSOR_MAP_DATA_TYPE_BFLOAT16, 2, ptr, gd, gs, bx, es, CU_TENSOR_MAP_INTERLEAVE_NONE,
            CU_TENSOR_MAP_SWIZZLE_128B, CU_TENSOR_MAP_L2_PROMOTION_L2_128B, CU_TENSOR_MAP_FLOAT_OOB_FILL_NONE);
    };
    mk2(&tbr, d_in[6], 32);
    mk2(&tbi, d_in[7], 32);
    mk2(&tcr, d_in[8], 64);
    mk2(&tci, d_in[9], 64);
    Params p;
    p.x0 = (const __nv_bfloat16*)d_in[0];
    p.w_r = (const __nv_bfloat16*)d_in[1];
    p.w_i = (const __nv_bfloat16*)d_in[2];
    p.lam_re = (const __nv_bfloat16*)d_in[4];
    p.lam_im = (const __nv_bfloat16*)d_in[5];
    p.log_dt = (const __nv_bfloat16*)d_in[10];
    p.dskip = (const __nv_bfloat16*)d_in[11];
    p.out = (float*)d_out;
    p.stop = stop;
    cudaLaunchConfig_t cfg = {};
    cfg.gridDim = dim3(NCTA); cfg.blockDim = dim3(NTHREADS); cfg.dynamicSmemBytes = SM_TOTAL; cfg.stream = cudaStreamPerThread;
    cudaLaunchAttribute at[1];
    at[0].id = cudaLaunchAttributeClusterDimension;
    at[0].val.clusterDim.x = 2; at[0].val.clusterDim.y = 1; at[0].val.clusterDim.z = 1;
    cfg.attrs = at; cfg.numAttrs = 1;
    cudaLaunchKernelEx(&cfg, fused_kernel, tx, tbr, tbi, tcr, tci, tcol, p);
}

}

extern "C" void kernel_launch(void* const* d_in, const int* in_sizes, int n_in, void* d_out, int out_size) {
    (void)in_sizes; (void)n_in; (void)out_size;
    launch_impl(d_in, d_out, 100);
}
```

```cpp
#include <cuda_runtime.h>
#include <cuda_bf16.h>
#include <cuda.h>
#include <stdint.h>

namespace {

constexpr int NCTA = 128;
constexpr int NTHREADS = 512;
constexpr int SM_A = 0;
constexpr int SM_X = 131072;
constexpr int SM_H = 196608;
constexpr int SM_HH = SM_X + 32768;
constexpr int SM_M = 229376;
constexpr int SM_TOTAL = 232448;
constexpr int SM_BAR = SM_M;
constexpr int SM_TGT = SM_M + 400;
constexpr int SM_LAM = SM_M + 424;
constexpr int SM_TAB = SM_M + 944;
constexpr int SM_RSTD = SM_M + 1920;
constexpr int SM_MEAN = SM_TAB;
constexpr int SM_T64 = SM_M + 2944;
constexpr int SM_B1ST = SM_H + 24576;
constexpr int SM_RAW = SM_X + 40960;
constexpr int SM_SSQ = SM_X + 57344;
constexpr int B_FULL0 = 0;
constexpr int B_EMPTY0 = 8;
constexpr int B_FULLC = 12;
constexpr int B_AFULL = 13;
constexpr int B_AEMPTY = 21;
constexpr int B_XFULL = 29;
constexpr int B_XEMPTY = 33;
constexpr int B_AFREE = 37;
constexpr int B_COL = 38;
constexpr int B_SSQ = 39;
constexpr int B_HPEER = 40;
constexpr int B_RFREE = 41;
constexpr int B_HDONE = 42;
constexpr int B_WRDY = 43;
constexpr int B_HPEER1 = 44;
constexpr int B_FULLB = 45;
constexpr int B_BFREE = 46;
constexpr int B_SETUP = 47;
constexpr int B_B1DONE = 48;
constexpr int B_WST = 49;
constexpr int NBARS = 50;

__device__ __align__(1024) uint8_t g_X[2 * 16 * 8 * 16384];
__device__ __align__(1024) uint8_t g_A1[8 * 8 * 16384];
__device__ __align__(1024) uint8_t g_A2[8 * 8 * 16384];
__device__ __align__(1024) uint8_t g_E[2 * 8 * 8 * 8192];
__device__ __align__(16) float g_ssq[2 * 2048];
__device__ __align__(16) float g_ssqc[2 * 16 * 2048];
__device__ __align__(16) float g_Dh[512];
__device__ __align__(16) uint4 g_Wfrag[128 * 4 * 256];
__device__ __align__(16) float4 g_Ebuf[2 * 16 * 512];
__device__ __align__(16) uint4 g_P[16 * 8 * 4 * 1024];
__device__ unsigned g_bar[8];
__device__ unsigned g_err;
#define TX(i)
#define TQ(i)
#define TS(i)
#define TC(i)

constexpr unsigned SPIN_LIMIT = 1u << 22;

__device__ __forceinline__ uint32_t s2u(const void* p) { return (uint32_t)__cvta_generic_to_shared(p); }
__device__ __forceinline__ void mbar_init(uint32_t a, uint32_t c) {
    asm volatile("mbarrier.init.shared::cta.b64 [%0], %1;" ::"r"(a), "r"(c) : "memory");
}
__device__ __forceinline__ void mbar_expect(uint32_t a, uint32_t bytes) {
    asm volatile("mbarrier.arrive.expect_tx.shared::cta.b64 _, [%0], %1;" ::"r"(a), "r"(bytes) : "memory");
}
__device__ __forceinline__ void mbar_arrive(uint32_t a, uint32_t cnt) {
    asm volatile("mbarrier.arrive.shared::cta.b64 _, [%0], %1;" ::"r"(a), "r"(cnt) : "memory");
}
__device__ __forceinline__ bool mbar_try(uint32_t a, uint32_t parity) {
    uint32_t ok;
    asm volatile("{\n.reg .pred p;\nmbarrier.try_wait.parity.shared::cta.b64 p, [%1], %2;\nselp.u32 %0, 1, 0, p;\n}"
                 : "=r"(ok) : "r"(a), "r"(parity) : "memory");
    return ok != 0;
}
__device__ __forceinline__ void mbar_wait(uint32_t a, uint32_t parity) {
    asm volatile("{\n.reg .pred p, q;\n.reg .u32 n;\nmov.u32 n, 0;\n"
                 "W_%=:\nmbarrier.try_wait.parity.shared::cta.b64 p, [%0], %1;\n@p bra D_%=;\n"
                 "add.u32 n, n, 1;\nsetp.lt.u32 q, n, 4194304;\n@q bra W_%=;\nD_%=:\n}" ::"r"(a), "r"(parity) : "memory");
}
__device__ __forceinline__ void bulk_g2s(uint32_t dst, const void* src, uint32_t bytes, uint32_t bar) {
    asm volatile("cp.async.bulk.shared::cluster.global.mbarrier::complete_tx::bytes [%0], [%1], %2, [%3];" ::"r"(dst),
                 "l"(src), "r"(bytes), "r"(bar) : "memory");
}
__device__ __forceinline__ void tma_2d(uint32_t dst, const CUtensorMap* m, int c0, int c1, uint32_t bar) {
    asm volatile("cp.async.bulk.tensor.2d.shared::cluster.global.mbarrier::complete_tx::bytes [%0], [%1, {%3,%4}], [%2];" ::"r"(dst),
                 "l"(m), "r"(bar), "r"(c0), "r"(c1) : "memory");
}
__device__ __forceinline__ void tma_5d(uint32_t dst, const CUtensorMap* m, int c0, int c1, int c2, int c3, int c4, uint32_t bar) {
    asm volatile("cp.async.bulk.tensor.5d.shared::cluster.global.mbarrier::complete_tx::bytes [%0], [%1, {%3,%4,%5,%6,%7}], [%2];" ::"r"(dst),
                 "l"(m), "r"(bar), "r"(c0), "r"(c1), "r"(c2), "r"(c3), "r"(c4) : "memory");
}
__device__ __forceinline__ void tma_2d_mc(uint32_t dst, const CUtensorMap* m, int c0, int c1, uint32_t bar) {
    asm volatile("cp.async.bulk.tensor.2d.shared::cluster.global.mbarrier::complete_tx::bytes.multicast::cluster [%0], [%1, {%3,%4}], [%2], %5;" ::"r"(dst),
                 "l"(m), "r"(bar), "r"(c0), "r"(c1), "h"((unsigned short)3) : "memory");
}
__device__ __forceinline__ void tma_5d_mc(uint32_t dst, const CUtensorMap* m, int c0, int c1, int c2, int c3, int c4, uint32_t bar) {
    asm volatile("cp.async.bulk.tensor.5d.shared::cluster.global.mbarrier::complete_tx::bytes.multicast::cluster [%0], [%1, {%3,%4,%5,%6,%7}], [%2], %8;" ::"r"(dst),
                 "l"(m), "r"(bar), "r"(c0), "r"(c1), "r"(c2), "r"(c3), "r"(c4), "h"((unsigned short)3) : "memory");
}
__device__ __forceinline__ void bulk_g2s_mc(uint32_t dst, const void* src, uint32_t bytes, uint32_t bar) {
    asm volatile("cp.async.bulk.shared::cluster.global.mbarrier::complete_tx::bytes.multicast::cluster [%0], [%1], %2, [%3], %4;" ::"r"(dst),
                 "l"(src), "r"(bytes), "r"(bar), "h"((unsigned short)3) : "memory");
}
__device__ __forceinline__ void tma_store_5d(const CUtensorMap* m, int c0, int c1, int c2, int c3, int c4, uint32_t src) {
    asm volatile("cp.async.bulk.tensor.5d.global.shared::cta.bulk_group [%0, {%2,%3,%4,%5,%6}], [%1];" ::"l"(m), "r"(src),
                 "r"(c0), "r"(c1), "r"(c2), "r"(c3), "r"(c4) : "memory");
}
__device__ __forceinline__ uint32_t lds32(uint32_t a) { uint32_t v; asm volatile("ld.shared.u32 %0, [%1];" : "=r"(v) : "r"(a) : "memory"); return v; }
__device__ __forceinline__ uint4 ld_relaxed_u4(const uint4* p) {
    uint4 v;
    asm volatile("ld.relaxed.gpu.global.v4.u32 {%0,%1,%2,%3}, [%4];" : "=r"(v.x), "=r"(v.y), "=r"(v.z), "=r"(v.w) : "l"(p) : "memory");
    return v;
}
__device__ __forceinline__ void fence_async() { asm volatile("fence.proxy.async.global;" ::: "memory"); }
__device__ __forceinline__ void red_relaxed(unsigned* p, unsigned v) {
    asm volatile("red.relaxed.gpu.global.add.u32 [%0], %1;" ::"l"(p), "r"(v) : "memory");
}
__device__ __forceinline__ uint32_t mapa(uint32_t a, uint32_t rank) {
    uint32_t d;
    asm("mapa.shared::cluster.u32 %0, %1, %2;" : "=r"(d) : "r"(a), "r"(rank));
    return d;
}
__device__ __forceinline__ void mbar_arrive_remote(uint32_t ra) {
    asm volatile("mbarrier.arrive.relaxed.cluster.shared::cluster.b64 _, [%0];" ::"r"(ra) : "memory");
}
__device__ __forceinline__ void mbar_wait_cluster(uint32_t a, uint32_t parity) {
    asm volatile("{\n.reg .pred p, q;\n.reg .u32 n;\nmov.u32 n, 0;\n"
                 "W_%=:\nmbarrier.try_wait.parity.acquire.cluster.shared::cta.b64 p, [%0], %1;\n@p bra D_%=;\n"
                 "add.u32 n, n, 1;\nsetp.lt.u32 q, n, 4194304;\n@q bra W_%=;\nD_%=:\n}" ::"r"(a), "r"(parity) : "memory");
}
__device__ __forceinline__ void bulk_s2peer(uint32_t rdst, uint32_t src, uint32_t bytes, uint32_t rbar) {
    asm volatile("cp.async.bulk.shared::cluster.shared::cta.mbarrier::complete_tx::bytes [%0], [%1], %2, [%3];" ::"r"(rdst),
                 "r"(src), "r"(bytes), "r"(rbar) : "memory");
}
__device__ __forceinline__ void fence_async_smem() { asm volatile("fence.proxy.async.shared::cta;" ::: "memory"); }
__device__ __forceinline__ void wg_fence() { asm volatile("wgmma.fence.sync.aligned;" ::: "memory"); }
__device__ __forceinline__ void wg_commit() { asm volatile("wgmma.commit_group.sync.aligned;" ::: "memory"); }
template <int N> __device__ __forceinline__ void wg_wait() { asm volatile("wgmma.wait_group.sync.aligned %0;" ::"n"(N) : "memory"); }
__device__ __forceinline__ void bar_sync(int id, int n) { asm volatile("bar.sync %0, %1;" ::"r"(id), "r"(n) : "memory"); }
__device__ __forceinline__ void bar_arrive(int id, int n) { asm volatile("bar.arrive %0, %1;" ::"r"(id), "r"(n) : "memory"); }
__device__ __forceinline__ unsigned ld_acquire(const unsigned* p) {
    unsigned v;
    asm volatile("ld.acquire.gpu.global.u32 %0, [%1];" : "=r"(v) : "l"(p) : "memory");
    return v;
}
__device__ __forceinline__ void red_release(unsigned* p, unsigned v) {
    asm volatile("red.release.gpu.global.add.u32 [%0], %1;" ::"l"(p), "r"(v) : "memory");
}
__device__ __forceinline__ void wait_count(const unsigned* p, unsigned target) {
    unsigned n = 0;
#pragma unroll 1
    while ((int)(ld_acquire(p) - target) < 0 && ++n < SPIN_LIMIT) {}
}
__device__ __forceinline__ float4 ld_relaxed_f4(const float4* p) {
    float4 v;
    asm volatile("ld.relaxed.gpu.global.v4.f32 {%0,%1,%2,%3}, [%4];" : "=f"(v.x), "=f"(v.y), "=f"(v.z), "=f"(v.w) : "l"(p) : "memory");
    return v;
}
__device__ __forceinline__ void st_relaxed_f4(float4* p, float4 v) {
    asm volatile("st.relaxed.gpu.global.v4.f32 [%0], {%1,%2,%3,%4};" ::"l"(p), "f"(v.x), "f"(v.y), "f"(v.z), "f"(v.w) : "memory");
}
__device__ __forceinline__ uint32_t pack_bf16(float lo, float hi) {
    uint32_t r;
    asm("cvt.rn.bf16x2.f32 %0, %1, %2;" : "=r"(r) : "f"(hi), "f"(lo));
    return r;
}
__device__ __forceinline__ uint32_t hmul2(uint32_t a, uint32_t b) {
    uint32_t r;
    asm("mul.rn.bf16x2 %0, %1, %2;" : "=r"(r) : "r"(a), "r"(b));
    return r;
}
__device__ __forceinline__ uint32_t hfma2(uint32_t a, uint32_t b, uint32_t c) {
    uint32_t r;
    asm("fma.rn.bf16x2 %0, %1, %2, %3;" : "=r"(r) : "r"(a), "r"(b), "r"(c));
    return r;
}
__device__ __forceinline__ float bf_lo(uint32_t v) { return __uint_as_float(v << 16); }
__device__ __forceinline__ float bf_hi(uint32_t v) { return __uint_as_float(v & 0xffff0000u); }
__device__ __forceinline__ void sts32(uint32_t a, uint32_t v) { asm volatile("st.shared.u32 [%0], %1;" ::"r"(a), "r"(v) : "memory"); }
__device__ __forceinline__ void sts128(uint32_t a, uint4 v) {
    asm volatile("st.shared.v4.u32 [%0], {%1,%2,%3,%4};" ::"r"(a), "r"(v.x), "r"(v.y), "r"(v.z), "r"(v.w) : "memory");
}

__device__ __forceinline__ uint64_t desc_ni(uint32_t addr, uint32_t lbo, uint32_t sbo) {
    return (uint64_t)((addr & 0x3FFFF) >> 4) | ((uint64_t)(lbo >> 4) << 16) | ((uint64_t)(sbo >> 4) << 32);
}
__device__ __forceinline__ uint64_t desc_a(uint32_t addr) { return desc_ni(addr, 128, 1024); }
template <int N> __device__ __forceinline__ uint64_t desc_b(uint32_t addr) { return desc_ni(addr, 16 * N, 128); }
__device__ __forceinline__ uint64_t desc_k(uint32_t addr) {
    return (uint64_t)((addr & 0x3FFFF) >> 4) | (1ull << 16) | (64ull << 32) | (1ull << 62);
}
__device__ __forceinline__ uint64_t desc_mn(uint32_t addr, uint32_t lbo) {
    return (uint64_t)((addr & 0x3FFFF) >> 4) | ((uint64_t)(lbo >> 4) << 16) | (64ull << 32) | (1ull << 62);
}

#define ACC8(d, o) "+f"(d[o + 0]), "+f"(d[o + 1]), "+f"(d[o + 2]), "+f"(d[o + 3]), "+f"(d[o + 4]), "+f"(d[o + 5]), "+f"(d[o + 6]), "+f"(d[o + 7])
template <int TB, int SA = 1>
__device__ __forceinline__ void wgmma_n128(float (&d)[64], uint64_t da, uint64_t db, int sd) {
    asm volatile(
        "{\n.reg .pred p;\nsetp.ne.b32 p, %66, 0;\n"
        "wgmma.mma_async.sync.aligned.m64n128k16.f32.bf16.bf16 "
        "{%0,%1,%2,%3,%4,%5,%6,%7,%8,%9,%10,%11,%12,%13,%14,%15,%16,%17,%18,%19,%20,%21,%22,%23,%24,%25,%26,%27,%28,%29,%30,%31,"
        "%32,%33,%34,%35,%36,%37,%38,%39,%40,%41,%42,%43,%44,%45,%46,%47,%48,%49,%50,%51,%52,%53,%54,%55,%56,%57,%58,%59,%60,%61,%62,%63},"
        " %64, %65, p, %68, 1, 0, %67;\n}"
        : ACC8(d, 0), ACC8(d, 8), ACC8(d, 16), ACC8(d, 24), ACC8(d, 32), ACC8(d, 40), ACC8(d, 48), ACC8(d, 56)
        : "l"(da), "l"(db), "r"(sd), "n"(TB), "n"(SA));
}
template <int N> __device__ __forceinline__ void acc_def(float (&d)[N]) {
#pragma unroll
    for (int i = 0; i < N; i++) d[i] = 0.f;
}
template <int TB>
__device__ __forceinline__ void wgmma_n64(float (&d)[32], uint64_t da, uint64_t db, int sd) {
    asm volatile(
        "{\n.reg .pred p;\nsetp.ne.b32 p, %34, 0;\n"
        "wgmma.mma_async.sync.aligned.m64n64k16.f32.bf16.bf16 "
        "{%0,%1,%2,%3,%4,%5,%6,%7,%8,%9,%10,%11,%12,%13,%14,%15,%16,%17,%18,%19,%20,%21,%22,%23,%24,%25,%26,%27,%28,%29,%30,%31},"
        " %32, %33, p, 1, 1, 0, %35;\n}"
        : ACC8(d, 0), ACC8(d, 8), ACC8(d, 16), ACC8(d, 24)
        : "l"(da), "l"(db), "r"(sd), "n"(TB));
}
template <int SA>
__device__ __forceinline__ void wgmma_n64s(float (&d)[32], uint64_t da, uint64_t db, int sd) {
    asm volatile(
        "{\n.reg .pred p;\nsetp.ne.b32 p, %34, 0;\n"
        "wgmma.mma_async.sync.aligned.m64n64k16.f32.bf16.bf16 "
        "{%0,%1,%2,%3,%4,%5,%6,%7,%8,%9,%10,%11,%12,%13,%14,%15,%16,%17,%18,%19,%20,%21,%22,%23,%24,%25,%26,%27,%28,%29,%30,%31},"
        " %32, %33, p, %35, 1, 0, 1;\n}"
        : ACC8(d, 0), ACC8(d, 8), ACC8(d, 16), ACC8(d, 24)
        : "l"(da), "l"(db), "r"(sd), "n"(SA));
}
__device__ __forceinline__ void wgmma_n64_rs(float (&d)[32], uint32_t a0, uint32_t a1, uint32_t a2, uint32_t a3, uint64_t db, int sd) {
    asm volatile(
        "{\n.reg .pred p;\nsetp.ne.b32 p, %37, 0;\n"
        "wgmma.mma_async.sync.aligned.m64n64k16.f32.bf16.bf16 "
        "{%0,%1,%2,%3,%4,%5,%6,%7,%8,%9,%10,%11,%12,%13,%14,%15,%16,%17,%18,%19,%20,%21,%22,%23,%24,%25,%26,%27,%28,%29,%30,%31},"
        " {%32,%33,%34,%35}, %36, p, 1, 1, 1;\n}"
        : ACC8(d, 0), ACC8(d, 8), ACC8(d, 16), ACC8(d, 24)
        : "r"(a0), "r"(a1), "r"(a2), "r"(a3), "l"(db), "r"(sd));
}

struct Params {
    const __nv_bfloat16* x0;
    const __nv_bfloat16* w_r;
    const __nv_bfloat16* w_i;
    const __nv_bfloat16* lam_re;
    const __nv_bfloat16* lam_im;
    const __nv_bfloat16* log_dt;
    const __nv_bfloat16* dskip;
    float* out;
    int stop;
};

__device__ __forceinline__ float ldbf(const __nv_bfloat16* p) { return __bfloat162float(*p); }

__device__ __forceinline__ void dft_fp(int j, int& f, int& ph) {
    int cs = j >> 1;
    if (j == 1) { f = 256; ph = 0; }
    else { f = cs; ph = (j & 1) ? 128 : 0; }
}

__device__ __forceinline__ void gen_col_consts(uint32_t sb, int tid) {
#pragma unroll 1
    for (int task = tid; task < 640; task += 256) {
        int f, c8;
        uint32_t a_cc, d_pi, d_po;
        if (task < 512) {
            f = task & 63; c8 = task >> 6;
            a_cc = sb + SM_X + (f >> 5) * 16384 + ((f >> 3) & 3) * 2048 + c8 * 128 + (f & 7) * 16;
            d_pi = 8192; d_po = 1024;
        } else {
            int n2 = task & 31;
            f = 2 * n2; c8 = (task >> 5) & 3;
            a_cc = sb + SM_X + 32768 + (n2 >> 3) * 1024 + c8 * 128 + (n2 & 7) * 16;
            d_pi = 4096; d_po = 512;
        }
        float cd, sd, cs, sn;
        __sincosf((float)(f >= 32 ? f - 64 : f) * (6.283185307179586f / 64.f), &sd, &cd);
        int a = (8 * c8 * f) & 63;
        __sincosf((float)(a >= 32 ? a - 64 : a) * (6.283185307179586f / 64.f), &sn, &cs);
        float cv[8], sv[8];
#pragma unroll
        for (int e = 0; e < 8; e++) {
            cv[e] = cs; sv[e] = sn;
            float t = cs * cd - sn * sd;
            sn = sn * cd + cs * sd;
            cs = t;
        }
        uint4 oc = make_uint4(pack_bf16(cv[0], cv[1]), pack_bf16(cv[2], cv[3]), pack_bf16(cv[4], cv[5]), pack_bf16(cv[6], cv[7]));
        uint4 os = make_uint4(pack_bf16(sv[0], sv[1]), pack_bf16(sv[2], sv[3]), pack_bf16(sv[4], sv[5]), pack_bf16(sv[6], sv[7]));
        sts128(a_cc, oc);
        sts128(a_cc + d_pi, os);
        sts128(a_cc + d_po, make_uint4(os.x ^ 0x80008000u, os.y ^ 0x80008000u, os.z ^ 0x80008000u, os.w ^ 0x80008000u));
        sts128(a_cc + d_pi + d_po, oc);
    }
}

__global__ void __launch_bounds__(NTHREADS, 1)
fused_kernel(const __grid_constant__ CUtensorMap tm_x, const __grid_constant__ CUtensorMap tm_bre,
             const __grid_constant__ CUtensorMap tm_bim, const __grid_constant__ CUtensorMap tm_cre,
             const __grid_constant__ CUtensorMap tm_cim, const __grid_constant__ CUtensorMap tm_col, const Params p) {
    extern __shared__ __align__(1024) uint8_t sm[];
    const uint32_t sb = s2u(sm);
    const int tid = threadIdx.x, b = blockIdx.x;
    const int c = b >> 3, r = b & 7;
    const int par = r & 1, pi_ = r >> 1, own = 4 * par + pi_;
    const int wg = __shfl_sync(~0u, tid >> 7, 0), w = __shfl_sync(~0u, (tid >> 5) & 3, 0), lane = tid & 31, g = lane >> 2, q = lane & 3;
    auto BAR = [&](int i) { return sb + SM_BAR + 8 * i; };
    unsigned* s_tgt = (unsigned*)(sm + SM_TGT);

    if (tid < NBARS) {
        int cnt = 1;
        if (tid >= B_EMPTY0 && tid < B_EMPTY0 + 4) cnt = 16;
        if (tid >= B_XEMPTY && tid < B_XEMPTY + 4) cnt = 24;
        if (tid == B_RFREE) cnt = 12;
        if (tid == B_HDONE || tid == B_WST) cnt = 2;
        if ((tid >= B_AEMPTY && tid < B_AEMPTY + 8) || tid == B_BFREE) cnt = 8;
        if (tid == B_AFREE) cnt = 4;
        mbar_init(BAR(tid), cnt);
        asm volatile("fence.mbarrier_init.release.cluster;" ::: "memory");
    }
    asm volatile("barrier.cluster.arrive.release.aligned;" ::: "memory");

    if (wg == 3) {
        asm volatile("setmaxnreg.dec.sync.aligned.u32 56;");
        if (w == 0 && lane < 6) {
            const CUtensorMap* tm = lane == 0 ? &tm_x : lane == 1 ? &tm_bre : lane == 2 ? &tm_bim : lane == 3 ? &tm_cre : lane == 4 ? &tm_cim : &tm_col;
            asm volatile("prefetch.tensormap [%0];" ::"l"(tm) : "memory");
        }
        __syncwarp();
        asm volatile("barrier.cluster.wait.acquire.aligned;" ::: "memory");
        if (w > 0) {
            if (w == 1) {
                float lr[3], li[3], ld[3];
#pragma unroll
                for (int k = 0; k < 3; k++) {
                    int ps = k < 2 ? 64 * r + 32 * k + lane : 32 * c + lane;
                    lr[k] = ldbf(p.lam_re + ps); li[k] = ldbf(p.lam_im + ps); ld[k] = ldbf(p.log_dt + ps);
                }
                if (lane < 6) s_tgt[lane] = ((ld_acquire(&g_bar[lane]) >> 7) + 1u) << 7;
#pragma unroll 1
                for (int k = 0; k < 3; k++) {
                    float a = k == 0 ? lr[0] : (k == 1 ? lr[1] : lr[2]), bq = k == 0 ? li[0] : (k == 1 ? li[1] : li[2]);
                    float dt = __bfloat162float(__float2bfloat16(expf(k == 0 ? ld[0] : (k == 1 ? ld[1] : ld[2]))));
                    float mag = expf(a * dt), t = bq * dt * 0.15915494309189535f, sn, cs;
                    t -= rintf(t);
                    sincospif(2.f * t, &sn, &cs);
                    float er = mag * cs, ei = mag * sn;
                    if (k < 2) {
                        *(float2*)(sm + SM_LAM + (32 * k + lane) * 8) = make_float2(er, ei);
                    } else {
                        er -= 1.f;
                        float inv = 1.f / (a * a + bq * bq);
                        *(float2*)(sm + SM_TAB + lane * 8) = make_float2((er * a + ei * bq) * inv, (ei * a - er * bq) * inv);
                    }
                }
                __syncwarp();
                bar_arrive(15, 160);
                if (lane == 0) mbar_arrive(BAR(B_SETUP), 1);
            }
            if (w > 1) bar_sync(0, 192);
            if (tid == 448) TX(14);
            if (w > 1) {
                if (lane < 8) {
                    const int cl = 8 * (w - 2) + lane;
                    asm volatile("cp.async.bulk.global.shared::cta.bulk_group [%0], [%1], 1024;" ::"l"(g_Wfrag + (uint32_t)((16 * (b & 7) + cl) * 1024 + (b >> 3) * 64)),
                                 "r"(sb + SM_H + cl * 1024) : "memory");
                }
                asm volatile("cp.async.bulk.commit_group;" ::: "memory");
                asm volatile("cp.async.bulk.wait_group 0;" ::: "memory");
                fence_async();
                __syncwarp();
                if (lane == 0) mbar_arrive(BAR(B_WST), 1);
                if (tid == 448) TX(15);
            }
#pragma unroll 1
            for (int i = tid - 448; i < 96 + 128 && w > 1; i += 64) {
                if (i < 96) g_P[(uint32_t)(b * 4 + i / 24) * 1024 + 640 + ((i % 24) >> 1) * 32 + 30 + (i & 1)] = make_uint4(0, 0, 0, 0);
                else g_Ebuf[b * 128 + i - 96] = make_float4(0.f, 0.f, 0.f, 0.f);
            }
            __syncwarp();
            if (w == 3) bar_arrive(11, 192);
            if (w == 2) {
                bar_sync(11, 192);
                if (lane == 0) { TX(7); red_release(&g_bar[4], 1);  }
            }
            if (w == 3) {
#pragma unroll 1
                for (int it = 0; it < 8; it++) {
                    const int m = 4 * c + (it >> 1), d = 64 * r + m, ch = lane + 32 * (it & 1);
                    float v[8];
#pragma unroll
                    for (int e = 0; e < 8; e++) {
                        int j = 8 * ch + e, f, ph;
                        dft_fp(j, f, ph);
                        int a = (d * f + ph) & 511;
                        a = a >= 256 ? a - 512 : a;
                        float wj = j == 0 ? 0.f : (j == 1 ? 1.f / 512.f : 2.f / 512.f);
                        v[e] = wj * __cosf((float)a * (6.283185307179586f / 512.f));
                    }
                    uint32_t off = (uint32_t)(64 + r * 8 + (ch >> 3)) * 8192 + (m >> 3) * 1024 + (ch & 7) * 128 + (m & 7) * 16;
                    *(uint4*)(g_E + off) = make_uint4(pack_bf16(v[0], v[1]), pack_bf16(v[2], v[3]), pack_bf16(v[4], v[5]), pack_bf16(v[6], v[7]));
                }
                __syncwarp();
                if (lane == 0) { fence_async(); red_release(&g_bar[6], 1); }
                return;
            }
            if (w == 2) {
#pragma unroll 1
                for (int it = 0; it < 4; it++) {
                    const int hf = it & 1;
                    __syncwarp();
                    if (hf == 0) bar_sync(13, 288); else bar_sync(6, 416);
                    if (lane == 0) {
                        const uint32_t src = sb + SM_HH + par * 32768 + hf * 16384;
                        bulk_s2peer(mapa(src, par ^ 1), src, 16384, mapa(BAR(hf ? B_HPEER1 : B_HPEER), par ^ 1));
                    }
                }
                return;
            }
            bar_sync(2, 288);
            if (lane == 0) {
                TX(5);
                fence_async();
                red_release(&g_bar[0], 1);
                TX(6);
            }
            __syncwarp();

            bar_sync(12, 160);
            if (lane == 0) {
                asm volatile("cp.async.bulk.global.shared::cta.bulk_group [%0], [%1], 8192;" ::"l"(g_A1 + (uint32_t)(((c >> 1) * 8 + r) * 16384 + (c & 1) * 8192)),
                             "r"(sb + SM_B1ST) : "memory");
                asm volatile("cp.async.bulk.commit_group;" ::: "memory");
                asm volatile("cp.async.bulk.wait_group 0;" ::: "memory");
                mbar_arrive(BAR(B_B1DONE), 1);
                fence_async();
                red_release(&g_bar[7], 1);
            }
#pragma unroll 1
            for (int layer = 0; layer < 2; layer++) {
                __syncwarp();
                bar_sync(5, 416);
                if (lane == 0) {
                    TX(0 + 8 * layer);
                    tma_store_5d(&tm_col, 32 * (b & 1), 0, b >> 1, 0, layer, sb + SM_RAW);
                    asm volatile("cp.reduce.async.bulk.global.shared::cta.bulk_group.add.f32 [%0], [%1], 8192;" ::"l"(g_ssqc + (layer * 16 + (b & 15)) * 2048),
                                 "r"(sb + SM_SSQ) : "memory");
                    asm volatile("cp.async.bulk.commit_group;" ::: "memory");
                    asm volatile("cp.async.bulk.wait_group 0;" ::: "memory");
                    TX(1 + 8 * layer);
                    fence_async();
                    red_release(&g_bar[1 + 2 * layer], 1);
                    TX(2 + 8 * layer);
                }
            }
        } else if (tid == 384) {
#pragma unroll 1
            for (int kb = 0; kb < 8; kb++) {
                uint32_t fb = BAR(B_FULL0 + kb);
                mbar_expect(fb, 16384);
                tma_5d_mc(sb + SM_A + 65536 + kb * 16384 + par * 8192, &tm_x, kb * 64, 0, 0, 8 * par, c, fb);
            }
#pragma unroll 1
            for (int k2 = 0; k2 < 8; k2++) {
                asm volatile("cp.async.bulk.prefetch.tensor.2d.L2.global [%0, {%1,%2}];" ::"l"(par ? &tm_bim : &tm_bre), "r"(k2 * 64), "r"(32 * c) : "memory");
                if ((k2 & 1) == par)
                    asm volatile("cp.async.bulk.prefetch.tensor.2d.L2.global [%0, {%1,%2}];" ::"l"((c & 1) ? &tm_cim : &tm_cre), "r"(64 * (c >> 1)), "r"(k2 * 64) : "memory");
            }
            mbar_wait(BAR(B_SETUP), 0);
#pragma unroll 1
            for (int layer = 0; layer < 2; layer++) {
                if (layer == 1) {
                    mbar_wait(BAR(B_AEMPTY + 6), 1);
                    mbar_expect(BAR(B_WRDY), 16384);
                    bulk_g2s(sb + SM_H + 16384, g_Wfrag + (uint32_t)b * 1024, 16384, BAR(B_WRDY));
                }
                wait_count(&g_bar[2 * layer], s_tgt[2 * layer]);
                TX(4 + 8 * layer);
                fence_async();
                mbar_expect(BAR(B_COL), 16384 + 8192);
                tma_5d(sb + SM_RAW, &tm_col, 32 * (b & 1), 0, b >> 1, 0, layer, BAR(B_COL));
                bulk_g2s(sb + SM_SSQ, g_ssq + layer * 2048, 8192, BAR(B_COL));
                if (layer == 0) {
                    wait_count(&g_bar[4], s_tgt[4]);
                    fence_async();
                    TX(16);
                    mbar_wait(BAR(B_B1DONE), 0);
                    TX(17);
                    mbar_expect(BAR(B_WRDY), 16384);
                    bulk_g2s(sb + SM_H + 16384, g_Wfrag + (uint32_t)b * 1024, 16384, BAR(B_WRDY));
                    wait_count(&g_bar[7], s_tgt[4]);
                    fence_async();
                }
                if (layer == 0) mbar_wait(BAR(B_AFREE), 0);
                mbar_wait(BAR(B_COL), layer);
#pragma unroll 1
                for (int s = 0; s < 8; s++) {
                    if (layer == 1) mbar_wait(BAR(B_AEMPTY + s), 1);
                    if (s >= 2) mbar_wait(BAR(B_AFULL + s - 2), 0);
                    mbar_expect(BAR(B_AFULL + s), 16384);
                    bulk_g2s(sb + SM_A + s * 16384, g_A1 + (uint32_t)(r * 8 + s) * 16384, 16384, BAR(B_AFULL + s));
                }
                if (layer == 1) wait_count(&g_bar[6], s_tgt[4]);
                wait_count(&g_bar[1 + 2 * layer], s_tgt[1 + 2 * layer]);
                TX(3 + 8 * layer);
                fence_async();
                const uint8_t* xsrc = g_X + (uint32_t)(layer * 16 + c) * 8 * 16384;
                const uint8_t* esrc = g_E + (uint32_t)(layer * 8 + own) * 8 * 8192;
                mbar_arrive(BAR(B_SSQ), 1);
                mbar_expect(BAR(B_HPEER), 16384);
                mbar_expect(BAR(B_HPEER1), 16384);
#pragma unroll 1
                for (int it = 0; it < 16; it++) {
                    if (it < 8) {
                        int st = it & 3, f = layer * 2 + (it >> 2);
                        if (f > 0) mbar_wait_cluster(BAR(B_XEMPTY + st), (f - 1) & 1);
                        mbar_expect(BAR(B_XFULL + st), 24576);
                        bulk_g2s_mc(sb + SM_X + st * 24576 + par * 8192, xsrc + (uint32_t)it * 16384 + par * 8192, 8192, BAR(B_XFULL + st));
                        bulk_g2s(sb + SM_X + st * 24576 + 16384, esrc + (uint32_t)it * 8192, 8192, BAR(B_XFULL + st));
                    }
                    if (it >= 8) {
                        if (it == 8) mbar_wait(BAR(B_AEMPTY + 5), 0);
                        int s = it - 8, tile = 4 * par + ((pi_ + 1 + (s >> 1)) & 3), sl = r ^ (s & 1);
                        mbar_wait(BAR(B_AEMPTY + s), 0);
                        uint32_t fb = BAR(B_AFULL + s), dst = sb + SM_A + s * 16384;
                        mbar_expect(fb, 16384);
                        if (layer == 1) {
                            tma_2d(dst, &tm_cre, 64 * sl, 64 * tile, fb);
                            tma_2d(dst + 8192, &tm_cim, 64 * sl, 64 * tile, fb);
                        } else {
                            bulk_g2s(dst, g_A2 + (uint32_t)(sl * 8 + tile) * 16384, 16384, fb);
                        }
                    }
                }
            }
        }
        return;
    }

    asm volatile("setmaxnreg.inc.sync.aligned.u32 152;");
    if (tid >= 96 && tid < 112) g_ssq[2048 + 16 * b + tid - 96] = 0.f;
    if (tid >= 128 && tid < 256) ((float4*)g_ssqc)[b * 128 + tid - 128] = make_float4(0.f, 0.f, 0.f, 0.f);
    TS(0);
    if (wg == 0) TC(30);
    {
        const int f = 32 * r + lane;
        float cd, sd;
        __sincosf((float)f * (6.283185307179586f / 512.f), &sd, &cd);
        const uint32_t dst = sb + SM_A + (lane >> 2) * 1024 + (lane & 3) * 32;
#pragma unroll 1
        for (int ch = tid >> 5; ch < 64; ch += 12) {
            int a = (8 * ch * f) & 511;
            a = a >= 256 ? a - 512 : a;
            float cs, sn;
            __sincosf((float)a * (6.283185307179586f / 512.f), &sn, &cs);
            float cv[8], sv[8];
#pragma unroll
            for (int e = 0; e < 8; e++) {
                cv[e] = cs; sv[e] = -sn;
                float t = cs * cd - sn * sd;
                sn = sn * cd + cs * sd;
                cs = t;
            }
            uint4 o1 = make_uint4(pack_bf16(sv[0], sv[1]), pack_bf16(sv[2], sv[3]), pack_bf16(sv[4], sv[5]), pack_bf16(sv[6], sv[7]));
            if (f == 0) o1 = make_uint4(0xbf803f80u, 0xbf803f80u, 0xbf803f80u, 0xbf803f80u);
            uint32_t a0 = dst + (ch >> 3) * 8192 + (ch & 7) * 128;
            sts128(a0, make_uint4(pack_bf16(cv[0], cv[1]), pack_bf16(cv[2], cv[3]), pack_bf16(cv[4], cv[5]), pack_bf16(cv[6], cv[7])));
            sts128(a0 + 16, o1);
        }
    }
    fence_async_smem();
    asm volatile("barrier.cluster.wait.acquire.aligned;" ::: "memory");
    bar_sync(10, 384);
    TS(1);
    if (wg < 2) {
        float acc[32];
        acc_def(acc);
        const int npos = 16 * r + 8 * wg + 2 * w;
        float sh0 = 0.f, sh1 = 0.f, s0 = 0.f, s1 = 0.f, q0 = 0.f, q1 = 0.f;
#pragma unroll 1
        for (int kb = 0; kb < 8; kb++) {
            uint32_t slot = sb + SM_A + 65536 + kb * 16384;
            mbar_wait(BAR(B_FULL0 + kb), 0);
            wg_fence();
#pragma unroll
            for (int ks = 0; ks < 4; ks++)
                wgmma_n64<0>(acc, desc_a(sb + SM_A + kb * 8192 + ks * 256), desc_k(slot + wg * 8192 + ks * 32), 1);
            wg_commit();
            {
                uint32_t v0 = lds32(slot + npos * 128 + lane * 4), v1 = lds32(slot + npos * 128 + 128 + lane * 4);
                if (kb == 0) { sh0 = __shfl_sync(~0u, bf_lo(v0), 0); sh1 = __shfl_sync(~0u, bf_lo(v1), 0); }
                float a = bf_lo(v0) - sh0, bq = bf_hi(v0) - sh0, cq = bf_lo(v1) - sh1, d = bf_hi(v1) - sh1;
                s0 += a + bq; q0 += a * a + bq * bq; s1 += cq + d; q1 += cq * cq + d * d;
            }
            wg_wait<1>();
            if (kb > 0 && kb <= 4 && lane == 0) { mbar_arrive(BAR(B_EMPTY0 + kb - 1), 1); mbar_arrive_remote(mapa(BAR(B_EMPTY0 + kb - 1), par ^ 1)); }
        }
#pragma unroll
        for (int o = 16; o; o >>= 1) {
            s0 += __shfl_xor_sync(~0u, s0, o); q0 += __shfl_xor_sync(~0u, q0, o);
            s1 += __shfl_xor_sync(~0u, s1, o); q1 += __shfl_xor_sync(~0u, q1, o);
        }
        if (lane == 0) *(float2*)(g_ssq + 128 * c + npos) = make_float2(fmaxf(q0 - s0 * s0 * (1.f / 512.f), 0.f), fmaxf(q1 - s1 * s1 * (1.f / 512.f), 0.f));
        wg_wait<0>();
        TS(2);
        uint8_t* dst = g_X + (uint32_t)((c * 8 + r) * 16384 + w * 4096 + wg * 1024 + g * 16 + 4 * q);
#pragma unroll
        for (int i = 0; i < 8; i++) {
            *(uint32_t*)(dst + i * 128) = pack_bf16(acc[4 * i], acc[4 * i + 1]);
            *(uint32_t*)(dst + 2048 + i * 128) = pack_bf16(acc[4 * i + 2], acc[4 * i + 3]);
        }
        bar_sync(2, 288);
        mbar_wait(BAR(B_SETUP), 0);
        TS(3);
    }

    if (wg == 2) {
        {
            const int cl = tid & 15, cb = 16 * (b & 7) + cl;
            const int c0 = cb == 0 ? 256 : 2 * cb, c1 = 2 * cb + 1;
            uint32_t wf[2][16];
#pragma unroll
            for (int h = 0; h < 2; h++) {
                const int kq = 16 * (b >> 3) + ((tid & 127) >> 4) + 8 * h, k1 = kq >> 2, qq = kq & 3;
                const unsigned short* wr_ = (const unsigned short*)p.w_r + (k1 + 128 * qq) * 257;
                const unsigned short* wi_ = (const unsigned short*)p.w_i + (k1 + 128 * qq) * 257;
#pragma unroll
                for (int i = 0; i < 4; i++) {
                    int o = 512 * i * 257;
                    wf[h][2 * i] = (uint32_t)__ldg(wr_ + o + c0) | ((uint32_t)__ldg(wr_ + o + 64 * 257 + c0) << 16);
                    wf[h][2 * i + 1] = ((uint32_t)__ldg(wi_ + o + c0) | ((uint32_t)__ldg(wi_ + o + 64 * 257 + c0) << 16)) ^ 0x80008000u;
                    wf[h][8 + 2 * i] = (uint32_t)__ldg(wr_ + o + c1) | ((uint32_t)__ldg(wr_ + o + 64 * 257 + c1) << 16);
                    wf[h][8 + 2 * i + 1] = ((uint32_t)__ldg(wi_ + o + c1) | ((uint32_t)__ldg(wi_ + o + 64 * 257 + c1) << 16)) ^ 0x80008000u;
                }
            }
            uint4 p0 = __ldg((const uint4*)p.dskip + 2 * lane), p1 = __ldg((const uint4*)p.dskip + 2 * lane + 1);
            uint32_t u[8] = {p0.x, p0.y, p0.z, p0.w, p1.x, p1.y, p1.z, p1.w};
            int j = 64 * r + 4 * c + w, f, ph;
            dft_fp(j, f, ph);
            float s = 0.f;
            int idx = 16 * lane * f + ph;
#pragma unroll
            for (int i = 0; i < 16; i++) {
                int a = idx & 511;
                idx += f;
                a = a >= 256 ? a - 512 : a;
                s += ((i & 1) ? bf_hi(u[i >> 1]) : bf_lo(u[i >> 1])) * __cosf((float)a * (6.283185307179586f / 512.f));
            }
#pragma unroll
            for (int o = 16; o; o >>= 1) s += __shfl_xor_sync(~0u, s, o);
            if (lane == 0) g_Dh[j] = s;
#pragma unroll
            for (int h = 0; h < 2; h++)
#pragma unroll
                for (int i = 0; i < 4; i++)
                    sts128(sb + SM_H + cl * 1024 + (((tid & 127) >> 4) + 8 * h) * 64 + ((i ^ ((tid >> 5) & 3)) << 4),
                           make_uint4(wf[h][4 * i], wf[h][4 * i + 1], wf[h][4 * i + 2], wf[h][4 * i + 3]));
            fence_async_smem();
            bar_arrive(0, 192);
            bar_arrive(11, 192);
        }
        bar_sync(15, 160);
        float acc[32];
        acc_def(acc);
        if (tid == 256) {
#pragma unroll 1
            for (int s = 0; s < 4; s++) mbar_wait_cluster(BAR(B_EMPTY0 + s), 0);
            mbar_expect(BAR(B_FULLB), 65536);
#pragma unroll 1
            for (int k2 = 0; k2 < 8; k2++)
                tma_2d_mc(sb + SM_A + 65536 + k2 * 8192 + par * 4096, par ? &tm_bim : &tm_bre, k2 * 64, 32 * c, BAR(B_FULLB));
        }
        __syncwarp();
        mbar_wait(BAR(B_FULLB), 0);
        wg_fence();
#pragma unroll 1
        for (int kb = 0; kb < 8; kb++) {
#pragma unroll
            for (int ks = 0; ks < 4; ks++)
                wgmma_n64<0>(acc, desc_a(sb + SM_A + kb * 8192 + ks * 256), desc_k(sb + SM_A + 65536 + kb * 8192 + ks * 32), 1);
            wg_commit();
        }
        wg_wait<0>();
        if (lane == 0) { mbar_arrive(BAR(B_BFREE), 1); mbar_arrive_remote(mapa(BAR(B_BFREE), par ^ 1)); }
        if (tid == 256) {
            mbar_wait_cluster(BAR(B_BFREE), 0);
            mbar_expect(BAR(B_FULLC), 65536);
#pragma unroll 1
            for (int k2 = par; k2 < 8; k2 += 2)
                tma_2d_mc(sb + SM_A + 65536 + k2 * 8192, (c & 1) ? &tm_cim : &tm_cre, 64 * (c >> 1), k2 * 64, BAR(B_FULLC));
        }
        __syncwarp();
        {
            uint8_t* dst = sm + SM_B1ST + w * 256 + q * 32 + g * 2;
            const float wj0 = (r == 0 && w == 0 && g < 2) ? (g == 0 ? 0.f : 1.f / 512.f) : 2.f / 512.f;
#pragma unroll
            for (int i = 0; i < 4; i++) {
#pragma unroll
                for (int e = 0; e < 2; e++) {
                    float2 cf = *(const float2*)(sm + SM_TAB + (8 * i + 2 * q + e) * 8);
#pragma unroll
                    for (int h = 0; h < 2; h++) {
                        float wj = h == 0 ? wj0 : 2.f / 512.f;
                        float pr = acc[4 * i + 2 * h + e] * wj, pi = acc[16 + 4 * i + 2 * h + e] * wj;
                        uint8_t* d2 = dst + i * 2048 + h * 128 + e * 16;
                        *(__nv_bfloat16*)(d2) = __float2bfloat16(cf.x * pr - cf.y * pi);
                        *(__nv_bfloat16*)(d2 + 1024) = __float2bfloat16(cf.x * pi + cf.y * pr);
                    }
                }
            }
            fence_async_smem();
            bar_arrive(12, 160);
        }
        acc_def(acc);
        mbar_wait(BAR(B_FULLC), 0);
        wg_fence();
#pragma unroll 1
        for (int kb = 0; kb < 8; kb++) {
#pragma unroll
            for (int ks = 0; ks < 4; ks++)
                wgmma_n64<1>(acc, desc_a(sb + SM_A + kb * 8192 + ks * 256), desc_mn(sb + SM_A + 65536 + kb * 8192 + ks * 2048, 8192), 1);
            wg_commit();
        }
        wg_wait<0>();
        fence_async_smem();
        if (lane == 0) mbar_arrive(BAR(B_AFREE), 1);
        uint8_t* dst = g_A2 + (uint32_t)(((c >> 1) * 8 + r) * 16384 + (c & 1) * 8192 + w * 2048 + g * 16 + 4 * q);
#pragma unroll
        for (int i = 0; i < 8; i++) {
            *(uint32_t*)(dst + i * 128) = pack_bf16(acc[4 * i], acc[4 * i + 1]);
            *(uint32_t*)(dst + 1024 + i * 128) = pack_bf16(acc[4 * i + 2], acc[4 * i + 3]);
        }
        {
            const int m = 4 * c + w, jp = 64 * r + m;
            int fp, php;
            dft_fp(jp, fp, php);
            const __nv_bfloat16* dh = (const __nv_bfloat16*)(sm + SM_RSTD);
            if (tid == 256) wait_count(&g_bar[4], s_tgt[4]);
            bar_sync(3, 128);
            float4 d4 = __ldcg((const float4*)g_Dh + (tid - 256));
            *(uint2*)(sm + SM_RSTD + (tid - 256) * 8) = make_uint2(pack_bf16(d4.x, d4.y), pack_bf16(d4.z, d4.w));
            bar_sync(3, 128);
#pragma unroll 1
            for (int it = 0; it < 2; it++) {
                const int ch = lane + 32 * it;
                float v[8];
#pragma unroll
                for (int e = 0; e < 8; e++) {
                    int j = 8 * ch + e, f, ph;
                    dft_fp(j, f, ph);
                    float wj = j == 0 ? 0.f : (j == 1 ? 1.f / 512.f : 2.f / 512.f);
                    float gsum = 0.f;
#pragma unroll
                    for (int sgn = 0; sgn < 2; sgn++) {
                        int mm = (sgn ? f - fp : f + fp) & 511, pp = (sgn ? ph - php : ph + php) & 511;
                        if (mm > 256) { mm = 512 - mm; pp = (512 - pp) & 511; }
                        int odd = (pp >> 7) & 1;
                        float t = __bfloat162float(dh[mm == 256 ? 1 : 2 * mm + odd]);
                        if (odd && (mm & 255) == 0) t = 0.f;
                        gsum += (pp & 256) ? -t : t;
                    }
                    v[e] = 0.5f * wj * gsum;
                }
                uint32_t off = (uint32_t)(r * 8 + (ch >> 3)) * 8192 + (m >> 3) * 1024 + (ch & 7) * 128 + (m & 7) * 16;
                *(uint4*)(g_E + off) = make_uint4(pack_bf16(v[0], v[1]), pack_bf16(v[2], v[3]), pack_bf16(v[4], v[5]), pack_bf16(v[6], v[7]));
            }
        }
    }

#pragma unroll 1
    for (int layer = 0; layer < 2; layer++) {
        if (wg < 2) {
            const int n1 = 32 * wg + 8 * w + g;
            const int ct = n1 >> 2;
            gen_col_consts(sb, tid);
            uint32_t tr2[4], ti2[4], tn2[4];
#pragma unroll
            for (int i = 0; i < 4; i++) {
                float cr[2], ci[2];
#pragma unroll
                for (int e = 0; e < 2; e++) {
                    int a = (n1 * (8 * i + 2 * q + e)) & 2047;
                    a = a >= 1024 ? a - 2048 : a;
                    float ang = (float)a * (-6.283185307179586f / 2048.f);
                    cr[e] = __cosf(ang); ci[e] = __sinf(ang);
                }
                tr2[i] = pack_bf16(cr[0], cr[1]); ti2[i] = pack_bf16(ci[0], ci[1]); tn2[i] = ti2[i] ^ 0x80008000u;
            }
            mbar_wait(BAR(B_WST), 0);
            mbar_wait(BAR(B_COL), layer);
            TS(4 + 12 * layer);
            if (wg == 0) TC(0 + 10 * layer);
            const uint32_t rw0 = sb + SM_RAW + ct * 1024 + q * 64 + ((q >> 1) << 4) + (g & 3) * 4, rw1 = rw0 ^ 16;
            const int pos0 = 128 * ct + 8 * q + 2 * (g & 3);
            const int sw = b == 0 ? 1 : 0;
            uint32_t xr[4][4];
            const uint32_t st0 = sb + SM_H + (n1 >> 3) * 1024 + g * 16 + 4 * q;
#pragma unroll
            for (int i = 0; i < 4; i++) {
                float2 sq = *(const float2*)(sm + SM_SSQ + (pos0 + 32 * i) * 4);
                const uint32_t rs2 = pack_bf16(rsqrtf(sq.x * (1.f / 512.f) + 1e-5f), rsqrtf(sq.y * (1.f / 512.f) + 1e-5f));
#pragma unroll
                for (int jj = 0; jj < 4; jj++) {
                    const int K = jj ^ (2 * (i & 1));
                    uint32_t a = ((K & 1) ? rw1 : rw0) + i * 256 + (K & 2) * 16;
                    if (jj < 2) a ^= sw << 4;
                    uint32_t v = lds32(a);
                    xr[jj][i] = v;
                    uint32_t o = hmul2(v, rs2);
                    if (jj == 1 && sw) o = 0u;
                    sts32(st0 + (jj & 1) * 8192 + (4 * (jj >> 1) + i) * 128, o);
                }
            }
            if (wg == 0) TC(1 + 10 * layer);
            fence_async_smem();
            bar_sync(1, 256);
            float acc[32];
            const uint32_t s1a = sb + SM_X + wg * 16384, s2b = sb + SM_X + 32768;
            wg_fence();
#pragma unroll
            for (int ks = 0; ks < 8; ks++)
                wgmma_n64<1>(acc, desc_a(s1a + (ks >> 2) * 8192 + (ks & 3) * 256), desc_b<64>(sb + SM_H + ks * 2048), ks != 0);
            wg_commit();
            wg_wait<0>();
            if (wg == 0) TC(2 + 10 * layer);
            uint32_t are[2][4], aim[2][4];
#pragma unroll
            for (int col = 0; col < 2; col++) {
#pragma unroll
                for (int i = 0; i < 4; i++) {
                    int o = 4 * (4 * col + i);
                    uint32_t zr = pack_bf16(acc[o], acc[o + 1]), zi = pack_bf16(acc[o + 2], acc[o + 3]);
                    are[col][i] = hfma2(zr, tr2[i], hmul2(zi, tn2[i]));
                    aim[col][i] = hfma2(zr, ti2[i], hmul2(zi, tr2[i]));
                }
            }
            wg_fence();
#pragma unroll
            for (int ks = 0; ks < 2; ks++)
                wgmma_n64_rs(acc, are[0][2 * ks], are[1][2 * ks], are[0][2 * ks + 1], are[1][2 * ks + 1], desc_b<64>(s2b + ks * 2048), ks != 0);
#pragma unroll
            for (int ks = 0; ks < 2; ks++)
                wgmma_n64_rs(acc, aim[0][2 * ks], aim[1][2 * ks], aim[0][2 * ks + 1], aim[1][2 * ks + 1], desc_b<64>(s2b + 4096 + ks * 2048), 1);
            wg_commit();
            uint32_t wf[16];
            mbar_wait(BAR(B_WRDY), layer);
#pragma unroll
            for (int i = 0; i < 4; i++) {
                const int kq = n1 * 4 + q;
                uint4 v = *(const uint4*)(sm + SM_H + 16384 + kq * 64 + ((i ^ ((kq >> 1) & 3)) << 4));
                wf[4 * i] = v.x; wf[4 * i + 1] = v.y; wf[4 * i + 2] = v.z; wf[4 * i + 3] = v.w;
            }
            wg_wait<0>();
            if (wg == 0) TC(3 + 10 * layer);
#pragma unroll
            for (int col = 0; col < 2; col++) {
#pragma unroll
                for (int i = 0; i < 4; i++) {
                    uint32_t wr = wf[col * 8 + 2 * i], wn = wf[col * 8 + 2 * i + 1];
                    uint32_t zr = pack_bf16(acc[4 * i + 2 * col], acc[4 * i + 2 * col + 1]);
                    uint32_t zi = pack_bf16(acc[16 + 4 * i + 2 * col], acc[16 + 4 * i + 2 * col + 1]);
                    are[col][i] = hfma2(zr, wr, hmul2(zi, wn));
                    aim[col][i] = hfma2(zr, wn, hmul2(zi ^ 0x80008000u, wr));
                }
            }
            wg_fence();
#pragma unroll
            for (int ks = 0; ks < 2; ks++)
                wgmma_n64_rs(acc, are[0][2 * ks], are[1][2 * ks], are[0][2 * ks + 1], are[1][2 * ks + 1], desc_b<64>(s2b + ks * 2048), ks != 0);
#pragma unroll
            for (int ks = 0; ks < 2; ks++)
                wgmma_n64_rs(acc, aim[0][2 * ks], aim[1][2 * ks], aim[0][2 * ks + 1], aim[1][2 * ks + 1], desc_b<64>(s2b + 4096 + ks * 2048), 1);
            wg_commit();
            wg_wait<0>();
            if (wg == 0) TC(4 + 10 * layer);
            bar_sync(1, 256);
#pragma unroll
            for (int col = 0; col < 2; col++) {
#pragma unroll
                for (int i = 0; i < 4; i++) {
                    uint32_t zr = pack_bf16(acc[4 * i + 2 * col], acc[4 * i + 2 * col + 1]);
                    uint32_t zi = pack_bf16(acc[16 + 4 * i + 2 * col], acc[16 + 4 * i + 2 * col + 1]);
                    sts32(st0 + 16384 + (4 * col + i) * 128, hfma2(zr, tr2[i], hmul2(zi, tn2[i])));
                    sts32(st0 + 16384 + 8192 + (4 * col + i) * 128, hfma2(zr, ti2[i], hmul2(zi, tr2[i])));
                }
            }
            if (wg == 0) TC(5 + 10 * layer);
            fence_async_smem();
            bar_sync(1, 256);
            wg_fence();
#pragma unroll
            for (int ks = 0; ks < 8; ks++)
                wgmma_n64<1>(acc, desc_a(s1a + (ks >> 2) * 8192 + (ks & 3) * 256), desc_b<64>(sb + SM_H + 16384 + ks * 2048), ks != 0);
            wg_commit();
            wg_wait<0>();
            if (wg == 0) TC(6 + 10 * layer);
            const float sc = 1.f / 2048.f;
            const float sci0 = sw ? 0.f : -sc;
            const float wr0 = sw ? 0.5f : 1.f, wi0 = sw ? 0.f : 1.f;
#pragma unroll
            for (int i = 0; i < 4; i++) {
                float ss0, ss1;
#pragma unroll
                for (int col = 0; col < 2; col++) {
                    int o = 4 * (4 * col + i);
                    uint32_t vr = xr[2 * col][i], vi = xr[2 * col + 1][i];
                    float si = col == 0 ? sci0 : -sc;
                    uint32_t nr = pack_bf16(fmaf(acc[o], sc, bf_lo(vr)), fmaf(acc[o + 1], sc, bf_hi(vr)));
                    uint32_t ni = pack_bf16(fmaf(acc[o + 2], si, bf_lo(vi)), fmaf(acc[o + 3], si, bf_hi(vi)));
                    float a0 = bf_lo(nr), a1 = bf_hi(nr), b0 = bf_lo(ni), b1 = bf_hi(ni);
                    if (col == 0) {
                        ss0 = wr0 * a0 * a0 + wi0 * b0 * b0;
                        ss1 = wr0 * a1 * a1 + wi0 * b1 * b1;
                    } else {
                        ss0 += a0 * a0 + b0 * b0;
                        ss1 += a1 * a1 + b1 * b1;
                    }
                    const int K = (2 * col) ^ (2 * (i & 1));
                    uint32_t a = rw0 + i * 256 + K * 16;
                    if (col == 0) a ^= sw << 4;
                    sts32(a, nr);
                    sts32(a ^ 16, ni);
                }
                *(float2*)(sm + SM_SSQ + (pos0 + 32 * i) * 4) = make_float2(ss0 * (2.f / 512.f), ss1 * (2.f / 512.f));
            }
            fence_async_smem();
        }
        TS(5 + 12 * layer);
        if (wg == 0) TC(7 + 10 * layer);
        bar_arrive(5, 416);

        float acc[64];
        float* s_rstd = (float*)(sm + SM_RSTD);
        float* s_mean = (float*)(sm + SM_MEAN);
        const unsigned epoch = s_tgt[0] >> 7;
        const uint32_t pt3 = 1u + (2u * epoch + layer) % 3u;
        const uint32_t ptag = (pt3 & 1u) | ((pt3 & 2u) << 15);
        const uint64_t dstep = layer == 0 ? 16 : 2;
        auto c_desc = [&](int s) { return layer == 0 ? desc_a(sb + SM_A + s * 16384) : desc_k(sb + SM_A + s * 16384); };
        if (wg < 2) {
            const int prow = 32 * wg + 8 * w + g;
            const float2 l1 = *(const float2*)(sm + SM_LAM + prow * 8);
            float lr32 = l1.x, li32 = l1.y;
#pragma unroll
            for (int i = 0; i < 5; i++) { float t = lr32 * lr32 - li32 * li32; li32 = 2.f * lr32 * li32; lr32 = t; }
            float lr128 = lr32, li128 = li32;
#pragma unroll
            for (int i = 0; i < 2; i++) { float t = lr128 * lr128 - li128 * li128; li128 = 2.f * lr128 * li128; lr128 = t; }
            const float lr1 = l1.x, li1 = l1.y;
            acc_def(acc);
#pragma unroll 1
            for (int kb = 0; kb < 8; kb++) {
                mbar_wait(BAR(B_AFULL + kb), 0);
                mbar_wait(BAR(B_XFULL + (kb & 3)), (kb >> 2) & 1);
                wg_fence();
#pragma unroll
                for (int ks = 0; ks < 4; ks++)
                    wgmma_n128<1>(acc, desc_a(sb + SM_A + kb * 16384 + wg * 8192 + ks * 256),
                                  desc_b<128>(sb + SM_X + (kb & 3) * 24576 + ks * 4096), 1);
                wg_commit();
                wg_wait<1>();
                if (kb > 0 && lane == 0) {
                    mbar_arrive(BAR(B_AEMPTY + kb - 1), 1); mbar_arrive(BAR(B_XEMPTY + ((kb - 1) & 3)), 1);
                    mbar_arrive_remote(mapa(BAR(B_XEMPTY + ((kb - 1) & 3)), par ^ 1));
                }
            }
            wg_wait<0>();
            if (lane == 0) {
                mbar_arrive(BAR(B_AEMPTY + 7), 1); mbar_arrive(BAR(B_XEMPTY + 3), 1);
                mbar_arrive_remote(mapa(BAR(B_XEMPTY + 3), par ^ 1)); mbar_arrive_remote(mapa(BAR(B_RFREE), par ^ 1));
            }
            bar_arrive(14, 384);
            TS(6 + 12 * layer);
            bar_sync(4, 384);
            TS(7 + 12 * layer);
            float er = 0.f, ei = 0.f;
#pragma unroll
            for (int i = 0; i < 16; i++) {
                float2 rs = *(const float2*)(s_rstd + 128 + 8 * i + 2 * q);
                acc[4 * i] *= rs.x; acc[4 * i + 1] *= rs.y; acc[4 * i + 2] *= rs.x; acc[4 * i + 3] *= rs.y;
                float nr = lr1 * er - li1 * ei + acc[4 * i], ni = lr1 * ei + li1 * er + acc[4 * i + 2];
                er = lr1 * nr - li1 * ni + acc[4 * i + 1];
                ei = lr1 * ni + li1 * nr + acc[4 * i + 3];
            }
            float cr = 0.f, ci = 0.f, tr = 0.f, ti = 0.f;
#pragma unroll
            for (int qq = 0; qq < 4; qq++) {
                float xr_ = __shfl_sync(~0u, er, (lane & ~3) | qq), xi_ = __shfl_sync(~0u, ei, (lane & ~3) | qq);
                if (qq == q) { cr = tr; ci = ti; }
                float nr = lr32 * tr - li32 * ti + xr_, ni = lr32 * ti + li32 * tr + xi_;
                tr = nr; ti = ni;
            }
            float4* eb = g_Ebuf + (uint32_t)(layer * 16 * 512 + 64 * r + prow);
            if (q == 0 && c < 15) st_relaxed_f4(eb + c * 512, make_float4(tr, ti, __uint_as_float(epoch), 0.f));
            TS(8 + 12 * layer);
            float pr[4], pi[4];
            {
                unsigned n = 0;
                bool ok;
#pragma unroll 1
                do {
                    ok = true;
#pragma unroll
                    for (int k = 0; k < 4; k++) {
                        float4 v = make_float4(0.f, 0.f, __uint_as_float(epoch), 0.f);
                        if (4 * k + q < c) v = ld_relaxed_f4(eb + (4 * k + q) * 512);
                        pr[k] = v.x; pi[k] = v.y;
                        ok = ok && __float_as_uint(v.z) == epoch;
                    }
                } while (!ok && ++n < SPIN_LIMIT);
            }
            __syncwarp();
            TS(9 + 12 * layer);
            float hr = 0.f, hi = 0.f;
#pragma unroll
            for (int cc = 0; cc < 15; cc++) {
                float xr_ = __shfl_sync(~0u, pr[cc >> 2], (lane & ~3) | (cc & 3)), xi_ = __shfl_sync(~0u, pi[cc >> 2], (lane & ~3) | (cc & 3));
                if (cc < c) {
                    float nr = lr128 * hr - li128 * hi + xr_, ni = lr128 * hi + li128 * hr + xi_;
                    hr = nr; hi = ni;
                }
            }
#pragma unroll
            for (int qq = 0; qq < 3; qq++) {
                if (qq < q) { float nr = lr32 * hr - li32 * hi, ni = lr32 * hi + li32 * hr; hr = nr; hi = ni; }
            }
            er = cr + hr; ei = ci + hi;
            bar_sync(7, 384);
            mbar_wait_cluster(BAR(B_RFREE), layer);
            const uint32_t ha = sb + SM_HH + par * 32768 + (prow >> 3) * 1024 + g * 16 + 4 * q;
#pragma unroll
            for (int i = 0; i < 16; i++) {
                float nr = lr1 * er - li1 * ei + acc[4 * i], ni = lr1 * ei + li1 * er + acc[4 * i + 2];
                er = lr1 * nr - li1 * ni + acc[4 * i + 1];
                ei = lr1 * ni + li1 * nr + acc[4 * i + 3];
                sts32(ha + (i >> 3) * 16384 + (i & 7) * 128, pack_bf16(nr, er));
                sts32(ha + (i >> 3) * 16384 + 8192 + (i & 7) * 128, pack_bf16(ni, ei));
                if (i == 7) { fence_async_smem(); bar_arrive(13, 288); }
            }
            fence_async_smem();
            acc_def(acc);
            float acc2[32];
            acc_def(acc2);
            TS(10 + 12 * layer);
            bar_sync(6, 416);
            TS(11 + 12 * layer);
            float (&a0)[32] = *reinterpret_cast<float (*)[32]>(&acc[0]);
            float (&a1)[32] = *reinterpret_cast<float (*)[32]>(&acc[32]);
            auto tile_mma = [&](float (&d)[32], int u) {
#pragma unroll 1
                for (int k = 0; k < 2; k++) {
                    const uint32_t hb = sb + SM_HH + (par ^ k) * 32768 + wg * 16384;
                    if (k == 1) mbar_wait(BAR(wg ? B_HPEER1 : B_HPEER), layer);
                    mbar_wait(BAR(B_AFULL + 2 * u + k), 1);
                    const uint64_t da = c_desc(2 * u + k);
                    wg_fence();
#pragma unroll
                    for (int ks = 0; ks < 4; ks++) wgmma_n64s<1>(d, da + ks * dstep, desc_b<64>(hb + ks * 2048), 1);
#pragma unroll
                    for (int ks = 0; ks < 4; ks++) wgmma_n64s<-1>(d, da + 512 + ks * dstep, desc_b<64>(hb + 8192 + ks * 2048), 1);
                }
                wg_commit();
            };
            auto tile_ship = [&](float (&d)[32], int u) {
                uint4* dst = g_P + (uint32_t)(((c * 8 + 2 * ((pi_ + 1 + u) & 3) + par) * 4 + pi_) * 1024 + wg * 512 + (tid & 127));
#pragma unroll
                for (int i = 0; i < 4; i++)
                    dst[i * 128] = make_uint4((pack_bf16(d[8 * i], d[8 * i + 1]) & 0xfffefffeu) | ptag, pack_bf16(d[8 * i + 2], d[8 * i + 3]),
                                              pack_bf16(d[8 * i + 4], d[8 * i + 5]), pack_bf16(d[8 * i + 6], d[8 * i + 7]));
            };
            tile_mma(a0, 0);
            if ((tid & 127) == 0) mbar_arrive_remote(mapa(BAR(B_HDONE), par ^ 1));
            __syncwarp();
            tile_mma(a1, 1);
            wg_wait<1>();
            tile_ship(a0, 0);
            tile_mma(acc2, 2);
            bar_arrive(12, 384);
            wg_wait<1>();
            tile_ship(a1, 1);
            wg_wait<0>();
            tile_ship(acc2, 2);
            if (lane < 6) mbar_arrive(BAR(B_AEMPTY + lane), 1);
            TS(12 + 12 * layer);
        } else {
            const int t2 = tid - 256;
            const uint8_t* ximg = g_X + (uint32_t)layer * 16 * 8 * 16384;
            mbar_wait(BAR(B_SSQ), layer);
            TS(6 + 12 * layer);
            float sqv[16];
#pragma unroll
            for (int i = 0; i < 16; i++) sqv[i] = __ldcg(g_ssqc + (layer * 16 + i) * 2048 + 128 * c + t2);
            const unsigned short xm = __ldcg((const unsigned short*)(ximg + (uint32_t)(c * 8 * 16384 + (t2 >> 3) * 128 + (t2 & 7) * 2)));
            acc_def(acc);
#pragma unroll 1
            for (int kb = 0; kb < 8; kb++) {
                if (kb == 4) {
                    wg_wait<0>();
                    if (lane == 0) { mbar_arrive(BAR(B_XEMPTY + 3), 1); mbar_arrive_remote(mapa(BAR(B_XEMPTY + 3), par ^ 1)); }
                    float tot = 0.f;
#pragma unroll
                    for (int i = 0; i < 16; i++) tot += sqv[i];
                    float rs = rsqrtf(tot * (1.f / 512.f) + 1e-5f);
                    s_rstd[t2] = rs;
                    s_rstd[128 + t2] = 2.f * rs;
                    s_mean[t2] = layer == 0 ? 0.f : __uint_as_float((uint32_t)xm << 16) * (1.f / 512.f);
                    TS(7 + 12 * layer);
                    bar_arrive(4, 384);
                    bar_sync(14, 384);
                }
                mbar_wait(BAR(B_XFULL + (kb & 3)), (kb >> 2) & 1);
                wg_fence();
#pragma unroll
                for (int ks = 0; ks < 4; ks++)
                    wgmma_n128<1>(acc, desc_a(sb + SM_X + (kb & 3) * 24576 + 16384 + ks * 256), desc_b<128>(sb + SM_X + (kb & 3) * 24576 + ks * 4096), 1);
                wg_commit();
                wg_wait<1>();
                if ((kb & 3) != 0 && lane == 0) { mbar_arrive(BAR(B_XEMPTY + ((kb - 1) & 3)), 1); mbar_arrive_remote(mapa(BAR(B_XEMPTY + ((kb - 1) & 3)), par ^ 1)); }
            }
            wg_wait<0>();
            if (lane == 0) { mbar_arrive(BAR(B_XEMPTY + 3), 1); mbar_arrive_remote(mapa(BAR(B_XEMPTY + 3), par ^ 1)); mbar_arrive_remote(mapa(BAR(B_RFREE), par ^ 1)); }
            bar_arrive(7, 384);
            bar_sync(3, 128);
            TS(9 + 12 * layer);
            const int m0 = 16 * w + g;
            const uint32_t xoff = (uint32_t)((c * 8 + own) * 16384 + w * 4096 + g * 16 + 4 * q);
            if (layer == 0) {
                const uint8_t* xs = g_X + xoff;
#pragma unroll
                for (int i = 0; i < 16; i++) {
                    float2 rs = *(const float2*)(s_rstd + 8 * i + 2 * q);
                    uint32_t x0v = __ldcg((const uint32_t*)(xs + i * 128)), x1v = __ldcg((const uint32_t*)(xs + 2048 + i * 128));
                    acc[4 * i] = acc[4 * i] * rs.x + bf_lo(x0v);
                    acc[4 * i + 1] = acc[4 * i + 1] * rs.y + bf_hi(x0v);
                    acc[4 * i + 2] = acc[4 * i + 2] * rs.x + bf_lo(x1v);
                    acc[4 * i + 3] = acc[4 * i + 3] * rs.y + bf_hi(x1v);
                }
            } else {
                float d0 = ldbf(p.dskip + 64 * own + m0), d1 = ldbf(p.dskip + 64 * own + m0 + 8);
#pragma unroll
                for (int i = 0; i < 16; i++) {
                    float2 rs = *(const float2*)(s_rstd + 8 * i + 2 * q);
                    float2 mn = *(const float2*)(s_mean + 8 * i + 2 * q);
                    acc[4 * i] = acc[4 * i] * (1.f + rs.x * d0) + mn.x;
                    acc[4 * i + 1] = acc[4 * i + 1] * (1.f + rs.y * d0) + mn.y;
                    acc[4 * i + 2] = acc[4 * i + 2] * (1.f + rs.x * d1) + mn.x;
                    acc[4 * i + 3] = acc[4 * i + 3] * (1.f + rs.y * d1) + mn.y;
                }
            }
            TS(10 + 12 * layer);
            bar_sync(6, 416);
            TS(11 + 12 * layer);
            {
                float (&a0)[32] = *reinterpret_cast<float (*)[32]>(&acc[0]);
                float (&a1)[32] = *reinterpret_cast<float (*)[32]>(&acc[32]);
#pragma unroll 1
                for (int k = 0; k < 2; k++) {
                    const uint32_t hb = sb + SM_HH + (par ^ k) * 32768;
                    if (k == 1) {
                        mbar_wait(BAR(B_HPEER), layer);
                        mbar_wait(BAR(B_HPEER1), layer);
                        bar_sync(12, 384);
                    }
                    mbar_wait(BAR(B_AFULL + 6 + k), 1);
                    const uint64_t da = c_desc(6 + k);
                    wg_fence();
#pragma unroll
                    for (int ks = 0; ks < 4; ks++) {
                        wgmma_n64s<1>(a0, da + ks * dstep, desc_b<64>(hb + ks * 2048), 1);
                        wgmma_n64s<1>(a1, da + ks * dstep, desc_b<64>(hb + 16384 + ks * 2048), 1);
                    }
#pragma unroll
                    for (int ks = 0; ks < 4; ks++) {
                        wgmma_n64s<-1>(a0, da + 512 + ks * dstep, desc_b<64>(hb + 8192 + ks * 2048), 1);
                        wgmma_n64s<-1>(a1, da + 512 + ks * dstep, desc_b<64>(hb + 16384 + 8192 + ks * 2048), 1);
                    }
                    wg_commit();
                }
                wg_wait<0>();
            }
#pragma unroll
            for (int i = 0; i < 16; i++)
                *(float4*)(sm + SM_A + 6 * 16384 + i * 2048 + t2 * 16) = make_float4(acc[4 * i], acc[4 * i + 1], acc[4 * i + 2], acc[4 * i + 3]);
            TS(12 + 12 * layer);
        }
        {
            const int t = tid & 127;
            const int nch = wg == 2 ? 2 : 3;
            const uint4* pb = g_P + (uint32_t)((c * 8 + r) * 4 * 1024 + wg * 128 + t);
            uint4 v[3][3];
            unsigned n = 0;
#pragma unroll 1
            while (true) {
                if (lane == 31) {
#pragma unroll 1
                    while (true) {
                        uint32_t bad = 0;
#pragma unroll
                        for (int sx = 0; sx < 3; sx++) {
                            uint32_t t0;
                            asm volatile("ld.relaxed.gpu.global.u32 %0, [%1];" : "=r"(t0) : "l"(pb + ((pi_ + 1 + sx) & 3) * 1024 + (nch - 1) * 384) : "memory");
                            bad |= t0 ^ ptag;
                        }
                        if (!(bad & 0x00010001u) || ++n >= SPIN_LIMIT) break;
                    }
                }
                __syncwarp();
                uint32_t bad = 0;
#pragma unroll
                for (int k = 0; k < 3; k++)
#pragma unroll
                    for (int sx = 0; sx < 3; sx++) {
                        v[k][sx] = make_uint4(ptag, 0, 0, 0);
                        if (k < nch) v[k][sx] = ld_relaxed_u4(pb + ((pi_ + 1 + sx) & 3) * 1024 + k * 384);
                        bad |= v[k][sx].x ^ ptag;
                    }
                if (!__any_sync(~0u, bad & 0x00010001u) || ++n >= SPIN_LIMIT) break;
            }
            bar_sync(8, 384);
            TS(13 + 12 * layer);
            const int m0 = 16 * w + g;
            const float w0 = (own == 0 && m0 < 2) ? (m0 == 0 ? 0.f : 0.5f) : 1.f;
#pragma unroll
            for (int k = 0; k < 3; k++) {
                if (k < nch) {
                    const int i = wg + 3 * k;
                    float4 a = *(const float4*)(sm + SM_A + 6 * 16384 + (2 * i) * 2048 + t * 16);
                    float4 bq = *(const float4*)(sm + SM_A + 6 * 16384 + (2 * i + 1) * 2048 + t * 16);
#pragma unroll
                    for (int sx = 0; sx < 3; sx++) {
                        a.x += bf_lo(v[k][sx].x); a.y += bf_hi(v[k][sx].x); a.z += bf_lo(v[k][sx].y); a.w += bf_hi(v[k][sx].y);
                        bq.x += bf_lo(v[k][sx].z); bq.y += bf_hi(v[k][sx].z); bq.z += bf_lo(v[k][sx].w); bq.w += bf_hi(v[k][sx].w);
                    }
                    if (layer == 0) {
                        uint8_t* xd = g_X + (uint32_t)((16 * 8 + c * 8 + own) * 16384 + w * 4096 + g * 16 + 4 * q + i * 256);
                        uint32_t v0 = pack_bf16(a.x, a.y), v1 = pack_bf16(a.z, a.w), v2 = pack_bf16(bq.x, bq.y), v3 = pack_bf16(bq.z, bq.w);
                        *(uint32_t*)(xd) = v0; *(uint32_t*)(xd + 2048) = v1; *(uint32_t*)(xd + 128) = v2; *(uint32_t*)(xd + 2048 + 128) = v3;
                        float sq[4];
                        sq[0] = w0 * bf_lo(v0) * bf_lo(v0) + bf_lo(v1) * bf_lo(v1);
                        sq[1] = w0 * bf_hi(v0) * bf_hi(v0) + bf_hi(v1) * bf_hi(v1);
                        sq[2] = w0 * bf_lo(v2) * bf_lo(v2) + bf_lo(v3) * bf_lo(v3);
                        sq[3] = w0 * bf_hi(v2) * bf_hi(v2) + bf_hi(v3) * bf_hi(v3);
                        float u0 = (g & 1) ? sq[2] : sq[0], u1 = (g & 1) ? sq[3] : sq[1];
                        u0 += __shfl_xor_sync(~0u, (g & 1) ? sq[0] : sq[2], 4);
                        u1 += __shfl_xor_sync(~0u, (g & 1) ? sq[1] : sq[3], 4);
                        float z = (g & 2) ? u1 : u0;
                        z += __shfl_xor_sync(~0u, (g & 2) ? u0 : u1, 8);
                        z += __shfl_xor_sync(~0u, z, 16);
                        if (g < 4) atomicAdd(s_mean + 16 * i + 8 * (g & 1) + 2 * q + (g >> 1), z);
                    } else {
                        float* o = p.out + (uint32_t)((128 * c + 32 * q + 4 * i) * 512 + 64 * own + m0);
                        o[0] = a.x; o[512] = a.y; o[8] = a.z; o[512 + 8] = a.w;
                        o[1024] = bq.x; o[1536] = bq.y; o[1024 + 8] = bq.z; o[1536 + 8] = bq.w;
                    }
                }
            }
            if (wg < 2) mbar_wait_cluster(BAR(B_HDONE), layer);
            if (layer == 0) {
                fence_async_smem();
                bar_sync(9, 384);
                TS(14 + 12 * layer);
                if (wg == 2) {
                    atomicAdd(g_ssq + 2048 + 128 * c + t, s_mean[t] * (2.f / 512.f));
                    bar_sync(3, 128);
                    if (lane == 0) { mbar_arrive(BAR(B_AEMPTY + 6), 2); mbar_arrive(BAR(B_AEMPTY + 7), 2); }
                    if (t == 0) { fence_async(); red_release(&g_bar[2], 1); }
                }
            }
        }
        TS(15 + 12 * layer);
        if (wg == 0) TC(31);
    }
}

typedef CUresult (*EncFn)(CUtensorMap*, CUtensorMapDataType, cuuint32_t, void*, const cuuint64_t*, const cuuint64_t*,
                          const cuuint32_t*, const cuuint32_t*, CUtensorMapInterleave, CUtensorMapSwizzle,
                          CUtensorMapL2promotion, CUtensorMapFloatOOBfill);

void launch_impl(void* const* d_in, void* d_out, int stop) {
    static EncFn enc = nullptr;
    if (!enc) {
        void* fn = nullptr;
        cudaDriverEntryPointQueryResult qr;
        cudaGetDriverEntryPoint("cuTensorMapEncodeTiled", &fn, cudaEnableDefault, &qr);
        enc = (EncFn)fn;
        cudaFuncSetAttribute(fused_kernel, cudaFuncAttributeMaxDynamicSharedMemorySize, SM_TOTAL);
    }
    CUtensorMap tx, tbr, tbi, tcr, tci, tcol;
    {
        void* gx = nullptr;
        cudaGetSymbolAddress(&gx, g_X);
        cuuint64_t gd[5] = {64, 16, 64, 16, 2};
        cuuint64_t gs[4] = {128, 2048, 128 * 1024, 2048 * 1024};
        cuuint32_t bx[5] = {32, 16, 1, 16, 1};
        cuuint32_t es[5] = {1, 1, 1, 1, 1};
        enc(&tcol, CU_TENSOR_MAP_DATA_TYPE_BFLOAT16, 5, gx, gd, gs, bx, es, CU_TENSOR_MAP_INTERLEAVE_NONE,
            CU_TENSOR_MAP_SWIZZLE_64B, CU_TENSOR_MAP_L2_PROMOTION_NONE, CU_TENSOR_MAP_FLOAT_OOB_FILL_NONE);
    }
    {
        cuuint64_t gd[5] = {512, 2, 4, 16, 16};
        cuuint64_t gs[4] = {1024, 32 * 1024, 2 * 1024, 128 * 1024};
        cuuint32_t bx[5] = {64, 2, 4, 8, 1};
        cuuint32_t es[5] = {1, 1, 1, 1, 1};
        enc(&tx, CU_TENSOR_MAP_DATA_TYPE_BFLOAT16, 5, d_in[0], gd, gs, bx, es, CU_TENSOR_MAP_INTERLEAVE_NONE,
            CU_TENSOR_MAP_SWIZZLE_128B, CU_TENSOR_MAP_L2_PROMOTION_L2_128B, CU_TENSOR_MAP_FLOAT_OOB_FILL_NONE);
    }
    auto mk2 = [&](CUtensorMap* m, void* ptr, cuuint32_t rows) {
        cuuint64_t gd[2] = {512, 512};
        cuuint64_t gs[1] = {1024};
        cuuint32_t bx[2] = {64, rows};
        cuuint32_t es[2] = {1, 1};
        enc(m, CU_TENSOR_MAP_DATA_TYPE_BFLOAT16, 2, ptr, gd, gs, bx, es, CU_TENSOR_MAP_INTERLEAVE_NONE,
            CU_TENSOR_MAP_SWIZZLE_128B, CU_TENSOR_MAP_L2_PROMOTION_L2_128B, CU_TENSOR_MAP_FLOAT_OOB_FILL_NONE);
    };
    mk2(&tbr, d_in[6], 32);
    mk2(&tbi, d_in[7], 32);
    mk2(&tcr, d_in[8], 64);
    mk2(&tci, d_in[9], 64);
    Params p;
    p.x0 = (const __nv_bfloat16*)d_in[0];
    p.w_r = (const __nv_bfloat16*)d_in[1];
    p.w_i = (const __nv_bfloat16*)d_in[2];
    p.lam_re = (const __nv_bfloat16*)d_in[4];
    p.lam_im = (const __nv_bfloat16*)d_in[5];
    p.log_dt = (const __nv_bfloat16*)d_in[10];
    p.dskip = (const __nv_bfloat16*)d_in[11];
    p.out = (float*)d_out;
    p.stop = stop;
    cudaLaunchConfig_t cfg = {};
    cfg.gridDim = dim3(NCTA); cfg.blockDim = dim3(NTHREADS); cfg.dynamicSmemBytes = SM_TOTAL; cfg.stream = cudaStreamPerThread;
    cudaLaunchAttribute at[1];
    at[0].id = cudaLaunchAttributeClusterDimension;
    at[0].val.clusterDim.x = 2; at[0].val.clusterDim.y = 1; at[0].val.clusterDim.z = 1;
    cfg.attrs = at; cfg.numAttrs = 1;
    cudaLaunchKernelEx(&cfg, fused_kernel, tx, tbr, tbi, tcr, tci, tcol, p);
}

}

extern "C" void kernel_launch(void* const* d_in, const int* in_sizes, int n_in, void* d_out, int out_size) {
    (void)in_sizes; (void)n_in; (void)out_size;
    launch_impl(d_in, d_out, 100);
}
```

```cpp
#include <cuda_runtime.h>
#include <cuda_bf16.h>
#include <cuda.h>
#include <stdint.h>

namespace {

constexpr int NCTA = 128;
constexpr int NTHREADS = 512;
constexpr int SM_A = 0;
constexpr int SM_X = 131072;
constexpr int SM_H = 196608;
constexpr int SM_HH = SM_X + 32768;
constexpr int SM_M = 229376;
constexpr int SM_TOTAL = 232448;
constexpr int SM_BAR = SM_M;
constexpr int SM_TGT = SM_M + 360;
constexpr int SM_LAM = SM_M + 384;
constexpr int SM_TAB = SM_M + 896;
constexpr int SM_RSTD = SM_M + 1920;
constexpr int SM_MEAN = SM_TAB;
constexpr int SM_T64 = SM_M + 2944;
constexpr int SM_B1ST = SM_H + 24576;
constexpr int SM_RAW = SM_X + 40960;
constexpr int SM_SSQ = SM_X + 57344;
constexpr int B_FULL0 = 0;
constexpr int B_EMPTY0 = 8;
constexpr int B_FULLC = 12;
constexpr int B_AFULL = 13;
constexpr int B_AEMPTY = 21;
constexpr int B_XFULL = 29;
constexpr int B_XEMPTY = 33;
constexpr int B_AFREE = 37;
constexpr int B_COL = 38;
constexpr int B_SSQ = 39;
constexpr int B_HPEER = 40;
constexpr int B_RFREE = 41;
constexpr int B_HDONE = 42;
constexpr int B_WRDY = 43;
constexpr int B_HPEER1 = 44;
constexpr int NBARS = 45;

__device__ __align__(1024) uint8_t g_X[2 * 16 * 8 * 16384];
__device__ __align__(1024) uint8_t g_A1[8 * 8 * 16384];
__device__ __align__(1024) uint8_t g_A2[8 * 8 * 16384];
__device__ __align__(1024) uint8_t g_E[2 * 8 * 8 * 8192];
__device__ __align__(16) float g_ssq[2 * 2048];
__device__ __align__(16) float g_ssqc[2 * 16 * 2048];
__device__ __align__(16) float g_Dh[512];
__device__ __align__(16) uint4 g_Wfrag[128 * 4 * 256];
__device__ __align__(16) float4 g_Ebuf[2 * 16 * 512];
__device__ __align__(16) uint4 g_P[16 * 8 * 4 * 1024];
__device__ unsigned g_bar[8];
__device__ unsigned g_err;
#define TX(i)
#define TQ(i)
#define TS(i)
#define TC(i)

constexpr unsigned SPIN_LIMIT = 1u << 22;

__device__ __forceinline__ uint32_t s2u(const void* p) { return (uint32_t)__cvta_generic_to_shared(p); }
__device__ __forceinline__ void mbar_init(uint32_t a, uint32_t c) {
    asm volatile("mbarrier.init.shared::cta.b64 [%0], %1;" ::"r"(a), "r"(c) : "memory");
}
__device__ __forceinline__ void mbar_expect(uint32_t a, uint32_t bytes) {
    asm volatile("mbarrier.arrive.expect_tx.shared::cta.b64 _, [%0], %1;" ::"r"(a), "r"(bytes) : "memory");
}
__device__ __forceinline__ void mbar_arrive(uint32_t a, uint32_t cnt) {
    asm volatile("mbarrier.arrive.shared::cta.b64 _, [%0], %1;" ::"r"(a), "r"(cnt) : "memory");
}
__device__ __forceinline__ bool mbar_try(uint32_t a, uint32_t parity) {
    uint32_t ok;
    asm volatile("{\n.reg .pred p;\nmbarrier.try_wait.parity.shared::cta.b64 p, [%1], %2;\nselp.u32 %0, 1, 0, p;\n}"
                 : "=r"(ok) : "r"(a), "r"(parity) : "memory");
    return ok != 0;
}
__device__ __forceinline__ void mbar_wait(uint32_t a, uint32_t parity) {
    asm volatile("{\n.reg .pred p, q;\n.reg .u32 n;\nmov.u32 n, 0;\n"
                 "W_%=:\nmbarrier.try_wait.parity.shared::cta.b64 p, [%0], %1;\n@p bra D_%=;\n"
                 "add.u32 n, n, 1;\nsetp.lt.u32 q, n, 4194304;\n@q bra W_%=;\nD_%=:\n}" ::"r"(a), "r"(parity) : "memory");
}
__device__ __forceinline__ void bulk_g2s(uint32_t dst, const void* src, uint32_t bytes, uint32_t bar) {
    asm volatile("cp.async.bulk.shared::cluster.global.mbarrier::complete_tx::bytes [%0], [%1], %2, [%3];" ::"r"(dst),
                 "l"(src), "r"(bytes), "r"(bar) : "memory");
}
__device__ __forceinline__ void tma_2d(uint32_t dst, const CUtensorMap* m, int c0, int c1, uint32_t bar) {
    asm volatile("cp.async.bulk.tensor.2d.shared::cluster.global.mbarrier::complete_tx::bytes [%0], [%1, {%3,%4}], [%2];" ::"r"(dst),
                 "l"(m), "r"(bar), "r"(c0), "r"(c1) : "memory");
}
__device__ __forceinline__ void tma_5d(uint32_t dst, const CUtensorMap* m, int c0, int c1, int c2, int c3, int c4, uint32_t bar) {
    asm volatile("cp.async.bulk.tensor.5d.shared::cluster.global.mbarrier::complete_tx::bytes [%0], [%1, {%3,%4,%5,%6,%7}], [%2];" ::"r"(dst),
                 "l"(m), "r"(bar), "r"(c0), "r"(c1), "r"(c2), "r"(c3), "r"(c4) : "memory");
}
__device__ __forceinline__ void tma_2d_mc(uint32_t dst, const CUtensorMap* m, int c0, int c1, uint32_t bar) {
    asm volatile("cp.async.bulk.tensor.2d.shared::cluster.global.mbarrier::complete_tx::bytes.multicast::cluster [%0], [%1, {%3,%4}], [%2], %5;" ::"r"(dst),
                 "l"(m), "r"(bar), "r"(c0), "r"(c1), "h"((unsigned short)3) : "memory");
}
__device__ __forceinline__ void tma_5d_mc(uint32_t dst, const CUtensorMap* m, int c0, int c1, int c2, int c3, int c4, uint32_t bar) {
    asm volatile("cp.async.bulk.tensor.5d.shared::cluster.global.mbarrier::complete_tx::bytes.multicast::cluster [%0], [%1, {%3,%4,%5,%6,%7}], [%2], %8;" ::"r"(dst),
                 "l"(m), "r"(bar), "r"(c0), "r"(c1), "r"(c2), "r"(c3), "r"(c4), "h"((unsigned short)3) : "memory");
}
__device__ __forceinline__ void bulk_g2s_mc(uint32_t dst, const void* src, uint32_t bytes, uint32_t bar) {
    asm volatile("cp.async.bulk.shared::cluster.global.mbarrier::complete_tx::bytes.multicast::cluster [%0], [%1], %2, [%3], %4;" ::"r"(dst),
                 "l"(src), "r"(bytes), "r"(bar), "h"((unsigned short)3) : "memory");
}
__device__ __forceinline__ void tma_store_5d(const CUtensorMap* m, int c0, int c1, int c2, int c3, int c4, uint32_t src) {
    asm volatile("cp.async.bulk.tensor.5d.global.shared::cta.bulk_group [%0, {%2,%3,%4,%5,%6}], [%1];" ::"l"(m), "r"(src),
                 "r"(c0), "r"(c1), "r"(c2), "r"(c3), "r"(c4) : "memory");
}
__device__ __forceinline__ uint32_t lds32(uint32_t a) { uint32_t v; asm volatile("ld.shared.u32 %0, [%1];" : "=r"(v) : "r"(a) : "memory"); return v; }
__device__ __forceinline__ uint4 ld_relaxed_u4(const uint4* p) {
    uint4 v;
    asm volatile("ld.relaxed.gpu.global.v4.u32 {%0,%1,%2,%3}, [%4];" : "=r"(v.x), "=r"(v.y), "=r"(v.z), "=r"(v.w) : "l"(p) : "memory");
    return v;
}
__device__ __forceinline__ void fence_async() { asm volatile("fence.proxy.async.global;" ::: "memory"); }
__device__ __forceinline__ void red_relaxed(unsigned* p, unsigned v) {
    asm volatile("red.relaxed.gpu.global.add.u32 [%0], %1;" ::"l"(p), "r"(v) : "memory");
}
__device__ __forceinline__ uint32_t mapa(uint32_t a, uint32_t rank) {
    uint32_t d;
    asm("mapa.shared::cluster.u32 %0, %1, %2;" : "=r"(d) : "r"(a), "r"(rank));
    return d;
}
__device__ __forceinline__ void mbar_arrive_remote(uint32_t ra) {
    asm volatile("mbarrier.arrive.relaxed.cluster.shared::cluster.b64 _, [%0];" ::"r"(ra) : "memory");
}
__device__ __forceinline__ void mbar_wait_cluster(uint32_t a, uint32_t parity) {
    asm volatile("{\n.reg .pred p, q;\n.reg .u32 n;\nmov.u32 n, 0;\n"
                 "W_%=:\nmbarrier.try_wait.parity.acquire.cluster.shared::cta.b64 p, [%0], %1;\n@p bra D_%=;\n"
                 "add.u32 n, n, 1;\nsetp.lt.u32 q, n, 4194304;\n@q bra W_%=;\nD_%=:\n}" ::"r"(a), "r"(parity) : "memory");
}
__device__ __forceinline__ void bulk_s2peer(uint32_t rdst, uint32_t src, uint32_t bytes, uint32_t rbar) {
    asm volatile("cp.async.bulk.shared::cluster.shared::cta.mbarrier::complete_tx::bytes [%0], [%1], %2, [%3];" ::"r"(rdst),
                 "r"(src), "r"(bytes), "r"(rbar) : "memory");
}
__device__ __forceinline__ void fence_async_smem() { asm volatile("fence.proxy.async.shared::cta;" ::: "memory"); }
__device__ __forceinline__ void wg_fence() { asm volatile("wgmma.fence.sync.aligned;" ::: "memory"); }
__device__ __forceinline__ void wg_commit() { asm volatile("wgmma.commit_group.sync.aligned;" ::: "memory"); }
template <int N> __device__ __forceinline__ void wg_wait() { asm volatile("wgmma.wait_group.sync.aligned %0;" ::"n"(N) : "memory"); }
__device__ __forceinline__ void bar_sync(int id, int n) { asm volatile("bar.sync %0, %1;" ::"r"(id), "r"(n) : "memory"); }
__device__ __forceinline__ void bar_arrive(int id, int n) { asm volatile("bar.arrive %0, %1;" ::"r"(id), "r"(n) : "memory"); }
__device__ __forceinline__ unsigned ld_acquire(const unsigned* p) {
    unsigned v;
    asm volatile("ld.acquire.gpu.global.u32 %0, [%1];" : "=r"(v) : "l"(p) : "memory");
    return v;
}
__device__ __forceinline__ void red_release(unsigned* p, unsigned v) {
    asm volatile("red.release.gpu.global.add.u32 [%0], %1;" ::"l"(p), "r"(v) : "memory");
}
__device__ __forceinline__ void wait_count(const unsigned* p, unsigned target) {
    unsigned n = 0;
#pragma unroll 1
    while ((int)(ld_acquire(p) - target) < 0 && ++n < SPIN_LIMIT) {}
}
__device__ __forceinline__ float4 ld_relaxed_f4(const float4* p) {
    float4 v;
    asm volatile("ld.relaxed.gpu.global.v4.f32 {%0,%1,%2,%3}, [%4];" : "=f"(v.x), "=f"(v.y), "=f"(v.z), "=f"(v.w) : "l"(p) : "memory");
    return v;
}
__device__ __forceinline__ void st_relaxed_f4(float4* p, float4 v) {
    asm volatile("st.relaxed.gpu.global.v4.f32 [%0], {%1,%2,%3,%4};" ::"l"(p), "f"(v.x), "f"(v.y), "f"(v.z), "f"(v.w) : "memory");
}
__device__ __forceinline__ uint32_t pack_bf16(float lo, float hi) {
    uint32_t r;
    asm("cvt.rn.bf16x2.f32 %0, %1, %2;" : "=r"(r) : "f"(hi), "f"(lo));
    return r;
}
__device__ __forceinline__ uint32_t hmul2(uint32_t a, uint32_t b) {
    uint32_t r;
    asm("mul.rn.bf16x2 %0, %1, %2;" : "=r"(r) : "r"(a), "r"(b));
    return r;
}
__device__ __forceinline__ uint32_t hfma2(uint32_t a, uint32_t b, uint32_t c) {
    uint32_t r;
    asm("fma.rn.bf16x2 %0, %1, %2, %3;" : "=r"(r) : "r"(a), "r"(b), "r"(c));
    return r;
}
__device__ __forceinline__ float bf_lo(uint32_t v) { return __uint_as_float(v << 16); }
__device__ __forceinline__ float bf_hi(uint32_t v) { return __uint_as_float(v & 0xffff0000u); }
__device__ __forceinline__ void sts32(uint32_t a, uint32_t v) { asm volatile("st.shared.u32 [%0], %1;" ::"r"(a), "r"(v) : "memory"); }
__device__ __forceinline__ void sts128(uint32_t a, uint4 v) {
    asm volatile("st.shared.v4.u32 [%0], {%1,%2,%3,%4};" ::"r"(a), "r"(v.x), "r"(v.y), "r"(v.z), "r"(v.w) : "memory");
}

__device__ __forceinline__ uint64_t desc_ni(uint32_t addr, uint32_t lbo, uint32_t sbo) {
    return (uint64_t)((addr & 0x3FFFF) >> 4) | ((uint64_t)(lbo >> 4) << 16) | ((uint64_t)(sbo >> 4) << 32);
}
__device__ __forceinline__ uint64_t desc_a(uint32_t addr) { return desc_ni(addr, 128, 1024); }
template <int N> __device__ __forceinline__ uint64_t desc_b(uint32_t addr) { return desc_ni(addr, 16 * N, 128); }
__device__ __forceinline__ uint64_t desc_k(uint32_t addr) {
    return (uint64_t)((addr & 0x3FFFF) >> 4) | (1ull << 16) | (64ull << 32) | (1ull << 62);
}
__device__ __forceinline__ uint64_t desc_mn(uint32_t addr, uint32_t lbo) {
    return (uint64_t)((addr & 0x3FFFF) >> 4) | ((uint64_t)(lbo >> 4) << 16) | (64ull << 32) | (1ull << 62);
}

#define ACC8(d, o) "+f"(d[o + 0]), "+f"(d[o + 1]), "+f"(d[o + 2]), "+f"(d[o + 3]), "+f"(d[o + 4]), "+f"(d[o + 5]), "+f"(d[o + 6]), "+f"(d[o + 7])
template <int TB, int SA = 1>
__device__ __forceinline__ void wgmma_n128(float (&d)[64], uint64_t da, uint64_t db, int sd) {
    asm volatile(
        "{\n.reg .pred p;\nsetp.ne.b32 p, %66, 0;\n"
        "wgmma.mma_async.sync.aligned.m64n128k16.f32.bf16.bf16 "
        "{%0,%1,%2,%3,%4,%5,%6,%7,%8,%9,%10,%11,%12,%13,%14,%15,%16,%17,%18,%19,%20,%21,%22,%23,%24,%25,%26,%27,%28,%29,%30,%31,"
        "%32,%33,%34,%35,%36,%37,%38,%39,%40,%41,%42,%43,%44,%45,%46,%47,%48,%49,%50,%51,%52,%53,%54,%55,%56,%57,%58,%59,%60,%61,%62,%63},"
        " %64, %65, p, %68, 1, 0, %67;\n}"
        : ACC8(d, 0), ACC8(d, 8), ACC8(d, 16), ACC8(d, 24), ACC8(d, 32), ACC8(d, 40), ACC8(d, 48), ACC8(d, 56)
        : "l"(da), "l"(db), "r"(sd), "n"(TB), "n"(SA));
}
template <int N> __device__ __forceinline__ void acc_def(float (&d)[N]) {
#pragma unroll
    for (int i = 0; i < N; i++) d[i] = 0.f;
}
template <int TB>
__device__ __forceinline__ void wgmma_n64(float (&d)[32], uint64_t da, uint64_t db, int sd) {
    asm volatile(
        "{\n.reg .pred p;\nsetp.ne.b32 p, %34, 0;\n"
        "wgmma.mma_async.sync.aligned.m64n64k16.f32.bf16.bf16 "
        "{%0,%1,%2,%3,%4,%5,%6,%7,%8,%9,%10,%11,%12,%13,%14,%15,%16,%17,%18,%19,%20,%21,%22,%23,%24,%25,%26,%27,%28,%29,%30,%31},"
        " %32, %33, p, 1, 1, 0, %35;\n}"
        : ACC8(d, 0), ACC8(d, 8), ACC8(d, 16), ACC8(d, 24)
        : "l"(da), "l"(db), "r"(sd), "n"(TB));
}
template <int SA>
__device__ __forceinline__ void wgmma_n64s(float (&d)[32], uint64_t da, uint64_t db, int sd) {
    asm volatile(
        "{\n.reg .pred p;\nsetp.ne.b32 p, %34, 0;\n"
        "wgmma.mma_async.sync.aligned.m64n64k16.f32.bf16.bf16 "
        "{%0,%1,%2,%3,%4,%5,%6,%7,%8,%9,%10,%11,%12,%13,%14,%15,%16,%17,%18,%19,%20,%21,%22,%23,%24,%25,%26,%27,%28,%29,%30,%31},"
        " %32, %33, p, %35, 1, 0, 1;\n}"
        : ACC8(d, 0), ACC8(d, 8), ACC8(d, 16), ACC8(d, 24)
        : "l"(da), "l"(db), "r"(sd), "n"(SA));
}
__device__ __forceinline__ void wgmma_n64_rs(float (&d)[32], uint32_t a0, uint32_t a1, uint32_t a2, uint32_t a3, uint64_t db, int sd) {
    asm volatile(
        "{\n.reg .pred p;\nsetp.ne.b32 p, %37, 0;\n"
        "wgmma.mma_async.sync.aligned.m64n64k16.f32.bf16.bf16 "
        "{%0,%1,%2,%3,%4,%5,%6,%7,%8,%9,%10,%11,%12,%13,%14,%15,%16,%17,%18,%19,%20,%21,%22,%23,%24,%25,%26,%27,%28,%29,%30,%31},"
        " {%32,%33,%34,%35}, %36, p, 1, 1, 1;\n}"
        : ACC8(d, 0), ACC8(d, 8), ACC8(d, 16), ACC8(d, 24)
        : "r"(a0), "r"(a1), "r"(a2), "r"(a3), "l"(db), "r"(sd));
}

struct Params {
    const __nv_bfloat16* x0;
    const __nv_bfloat16* w_r;
    const __nv_bfloat16* w_i;
    const __nv_bfloat16* lam_re;
    const __nv_bfloat16* lam_im;
    const __nv_bfloat16* log_dt;
    const __nv_bfloat16* dskip;
    float* out;
    int stop;
};

__device__ __forceinline__ float ldbf(const __nv_bfloat16* p) { return __bfloat162float(*p); }

__device__ __forceinline__ void dft_fp(int j, int& f, int& ph) {
    int cs = j >> 1;
    if (j == 1) { f = 256; ph = 0; }
    else { f = cs; ph = (j & 1) ? 128 : 0; }
}

__device__ __forceinline__ void gen_col_consts(uint32_t sb, int tid) {
#pragma unroll 1
    for (int task = tid; task < 640; task += 256) {
        int f, c8;
        uint32_t a_cc, d_pi, d_po;
        if (task < 512) {
            f = task & 63; c8 = task >> 6;
            a_cc = sb + SM_X + (f >> 5) * 16384 + ((f >> 3) & 3) * 2048 + c8 * 128 + (f & 7) * 16;
            d_pi = 8192; d_po = 1024;
        } else {
            int n2 = task & 31;
            f = 2 * n2; c8 = (task >> 5) & 3;
            a_cc = sb + SM_X + 32768 + (n2 >> 3) * 1024 + c8 * 128 + (n2 & 7) * 16;
            d_pi = 4096; d_po = 512;
        }
        float cd, sd, cs, sn;
        __sincosf((float)(f >= 32 ? f - 64 : f) * (6.283185307179586f / 64.f), &sd, &cd);
        int a = (8 * c8 * f) & 63;
        __sincosf((float)(a >= 32 ? a - 64 : a) * (6.283185307179586f / 64.f), &sn, &cs);
        float cv[8], sv[8];
#pragma unroll
        for (int e = 0; e < 8; e++) {
            cv[e] = cs; sv[e] = sn;
            float t = cs * cd - sn * sd;
            sn = sn * cd + cs * sd;
            cs = t;
        }
        uint4 oc = make_uint4(pack_bf16(cv[0], cv[1]), pack_bf16(cv[2], cv[3]), pack_bf16(cv[4], cv[5]), pack_bf16(cv[6], cv[7]));
        uint4 os = make_uint4(pack_bf16(sv[0], sv[1]), pack_bf16(sv[2], sv[3]), pack_bf16(sv[4], sv[5]), pack_bf16(sv[6], sv[7]));
        sts128(a_cc, oc);
        sts128(a_cc + d_pi, os);
        sts128(a_cc + d_po, make_uint4(os.x ^ 0x80008000u, os.y ^ 0x80008000u, os.z ^ 0x80008000u, os.w ^ 0x80008000u));
        sts128(a_cc + d_pi + d_po, oc);
    }
}

__global__ void __launch_bounds__(NTHREADS, 1)
fused_kernel(const __grid_constant__ CUtensorMap tm_x, const __grid_constant__ CUtensorMap tm_bre,
             const __grid_constant__ CUtensorMap tm_bim, const __grid_constant__ CUtensorMap tm_cre,
             const __grid_constant__ CUtensorMap tm_cim, const __grid_constant__ CUtensorMap tm_col, const Params p) {
    extern __shared__ __align__(1024) uint8_t sm[];
    const uint32_t sb = s2u(sm);
    const int tid = threadIdx.x, b = blockIdx.x;
    const int c = b >> 3, r = b & 7;
    const int par = r & 1, pi_ = r >> 1, own = 4 * par + pi_;
    const int wg = __shfl_sync(~0u, tid >> 7, 0), w = __shfl_sync(~0u, (tid >> 5) & 3, 0), lane = tid & 31, g = lane >> 2, q = lane & 3;
    auto BAR = [&](int i) { return sb + SM_BAR + 8 * i; };
    unsigned* s_tgt = (unsigned*)(sm + SM_TGT);

    if (tid < NBARS) {
        int cnt = 1;
        if ((tid >= B_EMPTY0 && tid < B_EMPTY0 + 4) || (tid >= B_XEMPTY && tid < B_XEMPTY + 4)) cnt = 24;
        if (tid == B_RFREE) cnt = 12;
        if (tid == B_HDONE) cnt = 2;
        if (tid >= B_AEMPTY && tid < B_AEMPTY + 8) cnt = 8;
        if (tid == B_AFREE) cnt = 4;
        mbar_init(BAR(tid), cnt);
        asm volatile("fence.mbarrier_init.release.cluster;" ::: "memory");
    }
    asm volatile("barrier.cluster.arrive.release.aligned;" ::: "memory");

    if (wg == 3) {
        asm volatile("setmaxnreg.dec.sync.aligned.u32 56;");
        if (w == 0 && lane < 6) {
            const CUtensorMap* tm = lane == 0 ? &tm_x : lane == 1 ? &tm_bre : lane == 2 ? &tm_bim : lane == 3 ? &tm_cre : lane == 4 ? &tm_cim : &tm_col;
            asm volatile("prefetch.tensormap [%0];" ::"l"(tm) : "memory");
        }
        __syncwarp();
        asm volatile("barrier.cluster.wait.acquire.aligned;" ::: "memory");
        if (w > 0) {
            {
                int i = tid - 416;
                int ps = i < 64 ? 64 * r + i : 32 * c + i - 64;
                float lr = ldbf(p.lam_re + ps), li = ldbf(p.lam_im + ps);
                float dt = __bfloat162float(__float2bfloat16(expf(ldbf(p.log_dt + ps))));
                if (i < 6) s_tgt[i] = ((ld_acquire(&g_bar[i]) >> 7) + 1u) << 7;
                float mag = expf(lr * dt), t = li * dt * 0.15915494309189535f, sn, cs;
                t -= rintf(t);
                sincospif(2.f * t, &sn, &cs);
                float er = mag * cs, ei = mag * sn;
                if (i < 64) {
                    *(float2*)(sm + SM_LAM + i * 8) = make_float2(er, ei);
                } else {
                    er -= 1.f;
                    float inv = 1.f / (lr * lr + li * li);
                    *(float2*)(sm + SM_RSTD + (i - 64) * 8) = make_float2((er * lr + ei * li) * inv, (ei * lr - er * li) * inv);
                }
                __syncwarp();
            }
            bar_arrive(15, 480);
            if (w == 2) {
                const int kq = 2 * b + (lane >> 4), row = (kq >> 2) + 128 * (kq & 3) + 512 * ((lane >> 1) & 3) + 64 * (lane & 1);
                const char* src = (const char*)(((lane >> 3) & 1) ? p.w_i : p.w_r) + (size_t)row * 514;
                size_t a0 = (size_t)src & ~(size_t)15;
                int bytes = row == 2047 ? 512 : 544;
                asm volatile("cp.async.bulk.prefetch.L2.global [%0], %1;" ::"l"(a0), "r"(bytes) : "memory");
            }
#pragma unroll 1
            for (int i = tid - 448; i < 96 + 128 && w > 1; i += 64) {
                if (i < 96) g_P[(uint32_t)(b * 4 + i / 24) * 1024 + 640 + ((i % 24) >> 1) * 32 + 30 + (i & 1)] = make_uint4(0, 0, 0, 0);
                else g_Ebuf[b * 128 + i - 96] = make_float4(0.f, 0.f, 0.f, 0.f);
            }
#pragma unroll 1
            for (int task = tid - 448; task < 256 && w > 1; task += 64) {
                const int cb = task & 127, kq = 2 * b + (task >> 7), k1 = kq >> 2, qq = kq & 3;
                const unsigned short* wr_ = (const unsigned short*)p.w_r + (k1 + 128 * qq) * 257;
                const unsigned short* wi_ = (const unsigned short*)p.w_i + (k1 + 128 * qq) * 257;
                const int c0 = cb == 0 ? 256 : 2 * cb, c1 = 2 * cb + 1;
                uint32_t wf[16];
#pragma unroll
                for (int i = 0; i < 4; i++) {
                    int o = 512 * i * 257;
                    wf[2 * i] = (uint32_t)__ldg(wr_ + o + c0) | ((uint32_t)__ldg(wr_ + o + 64 * 257 + c0) << 16);
                    wf[2 * i + 1] = ((uint32_t)__ldg(wi_ + o + c0) | ((uint32_t)__ldg(wi_ + o + 64 * 257 + c0) << 16)) ^ 0x80008000u;
                    wf[8 + 2 * i] = (uint32_t)__ldg(wr_ + o + c1) | ((uint32_t)__ldg(wr_ + o + 64 * 257 + c1) << 16);
                    wf[8 + 2 * i + 1] = ((uint32_t)__ldg(wi_ + o + c1) | ((uint32_t)__ldg(wi_ + o + 64 * 257 + c1) << 16)) ^ 0x80008000u;
                }
                uint4* wd = g_Wfrag + (uint32_t)(cb * 1024 + kq);
#pragma unroll
                for (int i = 0; i < 4; i++) wd[i * 256] = make_uint4(wf[4 * i], wf[4 * i + 1], wf[4 * i + 2], wf[4 * i + 3]);
            }
            __syncwarp();
            if (w > 1) bar_arrive(11, 96);
            if (w == 3) {
#pragma unroll 1
                for (int it = 0; it < 8; it++) {
                    const int m = 4 * c + (it >> 1), d = 64 * r + m, ch = lane + 32 * (it & 1);
                    float v[8];
#pragma unroll
                    for (int e = 0; e < 8; e++) {
                        int j = 8 * ch + e, f, ph;
                        dft_fp(j, f, ph);
                        int a = (d * f + ph) & 511;
                        a = a >= 256 ? a - 512 : a;
                        float wj = j == 0 ? 0.f : (j == 1 ? 1.f / 512.f : 2.f / 512.f);
                        v[e] = wj * __cosf((float)a * (6.283185307179586f / 512.f));
                    }
                    uint32_t off = (uint32_t)(64 + r * 8 + (ch >> 3)) * 8192 + (m >> 3) * 1024 + (ch & 7) * 128 + (m & 7) * 16;
                    *(uint4*)(g_E + off) = make_uint4(pack_bf16(v[0], v[1]), pack_bf16(v[2], v[3]), pack_bf16(v[4], v[5]), pack_bf16(v[6], v[7]));
                }
                __syncwarp();
                if (lane == 0) { fence_async(); red_release(&g_bar[6], 1); }
                return;
            }
            if (w == 2) {
#pragma unroll 1
                for (int it = 0; it < 4; it++) {
                    const int hf = it & 1;
                    __syncwarp();
                    if (hf == 0) bar_sync(13, 288); else bar_sync(6, 416);
                    if (lane == 0) {
                        const uint32_t src = sb + SM_HH + par * 32768 + hf * 16384;
                        bulk_s2peer(mapa(src, par ^ 1), src, 16384, mapa(BAR(hf ? B_HPEER1 : B_HPEER), par ^ 1));
                    }
                }
                return;
            }
            {
                uint4 p0 = __ldg((const uint4*)p.dskip + 2 * lane), p1 = __ldg((const uint4*)p.dskip + 2 * lane + 1);
                uint32_t u[8] = {p0.x, p0.y, p0.z, p0.w, p1.x, p1.y, p1.z, p1.w};
#pragma unroll 1
                for (int jj = 0; jj < 4; jj++) {
                    int j = 64 * r + 4 * c + jj, f, ph;
                    dft_fp(j, f, ph);
                    float s = 0.f;
                    int idx = 16 * lane * f + ph;
#pragma unroll
                    for (int i = 0; i < 16; i++) {
                        int a = idx & 511;
                        idx += f;
                        a = a >= 256 ? a - 512 : a;
                        s += ((i & 1) ? bf_hi(u[i >> 1]) : bf_lo(u[i >> 1])) * __cosf((float)a * (6.283185307179586f / 512.f));
                    }
#pragma unroll
                    for (int o = 16; o; o >>= 1) s += __shfl_xor_sync(~0u, s, o);
                    if (lane == 0) g_Dh[j] = s;
                }
                if (lane == 0) red_release(&g_bar[5], 1);
                __syncwarp();
            }
            bar_sync(2, 416);
            if (lane == 0) {
                TX(5);
                asm volatile("cp.async.bulk.global.shared::cta.bulk_group [%0], [%1], 8192;" ::"l"(g_A1 + (uint32_t)(((c >> 1) * 8 + r) * 16384 + (c & 1) * 8192)),
                             "r"(sb + SM_B1ST) : "memory");
                asm volatile("cp.async.bulk.commit_group;" ::: "memory");
                fence_async();
                red_release(&g_bar[0], 1);
                TX(6);
                asm volatile("cp.async.bulk.wait_group 0;" ::: "memory");
                fence_async();
            }
            __syncwarp();
            bar_sync(11, 96);
            if (lane == 0) red_release(&g_bar[4], 1);
#pragma unroll 1
            for (int layer = 0; layer < 2; layer++) {
                __syncwarp();
                bar_sync(5, 416);
                if (lane == 0) {
                    TX(0 + 8 * layer);
                    tma_store_5d(&tm_col, 32 * (b & 1), 0, b >> 1, 0, layer, sb + SM_RAW);
                    asm volatile("cp.reduce.async.bulk.global.shared::cta.bulk_group.add.f32 [%0], [%1], 8192;" ::"l"(g_ssqc + (layer * 16 + (b & 15)) * 2048),
                                 "r"(sb + SM_SSQ) : "memory");
                    asm volatile("cp.async.bulk.commit_group;" ::: "memory");
                    asm volatile("cp.async.bulk.wait_group 0;" ::: "memory");
                    TX(1 + 8 * layer);
                    fence_async();
                    red_release(&g_bar[1 + 2 * layer], 1);
                    TX(2 + 8 * layer);
                }
            }
        } else if (tid == 384) {
#pragma unroll 1
            for (int kb = 0; kb < 8; kb++) {
                int s = kb < 6 ? kb : kb - 4;
                uint32_t dst = s < 2 ? sb + SM_A + 65536 + s * 24576 : sb + SM_X + (s - 2) * 24576;
                if (kb >= 6) mbar_wait_cluster(BAR(B_EMPTY0 + s), 0);
                uint32_t fb = BAR(B_FULL0 + kb);
                mbar_expect(fb, 24576);
                tma_5d_mc(dst + par * 8192, &tm_x, kb * 64, 0, 0, 8 * par, c, fb);
                tma_2d_mc(dst + 16384 + par * 4096, par ? &tm_bim : &tm_bre, kb * 64, 32 * c, fb);
                if (kb == 5) {
#pragma unroll 1
                    for (int k2 = par; k2 < 8; k2 += 2) {
                        asm volatile("cp.async.bulk.prefetch.tensor.2d.L2.global [%0, {%1,%2}];" ::"l"((c & 1) ? &tm_cim : &tm_cre), "r"(64 * (c >> 1)), "r"(k2 * 64) : "memory");
                        if (k2 < 4) {
                            asm volatile("cp.async.bulk.prefetch.tensor.5d.L2.global [%0, {%1,%2,%3,%4,%5}];" ::"l"(&tm_x), "r"((6 + (k2 >> 1)) * 64), "r"(0), "r"(0), "r"(8 * par), "r"(c) : "memory");
                            asm volatile("cp.async.bulk.prefetch.tensor.2d.L2.global [%0, {%1,%2}];" ::"l"(par ? &tm_bim : &tm_bre), "r"((6 + (k2 >> 1)) * 64), "r"(32 * c) : "memory");
                        }
                    }
                }
                if (kb == 7) {
                    mbar_wait_cluster(BAR(B_EMPTY0 + 0), 0);
                    mbar_wait_cluster(BAR(B_EMPTY0 + 1), 0);
                    mbar_expect(BAR(B_FULLC), 65536);
#pragma unroll 1
                    for (int k2 = par; k2 < 8; k2 += 2)
                        tma_2d_mc(sb + SM_A + 65536 + k2 * 8192, (c & 1) ? &tm_cim : &tm_cre, 64 * (c >> 1), k2 * 64, BAR(B_FULLC));
                }
            }
#pragma unroll 1
            for (int layer = 0; layer < 2; layer++) {
                wait_count(&g_bar[2 * layer], s_tgt[2 * layer]);
                TX(4 + 8 * layer);
                fence_async();
                mbar_expect(BAR(B_COL), 16384 + 8192);
                tma_5d(sb + SM_RAW, &tm_col, 32 * (b & 1), 0, b >> 1, 0, layer, BAR(B_COL));
                bulk_g2s(sb + SM_SSQ, g_ssq + layer * 2048, 8192, BAR(B_COL));
                if (layer == 0) {
                    wait_count(&g_bar[4], s_tgt[4]);
                    mbar_arrive(BAR(B_WRDY), 1);
                    fence_async();
                }
                if (layer == 0) mbar_wait(BAR(B_AFREE), 0);
                mbar_wait(BAR(B_COL), layer);
#pragma unroll 1
                for (int s = 0; s < 8; s++) {
                    if (layer == 1) mbar_wait(BAR(B_AEMPTY + s), 1);
                    if (s >= 2) mbar_wait(BAR(B_AFULL + s - 2), 0);
                    mbar_expect(BAR(B_AFULL + s), 16384);
                    bulk_g2s(sb + SM_A + s * 16384, g_A1 + (uint32_t)(r * 8 + s) * 16384, 16384, BAR(B_AFULL + s));
                }
                if (layer == 1) wait_count(&g_bar[6], s_tgt[5]);
                wait_count(&g_bar[1 + 2 * layer], s_tgt[1 + 2 * layer]);
                TX(3 + 8 * layer);
                fence_async();
                const uint8_t* xsrc = g_X + (uint32_t)(layer * 16 + c) * 8 * 16384;
                const uint8_t* esrc = g_E + (uint32_t)(layer * 8 + own) * 8 * 8192;
                mbar_arrive(BAR(B_SSQ), 1);
                mbar_expect(BAR(B_HPEER), 16384);
                mbar_expect(BAR(B_HPEER1), 16384);
#pragma unroll 1
                for (int it = 0; it < 16; it++) {
                    if (it < 8) {
                        int st = it & 3, f = layer * 2 + (it >> 2);
                        if (f > 0) mbar_wait_cluster(BAR(B_XEMPTY + st), (f - 1) & 1);
                        mbar_expect(BAR(B_XFULL + st), 24576);
                        bulk_g2s_mc(sb + SM_X + st * 24576 + par * 8192, xsrc + (uint32_t)it * 16384 + par * 8192, 8192, BAR(B_XFULL + st));
                        bulk_g2s(sb + SM_X + st * 24576 + 16384, esrc + (uint32_t)it * 8192, 8192, BAR(B_XFULL + st));
                    }
                    if (it >= 8) {
                        if (it == 8) mbar_wait(BAR(B_AEMPTY + 5), 0);
                        int s = it - 8, tile = 4 * par + ((pi_ + 1 + (s >> 1)) & 3), sl = r ^ (s & 1);
                        mbar_wait(BAR(B_AEMPTY + s), 0);
                        uint32_t fb = BAR(B_AFULL + s), dst = sb + SM_A + s * 16384;
                        mbar_expect(fb, 16384);
                        if (layer == 1) {
                            tma_2d(dst, &tm_cre, 64 * sl, 64 * tile, fb);
                            tma_2d(dst + 8192, &tm_cim, 64 * sl, 64 * tile, fb);
                        } else {
                            bulk_g2s(dst, g_A2 + (uint32_t)(sl * 8 + tile) * 16384, 16384, fb);
                        }
                    }
                }
            }
        }
        return;
    }

    asm volatile("setmaxnreg.inc.sync.aligned.u32 152;");
    if (tid >= 96 && tid < 112) g_ssq[2048 + 16 * b + tid - 96] = 0.f;
    if (tid >= 128 && tid < 256) ((float4*)g_ssqc)[b * 128 + tid - 128] = make_float4(0.f, 0.f, 0.f, 0.f);
    TS(0);
    if (wg == 0) TC(30);
    {
        const int f = 32 * r + lane;
        float cd, sd;
        __sincosf((float)f * (6.283185307179586f / 512.f), &sd, &cd);
        const uint32_t dst = sb + SM_A + (lane >> 2) * 1024 + (lane & 3) * 32;
#pragma unroll 1
        for (int ch = tid >> 5; ch < 64; ch += 12) {
            int a = (8 * ch * f) & 511;
            a = a >= 256 ? a - 512 : a;
            float cs, sn;
            __sincosf((float)a * (6.283185307179586f / 512.f), &sn, &cs);
            float cv[8], sv[8];
#pragma unroll
            for (int e = 0; e < 8; e++) {
                cv[e] = cs; sv[e] = -sn;
                float t = cs * cd - sn * sd;
                sn = sn * cd + cs * sd;
                cs = t;
            }
            uint4 o1 = make_uint4(pack_bf16(sv[0], sv[1]), pack_bf16(sv[2], sv[3]), pack_bf16(sv[4], sv[5]), pack_bf16(sv[6], sv[7]));
            if (f == 0) o1 = make_uint4(0xbf803f80u, 0xbf803f80u, 0xbf803f80u, 0xbf803f80u);
            uint32_t a0 = dst + (ch >> 3) * 8192 + (ch & 7) * 128;
            sts128(a0, make_uint4(pack_bf16(cv[0], cv[1]), pack_bf16(cv[2], cv[3]), pack_bf16(cv[4], cv[5]), pack_bf16(cv[6], cv[7])));
            sts128(a0 + 16, o1);
        }
    }
    fence_async_smem();
    asm volatile("barrier.cluster.wait.acquire.aligned;" ::: "memory");
    bar_sync(10, 384);
    TS(1);
    {
        float acc[32];
        acc_def(acc);
        const int npos = 16 * r + 8 * (wg & 1) + 2 * w;
        float sh0 = 0.f, sh1 = 0.f, s0 = 0.f, s1 = 0.f, q0 = 0.f, q1 = 0.f;
#pragma unroll 1
        for (int kb = 0; kb < 8; kb++) {
            int s = kb < 6 ? kb : kb - 4;
            uint32_t slot = s < 2 ? sb + SM_A + 65536 + s * 24576 : sb + SM_X + (s - 2) * 24576;
            uint32_t src = slot + wg * 8192;
            mbar_wait(BAR(B_FULL0 + kb), 0);
            {
                uint32_t v0 = lds32(slot + npos * 128 + lane * 4), v1 = lds32(slot + npos * 128 + 128 + lane * 4);
                if (kb == 0) { sh0 = __shfl_sync(~0u, bf_lo(v0), 0); sh1 = __shfl_sync(~0u, bf_lo(v1), 0); }
                float a = bf_lo(v0) - sh0, bq = bf_hi(v0) - sh0, cq = bf_lo(v1) - sh1, d = bf_hi(v1) - sh1;
                s0 += a + bq; q0 += a * a + bq * bq; s1 += cq + d; q1 += cq * cq + d * d;
            }
            wg_fence();
#pragma unroll
            for (int ks = 0; ks < 4; ks++)
                wgmma_n64<0>(acc, desc_a(sb + SM_A + kb * 8192 + ks * 256), desc_k(src + ks * 32), 1);
            wg_commit();
            wg_wait<1>();
            if (kb == 1) bar_sync(15, 480);
            if (kb > 0 && kb <= 4 && lane == 0) { mbar_arrive(BAR(B_EMPTY0 + kb - 1), 1); mbar_arrive_remote(mapa(BAR(B_EMPTY0 + kb - 1), par ^ 1)); }
        }
        wg_wait<0>();
        TS(2);
        if (wg < 2) {
            uint8_t* dst = g_X + (uint32_t)((c * 8 + r) * 16384 + w * 4096 + wg * 1024 + g * 16 + 4 * q);
#pragma unroll
            for (int i = 0; i < 8; i++) {
                *(uint32_t*)(dst + i * 128) = pack_bf16(acc[4 * i], acc[4 * i + 1]);
                *(uint32_t*)(dst + 2048 + i * 128) = pack_bf16(acc[4 * i + 2], acc[4 * i + 3]);
            }
#pragma unroll
            for (int o = 16; o; o >>= 1) {
                s0 += __shfl_xor_sync(~0u, s0, o); q0 += __shfl_xor_sync(~0u, q0, o);
                s1 += __shfl_xor_sync(~0u, s1, o); q1 += __shfl_xor_sync(~0u, q1, o);
            }
            if (lane == 0) *(float2*)(g_ssq + 128 * c + npos) = make_float2(fmaxf(q0 - s0 * s0 * (1.f / 512.f), 0.f), fmaxf(q1 - s1 * s1 * (1.f / 512.f), 0.f));
        } else {
            uint8_t* dst = sm + SM_B1ST + w * 256 + q * 32 + g * 2;
            const float wj0 = (r == 0 && w == 0 && g < 2) ? (g == 0 ? 0.f : 1.f / 512.f) : 2.f / 512.f;
#pragma unroll
            for (int i = 0; i < 4; i++) {
#pragma unroll
                for (int e = 0; e < 2; e++) {
                    float2 cf = *(const float2*)(sm + SM_RSTD + (8 * i + 2 * q + e) * 8);
#pragma unroll
                    for (int h = 0; h < 2; h++) {
                        float wj = h == 0 ? wj0 : 2.f / 512.f;
                        float pr = acc[4 * i + 2 * h + e] * wj, pi = acc[16 + 4 * i + 2 * h + e] * wj;
                        uint8_t* d2 = dst + i * 2048 + h * 128 + e * 16;
                        *(__nv_bfloat16*)(d2) = __float2bfloat16(cf.x * pr - cf.y * pi);
                        *(__nv_bfloat16*)(d2 + 1024) = __float2bfloat16(cf.x * pi + cf.y * pr);
                    }
                }
            }
            fence_async_smem();
        }
        bar_sync(2, 416);
        TS(3);
    }

    if (wg == 2) {
        {
            const int m = 4 * c + w, jp = 64 * r + m;
            int fp, php;
            dft_fp(jp, fp, php);
            const __nv_bfloat16* dh = (const __nv_bfloat16*)(sm + SM_RSTD);
            if (tid == 256) wait_count(&g_bar[5], s_tgt[5]);
            bar_sync(3, 128);
            float4 d4 = __ldcg((const float4*)g_Dh + (tid - 256));
            *(uint2*)(sm + SM_RSTD + (tid - 256) * 8) = make_uint2(pack_bf16(d4.x, d4.y), pack_bf16(d4.z, d4.w));
            bar_sync(3, 128);
#pragma unroll 1
            for (int it = 0; it < 2; it++) {
                const int ch = lane + 32 * it;
                float v[8];
#pragma unroll
                for (int e = 0; e < 8; e++) {
                    int j = 8 * ch + e, f, ph;
                    dft_fp(j, f, ph);
                    float wj = j == 0 ? 0.f : (j == 1 ? 1.f / 512.f : 2.f / 512.f);
                    float gsum = 0.f;
#pragma unroll
                    for (int sgn = 0; sgn < 2; sgn++) {
                        int mm = (sgn ? f - fp : f + fp) & 511, pp = (sgn ? ph - php : ph + php) & 511;
                        if (mm > 256) { mm = 512 - mm; pp = (512 - pp) & 511; }
                        int odd = (pp >> 7) & 1;
                        float t = __bfloat162float(dh[mm == 256 ? 1 : 2 * mm + odd]);
                        if (odd && (mm & 255) == 0) t = 0.f;
                        gsum += (pp & 256) ? -t : t;
                    }
                    v[e] = 0.5f * wj * gsum;
                }
                uint32_t off = (uint32_t)(r * 8 + (ch >> 3)) * 8192 + (m >> 3) * 1024 + (ch & 7) * 128 + (m & 7) * 16;
                *(uint4*)(g_E + off) = make_uint4(pack_bf16(v[0], v[1]), pack_bf16(v[2], v[3]), pack_bf16(v[4], v[5]), pack_bf16(v[6], v[7]));
            }
        }
        float acc[32];
        acc_def(acc);
        mbar_wait(BAR(B_FULLC), 0);
        wg_fence();
#pragma unroll 1
        for (int kb = 0; kb < 8; kb++) {
#pragma unroll
            for (int ks = 0; ks < 4; ks++)
                wgmma_n64<1>(acc, desc_a(sb + SM_A + kb * 8192 + ks * 256), desc_mn(sb + SM_A + 65536 + kb * 8192 + ks * 2048, 8192), 1);
            wg_commit();
        }
        wg_wait<0>();
        fence_async_smem();
        if (lane == 0) mbar_arrive(BAR(B_AFREE), 1);
        uint8_t* dst = g_A2 + (uint32_t)(((c >> 1) * 8 + r) * 16384 + (c & 1) * 8192 + w * 2048 + g * 16 + 4 * q);
#pragma unroll
        for (int i = 0; i < 8; i++) {
            *(uint32_t*)(dst + i * 128) = pack_bf16(acc[4 * i], acc[4 * i + 1]);
            *(uint32_t*)(dst + 1024 + i * 128) = pack_bf16(acc[4 * i + 2], acc[4 * i + 3]);
        }
    }

#pragma unroll 1
    for (int layer = 0; layer < 2; layer++) {
        if (wg < 2) {
            const int n1 = 32 * wg + 8 * w + g;
            const int ct = n1 >> 2;
            gen_col_consts(sb, tid);
            uint32_t tr2[4], ti2[4], tn2[4];
#pragma unroll
            for (int i = 0; i < 4; i++) {
                float cr[2], ci[2];
#pragma unroll
                for (int e = 0; e < 2; e++) {
                    int a = (n1 * (8 * i + 2 * q + e)) & 2047;
                    a = a >= 1024 ? a - 2048 : a;
                    float ang = (float)a * (-6.283185307179586f / 2048.f);
                    cr[e] = __cosf(ang); ci[e] = __sinf(ang);
                }
                tr2[i] = pack_bf16(cr[0], cr[1]); ti2[i] = pack_bf16(ci[0], ci[1]); tn2[i] = ti2[i] ^ 0x80008000u;
            }
            uint32_t wf[16];
            const uint4* ws = g_Wfrag + (uint32_t)(b * 1024 + n1 * 4 + q);
#pragma unroll
            for (int i = 0; i < 4; i++) {
                uint4 v = make_uint4(0, 0, 0, 0);
                if (layer == 1) v = __ldcg(ws + i * 256);
                wf[4 * i] = v.x; wf[4 * i + 1] = v.y; wf[4 * i + 2] = v.z; wf[4 * i + 3] = v.w;
            }
            mbar_wait(BAR(B_COL), layer);
            TS(4 + 12 * layer);
            if (wg == 0) TC(0 + 10 * layer);
            const uint32_t rw0 = sb + SM_RAW + ct * 1024 + q * 64 + ((q >> 1) << 4) + (g & 3) * 4, rw1 = rw0 ^ 16;
            const int pos0 = 128 * ct + 8 * q + 2 * (g & 3);
            const int sw = b == 0 ? 1 : 0;
            uint32_t xr[4][4];
            const uint32_t st0 = sb + SM_H + (n1 >> 3) * 1024 + g * 16 + 4 * q;
#pragma unroll
            for (int i = 0; i < 4; i++) {
                float2 sq = *(const float2*)(sm + SM_SSQ + (pos0 + 32 * i) * 4);
                const uint32_t rs2 = pack_bf16(rsqrtf(sq.x * (1.f / 512.f) + 1e-5f), rsqrtf(sq.y * (1.f / 512.f) + 1e-5f));
#pragma unroll
                for (int jj = 0; jj < 4; jj++) {
                    const int K = jj ^ (2 * (i & 1));
                    uint32_t a = ((K & 1) ? rw1 : rw0) + i * 256 + (K & 2) * 16;
                    if (jj < 2) a ^= sw << 4;
                    uint32_t v = lds32(a);
                    xr[jj][i] = v;
                    uint32_t o = hmul2(v, rs2);
                    if (jj == 1 && sw) o = 0u;
                    sts32(st0 + (jj & 1) * 8192 + (4 * (jj >> 1) + i) * 128, o);
                }
            }
            if (wg == 0) TC(1 + 10 * layer);
            fence_async_smem();
            bar_sync(1, 256);
            float acc[32];
            const uint32_t s1a = sb + SM_X + wg * 16384, s2b = sb + SM_X + 32768;
            wg_fence();
#pragma unroll
            for (int ks = 0; ks < 8; ks++)
                wgmma_n64<1>(acc, desc_a(s1a + (ks >> 2) * 8192 + (ks & 3) * 256), desc_b<64>(sb + SM_H + ks * 2048), ks != 0);
            wg_commit();
            if (layer == 0) {
                mbar_wait(BAR(B_WRDY), 0);
#pragma unroll
                for (int i = 0; i < 4; i++) {
                    uint4 v = __ldcg(ws + i * 256);
                    wf[4 * i] = v.x; wf[4 * i + 1] = v.y; wf[4 * i + 2] = v.z; wf[4 * i + 3] = v.w;
                }
            }
            wg_wait<0>();
            if (wg == 0) TC(2 + 10 * layer);
            uint32_t are[2][4], aim[2][4];
#pragma unroll
            for (int col = 0; col < 2; col++) {
#pragma unroll
                for (int i = 0; i < 4; i++) {
                    int o = 4 * (4 * col + i);
                    uint32_t zr = pack_bf16(acc[o], acc[o + 1]), zi = pack_bf16(acc[o + 2], acc[o + 3]);
                    are[col][i] = hfma2(zr, tr2[i], hmul2(zi, tn2[i]));
                    aim[col][i] = hfma2(zr, ti2[i], hmul2(zi, tr2[i]));
                }
            }
            wg_fence();
#pragma unroll
            for (int ks = 0; ks < 2; ks++)
                wgmma_n64_rs(acc, are[0][2 * ks], are[1][2 * ks], are[0][2 * ks + 1], are[1][2 * ks + 1], desc_b<64>(s2b + ks * 2048), ks != 0);
#pragma unroll
            for (int ks = 0; ks < 2; ks++)
                wgmma_n64_rs(acc, aim[0][2 * ks], aim[1][2 * ks], aim[0][2 * ks + 1], aim[1][2 * ks + 1], desc_b<64>(s2b + 4096 + ks * 2048), 1);
            wg_commit();
            wg_wait<0>();
            if (wg == 0) TC(3 + 10 * layer);
#pragma unroll
            for (int col = 0; col < 2; col++) {
#pragma unroll
                for (int i = 0; i < 4; i++) {
                    uint32_t wr = wf[col * 8 + 2 * i], wn = wf[col * 8 + 2 * i + 1];
                    uint32_t zr = pack_bf16(acc[4 * i + 2 * col], acc[4 * i + 2 * col + 1]);
                    uint32_t zi = pack_bf16(acc[16 + 4 * i + 2 * col], acc[16 + 4 * i + 2 * col + 1]);
                    are[col][i] = hfma2(zr, wr, hmul2(zi, wn));
                    aim[col][i] = hfma2(zr, wn, hmul2(zi ^ 0x80008000u, wr));
                }
            }
            wg_fence();
#pragma unroll
            for (int ks = 0; ks < 2; ks++)
                wgmma_n64_rs(acc, are[0][2 * ks], are[1][2 * ks], are[0][2 * ks + 1], are[1][2 * ks + 1], desc_b<64>(s2b + ks * 2048), ks != 0);
#pragma unroll
            for (int ks = 0; ks < 2; ks++)
                wgmma_n64_rs(acc, aim[0][2 * ks], aim[1][2 * ks], aim[0][2 * ks + 1], aim[1][2 * ks + 1], desc_b<64>(s2b + 4096 + ks * 2048), 1);
            wg_commit();
            wg_wait<0>();
            if (wg == 0) TC(4 + 10 * layer);
#pragma unroll
            for (int col = 0; col < 2; col++) {
#pragma unroll
                for (int i = 0; i < 4; i++) {
                    uint32_t zr = pack_bf16(acc[4 * i + 2 * col], acc[4 * i + 2 * col + 1]);
                    uint32_t zi = pack_bf16(acc[16 + 4 * i + 2 * col], acc[16 + 4 * i + 2 * col + 1]);
                    sts32(st0 + 16384 + (4 * col + i) * 128, hfma2(zr, tr2[i], hmul2(zi, tn2[i])));
                    sts32(st0 + 16384 + 8192 + (4 * col + i) * 128, hfma2(zr, ti2[i], hmul2(zi, tr2[i])));
                }
            }
            if (wg == 0) TC(5 + 10 * layer);
            fence_async_smem();
            bar_sync(1, 256);
            wg_fence();
#pragma unroll
            for (int ks = 0; ks < 8; ks++)
                wgmma_n64<1>(acc, desc_a(s1a + (ks >> 2) * 8192 + (ks & 3) * 256), desc_b<64>(sb + SM_H + 16384 + ks * 2048), ks != 0);
            wg_commit();
            wg_wait<0>();
            if (wg == 0) TC(6 + 10 * layer);
            const float sc = 1.f / 2048.f;
            const float sci0 = sw ? 0.f : -sc;
            const float wr0 = sw ? 0.5f : 1.f, wi0 = sw ? 0.f : 1.f;
#pragma unroll
            for (int i = 0; i < 4; i++) {
                float ss0, ss1;
#pragma unroll
                for (int col = 0; col < 2; col++) {
                    int o = 4 * (4 * col + i);
                    uint32_t vr = xr[2 * col][i], vi = xr[2 * col + 1][i];
                    float si = col == 0 ? sci0 : -sc;
                    uint32_t nr = pack_bf16(fmaf(acc[o], sc, bf_lo(vr)), fmaf(acc[o + 1], sc, bf_hi(vr)));
                    uint32_t ni = pack_bf16(fmaf(acc[o + 2], si, bf_lo(vi)), fmaf(acc[o + 3], si, bf_hi(vi)));
                    float a0 = bf_lo(nr), a1 = bf_hi(nr), b0 = bf_lo(ni), b1 = bf_hi(ni);
                    if (col == 0) {
                        ss0 = wr0 * a0 * a0 + wi0 * b0 * b0;
                        ss1 = wr0 * a1 * a1 + wi0 * b1 * b1;
                    } else {
                        ss0 += a0 * a0 + b0 * b0;
                        ss1 += a1 * a1 + b1 * b1;
                    }
                    const int K = (2 * col) ^ (2 * (i & 1));
                    uint32_t a = rw0 + i * 256 + K * 16;
                    if (col == 0) a ^= sw << 4;
                    sts32(a, nr);
                    sts32(a ^ 16, ni);
                }
                *(float2*)(sm + SM_SSQ + (pos0 + 32 * i) * 4) = make_float2(ss0 * (2.f / 512.f), ss1 * (2.f / 512.f));
            }
            fence_async_smem();
        }
        TS(5 + 12 * layer);
        if (wg == 0) TC(7 + 10 * layer);
        bar_arrive(5, 416);

        float acc[64];
        float* s_rstd = (float*)(sm + SM_RSTD);
        float* s_mean = (float*)(sm + SM_MEAN);
        const unsigned epoch = s_tgt[0] >> 7;
        const uint32_t pt3 = 1u + (2u * epoch + layer) % 3u;
        const uint32_t ptag = (pt3 & 1u) | ((pt3 & 2u) << 15);
        const uint64_t dstep = layer == 0 ? 16 : 2;
        auto c_desc = [&](int s) { return layer == 0 ? desc_a(sb + SM_A + s * 16384) : desc_k(sb + SM_A + s * 16384); };
        if (wg < 2) {
            const int prow = 32 * wg + 8 * w + g;
            const float2 l1 = *(const float2*)(sm + SM_LAM + prow * 8);
            float lr32 = l1.x, li32 = l1.y;
#pragma unroll
            for (int i = 0; i < 5; i++) { float t = lr32 * lr32 - li32 * li32; li32 = 2.f * lr32 * li32; lr32 = t; }
            float lr128 = lr32, li128 = li32;
#pragma unroll
            for (int i = 0; i < 2; i++) { float t = lr128 * lr128 - li128 * li128; li128 = 2.f * lr128 * li128; lr128 = t; }
            const float lr1 = l1.x, li1 = l1.y;
            acc_def(acc);
#pragma unroll 1
            for (int kb = 0; kb < 8; kb++) {
                mbar_wait(BAR(B_AFULL + kb), 0);
                mbar_wait(BAR(B_XFULL + (kb & 3)), (kb >> 2) & 1);
                wg_fence();
#pragma unroll
                for (int ks = 0; ks < 4; ks++)
                    wgmma_n128<1>(acc, desc_a(sb + SM_A + kb * 16384 + wg * 8192 + ks * 256),
                                  desc_b<128>(sb + SM_X + (kb & 3) * 24576 + ks * 4096), 1);
                wg_commit();
                wg_wait<1>();
                if (kb > 0 && lane == 0) {
                    mbar_arrive(BAR(B_AEMPTY + kb - 1), 1); mbar_arrive(BAR(B_XEMPTY + ((kb - 1) & 3)), 1);
                    mbar_arrive_remote(mapa(BAR(B_XEMPTY + ((kb - 1) & 3)), par ^ 1));
                }
            }
            wg_wait<0>();
            if (lane == 0) {
                mbar_arrive(BAR(B_AEMPTY + 7), 1); mbar_arrive(BAR(B_XEMPTY + 3), 1);
                mbar_arrive_remote(mapa(BAR(B_XEMPTY + 3), par ^ 1)); mbar_arrive_remote(mapa(BAR(B_RFREE), par ^ 1));
            }
            bar_arrive(14, 384);
            TS(6 + 12 * layer);
            bar_sync(4, 384);
            TS(7 + 12 * layer);
            float er = 0.f, ei = 0.f;
#pragma unroll
            for (int i = 0; i < 16; i++) {
                float2 rs = *(const float2*)(s_rstd + 128 + 8 * i + 2 * q);
                acc[4 * i] *= rs.x; acc[4 * i + 1] *= rs.y; acc[4 * i + 2] *= rs.x; acc[4 * i + 3] *= rs.y;
                float nr = lr1 * er - li1 * ei + acc[4 * i], ni = lr1 * ei + li1 * er + acc[4 * i + 2];
                er = lr1 * nr - li1 * ni + acc[4 * i + 1];
                ei = lr1 * ni + li1 * nr + acc[4 * i + 3];
            }
            float cr = 0.f, ci = 0.f, tr = 0.f, ti = 0.f;
#pragma unroll
            for (int qq = 0; qq < 4; qq++) {
                float xr_ = __shfl_sync(~0u, er, (lane & ~3) | qq), xi_ = __shfl_sync(~0u, ei, (lane & ~3) | qq);
                if (qq == q) { cr = tr; ci = ti; }
                float nr = lr32 * tr - li32 * ti + xr_, ni = lr32 * ti + li32 * tr + xi_;
                tr = nr; ti = ni;
            }
            float4* eb = g_Ebuf + (uint32_t)(layer * 16 * 512 + 64 * r + prow);
            if (q == 0 && c < 15) st_relaxed_f4(eb + c * 512, make_float4(tr, ti, __uint_as_float(epoch), 0.f));
            TS(8 + 12 * layer);
            float pr[4], pi[4];
            {
                unsigned n = 0;
                bool ok;
#pragma unroll 1
                do {
                    ok = true;
#pragma unroll
                    for (int k = 0; k < 4; k++) {
                        float4 v = make_float4(0.f, 0.f, __uint_as_float(epoch), 0.f);
                        if (4 * k + q < c) v = ld_relaxed_f4(eb + (4 * k + q) * 512);
                        pr[k] = v.x; pi[k] = v.y;
                        ok = ok && __float_as_uint(v.z) == epoch;
                    }
                } while (!ok && ++n < SPIN_LIMIT);
            }
            __syncwarp();
            TS(9 + 12 * layer);
            float hr = 0.f, hi = 0.f;
#pragma unroll
            for (int cc = 0; cc < 15; cc++) {
                float xr_ = __shfl_sync(~0u, pr[cc >> 2], (lane & ~3) | (cc & 3)), xi_ = __shfl_sync(~0u, pi[cc >> 2], (lane & ~3) | (cc & 3));
                if (cc < c) {
                    float nr = lr128 * hr - li128 * hi + xr_, ni = lr128 * hi + li128 * hr + xi_;
                    hr = nr; hi = ni;
                }
            }
#pragma unroll
            for (int qq = 0; qq < 3; qq++) {
                if (qq < q) { float nr = lr32 * hr - li32 * hi, ni = lr32 * hi + li32 * hr; hr = nr; hi = ni; }
            }
            er = cr + hr; ei = ci + hi;
            bar_sync(7, 384);
            mbar_wait_cluster(BAR(B_RFREE), layer);
            const uint32_t ha = sb + SM_HH + par * 32768 + (prow >> 3) * 1024 + g * 16 + 4 * q;
#pragma unroll
            for (int i = 0; i < 16; i++) {
                float nr = lr1 * er - li1 * ei + acc[4 * i], ni = lr1 * ei + li1 * er + acc[4 * i + 2];
                er = lr1 * nr - li1 * ni + acc[4 * i + 1];
                ei = lr1 * ni + li1 * nr + acc[4 * i + 3];
                sts32(ha + (i >> 3) * 16384 + (i & 7) * 128, pack_bf16(nr, er));
                sts32(ha + (i >> 3) * 16384 + 8192 + (i & 7) * 128, pack_bf16(ni, ei));
                if (i == 7) { fence_async_smem(); bar_arrive(13, 288); }
            }
            fence_async_smem();
            acc_def(acc);
            float acc2[32];
            acc_def(acc2);
            TS(10 + 12 * layer);
            bar_sync(6, 416);
            TS(11 + 12 * layer);
            float (&a0)[32] = *reinterpret_cast<float (*)[32]>(&acc[0]);
            float (&a1)[32] = *reinterpret_cast<float (*)[32]>(&acc[32]);
            auto tile_mma = [&](float (&d)[32], int u) {
#pragma unroll 1
                for (int k = 0; k < 2; k++) {
                    const uint32_t hb = sb + SM_HH + (par ^ k) * 32768 + wg * 16384;
                    if (k == 1) mbar_wait(BAR(wg ? B_HPEER1 : B_HPEER), layer);
                    mbar_wait(BAR(B_AFULL + 2 * u + k), 1);
                    const uint64_t da = c_desc(2 * u + k);
                    wg_fence();
#pragma unroll
                    for (int ks = 0; ks < 4; ks++) wgmma_n64s<1>(d, da + ks * dstep, desc_b<64>(hb + ks * 2048), 1);
#pragma unroll
                    for (int ks = 0; ks < 4; ks++) wgmma_n64s<-1>(d, da + 512 + ks * dstep, desc_b<64>(hb + 8192 + ks * 2048), 1);
                }
                wg_commit();
            };
            auto tile_ship = [&](float (&d)[32], int u) {
                uint4* dst = g_P + (uint32_t)(((c * 8 + 2 * ((pi_ + 1 + u) & 3) + par) * 4 + pi_) * 1024 + wg * 512 + (tid & 127));
#pragma unroll
                for (int i = 0; i < 4; i++)
                    dst[i * 128] = make_uint4((pack_bf16(d[8 * i], d[8 * i + 1]) & 0xfffefffeu) | ptag, pack_bf16(d[8 * i + 2], d[8 * i + 3]),
                                              pack_bf16(d[8 * i + 4], d[8 * i + 5]), pack_bf16(d[8 * i + 6], d[8 * i + 7]));
            };
            tile_mma(a0, 0);
            if ((tid & 127) == 0) mbar_arrive_remote(mapa(BAR(B_HDONE), par ^ 1));
            __syncwarp();
            tile_mma(a1, 1);
            wg_wait<1>();
            tile_ship(a0, 0);
            tile_mma(acc2, 2);
            bar_arrive(12, 384);
            wg_wait<1>();
            tile_ship(a1, 1);
            wg_wait<0>();
            tile_ship(acc2, 2);
            if (lane < 6) mbar_arrive(BAR(B_AEMPTY + lane), 1);
            TS(12 + 12 * layer);
        } else {
            const int t2 = tid - 256;
            const uint8_t* ximg = g_X + (uint32_t)layer * 16 * 8 * 16384;
            mbar_wait(BAR(B_SSQ), layer);
            TS(6 + 12 * layer);
            float sqv[16];
#pragma unroll
            for (int i = 0; i < 16; i++) sqv[i] = __ldcg(g_ssqc + (layer * 16 + i) * 2048 + 128 * c + t2);
            const unsigned short xm = __ldcg((const unsigned short*)(ximg + (uint32_t)(c * 8 * 16384 + (t2 >> 3) * 128 + (t2 & 7) * 2)));
            acc_def(acc);
#pragma unroll 1
            for (int kb = 0; kb < 8; kb++) {
                if (kb == 4) {
                    wg_wait<0>();
                    if (lane == 0) { mbar_arrive(BAR(B_XEMPTY + 3), 1); mbar_arrive_remote(mapa(BAR(B_XEMPTY + 3), par ^ 1)); }
                    float tot = 0.f;
#pragma unroll
                    for (int i = 0; i < 16; i++) tot += sqv[i];
                    float rs = rsqrtf(tot * (1.f / 512.f) + 1e-5f);
                    s_rstd[t2] = rs;
                    s_rstd[128 + t2] = 2.f * rs;
                    s_mean[t2] = layer == 0 ? 0.f : __uint_as_float((uint32_t)xm << 16) * (1.f / 512.f);
                    TS(7 + 12 * layer);
                    bar_arrive(4, 384);
                    bar_sync(14, 384);
                }
                mbar_wait(BAR(B_XFULL + (kb & 3)), (kb >> 2) & 1);
                wg_fence();
#pragma unroll
                for (int ks = 0; ks < 4; ks++)
                    wgmma_n128<1>(acc, desc_a(sb + SM_X + (kb & 3) * 24576 + 16384 + ks * 256), desc_b<128>(sb + SM_X + (kb & 3) * 24576 + ks * 4096), 1);
                wg_commit();
                wg_wait<1>();
                if ((kb & 3) != 0 && lane == 0) { mbar_arrive(BAR(B_XEMPTY + ((kb - 1) & 3)), 1); mbar_arrive_remote(mapa(BAR(B_XEMPTY + ((kb - 1) & 3)), par ^ 1)); }
            }
            wg_wait<0>();
            if (lane == 0) { mbar_arrive(BAR(B_XEMPTY + 3), 1); mbar_arrive_remote(mapa(BAR(B_XEMPTY + 3), par ^ 1)); mbar_arrive_remote(mapa(BAR(B_RFREE), par ^ 1)); }
            bar_arrive(7, 384);
            bar_sync(3, 128);
            TS(9 + 12 * layer);
            const int m0 = 16 * w + g;
            const uint32_t xoff = (uint32_t)((c * 8 + own) * 16384 + w * 4096 + g * 16 + 4 * q);
            if (layer == 0) {
                const uint8_t* xs = g_X + xoff;
#pragma unroll
                for (int i = 0; i < 16; i++) {
                    float2 rs = *(const float2*)(s_rstd + 8 * i + 2 * q);
                    uint32_t x0v = __ldcg((const uint32_t*)(xs + i * 128)), x1v = __ldcg((const uint32_t*)(xs + 2048 + i * 128));
                    acc[4 * i] = acc[4 * i] * rs.x + bf_lo(x0v);
                    acc[4 * i + 1] = acc[4 * i + 1] * rs.y + bf_hi(x0v);
                    acc[4 * i + 2] = acc[4 * i + 2] * rs.x + bf_lo(x1v);
                    acc[4 * i + 3] = acc[4 * i + 3] * rs.y + bf_hi(x1v);
                }
            } else {
                float d0 = ldbf(p.dskip + 64 * own + m0), d1 = ldbf(p.dskip + 64 * own + m0 + 8);
#pragma unroll
                for (int i = 0; i < 16; i++) {
                    float2 rs = *(const float2*)(s_rstd + 8 * i + 2 * q);
                    float2 mn = *(const float2*)(s_mean + 8 * i + 2 * q);
                    acc[4 * i] = acc[4 * i] * (1.f + rs.x * d0) + mn.x;
                    acc[4 * i + 1] = acc[4 * i + 1] * (1.f + rs.y * d0) + mn.y;
                    acc[4 * i + 2] = acc[4 * i + 2] * (1.f + rs.x * d1) + mn.x;
                    acc[4 * i + 3] = acc[4 * i + 3] * (1.f + rs.y * d1) + mn.y;
                }
            }
            TS(10 + 12 * layer);
            bar_sync(6, 416);
            TS(11 + 12 * layer);
            {
                float (&a0)[32] = *reinterpret_cast<float (*)[32]>(&acc[0]);
                float (&a1)[32] = *reinterpret_cast<float (*)[32]>(&acc[32]);
#pragma unroll 1
                for (int k = 0; k < 2; k++) {
                    const uint32_t hb = sb + SM_HH + (par ^ k) * 32768;
                    if (k == 1) {
                        mbar_wait(BAR(B_HPEER), layer);
                        mbar_wait(BAR(B_HPEER1), layer);
                        bar_sync(12, 384);
                    }
                    mbar_wait(BAR(B_AFULL + 6 + k), 1);
                    const uint64_t da = c_desc(6 + k);
                    wg_fence();
#pragma unroll
                    for (int ks = 0; ks < 4; ks++) {
                        wgmma_n64s<1>(a0, da + ks * dstep, desc_b<64>(hb + ks * 2048), 1);
                        wgmma_n64s<1>(a1, da + ks * dstep, desc_b<64>(hb + 16384 + ks * 2048), 1);
                    }
#pragma unroll
                    for (int ks = 0; ks < 4; ks++) {
                        wgmma_n64s<-1>(a0, da + 512 + ks * dstep, desc_b<64>(hb + 8192 + ks * 2048), 1);
                        wgmma_n64s<-1>(a1, da + 512 + ks * dstep, desc_b<64>(hb + 16384 + 8192 + ks * 2048), 1);
                    }
                    wg_commit();
                }
                wg_wait<0>();
            }
#pragma unroll
            for (int i = 0; i < 16; i++)
                *(float4*)(sm + SM_A + 6 * 16384 + i * 2048 + t2 * 16) = make_float4(acc[4 * i], acc[4 * i + 1], acc[4 * i + 2], acc[4 * i + 3]);
            TS(12 + 12 * layer);
        }
        {
            const int t = tid & 127;
            const int nch = wg == 2 ? 2 : 3;
            const uint4* pb = g_P + (uint32_t)((c * 8 + r) * 4 * 1024 + wg * 128 + t);
            uint4 v[3][3];
            unsigned n = 0;
#pragma unroll 1
            while (true) {
                if (lane == 31) {
#pragma unroll 1
                    while (true) {
                        uint32_t bad = 0;
#pragma unroll
                        for (int sx = 0; sx < 3; sx++) {
                            uint32_t t0;
                            asm volatile("ld.relaxed.gpu.global.u32 %0, [%1];" : "=r"(t0) : "l"(pb + ((pi_ + 1 + sx) & 3) * 1024 + (nch - 1) * 384) : "memory");
                            bad |= t0 ^ ptag;
                        }
                        if (!(bad & 0x00010001u) || ++n >= SPIN_LIMIT) break;
                    }
                }
                __syncwarp();
                uint32_t bad = 0;
#pragma unroll
                for (int k = 0; k < 3; k++)
#pragma unroll
                    for (int sx = 0; sx < 3; sx++) {
                        v[k][sx] = make_uint4(ptag, 0, 0, 0);
                        if (k < nch) v[k][sx] = ld_relaxed_u4(pb + ((pi_ + 1 + sx) & 3) * 1024 + k * 384);
                        bad |= v[k][sx].x ^ ptag;
                    }
                if (!__any_sync(~0u, bad & 0x00010001u) || ++n >= SPIN_LIMIT) break;
            }
            bar_sync(8, 384);
            TS(13 + 12 * layer);
            const int m0 = 16 * w + g;
            const float w0 = (own == 0 && m0 < 2) ? (m0 == 0 ? 0.f : 0.5f) : 1.f;
#pragma unroll
            for (int k = 0; k < 3; k++) {
                if (k < nch) {
                    const int i = wg + 3 * k;
                    float4 a = *(const float4*)(sm + SM_A + 6 * 16384 + (2 * i) * 2048 + t * 16);
                    float4 bq = *(const float4*)(sm + SM_A + 6 * 16384 + (2 * i + 1) * 2048 + t * 16);
#pragma unroll
                    for (int sx = 0; sx < 3; sx++) {
                        a.x += bf_lo(v[k][sx].x); a.y += bf_hi(v[k][sx].x); a.z += bf_lo(v[k][sx].y); a.w += bf_hi(v[k][sx].y);
                        bq.x += bf_lo(v[k][sx].z); bq.y += bf_hi(v[k][sx].z); bq.z += bf_lo(v[k][sx].w); bq.w += bf_hi(v[k][sx].w);
                    }
                    if (layer == 0) {
                        uint8_t* xd = g_X + (uint32_t)((16 * 8 + c * 8 + own) * 16384 + w * 4096 + g * 16 + 4 * q + i * 256);
                        uint32_t v0 = pack_bf16(a.x, a.y), v1 = pack_bf16(a.z, a.w), v2 = pack_bf16(bq.x, bq.y), v3 = pack_bf16(bq.z, bq.w);
                        *(uint32_t*)(xd) = v0; *(uint32_t*)(xd + 2048) = v1; *(uint32_t*)(xd + 128) = v2; *(uint32_t*)(xd + 2048 + 128) = v3;
                        float sq[4];
                        sq[0] = w0 * bf_lo(v0) * bf_lo(v0) + bf_lo(v1) * bf_lo(v1);
                        sq[1] = w0 * bf_hi(v0) * bf_hi(v0) + bf_hi(v1) * bf_hi(v1);
                        sq[2] = w0 * bf_lo(v2) * bf_lo(v2) + bf_lo(v3) * bf_lo(v3);
                        sq[3] = w0 * bf_hi(v2) * bf_hi(v2) + bf_hi(v3) * bf_hi(v3);
                        float u0 = (g & 1) ? sq[2] : sq[0], u1 = (g & 1) ? sq[3] : sq[1];
                        u0 += __shfl_xor_sync(~0u, (g & 1) ? sq[0] : sq[2], 4);
                        u1 += __shfl_xor_sync(~0u, (g & 1) ? sq[1] : sq[3], 4);
                        float z = (g & 2) ? u1 : u0;
                        z += __shfl_xor_sync(~0u, (g & 2) ? u0 : u1, 8);
                        z += __shfl_xor_sync(~0u, z, 16);
                        if (g < 4) atomicAdd(s_mean + 16 * i + 8 * (g & 1) + 2 * q + (g >> 1), z);
                    } else {
                        float* o = p.out + (uint32_t)((128 * c + 32 * q + 4 * i) * 512 + 64 * own + m0);
                        o[0] = a.x; o[512] = a.y; o[8] = a.z; o[512 + 8] = a.w;
                        o[1024] = bq.x; o[1536] = bq.y; o[1024 + 8] = bq.z; o[1536 + 8] = bq.w;
                    }
                }
            }
            if (wg < 2) mbar_wait_cluster(BAR(B_HDONE), layer);
            if (layer == 0) {
                fence_async_smem();
                bar_sync(9, 384);
                TS(14 + 12 * layer);
                if (wg == 2) {
                    atomicAdd(g_ssq + 2048 + 128 * c + t, s_mean[t] * (2.f / 512.f));
                    bar_sync(3, 128);
                    if (lane == 0) { mbar_arrive(BAR(B_AEMPTY + 6), 2); mbar_arrive(BAR(B_AEMPTY + 7), 2); }
                    if (t == 0) { fence_async(); red_release(&g_bar[2], 1); }
                }
            }
        }
        TS(15 + 12 * layer);
        if (wg == 0) TC(31);
    }
}

typedef CUresult (*EncFn)(CUtensorMap*, CUtensorMapDataType, cuuint32_t, void*, const cuuint64_t*, const cuuint64_t*,
                          const cuuint32_t*, const cuuint32_t*, CUtensorMapInterleave, CUtensorMapSwizzle,
                          CUtensorMapL2promotion, CUtensorMapFloatOOBfill);

void launch_impl(void* const* d_in, void* d_out, int stop) {
    static EncFn enc = nullptr;
    if (!enc) {
        void* fn = nullptr;
        cudaDriverEntryPointQueryResult qr;
        cudaGetDriverEntryPoint("cuTensorMapEncodeTiled", &fn, cudaEnableDefault, &qr);
        enc = (EncFn)fn;
        cudaFuncSetAttribute(fused_kernel, cudaFuncAttributeMaxDynamicSharedMemorySize, SM_TOTAL);
    }
    CUtensorMap tx, tbr, tbi, tcr, tci, tcol;
    {
        void* gx = nullptr;
        cudaGetSymbolAddress(&gx, g_X);
        cuuint64_t gd[5] = {64, 16, 64, 16, 2};
        cuuint64_t gs[4] = {128, 2048, 128 * 1024, 2048 * 1024};
        cuuint32_t bx[5] = {32, 16, 1, 16, 1};
        cuuint32_t es[5] = {1, 1, 1, 1, 1};
        enc(&tcol, CU_TENSOR_MAP_DATA_TYPE_BFLOAT16, 5, gx, gd, gs, bx, es, CU_TENSOR_MAP_INTERLEAVE_NONE,
            CU_TENSOR_MAP_SWIZZLE_64B, CU_TENSOR_MAP_L2_PROMOTION_NONE, CU_TENSOR_MAP_FLOAT_OOB_FILL_NONE);
    }
    {
        cuuint64_t gd[5] = {512, 2, 4, 16, 16};
        cuuint64_t gs[4] = {1024, 32 * 1024, 2 * 1024, 128 * 1024};
        cuuint32_t bx[5] = {64, 2, 4, 8, 1};
        cuuint32_t es[5] = {1, 1, 1, 1, 1};
        enc(&tx, CU_TENSOR_MAP_DATA_TYPE_BFLOAT16, 5, d_in[0], gd, gs, bx, es, CU_TENSOR_MAP_INTERLEAVE_NONE,
            CU_TENSOR_MAP_SWIZZLE_128B, CU_TENSOR_MAP_L2_PROMOTION_L2_128B, CU_TENSOR_MAP_FLOAT_OOB_FILL_NONE);
    }
    auto mk2 = [&](CUtensorMap* m, void* ptr, cuuint32_t rows) {
        cuuint64_t gd[2] = {512, 512};
        cuuint64_t gs[1] = {1024};
        cuuint32_t bx[2] = {64, rows};
        cuuint32_t es[2] = {1, 1};
        enc(m, CU_TENSOR_MAP_DATA_TYPE_BFLOAT16, 2, ptr, gd, gs, bx, es, CU_TENSOR_MAP_INTERLEAVE_NONE,
            CU_TENSOR_MAP_SWIZZLE_128B, CU_TENSOR_MAP_L2_PROMOTION_L2_128B, CU_TENSOR_MAP_FLOAT_OOB_FILL_NONE);
    };
    mk2(&tbr, d_in[6], 32);
    mk2(&tbi, d_in[7], 32);
    mk2(&tcr, d_in[8], 64);
    mk2(&tci, d_in[9], 64);
    Params p;
    p.x0 = (const __nv_bfloat16*)d_in[0];
    p.w_r = (const __nv_bfloat16*)d_in[1];
    p.w_i = (const __nv_bfloat16*)d_in[2];
    p.lam_re = (const __nv_bfloat16*)d_in[4];
    p.lam_im = (const __nv_bfloat16*)d_in[5];
    p.log_dt = (const __nv_bfloat16*)d_in[10];
    p.dskip = (const __nv_bfloat16*)d_in[11];
    p.out = (float*)d_out;
    p.stop = stop;
    cudaLaunchConfig_t cfg = {};
    cfg.gridDim = dim3(NCTA); cfg.blockDim = dim3(NTHREADS); cfg.dynamicSmemBytes = SM_TOTAL; cfg.stream = cudaStreamPerThread;
    cudaLaunchAttribute at[1];
    at[0].id = cudaLaunchAttributeClusterDimension;
    at[0].val.clusterDim.x = 2; at[0].val.clusterDim.y = 1; at[0].val.clusterDim.z = 1;
    cfg.attrs = at; cfg.numAttrs = 1;
    cudaLaunchKernelEx(&cfg, fused_kernel, tx, tbr, tbi, tcr, tci, tcol, p);
}

}

extern "C" void kernel_launch(void* const* d_in, const int* in_sizes, int n_in, void* d_out, int out_size) {
    (void)in_sizes; (void)n_in; (void)out_size;
    launch_impl(d_in, d_out, 100);
}
```

```cpp
#include <cuda_runtime.h>
#include <cuda_bf16.h>
#include <cuda.h>
#include <stdint.h>

namespace {

constexpr int NCTA = 128;
constexpr int NTHREADS = 512;
constexpr int SM_A = 0;
constexpr int SM_X = 131072;
constexpr int SM_H = 196608;
constexpr int SM_HH = SM_X + 32768;
constexpr int SM_M = 229376;
constexpr int SM_TOTAL = 232448;
constexpr int SM_BAR = SM_M;
constexpr int SM_TGT = SM_M + 400;
constexpr int SM_LAM = SM_M + 424;
constexpr int SM_TAB = SM_M + 944;
constexpr int SM_RSTD = SM_M + 1920;
constexpr int SM_MEAN = SM_TAB;
constexpr int SM_T64 = SM_M + 2944;
constexpr int SM_B1ST = SM_H + 24576;
constexpr int SM_RAW = SM_X + 40960;
constexpr int SM_SSQ = SM_X + 57344;
constexpr int B_FULL0 = 0;
constexpr int B_EMPTY0 = 8;
constexpr int B_FULLC = 12;
constexpr int B_AFULL = 13;
constexpr int B_AEMPTY = 21;
constexpr int B_XFULL = 29;
constexpr int B_XEMPTY = 33;
constexpr int B_AFREE = 37;
constexpr int B_COL = 38;
constexpr int B_SSQ = 39;
constexpr int B_HPEER = 40;
constexpr int B_RFREE = 41;
constexpr int B_HDONE = 42;
constexpr int B_WRDY = 43;
constexpr int B_HPEER1 = 44;
constexpr int B_FULLB = 45;
constexpr int B_BFREE = 46;
constexpr int B_SETUP = 47;
constexpr int B_B1DONE = 48;
constexpr int B_WST = 49;
constexpr int NBARS = 50;

__device__ __align__(1024) uint8_t g_X[2 * 16 * 8 * 16384];
__device__ __align__(1024) uint8_t g_A1[8 * 8 * 16384];
__device__ __align__(1024) uint8_t g_A2[8 * 8 * 16384];
__device__ __align__(1024) uint8_t g_E[2 * 8 * 8 * 8192];
__device__ __align__(16) float g_ssq[2 * 2048];
__device__ __align__(16) float g_ssqc[2 * 16 * 2048];
__device__ __align__(16) float g_Dh[512];
__device__ __align__(16) uint4 g_Wfrag[128 * 4 * 256];
__device__ __align__(16) float4 g_Ebuf[2 * 16 * 512];
__device__ __align__(16) uint4 g_P[16 * 8 * 4 * 1024];
__device__ unsigned g_bar[8];
__device__ unsigned g_err;
#define TX(i)
#define TQ(i)
#define TS(i)
#define TC(i)

constexpr unsigned SPIN_LIMIT = 1u << 22;

__device__ __forceinline__ uint32_t s2u(const void* p) { return (uint32_t)__cvta_generic_to_shared(p); }
__device__ __forceinline__ void mbar_init(uint32_t a, uint32_t c) {
    asm volatile("mbarrier.init.shared::cta.b64 [%0], %1;" ::"r"(a), "r"(c) : "memory");
}
__device__ __forceinline__ void mbar_expect(uint32_t a, uint32_t bytes) {
    asm volatile("mbarrier.arrive.expect_tx.shared::cta.b64 _, [%0], %1;" ::"r"(a), "r"(bytes) : "memory");
}
__device__ __forceinline__ void mbar_arrive(uint32_t a, uint32_t cnt) {
    asm volatile("mbarrier.arrive.shared::cta.b64 _, [%0], %1;" ::"r"(a), "r"(cnt) : "memory");
}
__device__ __forceinline__ bool mbar_try(uint32_t a, uint32_t parity) {
    uint32_t ok;
    asm volatile("{\n.reg .pred p;\nmbarrier.try_wait.parity.shared::cta.b64 p, [%1], %2;\nselp.u32 %0, 1, 0, p;\n}"
                 : "=r"(ok) : "r"(a), "r"(parity) : "memory");
    return ok != 0;
}
__device__ __forceinline__ void mbar_wait(uint32_t a, uint32_t parity) {
    asm volatile("{\n.reg .pred p, q;\n.reg .u32 n;\nmov.u32 n, 0;\n"
                 "W_%=:\nmbarrier.try_wait.parity.shared::cta.b64 p, [%0], %1;\n@p bra D_%=;\n"
                 "add.u32 n, n, 1;\nsetp.lt.u32 q, n, 4194304;\n@q bra W_%=;\nD_%=:\n}" ::"r"(a), "r"(parity) : "memory");
}
__device__ __forceinline__ void bulk_g2s(uint32_t dst, const void* src, uint32_t bytes, uint32_t bar) {
    asm volatile("cp.async.bulk.shared::cluster.global.mbarrier::complete_tx::bytes [%0], [%1], %2, [%3];" ::"r"(dst),
                 "l"(src), "r"(bytes), "r"(bar) : "memory");
}
__device__ __forceinline__ void tma_2d(uint32_t dst, const CUtensorMap* m, int c0, int c1, uint32_t bar) {
    asm volatile("cp.async.bulk.tensor.2d.shared::cluster.global.mbarrier::complete_tx::bytes [%0], [%1, {%3,%4}], [%2];" ::"r"(dst),
                 "l"(m), "r"(bar), "r"(c0), "r"(c1) : "memory");
}
__device__ __forceinline__ void tma_5d(uint32_t dst, const CUtensorMap* m, int c0, int c1, int c2, int c3, int c4, uint32_t bar) {
    asm volatile("cp.async.bulk.tensor.5d.shared::cluster.global.mbarrier::complete_tx::bytes [%0], [%1, {%3,%4,%5,%6,%7}], [%2];" ::"r"(dst),
                 "l"(m), "r"(bar), "r"(c0), "r"(c1), "r"(c2), "r"(c3), "r"(c4) : "memory");
}
__device__ __forceinline__ void tma_2d_mc(uint32_t dst, const CUtensorMap* m, int c0, int c1, uint32_t bar) {
    asm volatile("cp.async.bulk.tensor.2d.shared::cluster.global.mbarrier::complete_tx::bytes.multicast::cluster [%0], [%1, {%3,%4}], [%2], %5;" ::"r"(dst),
                 "l"(m), "r"(bar), "r"(c0), "r"(c1), "h"((unsigned short)3) : "memory");
}
__device__ __forceinline__ void tma_5d_mc(uint32_t dst, const CUtensorMap* m, int c0, int c1, int c2, int c3, int c4, uint32_t bar) {
    asm volatile("cp.async.bulk.tensor.5d.shared::cluster.global.mbarrier::complete_tx::bytes.multicast::cluster [%0], [%1, {%3,%4,%5,%6,%7}], [%2], %8;" ::"r"(dst),
                 "l"(m), "r"(bar), "r"(c0), "r"(c1), "r"(c2), "r"(c3), "r"(c4), "h"((unsigned short)3) : "memory");
}
__device__ __forceinline__ void bulk_g2s_mc(uint32_t dst, const void* src, uint32_t bytes, uint32_t bar) {
    asm volatile("cp.async.bulk.shared::cluster.global.mbarrier::complete_tx::bytes.multicast::cluster [%0], [%1], %2, [%3], %4;" ::"r"(dst),
                 "l"(src), "r"(bytes), "r"(bar), "h"((unsigned short)3) : "memory");
}
__device__ __forceinline__ void tma_store_5d(const CUtensorMap* m, int c0, int c1, int c2, int c3, int c4, uint32_t src) {
    asm volatile("cp.async.bulk.tensor.5d.global.shared::cta.bulk_group [%0, {%2,%3,%4,%5,%6}], [%1];" ::"l"(m), "r"(src),
                 "r"(c0), "r"(c1), "r"(c2), "r"(c3), "r"(c4) : "memory");
}
__device__ __forceinline__ uint32_t lds32(uint32_t a) { uint32_t v; asm volatile("ld.shared.u32 %0, [%1];" : "=r"(v) : "r"(a) : "memory"); return v; }
__device__ __forceinline__ uint4 ld_relaxed_u4(const uint4* p) {
    uint4 v;
    asm volatile("ld.relaxed.gpu.global.v4.u32 {%0,%1,%2,%3}, [%4];" : "=r"(v.x), "=r"(v.y), "=r"(v.z), "=r"(v.w) : "l"(p) : "memory");
    return v;
}
__device__ __forceinline__ void fence_async() { asm volatile("fence.proxy.async.global;" ::: "memory"); }
__device__ __forceinline__ void red_relaxed(unsigned* p, unsigned v) {
    asm volatile("red.relaxed.gpu.global.add.u32 [%0], %1;" ::"l"(p), "r"(v) : "memory");
}
__device__ __forceinline__ uint32_t mapa(uint32_t a, uint32_t rank) {
    uint32_t d;
    asm("mapa.shared::cluster.u32 %0, %1, %2;" : "=r"(d) : "r"(a), "r"(rank));
    return d;
}
__device__ __forceinline__ void mbar_arrive_remote(uint32_t ra) {
    asm volatile("mbarrier.arrive.relaxed.cluster.shared::cluster.b64 _, [%0];" ::"r"(ra) : "memory");
}
__device__ __forceinline__ void mbar_wait_cluster(uint32_t a, uint32_t parity) {
    asm volatile("{\n.reg .pred p, q;\n.reg .u32 n;\nmov.u32 n, 0;\n"
                 "W_%=:\nmbarrier.try_wait.parity.acquire.cluster.shared::cta.b64 p, [%0], %1;\n@p bra D_%=;\n"
                 "add.u32 n, n, 1;\nsetp.lt.u32 q, n, 4194304;\n@q bra W_%=;\nD_%=:\n}" ::"r"(a), "r"(parity) : "memory");
}
__device__ __forceinline__ void bulk_s2peer(uint32_t rdst, uint32_t src, uint32_t bytes, uint32_t rbar) {
    asm volatile("cp.async.bulk.shared::cluster.shared::cta.mbarrier::complete_tx::bytes [%0], [%1], %2, [%3];" ::"r"(rdst),
                 "r"(src), "r"(bytes), "r"(rbar) : "memory");
}
__device__ __forceinline__ void fence_async_smem() { asm volatile("fence.proxy.async.shared::cta;" ::: "memory"); }
__device__ __forceinline__ void wg_fence() { asm volatile("wgmma.fence.sync.aligned;" ::: "memory"); }
__device__ __forceinline__ void wg_commit() { asm volatile("wgmma.commit_group.sync.aligned;" ::: "memory"); }
template <int N> __device__ __forceinline__ void wg_wait() { asm volatile("wgmma.wait_group.sync.aligned %0;" ::"n"(N) : "memory"); }
__device__ __forceinline__ void bar_sync(int id, int n) { asm volatile("bar.sync %0, %1;" ::"r"(id), "r"(n) : "memory"); }
__device__ __forceinline__ void bar_arrive(int id, int n) { asm volatile("bar.arrive %0, %1;" ::"r"(id), "r"(n) : "memory"); }
__device__ __forceinline__ unsigned ld_acquire(const unsigned* p) {
    unsigned v;
    asm volatile("ld.acquire.gpu.global.u32 %0, [%1];" : "=r"(v) : "l"(p) : "memory");
    return v;
}
__device__ __forceinline__ void red_release(unsigned* p, unsigned v) {
    asm volatile("red.release.gpu.global.add.u32 [%0], %1;" ::"l"(p), "r"(v) : "memory");
}
__device__ __forceinline__ void wait_count(const unsigned* p, unsigned target) {
    unsigned n = 0;
#pragma unroll 1
    while ((int)(ld_acquire(p) - target) < 0 && ++n < SPIN_LIMIT) {}
}
__device__ __forceinline__ float4 ld_relaxed_f4(const float4* p) {
    float4 v;
    asm volatile("ld.relaxed.gpu.global.v4.f32 {%0,%1,%2,%3}, [%4];" : "=f"(v.x), "=f"(v.y), "=f"(v.z), "=f"(v.w) : "l"(p) : "memory");
    return v;
}
__device__ __forceinline__ void st_relaxed_f4(float4* p, float4 v) {
    asm volatile("st.relaxed.gpu.global.v4.f32 [%0], {%1,%2,%3,%4};" ::"l"(p), "f"(v.x), "f"(v.y), "f"(v.z), "f"(v.w) : "memory");
}
__device__ __forceinline__ uint32_t pack_bf16(float lo, float hi) {
    uint32_t r;
    asm("cvt.rn.bf16x2.f32 %0, %1, %2;" : "=r"(r) : "f"(hi), "f"(lo));
    return r;
}
__device__ __forceinline__ uint32_t hmul2(uint32_t a, uint32_t b) {
    uint32_t r;
    asm("mul.rn.bf16x2 %0, %1, %2;" : "=r"(r) : "r"(a), "r"(b));
    return r;
}
__device__ __forceinline__ uint32_t hfma2(uint32_t a, uint32_t b, uint32_t c) {
    uint32_t r;
    asm("fma.rn.bf16x2 %0, %1, %2, %3;" : "=r"(r) : "r"(a), "r"(b), "r"(c));
    return r;
}
__device__ __forceinline__ float bf_lo(uint32_t v) { return __uint_as_float(v << 16); }
__device__ __forceinline__ float bf_hi(uint32_t v) { return __uint_as_float(v & 0xffff0000u); }
__device__ __forceinline__ void sts32(uint32_t a, uint32_t v) { asm volatile("st.shared.u32 [%0], %1;" ::"r"(a), "r"(v) : "memory"); }
__device__ __forceinline__ void sts128(uint32_t a, uint4 v) {
    asm volatile("st.shared.v4.u32 [%0], {%1,%2,%3,%4};" ::"r"(a), "r"(v.x), "r"(v.y), "r"(v.z), "r"(v.w) : "memory");
}

__device__ __forceinline__ uint64_t desc_ni(uint32_t addr, uint32_t lbo, uint32_t sbo) {
    return (uint64_t)((addr & 0x3FFFF) >> 4) | ((uint64_t)(lbo >> 4) << 16) | ((uint64_t)(sbo >> 4) << 32);
}
__device__ __forceinline__ uint64_t desc_a(uint32_t addr) { return desc_ni(addr, 128, 1024); }
template <int N> __device__ __forceinline__ uint64_t desc_b(uint32_t addr) { return desc_ni(addr, 16 * N, 128); }
__device__ __forceinline__ uint64_t desc_k(uint32_t addr) {
    return (uint64_t)((addr & 0x3FFFF) >> 4) | (1ull << 16) | (64ull << 32) | (1ull << 62);
}
__device__ __forceinline__ uint64_t desc_mn(uint32_t addr, uint32_t lbo) {
    return (uint64_t)((addr & 0x3FFFF) >> 4) | ((uint64_t)(lbo >> 4) << 16) | (64ull << 32) | (1ull << 62);
}

#define ACC8(d, o) "+f"(d[o + 0]), "+f"(d[o + 1]), "+f"(d[o + 2]), "+f"(d[o + 3]), "+f"(d[o + 4]), "+f"(d[o + 5]), "+f"(d[o + 6]), "+f"(d[o + 7])
template <int TB, int SA = 1>
__device__ __forceinline__ void wgmma_n128(float (&d)[64], uint64_t da, uint64_t db, int sd) {
    asm volatile(
        "{\n.reg .pred p;\nsetp.ne.b32 p, %66, 0;\n"
        "wgmma.mma_async.sync.aligned.m64n128k16.f32.bf16.bf16 "
        "{%0,%1,%2,%3,%4,%5,%6,%7,%8,%9,%10,%11,%12,%13,%14,%15,%16,%17,%18,%19,%20,%21,%22,%23,%24,%25,%26,%27,%28,%29,%30,%31,"
        "%32,%33,%34,%35,%36,%37,%38,%39,%40,%41,%42,%43,%44,%45,%46,%47,%48,%49,%50,%51,%52,%53,%54,%55,%56,%57,%58,%59,%60,%61,%62,%63},"
        " %64, %65, p, %68, 1, 0, %67;\n}"
        : ACC8(d, 0), ACC8(d, 8), ACC8(d, 16), ACC8(d, 24), ACC8(d, 32), ACC8(d, 40), ACC8(d, 48), ACC8(d, 56)
        : "l"(da), "l"(db), "r"(sd), "n"(TB), "n"(SA));
}
template <int N> __device__ __forceinline__ void acc_def(float (&d)[N]) {
#pragma unroll
    for (int i = 0; i < N; i++) d[i] = 0.f;
}
template <int TB>
__device__ __forceinline__ void wgmma_n64(float (&d)[32], uint64_t da, uint64_t db, int sd) {
    asm volatile(
        "{\n.reg .pred p;\nsetp.ne.b32 p, %34, 0;\n"
        "wgmma.mma_async.sync.aligned.m64n64k16.f32.bf16.bf16 "
        "{%0,%1,%2,%3,%4,%5,%6,%7,%8,%9,%10,%11,%12,%13,%14,%15,%16,%17,%18,%19,%20,%21,%22,%23,%24,%25,%26,%27,%28,%29,%30,%31},"
        " %32, %33, p, 1, 1, 0, %35;\n}"
        : ACC8(d, 0), ACC8(d, 8), ACC8(d, 16), ACC8(d, 24)
        : "l"(da), "l"(db), "r"(sd), "n"(TB));
}
template <int SA>
__device__ __forceinline__ void wgmma_n64s(float (&d)[32], uint64_t da, uint64_t db, int sd) {
    asm volatile(
        "{\n.reg .pred p;\nsetp.ne.b32 p, %34, 0;\n"
        "wgmma.mma_async.sync.aligned.m64n64k16.f32.bf16.bf16 "
        "{%0,%1,%2,%3,%4,%5,%6,%7,%8,%9,%10,%11,%12,%13,%14,%15,%16,%17,%18,%19,%20,%21,%22,%23,%24,%25,%26,%27,%28,%29,%30,%31},"
        " %32, %33, p, %35, 1, 0, 1;\n}"
        : ACC8(d, 0), ACC8(d, 8), ACC8(d, 16), ACC8(d, 24)
        : "l"(da), "l"(db), "r"(sd), "n"(SA));
}
__device__ __forceinline__ void wgmma_n64_rs(float (&d)[32], uint32_t a0, uint32_t a1, uint32_t a2, uint32_t a3, uint64_t db, int sd) {
    asm volatile(
        "{\n.reg .pred p;\nsetp.ne.b32 p, %37, 0;\n"
        "wgmma.mma_async.sync.aligned.m64n64k16.f32.bf16.bf16 "
        "{%0,%1,%2,%3,%4,%5,%6,%7,%8,%9,%10,%11,%12,%13,%14,%15,%16,%17,%18,%19,%20,%21,%22,%23,%24,%25,%26,%27,%28,%29,%30,%31},"
        " {%32,%33,%34,%35}, %36, p, 1, 1, 1;\n}"
        : ACC8(d, 0), ACC8(d, 8), ACC8(d, 16), ACC8(d, 24)
        : "r"(a0), "r"(a1), "r"(a2), "r"(a3), "l"(db), "r"(sd));
}

struct Params {
    const __nv_bfloat16* x0;
    const __nv_bfloat16* w_r;
    const __nv_bfloat16* w_i;
    const __nv_bfloat16* lam_re;
    const __nv_bfloat16* lam_im;
    const __nv_bfloat16* log_dt;
    const __nv_bfloat16* dskip;
    float* out;
    int stop;
};

__device__ __forceinline__ float ldbf(const __nv_bfloat16* p) { return __bfloat162float(*p); }

__device__ __forceinline__ void dft_fp(int j, int& f, int& ph) {
    int cs = j >> 1;
    if (j == 1) { f = 256; ph = 0; }
    else { f = cs; ph = (j & 1) ? 128 : 0; }
}

__device__ __forceinline__ void gen_col_consts(uint32_t sb, int tid) {
#pragma unroll 1
    for (int task = tid; task < 640; task += 256) {
        int f, c8;
        uint32_t a_cc, d_pi, d_po;
        if (task < 512) {
            f = task & 63; c8 = task >> 6;
            a_cc = sb + SM_X + (f >> 5) * 16384 + ((f >> 3) & 3) * 2048 + c8 * 128 + (f & 7) * 16;
            d_pi = 8192; d_po = 1024;
        } else {
            int n2 = task & 31;
            f = 2 * n2; c8 = (task >> 5) & 3;
            a_cc = sb + SM_X + 32768 + (n2 >> 3) * 1024 + c8 * 128 + (n2 & 7) * 16;
            d_pi = 4096; d_po = 512;
        }
        float cd, sd, cs, sn;
        __sincosf((float)(f >= 32 ? f - 64 : f) * (6.283185307179586f / 64.f), &sd, &cd);
        int a = (8 * c8 * f) & 63;
        __sincosf((float)(a >= 32 ? a - 64 : a) * (6.283185307179586f / 64.f), &sn, &cs);
        float cv[8], sv[8];
#pragma unroll
        for (int e = 0; e < 8; e++) {
            cv[e] = cs; sv[e] = sn;
            float t = cs * cd - sn * sd;
            sn = sn * cd + cs * sd;
            cs = t;
        }
        uint4 oc = make_uint4(pack_bf16(cv[0], cv[1]), pack_bf16(cv[2], cv[3]), pack_bf16(cv[4], cv[5]), pack_bf16(cv[6], cv[7]));
        uint4 os = make_uint4(pack_bf16(sv[0], sv[1]), pack_bf16(sv[2], sv[3]), pack_bf16(sv[4], sv[5]), pack_bf16(sv[6], sv[7]));
        sts128(a_cc, oc);
        sts128(a_cc + d_pi, os);
        sts128(a_cc + d_po, make_uint4(os.x ^ 0x80008000u, os.y ^ 0x80008000u, os.z ^ 0x80008000u, os.w ^ 0x80008000u));
        sts128(a_cc + d_pi + d_po, oc);
    }
}

__global__ void __launch_bounds__(NTHREADS, 1)
fused_kernel(const __grid_constant__ CUtensorMap tm_x, const __grid_constant__ CUtensorMap tm_bre,
             const __grid_constant__ CUtensorMap tm_bim, const __grid_constant__ CUtensorMap tm_cre,
             const __grid_constant__ CUtensorMap tm_cim, const __grid_constant__ CUtensorMap tm_col, const Params p) {
    extern __shared__ __align__(1024) uint8_t sm[];
    const uint32_t sb = s2u(sm);
    const int tid = threadIdx.x, b = blockIdx.x;
    const int c = b >> 3, r = b & 7;
    const int par = r & 1, pi_ = r >> 1, own = 4 * par + pi_;
    const int wg = __shfl_sync(~0u, tid >> 7, 0), w = __shfl_sync(~0u, (tid >> 5) & 3, 0), lane = tid & 31, g = lane >> 2, q = lane & 3;
    auto BAR = [&](int i) { return sb + SM_BAR + 8 * i; };
    unsigned* s_tgt = (unsigned*)(sm + SM_TGT);

    if (tid < NBARS) {
        int cnt = 1;
        if (tid >= B_EMPTY0 && tid < B_EMPTY0 + 4) cnt = 16;
        if (tid >= B_XEMPTY && tid < B_XEMPTY + 4) cnt = 24;
        if (tid == B_RFREE) cnt = 12;
        if (tid == B_HDONE || tid == B_WST) cnt = 2;
        if ((tid >= B_AEMPTY && tid < B_AEMPTY + 8) || tid == B_BFREE) cnt = 8;
        if (tid == B_AFREE) cnt = 4;
        mbar_init(BAR(tid), cnt);
        asm volatile("fence.mbarrier_init.release.cluster;" ::: "memory");
    }
    asm volatile("barrier.cluster.arrive.release.aligned;" ::: "memory");

    if (wg == 3) {
        asm volatile("setmaxnreg.dec.sync.aligned.u32 56;");
        if (w == 0 && lane < 6) {
            const CUtensorMap* tm = lane == 0 ? &tm_x : lane == 1 ? &tm_bre : lane == 2 ? &tm_bim : lane == 3 ? &tm_cre : lane == 4 ? &tm_cim : &tm_col;
            asm volatile("prefetch.tensormap [%0];" ::"l"(tm) : "memory");
        }
        __syncwarp();
        asm volatile("barrier.cluster.wait.acquire.aligned;" ::: "memory");
        if (w > 0) {
            if (w == 1) {
                float lr[3], li[3], ld[3];
#pragma unroll
                for (int k = 0; k < 3; k++) {
                    int ps = k < 2 ? 64 * r + 32 * k + lane : 32 * c + lane;
                    lr[k] = ldbf(p.lam_re + ps); li[k] = ldbf(p.lam_im + ps); ld[k] = ldbf(p.log_dt + ps);
                }
                if (lane < 6) s_tgt[lane] = ((ld_acquire(&g_bar[lane]) >> 7) + 1u) << 7;
#pragma unroll 1
                for (int k = 0; k < 3; k++) {
                    float a = k == 0 ? lr[0] : (k == 1 ? lr[1] : lr[2]), bq = k == 0 ? li[0] : (k == 1 ? li[1] : li[2]);
                    float dt = __bfloat162float(__float2bfloat16(expf(k == 0 ? ld[0] : (k == 1 ? ld[1] : ld[2]))));
                    float mag = expf(a * dt), t = bq * dt * 0.15915494309189535f, sn, cs;
                    t -= rintf(t);
                    sincospif(2.f * t, &sn, &cs);
                    float er = mag * cs, ei = mag * sn;
                    if (k < 2) {
                        *(float2*)(sm + SM_LAM + (32 * k + lane) * 8) = make_float2(er, ei);
                    } else {
                        er -= 1.f;
                        float inv = 1.f / (a * a + bq * bq);
                        *(float2*)(sm + SM_TAB + lane * 8) = make_float2((er * a + ei * bq) * inv, (ei * a - er * bq) * inv);
                    }
                }
                __syncwarp();
                bar_arrive(15, 160);
                if (lane == 0) mbar_arrive(BAR(B_SETUP), 1);
            }
            if (w == 2 && lane < 2) {
                const char* src = (const char*)(lane ? p.w_i : p.w_r) + (size_t)b * 8224;
                asm volatile("cp.async.bulk.prefetch.L2.global [%0], 8224;" ::"l"(src) : "memory");
            }
#pragma unroll 1
            for (int i = tid - 448; i < 96 + 128 && w > 1; i += 64) {
                if (i < 96) g_P[(uint32_t)(b * 4 + i / 24) * 1024 + 640 + ((i % 24) >> 1) * 32 + 30 + (i & 1)] = make_uint4(0, 0, 0, 0);
                else g_Ebuf[b * 128 + i - 96] = make_float4(0.f, 0.f, 0.f, 0.f);
            }
            __syncwarp();
            if (w > 1) bar_sync(0, 192);
            if (tid == 448) TX(14);
            if (w > 1) {
                if (lane < 8) {
                    const int cl = 8 * (w - 2) + lane;
                    asm volatile("cp.async.bulk.global.shared::cta.bulk_group [%0], [%1], 1024;" ::"l"(g_Wfrag + (uint32_t)((16 * (b & 7) + cl) * 1024 + (b >> 3) * 64)),
                                 "r"(sb + SM_H + cl * 1024) : "memory");
                }
                asm volatile("cp.async.bulk.commit_group;" ::: "memory");
                asm volatile("cp.async.bulk.wait_group 0;" ::: "memory");
                fence_async();
                __syncwarp();
                if (lane == 0) mbar_arrive(BAR(B_WST), 1);
                if (tid == 448) TX(15);
            }
            __syncwarp();
            if (w == 3) bar_arrive(11, 192);
            if (w == 2) {
                bar_sync(11, 192);
                if (lane == 0) { TX(7); red_release(&g_bar[4], 1);  }
            }
            if (w == 3) {
#pragma unroll 1
                for (int it = 0; it < 8; it++) {
                    const int m = 4 * c + (it >> 1), d = 64 * r + m, ch = lane + 32 * (it & 1);
                    float v[8];
#pragma unroll
                    for (int e = 0; e < 8; e++) {
                        int j = 8 * ch + e, f, ph;
                        dft_fp(j, f, ph);
                        int a = (d * f + ph) & 511;
                        a = a >= 256 ? a - 512 : a;
                        float wj = j == 0 ? 0.f : (j == 1 ? 1.f / 512.f : 2.f / 512.f);
                        v[e] = wj * __cosf((float)a * (6.283185307179586f / 512.f));
                    }
                    uint32_t off = (uint32_t)(64 + r * 8 + (ch >> 3)) * 8192 + (m >> 3) * 1024 + (ch & 7) * 128 + (m & 7) * 16;
                    *(uint4*)(g_E + off) = make_uint4(pack_bf16(v[0], v[1]), pack_bf16(v[2], v[3]), pack_bf16(v[4], v[5]), pack_bf16(v[6], v[7]));
                }
                __syncwarp();
                if (lane == 0) { fence_async(); red_release(&g_bar[6], 1); }
                return;
            }
            if (w == 2) {
#pragma unroll 1
                for (int it = 0; it < 4; it++) {
                    const int hf = it & 1;
                    __syncwarp();
                    if (hf == 0) bar_sync(13, 288); else bar_sync(6, 416);
                    if (lane == 0) {
                        const uint32_t src = sb + SM_HH + par * 32768 + hf * 16384;
                        bulk_s2peer(mapa(src, par ^ 1), src, 16384, mapa(BAR(hf ? B_HPEER1 : B_HPEER), par ^ 1));
                    }
                }
                return;
            }
            bar_sync(2, 288);
            if (lane == 0) {
                TX(5);
                fence_async();
                red_release(&g_bar[0], 1);
                TX(6);
            }
            __syncwarp();

            bar_sync(12, 160);
            if (lane == 0) {
                asm volatile("cp.async.bulk.global.shared::cta.bulk_group [%0], [%1], 8192;" ::"l"(g_A1 + (uint32_t)(((c >> 1) * 8 + r) * 16384 + (c & 1) * 8192)),
                             "r"(sb + SM_B1ST) : "memory");
                asm volatile("cp.async.bulk.commit_group;" ::: "memory");
                asm volatile("cp.async.bulk.wait_group 0;" ::: "memory");
                mbar_arrive(BAR(B_B1DONE), 1);
                fence_async();
                red_release(&g_bar[7], 1);
            }
#pragma unroll 1
            for (int layer = 0; layer < 2; layer++) {
                __syncwarp();
                bar_sync(5, 416);
                if (lane == 0) {
                    TX(0 + 8 * layer);
                    tma_store_5d(&tm_col, 32 * (b & 1), 0, b >> 1, 0, layer, sb + SM_RAW);
                    asm volatile("cp.reduce.async.bulk.global.shared::cta.bulk_group.add.f32 [%0], [%1], 8192;" ::"l"(g_ssqc + (layer * 16 + (b & 15)) * 2048),
                                 "r"(sb + SM_SSQ) : "memory");
                    asm volatile("cp.async.bulk.commit_group;" ::: "memory");
                    asm volatile("cp.async.bulk.wait_group 0;" ::: "memory");
                    TX(1 + 8 * layer);
                    fence_async();
                    red_release(&g_bar[1 + 2 * layer], 1);
                    TX(2 + 8 * layer);
                }
            }
        } else if (tid == 384) {
#pragma unroll 1
            for (int kb = 0; kb < 8; kb++) {
                uint32_t fb = BAR(B_FULL0 + kb);
                mbar_expect(fb, 16384);
                tma_5d_mc(sb + SM_A + 65536 + kb * 16384 + par * 8192, &tm_x, kb * 64, 0, 0, 8 * par, c, fb);
            }
#pragma unroll 1
            for (int k2 = 0; k2 < 8; k2++) {
                asm volatile("cp.async.bulk.prefetch.tensor.2d.L2.global [%0, {%1,%2}];" ::"l"(par ? &tm_bim : &tm_bre), "r"(k2 * 64), "r"(32 * c) : "memory");
                if ((k2 & 1) == par)
                    asm volatile("cp.async.bulk.prefetch.tensor.2d.L2.global [%0, {%1,%2}];" ::"l"((c & 1) ? &tm_cim : &tm_cre), "r"(64 * (c >> 1)), "r"(k2 * 64) : "memory");
            }
            mbar_wait(BAR(B_SETUP), 0);
#pragma unroll 1
            for (int layer = 0; layer < 2; layer++) {
                if (layer == 1) {
                    mbar_wait(BAR(B_AEMPTY + 6), 1);
                    mbar_expect(BAR(B_WRDY), 16384);
                    bulk_g2s(sb + SM_H + 16384, g_Wfrag + (uint32_t)b * 1024, 16384, BAR(B_WRDY));
                }
                wait_count(&g_bar[2 * layer], s_tgt[2 * layer]);
                TX(4 + 8 * layer);
                fence_async();
                mbar_expect(BAR(B_COL), 16384 + 8192);
                tma_5d(sb + SM_RAW, &tm_col, 32 * (b & 1), 0, b >> 1, 0, layer, BAR(B_COL));
                bulk_g2s(sb + SM_SSQ, g_ssq + layer * 2048, 8192, BAR(B_COL));
                if (layer == 0) {
                    wait_count(&g_bar[4], s_tgt[4]);
                    fence_async();
                    TX(16);
                    mbar_wait(BAR(B_B1DONE), 0);
                    TX(17);
                    mbar_expect(BAR(B_WRDY), 16384);
                    bulk_g2s(sb + SM_H + 16384, g_Wfrag + (uint32_t)b * 1024, 16384, BAR(B_WRDY));
                    wait_count(&g_bar[7], s_tgt[4]);
                    fence_async();
                }
                if (layer == 0) mbar_wait(BAR(B_AFREE), 0);
                mbar_wait(BAR(B_COL), layer);
#pragma unroll 1
                for (int s = 0; s < 8; s++) {
                    if (layer == 1) mbar_wait(BAR(B_AEMPTY + s), 1);
                    if (s >= 2) mbar_wait(BAR(B_AFULL + s - 2), 0);
                    mbar_expect(BAR(B_AFULL + s), 16384);
                    bulk_g2s(sb + SM_A + s * 16384, g_A1 + (uint32_t)(r * 8 + s) * 16384, 16384, BAR(B_AFULL + s));
                }
                if (layer == 1) wait_count(&g_bar[6], s_tgt[4]);
                wait_count(&g_bar[1 + 2 * layer], s_tgt[1 + 2 * layer]);
                TX(3 + 8 * layer);
                fence_async();
                const uint8_t* xsrc = g_X + (uint32_t)(layer * 16 + c) * 8 * 16384;
                const uint8_t* esrc = g_E + (uint32_t)(layer * 8 + own) * 8 * 8192;
                mbar_arrive(BAR(B_SSQ), 1);
                mbar_expect(BAR(B_HPEER), 16384);
                mbar_expect(BAR(B_HPEER1), 16384);
#pragma unroll 1
                for (int it = 0; it < 16; it++) {
                    if (it < 8) {
                        int st = it & 3, f = layer * 2 + (it >> 2);
                        if (f > 0) mbar_wait_cluster(BAR(B_XEMPTY + st), (f - 1) & 1);
                        mbar_expect(BAR(B_XFULL + st), 24576);
                        bulk_g2s_mc(sb + SM_X + st * 24576 + par * 8192, xsrc + (uint32_t)it * 16384 + par * 8192, 8192, BAR(B_XFULL + st));
                        bulk_g2s(sb + SM_X + st * 24576 + 16384, esrc + (uint32_t)it * 8192, 8192, BAR(B_XFULL + st));
                    }
                    if (it >= 8) {
                        if (it == 8) mbar_wait(BAR(B_AEMPTY + 5), 0);
                        int s = it - 8, tile = 4 * par + ((pi_ + 1 + (s >> 1)) & 3), sl = r ^ (s & 1);
                        mbar_wait(BAR(B_AEMPTY + s), 0);
                        uint32_t fb = BAR(B_AFULL + s), dst = sb + SM_A + s * 16384;
                        mbar_expect(fb, 16384);
                        if (layer == 1) {
                            tma_2d(dst, &tm_cre, 64 * sl, 64 * tile, fb);
                            tma_2d(dst + 8192, &tm_cim, 64 * sl, 64 * tile, fb);
                        } else {
                            bulk_g2s(dst, g_A2 + (uint32_t)(sl * 8 + tile) * 16384, 16384, fb);
                        }
                    }
                }
            }
        }
        return;
    }

    asm volatile("setmaxnreg.inc.sync.aligned.u32 152;");
    if (tid >= 96 && tid < 112) g_ssq[2048 + 16 * b + tid - 96] = 0.f;
    if (tid >= 128 && tid < 256) ((float4*)g_ssqc)[b * 128 + tid - 128] = make_float4(0.f, 0.f, 0.f, 0.f);
    TS(0);
    if (wg == 0) TC(30);
    {
        const int f = 32 * r + lane;
        float cd, sd;
        __sincosf((float)f * (6.283185307179586f / 512.f), &sd, &cd);
        const uint32_t dst = sb + SM_A + (lane >> 2) * 1024 + (lane & 3) * 32;
#pragma unroll 1
        for (int ch = tid >> 5; ch < 64; ch += 12) {
            int a = (8 * ch * f) & 511;
            a = a >= 256 ? a - 512 : a;
            float cs, sn;
            __sincosf((float)a * (6.283185307179586f / 512.f), &sn, &cs);
            float cv[8], sv[8];
#pragma unroll
            for (int e = 0; e < 8; e++) {
                cv[e] = cs; sv[e] = -sn;
                float t = cs * cd - sn * sd;
                sn = sn * cd + cs * sd;
                cs = t;
            }
            uint4 o1 = make_uint4(pack_bf16(sv[0], sv[1]), pack_bf16(sv[2], sv[3]), pack_bf16(sv[4], sv[5]), pack_bf16(sv[6], sv[7]));
            if (f == 0) o1 = make_uint4(0xbf803f80u, 0xbf803f80u, 0xbf803f80u, 0xbf803f80u);
            uint32_t a0 = dst + (ch >> 3) * 8192 + (ch & 7) * 128;
            sts128(a0, make_uint4(pack_bf16(cv[0], cv[1]), pack_bf16(cv[2], cv[3]), pack_bf16(cv[4], cv[5]), pack_bf16(cv[6], cv[7])));
            sts128(a0 + 16, o1);
        }
    }
    fence_async_smem();
    asm volatile("barrier.cluster.wait.acquire.aligned;" ::: "memory");
    bar_sync(10, 384);
    TS(1);
    if (wg < 2) {
        float acc[32];
        acc_def(acc);
        const int npos = 16 * r + 8 * wg + 2 * w;
        float sh0 = 0.f, sh1 = 0.f, s0 = 0.f, s1 = 0.f, q0 = 0.f, q1 = 0.f;
#pragma unroll 1
        for (int kb = 0; kb < 8; kb++) {
            uint32_t slot = sb + SM_A + 65536 + kb * 16384;
            mbar_wait(BAR(B_FULL0 + kb), 0);
            wg_fence();
#pragma unroll
            for (int ks = 0; ks < 4; ks++)
                wgmma_n64<0>(acc, desc_a(sb + SM_A + kb * 8192 + ks * 256), desc_k(slot + wg * 8192 + ks * 32), 1);
            wg_commit();
            {
                uint32_t v0 = lds32(slot + npos * 128 + lane * 4), v1 = lds32(slot + npos * 128 + 128 + lane * 4);
                if (kb == 0) { sh0 = __shfl_sync(~0u, bf_lo(v0), 0); sh1 = __shfl_sync(~0u, bf_lo(v1), 0); }
                float a = bf_lo(v0) - sh0, bq = bf_hi(v0) - sh0, cq = bf_lo(v1) - sh1, d = bf_hi(v1) - sh1;
                s0 += a + bq; q0 += a * a + bq * bq; s1 += cq + d; q1 += cq * cq + d * d;
            }
            wg_wait<1>();
            if (kb > 0 && kb <= 4 && lane == 0) { mbar_arrive(BAR(B_EMPTY0 + kb - 1), 1); mbar_arrive_remote(mapa(BAR(B_EMPTY0 + kb - 1), par ^ 1)); }
        }
#pragma unroll
        for (int o = 16; o; o >>= 1) {
            s0 += __shfl_xor_sync(~0u, s0, o); q0 += __shfl_xor_sync(~0u, q0, o);
            s1 += __shfl_xor_sync(~0u, s1, o); q1 += __shfl_xor_sync(~0u, q1, o);
        }
        if (lane == 0) *(float2*)(g_ssq + 128 * c + npos) = make_float2(fmaxf(q0 - s0 * s0 * (1.f / 512.f), 0.f), fmaxf(q1 - s1 * s1 * (1.f / 512.f), 0.f));
        wg_wait<0>();
        TS(2);
        uint8_t* dst = g_X + (uint32_t)((c * 8 + r) * 16384 + w * 4096 + wg * 1024 + g * 16 + 4 * q);
#pragma unroll
        for (int i = 0; i < 8; i++) {
            *(uint32_t*)(dst + i * 128) = pack_bf16(acc[4 * i], acc[4 * i + 1]);
            *(uint32_t*)(dst + 2048 + i * 128) = pack_bf16(acc[4 * i + 2], acc[4 * i + 3]);
        }
        bar_sync(2, 288);
        mbar_wait(BAR(B_SETUP), 0);
        TS(3);
    }

    if (wg == 2) {
        {
            uint4 p0 = __ldg((const uint4*)p.dskip + 2 * lane), p1 = __ldg((const uint4*)p.dskip + 2 * lane + 1);
            uint32_t u[8] = {p0.x, p0.y, p0.z, p0.w, p1.x, p1.y, p1.z, p1.w};
            int j = 64 * r + 4 * c + w, f, ph;
            dft_fp(j, f, ph);
            float s = 0.f;
            int idx = 16 * lane * f + ph;
#pragma unroll
            for (int i = 0; i < 16; i++) {
                int a = idx & 511;
                idx += f;
                a = a >= 256 ? a - 512 : a;
                s += ((i & 1) ? bf_hi(u[i >> 1]) : bf_lo(u[i >> 1])) * __cosf((float)a * (6.283185307179586f / 512.f));
            }
#pragma unroll
            for (int o = 16; o; o >>= 1) s += __shfl_xor_sync(~0u, s, o);
            if (lane == 0) g_Dh[j] = s;
        }
        mbar_wait(BAR(B_FULL0 + 7), 0);
        if (tid == 256) {
#pragma unroll 1
            for (int s = 0; s < 4; s++) mbar_wait_cluster(BAR(B_EMPTY0 + s), 0);
            mbar_expect(BAR(B_FULLB), 65536);
#pragma unroll 1
            for (int k2 = 0; k2 < 8; k2++)
                tma_2d_mc(sb + SM_A + 65536 + k2 * 8192 + par * 4096, par ? &tm_bim : &tm_bre, k2 * 64, 32 * c, BAR(B_FULLB));
        }
        __syncwarp();
        {
            const int cl = tid & 15, cb = 16 * (b & 7) + cl;
            const int c0 = cb == 0 ? 256 : 2 * cb, c1 = 2 * cb + 1;
            uint32_t wf[2][16];
#pragma unroll
            for (int h = 0; h < 2; h++) {
                const int kq = 16 * (b >> 3) + ((tid & 127) >> 4) + 8 * h, k1 = kq >> 2, qq = kq & 3;
                const unsigned short* wr_ = (const unsigned short*)p.w_r + (k1 + 128 * qq) * 257;
                const unsigned short* wi_ = (const unsigned short*)p.w_i + (k1 + 128 * qq) * 257;
#pragma unroll
                for (int i = 0; i < 4; i++) {
                    int o = 512 * i * 257;
                    wf[h][2 * i] = (uint32_t)__ldg(wr_ + o + c0) | ((uint32_t)__ldg(wr_ + o + 64 * 257 + c0) << 16);
                    wf[h][2 * i + 1] = ((uint32_t)__ldg(wi_ + o + c0) | ((uint32_t)__ldg(wi_ + o + 64 * 257 + c0) << 16)) ^ 0x80008000u;
                    wf[h][8 + 2 * i] = (uint32_t)__ldg(wr_ + o + c1) | ((uint32_t)__ldg(wr_ + o + 64 * 257 + c1) << 16);
                    wf[h][8 + 2 * i + 1] = ((uint32_t)__ldg(wi_ + o + c1) | ((uint32_t)__ldg(wi_ + o + 64 * 257 + c1) << 16)) ^ 0x80008000u;
                }
            }
#pragma unroll
            for (int h = 0; h < 2; h++)
#pragma unroll
                for (int i = 0; i < 4; i++)
                    sts128(sb + SM_H + cl * 1024 + (((tid & 127) >> 4) + 8 * h) * 64 + ((i ^ ((tid >> 5) & 3)) << 4),
                           make_uint4(wf[h][4 * i], wf[h][4 * i + 1], wf[h][4 * i + 2], wf[h][4 * i + 3]));
            fence_async_smem();
            bar_arrive(0, 192);
            bar_arrive(11, 192);
        }
        bar_sync(15, 160);
        float acc[32];
        acc_def(acc);
        mbar_wait(BAR(B_FULLB), 0);
        wg_fence();
#pragma unroll 1
        for (int kb = 0; kb < 8; kb++) {
#pragma unroll
            for (int ks = 0; ks < 4; ks++)
                wgmma_n64<0>(acc, desc_a(sb + SM_A + kb * 8192 + ks * 256), desc_k(sb + SM_A + 65536 + kb * 8192 + ks * 32), 1);
            wg_commit();
        }
        wg_wait<0>();
        if (lane == 0) { mbar_arrive(BAR(B_BFREE), 1); mbar_arrive_remote(mapa(BAR(B_BFREE), par ^ 1)); }
        if (tid == 256) {
            mbar_wait_cluster(BAR(B_BFREE), 0);
            mbar_expect(BAR(B_FULLC), 65536);
#pragma unroll 1
            for (int k2 = par; k2 < 8; k2 += 2)
                tma_2d_mc(sb + SM_A + 65536 + k2 * 8192, (c & 1) ? &tm_cim : &tm_cre, 64 * (c >> 1), k2 * 64, BAR(B_FULLC));
        }
        __syncwarp();
        {
            uint8_t* dst = sm + SM_B1ST + w * 256 + q * 32 + g * 2;
            const float wj0 = (r == 0 && w == 0 && g < 2) ? (g == 0 ? 0.f : 1.f / 512.f) : 2.f / 512.f;
#pragma unroll
            for (int i = 0; i < 4; i++) {
#pragma unroll
                for (int e = 0; e < 2; e++) {
                    float2 cf = *(const float2*)(sm + SM_TAB + (8 * i + 2 * q + e) * 8);
#pragma unroll
                    for (int h = 0; h < 2; h++) {
                        float wj = h == 0 ? wj0 : 2.f / 512.f;
                        float pr = acc[4 * i + 2 * h + e] * wj, pi = acc[16 + 4 * i + 2 * h + e] * wj;
                        uint8_t* d2 = dst + i * 2048 + h * 128 + e * 16;
                        *(__nv_bfloat16*)(d2) = __float2bfloat16(cf.x * pr - cf.y * pi);
                        *(__nv_bfloat16*)(d2 + 1024) = __float2bfloat16(cf.x * pi + cf.y * pr);
                    }
                }
            }
            fence_async_smem();
            bar_arrive(12, 160);
        }
        acc_def(acc);
        mbar_wait(BAR(B_FULLC), 0);
        wg_fence();
#pragma unroll 1
        for (int kb = 0; kb < 8; kb++) {
#pragma unroll
            for (int ks = 0; ks < 4; ks++)
                wgmma_n64<1>(acc, desc_a(sb + SM_A + kb * 8192 + ks * 256), desc_mn(sb + SM_A + 65536 + kb * 8192 + ks * 2048, 8192), 1);
            wg_commit();
        }
        wg_wait<0>();
        fence_async_smem();
        if (lane == 0) mbar_arrive(BAR(B_AFREE), 1);
        uint8_t* dst = g_A2 + (uint32_t)(((c >> 1) * 8 + r) * 16384 + (c & 1) * 8192 + w * 2048 + g * 16 + 4 * q);
#pragma unroll
        for (int i = 0; i < 8; i++) {
            *(uint32_t*)(dst + i * 128) = pack_bf16(acc[4 * i], acc[4 * i + 1]);
            *(uint32_t*)(dst + 1024 + i * 128) = pack_bf16(acc[4 * i + 2], acc[4 * i + 3]);
        }
        {
            const int m = 4 * c + w, jp = 64 * r + m;
            int fp, php;
            dft_fp(jp, fp, php);
            const __nv_bfloat16* dh = (const __nv_bfloat16*)(sm + SM_RSTD);
            if (tid == 256) wait_count(&g_bar[4], s_tgt[4]);
            bar_sync(3, 128);
            float4 d4 = __ldcg((const float4*)g_Dh + (tid - 256));
            *(uint2*)(sm + SM_RSTD + (tid - 256) * 8) = make_uint2(pack_bf16(d4.x, d4.y), pack_bf16(d4.z, d4.w));
            bar_sync(3, 128);
#pragma unroll 1
            for (int it = 0; it < 2; it++) {
                const int ch = lane + 32 * it;
                float v[8];
#pragma unroll
                for (int e = 0; e < 8; e++) {
                    int j = 8 * ch + e, f, ph;
                    dft_fp(j, f, ph);
                    float wj = j == 0 ? 0.f : (j == 1 ? 1.f / 512.f : 2.f / 512.f);
                    float gsum = 0.f;
#pragma unroll
                    for (int sgn = 0; sgn < 2; sgn++) {
                        int mm = (sgn ? f - fp : f + fp) & 511, pp = (sgn ? ph - php : ph + php) & 511;
                        if (mm > 256) { mm = 512 - mm; pp = (512 - pp) & 511; }
                        int odd = (pp >> 7) & 1;
                        float t = __bfloat162float(dh[mm == 256 ? 1 : 2 * mm + odd]);
                        if (odd && (mm & 255) == 0) t = 0.f;
                        gsum += (pp & 256) ? -t : t;
                    }
                    v[e] = 0.5f * wj * gsum;
                }
                uint32_t off = (uint32_t)(r * 8 + (ch >> 3)) * 8192 + (m >> 3) * 1024 + (ch & 7) * 128 + (m & 7) * 16;
                *(uint4*)(g_E + off) = make_uint4(pack_bf16(v[0], v[1]), pack_bf16(v[2], v[3]), pack_bf16(v[4], v[5]), pack_bf16(v[6], v[7]));
            }
        }
    }

#pragma unroll 1
    for (int layer = 0; layer < 2; layer++) {
        if (wg < 2) {
            const int n1 = 32 * wg + 8 * w + g;
            const int ct = n1 >> 2;
            gen_col_consts(sb, tid);
            uint32_t tr2[4], ti2[4], tn2[4];
#pragma unroll
            for (int i = 0; i < 4; i++) {
                float cr[2], ci[2];
#pragma unroll
                for (int e = 0; e < 2; e++) {
                    int a = (n1 * (8 * i + 2 * q + e)) & 2047;
                    a = a >= 1024 ? a - 2048 : a;
                    float ang = (float)a * (-6.283185307179586f / 2048.f);
                    cr[e] = __cosf(ang); ci[e] = __sinf(ang);
                }
                tr2[i] = pack_bf16(cr[0], cr[1]); ti2[i] = pack_bf16(ci[0], ci[1]); tn2[i] = ti2[i] ^ 0x80008000u;
            }
            mbar_wait(BAR(B_WST), 0);
            mbar_wait(BAR(B_COL), layer);
            TS(4 + 12 * layer);
            if (wg == 0) TC(0 + 10 * layer);
            const uint32_t rw0 = sb + SM_RAW + ct * 1024 + q * 64 + ((q >> 1) << 4) + (g & 3) * 4, rw1 = rw0 ^ 16;
            const int pos0 = 128 * ct + 8 * q + 2 * (g & 3);
            const int sw = b == 0 ? 1 : 0;
            uint32_t xr[4][4];
            const uint32_t st0 = sb + SM_H + (n1 >> 3) * 1024 + g * 16 + 4 * q;
#pragma unroll
            for (int i = 0; i < 4; i++) {
                float2 sq = *(const float2*)(sm + SM_SSQ + (pos0 + 32 * i) * 4);
                const uint32_t rs2 = pack_bf16(rsqrtf(sq.x * (1.f / 512.f) + 1e-5f), rsqrtf(sq.y * (1.f / 512.f) + 1e-5f));
#pragma unroll
                for (int jj = 0; jj < 4; jj++) {
                    const int K = jj ^ (2 * (i & 1));
                    uint32_t a = ((K & 1) ? rw1 : rw0) + i * 256 + (K & 2) * 16;
                    if (jj < 2) a ^= sw << 4;
                    uint32_t v = lds32(a);
                    xr[jj][i] = v;
                    uint32_t o = hmul2(v, rs2);
                    if (jj == 1 && sw) o = 0u;
                    sts32(st0 + (jj & 1) * 8192 + (4 * (jj >> 1) + i) * 128, o);
                }
            }
            if (wg == 0) TC(1 + 10 * layer);
            fence_async_smem();
            bar_sync(1, 256);
            float acc[32];
            const uint32_t s1a = sb + SM_X + wg * 16384, s2b = sb + SM_X + 32768;
            wg_fence();
#pragma unroll
            for (int ks = 0; ks < 8; ks++)
                wgmma_n64<1>(acc, desc_a(s1a + (ks >> 2) * 8192 + (ks & 3) * 256), desc_b<64>(sb + SM_H + ks * 2048), ks != 0);
            wg_commit();
            wg_wait<0>();
            if (wg == 0) TC(2 + 10 * layer);
            uint32_t are[2][4], aim[2][4];
#pragma unroll
            for (int col = 0; col < 2; col++) {
#pragma unroll
                for (int i = 0; i < 4; i++) {
                    int o = 4 * (4 * col + i);
                    uint32_t zr = pack_bf16(acc[o], acc[o + 1]), zi = pack_bf16(acc[o + 2], acc[o + 3]);
                    are[col][i] = hfma2(zr, tr2[i], hmul2(zi, tn2[i]));
                    aim[col][i] = hfma2(zr, ti2[i], hmul2(zi, tr2[i]));
                }
            }
            wg_fence();
#pragma unroll
            for (int ks = 0; ks < 2; ks++)
                wgmma_n64_rs(acc, are[0][2 * ks], are[1][2 * ks], are[0][2 * ks + 1], are[1][2 * ks + 1], desc_b<64>(s2b + ks * 2048), ks != 0);
#pragma unroll
            for (int ks = 0; ks < 2; ks++)
                wgmma_n64_rs(acc, aim[0][2 * ks], aim[1][2 * ks], aim[0][2 * ks + 1], aim[1][2 * ks + 1], desc_b<64>(s2b + 4096 + ks * 2048), 1);
            wg_commit();
            uint32_t wf[16];
            mbar_wait(BAR(B_WRDY), layer);
#pragma unroll
            for (int i = 0; i < 4; i++) {
                const int kq = n1 * 4 + q;
                uint4 v = *(const uint4*)(sm + SM_H + 16384 + kq * 64 + ((i ^ ((kq >> 1) & 3)) << 4));
                wf[4 * i] = v.x; wf[4 * i + 1] = v.y; wf[4 * i + 2] = v.z; wf[4 * i + 3] = v.w;
            }
            wg_wait<0>();
            if (wg == 0) TC(3 + 10 * layer);
#pragma unroll
            for (int col = 0; col < 2; col++) {
#pragma unroll
                for (int i = 0; i < 4; i++) {
                    uint32_t wr = wf[col * 8 + 2 * i], wn = wf[col * 8 + 2 * i + 1];
                    uint32_t zr = pack_bf16(acc[4 * i + 2 * col], acc[4 * i + 2 * col + 1]);
                    uint32_t zi = pack_bf16(acc[16 + 4 * i + 2 * col], acc[16 + 4 * i + 2 * col + 1]);
                    are[col][i] = hfma2(zr, wr, hmul2(zi, wn));
                    aim[col][i] = hfma2(zr, wn, hmul2(zi ^ 0x80008000u, wr));
                }
            }
            wg_fence();
#pragma unroll
            for (int ks = 0; ks < 2; ks++)
                wgmma_n64_rs(acc, are[0][2 * ks], are[1][2 * ks], are[0][2 * ks + 1], are[1][2 * ks + 1], desc_b<64>(s2b + ks * 2048), ks != 0);
#pragma unroll
            for (int ks = 0; ks < 2; ks++)
                wgmma_n64_rs(acc, aim[0][2 * ks], aim[1][2 * ks], aim[0][2 * ks + 1], aim[1][2 * ks + 1], desc_b<64>(s2b + 4096 + ks * 2048), 1);
            wg_commit();
            wg_wait<0>();
            if (wg == 0) TC(4 + 10 * layer);
            bar_sync(1, 256);
#pragma unroll
            for (int col = 0; col < 2; col++) {
#pragma unroll
                for (int i = 0; i < 4; i++) {
                    uint32_t zr = pack_bf16(acc[4 * i + 2 * col], acc[4 * i + 2 * col + 1]);
                    uint32_t zi = pack_bf16(acc[16 + 4 * i + 2 * col], acc[16 + 4 * i + 2 * col + 1]);
                    sts32(st0 + 16384 + (4 * col + i) * 128, hfma2(zr, tr2[i], hmul2(zi, tn2[i])));
                    sts32(st0 + 16384 + 8192 + (4 * col + i) * 128, hfma2(zr, ti2[i], hmul2(zi, tr2[i])));
                }
            }
            if (wg == 0) TC(5 + 10 * layer);
            fence_async_smem();
            bar_sync(1, 256);
            wg_fence();
#pragma unroll
            for (int ks = 0; ks < 8; ks++)
                wgmma_n64<1>(acc, desc_a(s1a + (ks >> 2) * 8192 + (ks & 3) * 256), desc_b<64>(sb + SM_H + 16384 + ks * 2048), ks != 0);
            wg_commit();
            wg_wait<0>();
            if (wg == 0) TC(6 + 10 * layer);
            const float sc = 1.f / 2048.f;
            const float sci0 = sw ? 0.f : -sc;
            const float wr0 = sw ? 0.5f : 1.f, wi0 = sw ? 0.f : 1.f;
#pragma unroll
            for (int i = 0; i < 4; i++) {
                float ss0, ss1;
#pragma unroll
                for (int col = 0; col < 2; col++) {
                    int o = 4 * (4 * col + i);
                    uint32_t vr = xr[2 * col][i], vi = xr[2 * col + 1][i];
                    float si = col == 0 ? sci0 : -sc;
                    uint32_t nr = pack_bf16(fmaf(acc[o], sc, bf_lo(vr)), fmaf(acc[o + 1], sc, bf_hi(vr)));
                    uint32_t ni = pack_bf16(fmaf(acc[o + 2], si, bf_lo(vi)), fmaf(acc[o + 3], si, bf_hi(vi)));
                    float a0 = bf_lo(nr), a1 = bf_hi(nr), b0 = bf_lo(ni), b1 = bf_hi(ni);
                    if (col == 0) {
                        ss0 = wr0 * a0 * a0 + wi0 * b0 * b0;
                        ss1 = wr0 * a1 * a1 + wi0 * b1 * b1;
                    } else {
                        ss0 += a0 * a0 + b0 * b0;
                        ss1 += a1 * a1 + b1 * b1;
                    }
                    const int K = (2 * col) ^ (2 * (i & 1));
                    uint32_t a = rw0 + i * 256 + K * 16;
                    if (col == 0) a ^= sw << 4;
                    sts32(a, nr);
                    sts32(a ^ 16, ni);
                }
                *(float2*)(sm + SM_SSQ + (pos0 + 32 * i) * 4) = make_float2(ss0 * (2.f / 512.f), ss1 * (2.f / 512.f));
            }
            fence_async_smem();
        }
        TS(5 + 12 * layer);
        if (wg == 0) TC(7 + 10 * layer);
        bar_arrive(5, 416);

        float acc[64];
        float* s_rstd = (float*)(sm + SM_RSTD);
        float* s_mean = (float*)(sm + SM_MEAN);
        const unsigned epoch = s_tgt[0] >> 7;
        const uint32_t pt3 = 1u + (2u * epoch + layer) % 3u;
        const uint32_t ptag = (pt3 & 1u) | ((pt3 & 2u) << 15);
        const uint64_t dstep = layer == 0 ? 16 : 2;
        auto c_desc = [&](int s) { return layer == 0 ? desc_a(sb + SM_A + s * 16384) : desc_k(sb + SM_A + s * 16384); };
        if (wg < 2) {
            const int prow = 32 * wg + 8 * w + g;
            const float2 l1 = *(const float2*)(sm + SM_LAM + prow * 8);
            float lr32 = l1.x, li32 = l1.y;
#pragma unroll
            for (int i = 0; i < 5; i++) { float t = lr32 * lr32 - li32 * li32; li32 = 2.f * lr32 * li32; lr32 = t; }
            float lr128 = lr32, li128 = li32;
#pragma unroll
            for (int i = 0; i < 2; i++) { float t = lr128 * lr128 - li128 * li128; li128 = 2.f * lr128 * li128; lr128 = t; }
            const float lr1 = l1.x, li1 = l1.y;
            acc_def(acc);
#pragma unroll 1
            for (int kb = 0; kb < 8; kb++) {
                mbar_wait(BAR(B_AFULL + kb), 0);
                mbar_wait(BAR(B_XFULL + (kb & 3)), (kb >> 2) & 1);
                wg_fence();
#pragma unroll
                for (int ks = 0; ks < 4; ks++)
                    wgmma_n128<1>(acc, desc_a(sb + SM_A + kb * 16384 + wg * 8192 + ks * 256),
                                  desc_b<128>(sb + SM_X + (kb & 3) * 24576 + ks * 4096), 1);
                wg_commit();
                wg_wait<1>();
                if (kb > 0 && lane == 0) {
                    mbar_arrive(BAR(B_AEMPTY + kb - 1), 1); mbar_arrive(BAR(B_XEMPTY + ((kb - 1) & 3)), 1);
                    mbar_arrive_remote(mapa(BAR(B_XEMPTY + ((kb - 1) & 3)), par ^ 1));
                }
            }
            wg_wait<0>();
            if (lane == 0) {
                mbar_arrive(BAR(B_AEMPTY + 7), 1); mbar_arrive(BAR(B_XEMPTY + 3), 1);
                mbar_arrive_remote(mapa(BAR(B_XEMPTY + 3), par ^ 1)); mbar_arrive_remote(mapa(BAR(B_RFREE), par ^ 1));
            }
            bar_arrive(14, 384);
            TS(6 + 12 * layer);
            bar_sync(4, 384);
            TS(7 + 12 * layer);
            float er = 0.f, ei = 0.f;
#pragma unroll
            for (int i = 0; i < 16; i++) {
                float2 rs = *(const float2*)(s_rstd + 128 + 8 * i + 2 * q);
                acc[4 * i] *= rs.x; acc[4 * i + 1] *= rs.y; acc[4 * i + 2] *= rs.x; acc[4 * i + 3] *= rs.y;
                float nr = lr1 * er - li1 * ei + acc[4 * i], ni = lr1 * ei + li1 * er + acc[4 * i + 2];
                er = lr1 * nr - li1 * ni + acc[4 * i + 1];
                ei = lr1 * ni + li1 * nr + acc[4 * i + 3];
            }
            float cr = 0.f, ci = 0.f, tr = 0.f, ti = 0.f;
#pragma unroll
            for (int qq = 0; qq < 4; qq++) {
                float xr_ = __shfl_sync(~0u, er, (lane & ~3) | qq), xi_ = __shfl_sync(~0u, ei, (lane & ~3) | qq);
                if (qq == q) { cr = tr; ci = ti; }
                float nr = lr32 * tr - li32 * ti + xr_, ni = lr32 * ti + li32 * tr + xi_;
                tr = nr; ti = ni;
            }
            float4* eb = g_Ebuf + (uint32_t)(layer * 16 * 512 + 64 * r + prow);
            if (q == 0 && c < 15) st_relaxed_f4(eb + c * 512, make_float4(tr, ti, __uint_as_float(epoch), 0.f));
            TS(8 + 12 * layer);
            float pr[4], pi[4];
            {
                unsigned n = 0;
                bool ok;
#pragma unroll 1
                do {
                    ok = true;
#pragma unroll
                    for (int k = 0; k < 4; k++) {
                        float4 v = make_float4(0.f, 0.f, __uint_as_float(epoch), 0.f);
                        if (4 * k + q < c) v = ld_relaxed_f4(eb + (4 * k + q) * 512);
                        pr[k] = v.x; pi[k] = v.y;
                        ok = ok && __float_as_uint(v.z) == epoch;
                    }
                } while (!ok && ++n < SPIN_LIMIT);
            }
            __syncwarp();
            TS(9 + 12 * layer);
            float hr = 0.f, hi = 0.f;
#pragma unroll
            for (int cc = 0; cc < 15; cc++) {
                float xr_ = __shfl_sync(~0u, pr[cc >> 2], (lane & ~3) | (cc & 3)), xi_ = __shfl_sync(~0u, pi[cc >> 2], (lane & ~3) | (cc & 3));
                if (cc < c) {
                    float nr = lr128 * hr - li128 * hi + xr_, ni = lr128 * hi + li128 * hr + xi_;
                    hr = nr; hi = ni;
                }
            }
#pragma unroll
            for (int qq = 0; qq < 3; qq++) {
                if (qq < q) { float nr = lr32 * hr - li32 * hi, ni = lr32 * hi + li32 * hr; hr = nr; hi = ni; }
            }
            er = cr + hr; ei = ci + hi;
            bar_sync(7, 384);
            mbar_wait_cluster(BAR(B_RFREE), layer);
            const uint32_t ha = sb + SM_HH + par * 32768 + (prow >> 3) * 1024 + g * 16 + 4 * q;
#pragma unroll
            for (int i = 0; i < 16; i++) {
                float nr = lr1 * er - li1 * ei + acc[4 * i], ni = lr1 * ei + li1 * er + acc[4 * i + 2];
                er = lr1 * nr - li1 * ni + acc[4 * i + 1];
                ei = lr1 * ni + li1 * nr + acc[4 * i + 3];
                sts32(ha + (i >> 3) * 16384 + (i & 7) * 128, pack_bf16(nr, er));
                sts32(ha + (i >> 3) * 16384 + 8192 + (i & 7) * 128, pack_bf16(ni, ei));
                if (i == 7) { fence_async_smem(); bar_arrive(13, 288); }
            }
            fence_async_smem();
            acc_def(acc);
            float acc2[32];
            acc_def(acc2);
            TS(10 + 12 * layer);
            bar_sync(6, 416);
            TS(11 + 12 * layer);
            float (&a0)[32] = *reinterpret_cast<float (*)[32]>(&acc[0]);
            float (&a1)[32] = *reinterpret_cast<float (*)[32]>(&acc[32]);
            auto tile_mma = [&](float (&d)[32], int u) {
#pragma unroll 1
                for (int k = 0; k < 2; k++) {
                    const uint32_t hb = sb + SM_HH + (par ^ k) * 32768 + wg * 16384;
                    if (k == 1) mbar_wait(BAR(wg ? B_HPEER1 : B_HPEER), layer);
                    mbar_wait(BAR(B_AFULL + 2 * u + k), 1);
                    const uint64_t da = c_desc(2 * u + k);
                    wg_fence();
#pragma unroll
                    for (int ks = 0; ks < 4; ks++) wgmma_n64s<1>(d, da + ks * dstep, desc_b<64>(hb + ks * 2048), 1);
#pragma unroll
                    for (int ks = 0; ks < 4; ks++) wgmma_n64s<-1>(d, da + 512 + ks * dstep, desc_b<64>(hb + 8192 + ks * 2048), 1);
                }
                wg_commit();
            };
            auto tile_ship = [&](float (&d)[32], int u) {
                uint4* dst = g_P + (uint32_t)(((c * 8 + 2 * ((pi_ + 1 + u) & 3) + par) * 4 + pi_) * 1024 + wg * 512 + (tid & 127));
#pragma unroll
                for (int i = 0; i < 4; i++)
                    dst[i * 128] = make_uint4((pack_bf16(d[8 * i], d[8 * i + 1]) & 0xfffefffeu) | ptag, pack_bf16(d[8 * i + 2], d[8 * i + 3]),
                                              pack_bf16(d[8 * i + 4], d[8 * i + 5]), pack_bf16(d[8 * i + 6], d[8 * i + 7]));
            };
            tile_mma(a0, 0);
            if ((tid & 127) == 0) mbar_arrive_remote(mapa(BAR(B_HDONE), par ^ 1));
            __syncwarp();
            tile_mma(a1, 1);
            wg_wait<1>();
            tile_ship(a0, 0);
            tile_mma(acc2, 2);
            bar_arrive(12, 384);
            wg_wait<1>();
            tile_ship(a1, 1);
            wg_wait<0>();
            tile_ship(acc2, 2);
            if (lane < 6) mbar_arrive(BAR(B_AEMPTY + lane), 1);
            TS(12 + 12 * layer);
        } else {
            const int t2 = tid - 256;
            const uint8_t* ximg = g_X + (uint32_t)layer * 16 * 8 * 16384;
            mbar_wait(BAR(B_SSQ), layer);
            TS(6 + 12 * layer);
            float sqv[16];
#pragma unroll
            for (int i = 0; i < 16; i++) sqv[i] = __ldcg(g_ssqc + (layer * 16 + i) * 2048 + 128 * c + t2);
            const unsigned short xm = __ldcg((const unsigned short*)(ximg + (uint32_t)(c * 8 * 16384 + (t2 >> 3) * 128 + (t2 & 7) * 2)));
            acc_def(acc);
#pragma unroll 1
            for (int kb = 0; kb < 8; kb++) {
                if (kb == 4) {
                    wg_wait<0>();
                    if (lane == 0) { mbar_arrive(BAR(B_XEMPTY + 3), 1); mbar_arrive_remote(mapa(BAR(B_XEMPTY + 3), par ^ 1)); }
                    float tot = 0.f;
#pragma unroll
                    for (int i = 0; i < 16; i++) tot += sqv[i];
                    float rs = rsqrtf(tot * (1.f / 512.f) + 1e-5f);
                    s_rstd[t2] = rs;
                    s_rstd[128 + t2] = 2.f * rs;
                    s_mean[t2] = layer == 0 ? 0.f : __uint_as_float((uint32_t)xm << 16) * (1.f / 512.f);
                    TS(7 + 12 * layer);
                    bar_arrive(4, 384);
                    bar_sync(14, 384);
                }
                mbar_wait(BAR(B_XFULL + (kb & 3)), (kb >> 2) & 1);
                wg_fence();
#pragma unroll
                for (int ks = 0; ks < 4; ks++)
                    wgmma_n128<1>(acc, desc_a(sb + SM_X + (kb & 3) * 24576 + 16384 + ks * 256), desc_b<128>(sb + SM_X + (kb & 3) * 24576 + ks * 4096), 1);
                wg_commit();
                wg_wait<1>();
                if ((kb & 3) != 0 && lane == 0) { mbar_arrive(BAR(B_XEMPTY + ((kb - 1) & 3)), 1); mbar_arrive_remote(mapa(BAR(B_XEMPTY + ((kb - 1) & 3)), par ^ 1)); }
            }
            wg_wait<0>();
            if (lane == 0) { mbar_arrive(BAR(B_XEMPTY + 3), 1); mbar_arrive_remote(mapa(BAR(B_XEMPTY + 3), par ^ 1)); mbar_arrive_remote(mapa(BAR(B_RFREE), par ^ 1)); }
            bar_arrive(7, 384);
            bar_sync(3, 128);
            TS(9 + 12 * layer);
            const int m0 = 16 * w + g;
            const uint32_t xoff = (uint32_t)((c * 8 + own) * 16384 + w * 4096 + g * 16 + 4 * q);
            if (layer == 0) {
                const uint8_t* xs = g_X + xoff;
#pragma unroll
                for (int i = 0; i < 16; i++) {
                    float2 rs = *(const float2*)(s_rstd + 8 * i + 2 * q);
                    uint32_t x0v = __ldcg((const uint32_t*)(xs + i * 128)), x1v = __ldcg((const uint32_t*)(xs + 2048 + i * 128));
                    acc[4 * i] = acc[4 * i] * rs.x + bf_lo(x0v);
                    acc[4 * i + 1] = acc[4 * i + 1] * rs.y + bf_hi(x0v);
                    acc[4 * i + 2] = acc[4 * i + 2] * rs.x + bf_lo(x1v);
                    acc[4 * i + 3] = acc[4 * i + 3] * rs.y + bf_hi(x1v);
                }
            } else {
                float d0 = ldbf(p.dskip + 64 * own + m0), d1 = ldbf(p.dskip + 64 * own + m0 + 8);
#pragma unroll
                for (int i = 0; i < 16; i++) {
                    float2 rs = *(const float2*)(s_rstd + 8 * i + 2 * q);
                    float2 mn = *(const float2*)(s_mean + 8 * i + 2 * q);
                    acc[4 * i] = acc[4 * i] * (1.f + rs.x * d0) + mn.x;
                    acc[4 * i + 1] = acc[4 * i + 1] * (1.f + rs.y * d0) + mn.y;
                    acc[4 * i + 2] = acc[4 * i + 2] * (1.f + rs.x * d1) + mn.x;
                    acc[4 * i + 3] = acc[4 * i + 3] * (1.f + rs.y * d1) + mn.y;
                }
            }
            TS(10 + 12 * layer);
            bar_sync(6, 416);
            TS(11 + 12 * layer);
            {
                float (&a0)[32] = *reinterpret_cast<float (*)[32]>(&acc[0]);
                float (&a1)[32] = *reinterpret_cast<float (*)[32]>(&acc[32]);
#pragma unroll 1
                for (int k = 0; k < 2; k++) {
                    const uint32_t hb = sb + SM_HH + (par ^ k) * 32768;
                    if (k == 1) {
                        mbar_wait(BAR(B_HPEER), layer);
                        mbar_wait(BAR(B_HPEER1), layer);
                        bar_sync(12, 384);
                    }
                    mbar_wait(BAR(B_AFULL + 6 + k), 1);
                    const uint64_t da = c_desc(6 + k);
                    wg_fence();
#pragma unroll
                    for (int ks = 0; ks < 4; ks++) {
                        wgmma_n64s<1>(a0, da + ks * dstep, desc_b<64>(hb + ks * 2048), 1);
                        wgmma_n64s<1>(a1, da + ks * dstep, desc_b<64>(hb + 16384 + ks * 2048), 1);
                    }
#pragma unroll
                    for (int ks = 0; ks < 4; ks++) {
                        wgmma_n64s<-1>(a0, da + 512 + ks * dstep, desc_b<64>(hb + 8192 + ks * 2048), 1);
                        wgmma_n64s<-1>(a1, da + 512 + ks * dstep, desc_b<64>(hb + 16384 + 8192 + ks * 2048), 1);
                    }
                    wg_commit();
                }
                wg_wait<0>();
            }
#pragma unroll
            for (int i = 0; i < 16; i++)
                *(float4*)(sm + SM_A + 6 * 16384 + i * 2048 + t2 * 16) = make_float4(acc[4 * i], acc[4 * i + 1], acc[4 * i + 2], acc[4 * i + 3]);
            TS(12 + 12 * layer);
        }
        {
            const int t = tid & 127;
            const int nch = wg == 2 ? 2 : 3;
            const uint4* pb = g_P + (uint32_t)((c * 8 + r) * 4 * 1024 + wg * 128 + t);
            uint4 v[3][3];
            unsigned n = 0;
#pragma unroll 1
            while (true) {
                if (lane == 31) {
#pragma unroll 1
                    while (true) {
                        uint32_t bad = 0;
#pragma unroll
                        for (int sx = 0; sx < 3; sx++) {
                            uint32_t t0;
                            asm volatile("ld.relaxed.gpu.global.u32 %0, [%1];" : "=r"(t0) : "l"(pb + ((pi_ + 1 + sx) & 3) * 1024 + (nch - 1) * 384) : "memory");
                            bad |= t0 ^ ptag;
                        }
                        if (!(bad & 0x00010001u) || ++n >= SPIN_LIMIT) break;
                    }
                }
                __syncwarp();
                uint32_t bad = 0;
#pragma unroll
                for (int k = 0; k < 3; k++)
#pragma unroll
                    for (int sx = 0; sx < 3; sx++) {
                        v[k][sx] = make_uint4(ptag, 0, 0, 0);
                        if (k < nch) v[k][sx] = ld_relaxed_u4(pb + ((pi_ + 1 + sx) & 3) * 1024 + k * 384);
                        bad |= v[k][sx].x ^ ptag;
                    }
                if (!__any_sync(~0u, bad & 0x00010001u) || ++n >= SPIN_LIMIT) break;
            }
            bar_sync(8, 384);
            TS(13 + 12 * layer);
            const int m0 = 16 * w + g;
            const float w0 = (own == 0 && m0 < 2) ? (m0 == 0 ? 0.f : 0.5f) : 1.f;
#pragma unroll
            for (int k = 0; k < 3; k++) {
                if (k < nch) {
                    const int i = wg + 3 * k;
                    float4 a = *(const float4*)(sm + SM_A + 6 * 16384 + (2 * i) * 2048 + t * 16);
                    float4 bq = *(const float4*)(sm + SM_A + 6 * 16384 + (2 * i + 1) * 2048 + t * 16);
#pragma unroll
                    for (int sx = 0; sx < 3; sx++) {
                        a.x += bf_lo(v[k][sx].x); a.y += bf_hi(v[k][sx].x); a.z += bf_lo(v[k][sx].y); a.w += bf_hi(v[k][sx].y);
                        bq.x += bf_lo(v[k][sx].z); bq.y += bf_hi(v[k][sx].z); bq.z += bf_lo(v[k][sx].w); bq.w += bf_hi(v[k][sx].w);
                    }
                    if (layer == 0) {
                        uint8_t* xd = g_X + (uint32_t)((16 * 8 + c * 8 + own) * 16384 + w * 4096 + g * 16 + 4 * q + i * 256);
                        uint32_t v0 = pack_bf16(a.x, a.y), v1 = pack_bf16(a.z, a.w), v2 = pack_bf16(bq.x, bq.y), v3 = pack_bf16(bq.z, bq.w);
                        *(uint32_t*)(xd) = v0; *(uint32_t*)(xd + 2048) = v1; *(uint32_t*)(xd + 128) = v2; *(uint32_t*)(xd + 2048 + 128) = v3;
                        float sq[4];
                        sq[0] = w0 * bf_lo(v0) * bf_lo(v0) + bf_lo(v1) * bf_lo(v1);
                        sq[1] = w0 * bf_hi(v0) * bf_hi(v0) + bf_hi(v1) * bf_hi(v1);
                        sq[2] = w0 * bf_lo(v2) * bf_lo(v2) + bf_lo(v3) * bf_lo(v3);
                        sq[3] = w0 * bf_hi(v2) * bf_hi(v2) + bf_hi(v3) * bf_hi(v3);
                        float u0 = (g & 1) ? sq[2] : sq[0], u1 = (g & 1) ? sq[3] : sq[1];
                        u0 += __shfl_xor_sync(~0u, (g & 1) ? sq[0] : sq[2], 4);
                        u1 += __shfl_xor_sync(~0u, (g & 1) ? sq[1] : sq[3], 4);
                        float z = (g & 2) ? u1 : u0;
                        z += __shfl_xor_sync(~0u, (g & 2) ? u0 : u1, 8);
                        z += __shfl_xor_sync(~0u, z, 16);
                        if (g < 4) atomicAdd(s_mean + 16 * i + 8 * (g & 1) + 2 * q + (g >> 1), z);
                    } else {
                        float* o = p.out + (uint32_t)((128 * c + 32 * q + 4 * i) * 512 + 64 * own + m0);
                        o[0] = a.x; o[512] = a.y; o[8] = a.z; o[512 + 8] = a.w;
                        o[1024] = bq.x; o[1536] = bq.y; o[1024 + 8] = bq.z; o[1536 + 8] = bq.w;
                    }
                }
            }
            if (wg < 2) mbar_wait_cluster(BAR(B_HDONE), layer);
            if (layer == 0) {
                fence_async_smem();
                bar_sync(9, 384);
                TS(14 + 12 * layer);
                if (wg == 2) {
                    atomicAdd(g_ssq + 2048 + 128 * c + t, s_mean[t] * (2.f / 512.f));
                    bar_sync(3, 128);
                    if (lane == 0) { mbar_arrive(BAR(B_AEMPTY + 6), 2); mbar_arrive(BAR(B_AEMPTY + 7), 2); }
                    if (t == 0) { fence_async(); red_release(&g_bar[2], 1); }
                }
            }
        }
        TS(15 + 12 * layer);
        if (wg == 0) TC(31);
    }
}

typedef CUresult (*EncFn)(CUtensorMap*, CUtensorMapDataType, cuuint32_t, void*, const cuuint64_t*, const cuuint64_t*,
                          const cuuint32_t*, const cuuint32_t*, CUtensorMapInterleave, CUtensorMapSwizzle,
                          CUtensorMapL2promotion, CUtensorMapFloatOOBfill);

void launch_impl(void* const* d_in, void* d_out, int stop) {
    static EncFn enc = nullptr;
    if (!enc) {
        void* fn = nullptr;
        cudaDriverEntryPointQueryResult qr;
        cudaGetDriverEntryPoint("cuTensorMapEncodeTiled", &fn, cudaEnableDefault, &qr);
        enc = (EncFn)fn;
        cudaFuncSetAttribute(fused_kernel, cudaFuncAttributeMaxDynamicSharedMemorySize, SM_TOTAL);
    }
    CUtensorMap tx, tbr, tbi, tcr, tci, tcol;
    {
        void* gx = nullptr;
        cudaGetSymbolAddress(&gx, g_X);
        cuuint64_t gd[5] = {64, 16, 64, 16, 2};
        cuuint64_t gs[4] = {128, 2048, 128 * 1024, 2048 * 1024};
        cuuint32_t bx[5] = {32, 16, 1, 16, 1};
        cuuint32_t es[5] = {1, 1, 1, 1, 1};
        enc(&tcol, CU_TENSOR_MAP_DATA_TYPE_BFLOAT16, 5, gx, gd, gs, bx, es, CU_TENSOR_MAP_INTERLEAVE_NONE,
            CU_TENSOR_MAP_SWIZZLE_64B, CU_TENSOR_MAP_L2_PROMOTION_NONE, CU_TENSOR_MAP_FLOAT_OOB_FILL_NONE);
    }
    {
        cuuint64_t gd[5] = {512, 2, 4, 16, 16};
        cuuint64_t gs[4] = {1024, 32 * 1024, 2 * 1024, 128 * 1024};
        cuuint32_t bx[5] = {64, 2, 4, 8, 1};
        cuuint32_t es[5] = {1, 1, 1, 1, 1};
        enc(&tx, CU_TENSOR_MAP_DATA_TYPE_BFLOAT16, 5, d_in[0], gd, gs, bx, es, CU_TENSOR_MAP_INTERLEAVE_NONE,
            CU_TENSOR_MAP_SWIZZLE_128B, CU_TENSOR_MAP_L2_PROMOTION_L2_128B, CU_TENSOR_MAP_FLOAT_OOB_FILL_NONE);
    }
    auto mk2 = [&](CUtensorMap* m, void* ptr, cuuint32_t rows) {
        cuuint64_t gd[2] = {512, 512};
        cuuint64_t gs[1] = {1024};
        cuuint32_t bx[2] = {64, rows};
        cuuint32_t es[2] = {1, 1};
        enc(m, CU_TENSOR_MAP_DATA_TYPE_BFLOAT16, 2, ptr, gd, gs, bx, es, CU_TENSOR_MAP_INTERLEAVE_NONE,
            CU_TENSOR_MAP_SWIZZLE_128B, CU_TENSOR_MAP_L2_PROMOTION_L2_128B, CU_TENSOR_MAP_FLOAT_OOB_FILL_NONE);
    };
    mk2(&tbr, d_in[6], 32);
    mk2(&tbi, d_in[7], 32);
    mk2(&tcr, d_in[8], 64);
    mk2(&tci, d_in[9], 64);
    Params p;
    p.x0 = (const __nv_bfloat16*)d_in[0];
    p.w_r = (const __nv_bfloat16*)d_in[1];
    p.w_i = (const __nv_bfloat16*)d_in[2];
    p.lam_re = (const __nv_bfloat16*)d_in[4];
    p.lam_im = (const __nv_bfloat16*)d_in[5];
    p.log_dt = (const __nv_bfloat16*)d_in[10];
    p.dskip = (const __nv_bfloat16*)d_in[11];
    p.out = (float*)d_out;
    p.stop = stop;
    cudaLaunchConfig_t cfg = {};
    cfg.gridDim = dim3(NCTA); cfg.blockDim = dim3(NTHREADS); cfg.dynamicSmemBytes = SM_TOTAL; cfg.stream = cudaStreamPerThread;
    cudaLaunchAttribute at[1];
    at[0].id = cudaLaunchAttributeClusterDimension;
    at[0].val.clusterDim.x = 2; at[0].val.clusterDim.y = 1; at[0].val.clusterDim.z = 1;
    cfg.attrs = at; cfg.numAttrs = 1;
    cudaLaunchKernelEx(&cfg, fused_kernel, tx, tbr, tbi, tcr, tci, tcol, p);
}

}

extern "C" void kernel_launch(void* const* d_in, const int* in_sizes, int n_in, void* d_out, int out_size) {
    (void)in_sizes; (void)n_in; (void)out_size;
    launch_impl(d_in, d_out, 100);
}
```

```cpp
#include <cuda_runtime.h>
#include <cuda_bf16.h>
#include <cuda.h>
#include <stdint.h>

namespace {

constexpr int NCTA = 128;
constexpr int NTHREADS = 512;
constexpr int SM_A = 0;
constexpr int SM_X = 131072;
constexpr int SM_H = 196608;
constexpr int SM_HH = SM_X + 32768;
constexpr int SM_M = 229376;
constexpr int SM_TOTAL = 232448;
constexpr int SM_BAR = SM_M;
constexpr int SM_TGT = SM_M + 400;
constexpr int SM_LAM = SM_M + 424;
constexpr int SM_TAB = SM_M + 944;
constexpr int SM_RSTD = SM_M + 1920;
constexpr int SM_MEAN = SM_TAB;
constexpr int SM_T64 = SM_M + 2944;
constexpr int SM_B1ST = SM_H + 24576;
constexpr int SM_RAW = SM_X + 40960;
constexpr int SM_SSQ = SM_X + 57344;
constexpr int B_FULL0 = 0;
constexpr int B_EMPTY0 = 8;
constexpr int B_FULLC = 12;
constexpr int B_AFULL = 13;
constexpr int B_AEMPTY = 21;
constexpr int B_XFULL = 29;
constexpr int B_XEMPTY = 33;
constexpr int B_AFREE = 37;
constexpr int B_COL = 38;
constexpr int B_SSQ = 39;
constexpr int B_HPEER = 40;
constexpr int B_RFREE = 41;
constexpr int B_HDONE = 42;
constexpr int B_WRDY = 43;
constexpr int B_HPEER1 = 44;
constexpr int B_FULLB = 45;
constexpr int B_BFREE = 46;
constexpr int B_SETUP = 47;
constexpr int B_B1DONE = 48;
constexpr int B_WST = 49;
constexpr int NBARS = 50;

__device__ __align__(1024) uint8_t g_X[2 * 16 * 8 * 16384];
__device__ __align__(1024) uint8_t g_A1[8 * 8 * 16384];
__device__ __align__(1024) uint8_t g_A2[8 * 8 * 16384];
__device__ __align__(1024) uint8_t g_E[2 * 8 * 8 * 8192];
__device__ __align__(16) float g_ssq[2 * 2048];
__device__ __align__(16) float g_ssqc[2 * 16 * 2048];
__device__ __align__(16) float g_Dh[512];
__device__ __align__(16) uint4 g_Wfrag[128 * 4 * 256];
__device__ __align__(16) float4 g_Ebuf[2 * 16 * 512];
__device__ __align__(16) uint4 g_P[16 * 8 * 4 * 1024];
__device__ unsigned g_bar[8];
__device__ unsigned g_err;
#define TX(i)
#define TQ(i)
#define TS(i)
#define TC(i)

constexpr unsigned SPIN_LIMIT = 1u << 22;

__device__ __forceinline__ uint32_t s2u(const void* p) { return (uint32_t)__cvta_generic_to_shared(p); }
__device__ __forceinline__ void mbar_init(uint32_t a, uint32_t c) {
    asm volatile("mbarrier.init.shared::cta.b64 [%0], %1;" ::"r"(a), "r"(c) : "memory");
}
__device__ __forceinline__ void mbar_expect(uint32_t a, uint32_t bytes) {
    asm volatile("mbarrier.arrive.expect_tx.shared::cta.b64 _, [%0], %1;" ::"r"(a), "r"(bytes) : "memory");
}
__device__ __forceinline__ void mbar_arrive(uint32_t a, uint32_t cnt) {
    asm volatile("mbarrier.arrive.shared::cta.b64 _, [%0], %1;" ::"r"(a), "r"(cnt) : "memory");
}
__device__ __forceinline__ bool mbar_try(uint32_t a, uint32_t parity) {
    uint32_t ok;
    asm volatile("{\n.reg .pred p;\nmbarrier.try_wait.parity.shared::cta.b64 p, [%1], %2;\nselp.u32 %0, 1, 0, p;\n}"
                 : "=r"(ok) : "r"(a), "r"(parity) : "memory");
    return ok != 0;
}
__device__ __forceinline__ void mbar_wait(uint32_t a, uint32_t parity) {
    asm volatile("{\n.reg .pred p, q;\n.reg .u32 n;\nmov.u32 n, 0;\n"
                 "W_%=:\nmbarrier.try_wait.parity.shared::cta.b64 p, [%0], %1;\n@p bra D_%=;\n"
                 "add.u32 n, n, 1;\nsetp.lt.u32 q, n, 4194304;\n@q bra W_%=;\nD_%=:\n}" ::"r"(a), "r"(parity) : "memory");
}
__device__ __forceinline__ void bulk_g2s(uint32_t dst, const void* src, uint32_t bytes, uint32_t bar) {
    asm volatile("cp.async.bulk.shared::cluster.global.mbarrier::complete_tx::bytes [%0], [%1], %2, [%3];" ::"r"(dst),
                 "l"(src), "r"(bytes), "r"(bar) : "memory");
}
__device__ __forceinline__ void tma_2d(uint32_t dst, const CUtensorMap* m, int c0, int c1, uint32_t bar) {
    asm volatile("cp.async.bulk.tensor.2d.shared::cluster.global.mbarrier::complete_tx::bytes [%0], [%1, {%3,%4}], [%2];" ::"r"(dst),
                 "l"(m), "r"(bar), "r"(c0), "r"(c1) : "memory");
}
__device__ __forceinline__ void tma_5d(uint32_t dst, const CUtensorMap* m, int c0, int c1, int c2, int c3, int c4, uint32_t bar) {
    asm volatile("cp.async.bulk.tensor.5d.shared::cluster.global.mbarrier::complete_tx::bytes [%0], [%1, {%3,%4,%5,%6,%7}], [%2];" ::"r"(dst),
                 "l"(m), "r"(bar), "r"(c0), "r"(c1), "r"(c2), "r"(c3), "r"(c4) : "memory");
}
__device__ __forceinline__ void tma_2d_mc(uint32_t dst, const CUtensorMap* m, int c0, int c1, uint32_t bar) {
    asm volatile("cp.async.bulk.tensor.2d.shared::cluster.global.mbarrier::complete_tx::bytes.multicast::cluster [%0], [%1, {%3,%4}], [%2], %5;" ::"r"(dst),
                 "l"(m), "r"(bar), "r"(c0), "r"(c1), "h"((unsigned short)3) : "memory");
}
__device__ __forceinline__ void tma_5d_mc(uint32_t dst, const CUtensorMap* m, int c0, int c1, int c2, int c3, int c4, uint32_t bar) {
    asm volatile("cp.async.bulk.tensor.5d.shared::cluster.global.mbarrier::complete_tx::bytes.multicast::cluster [%0], [%1, {%3,%4,%5,%6,%7}], [%2], %8;" ::"r"(dst),
                 "l"(m), "r"(bar), "r"(c0), "r"(c1), "r"(c2), "r"(c3), "r"(c4), "h"((unsigned short)3) : "memory");
}
__device__ __forceinline__ void bulk_g2s_mc(uint32_t dst, const void* src, uint32_t bytes, uint32_t bar) {
    asm volatile("cp.async.bulk.shared::cluster.global.mbarrier::complete_tx::bytes.multicast::cluster [%0], [%1], %2, [%3], %4;" ::"r"(dst),
                 "l"(src), "r"(bytes), "r"(bar), "h"((unsigned short)3) : "memory");
}
__device__ __forceinline__ void tma_store_5d(const CUtensorMap* m, int c0, int c1, int c2, int c3, int c4, uint32_t src) {
    asm volatile("cp.async.bulk.tensor.5d.global.shared::cta.bulk_group [%0, {%2,%3,%4,%5,%6}], [%1];" ::"l"(m), "r"(src),
                 "r"(c0), "r"(c1), "r"(c2), "r"(c3), "r"(c4) : "memory");
}
__device__ __forceinline__ uint32_t lds32(uint32_t a) { uint32_t v; asm volatile("ld.shared.u32 %0, [%1];" : "=r"(v) : "r"(a) : "memory"); return v; }
__device__ __forceinline__ uint4 ld_relaxed_u4(const uint4* p) {
    uint4 v;
    asm volatile("ld.relaxed.gpu.global.v4.u32 {%0,%1,%2,%3}, [%4];" : "=r"(v.x), "=r"(v.y), "=r"(v.z), "=r"(v.w) : "l"(p) : "memory");
    return v;
}
__device__ __forceinline__ void fence_async() { asm volatile("fence.proxy.async.global;" ::: "memory"); }
__device__ __forceinline__ void red_relaxed(unsigned* p, unsigned v) {
    asm volatile("red.relaxed.gpu.global.add.u32 [%0], %1;" ::"l"(p), "r"(v) : "memory");
}
__device__ __forceinline__ uint32_t mapa(uint32_t a, uint32_t rank) {
    uint32_t d;
    asm("mapa.shared::cluster.u32 %0, %1, %2;" : "=r"(d) : "r"(a), "r"(rank));
    return d;
}
__device__ __forceinline__ void mbar_arrive_remote(uint32_t ra) {
    asm volatile("mbarrier.arrive.relaxed.cluster.shared::cluster.b64 _, [%0];" ::"r"(ra) : "memory");
}
__device__ __forceinline__ void mbar_wait_cluster(uint32_t a, uint32_t parity) {
    asm volatile("{\n.reg .pred p, q;\n.reg .u32 n;\nmov.u32 n, 0;\n"
                 "W_%=:\nmbarrier.try_wait.parity.acquire.cluster.shared::cta.b64 p, [%0], %1;\n@p bra D_%=;\n"
                 "add.u32 n, n, 1;\nsetp.lt.u32 q, n, 4194304;\n@q bra W_%=;\nD_%=:\n}" ::"r"(a), "r"(parity) : "memory");
}
__device__ __forceinline__ void bulk_s2peer(uint32_t rdst, uint32_t src, uint32_t bytes, uint32_t rbar) {
    asm volatile("cp.async.bulk.shared::cluster.shared::cta.mbarrier::complete_tx::bytes [%0], [%1], %2, [%3];" ::"r"(rdst),
                 "r"(src), "r"(bytes), "r"(rbar) : "memory");
}
__device__ __forceinline__ void fence_async_smem() { asm volatile("fence.proxy.async.shared::cta;" ::: "memory"); }
__device__ __forceinline__ void wg_fence() { asm volatile("wgmma.fence.sync.aligned;" ::: "memory"); }
__device__ __forceinline__ void wg_commit() { asm volatile("wgmma.commit_group.sync.aligned;" ::: "memory"); }
template <int N> __device__ __forceinline__ void wg_wait() { asm volatile("wgmma.wait_group.sync.aligned %0;" ::"n"(N) : "memory"); }
__device__ __forceinline__ void bar_sync(int id, int n) { asm volatile("bar.sync %0, %1;" ::"r"(id), "r"(n) : "memory"); }
__device__ __forceinline__ void bar_arrive(int id, int n) { asm volatile("bar.arrive %0, %1;" ::"r"(id), "r"(n) : "memory"); }
__device__ __forceinline__ unsigned ld_acquire(const unsigned* p) {
    unsigned v;
    asm volatile("ld.acquire.gpu.global.u32 %0, [%1];" : "=r"(v) : "l"(p) : "memory");
    return v;
}
__device__ __forceinline__ void red_release(unsigned* p, unsigned v) {
    asm volatile("red.release.gpu.global.add.u32 [%0], %1;" ::"l"(p), "r"(v) : "memory");
}
__device__ __forceinline__ void wait_count(const unsigned* p, unsigned target) {
    unsigned n = 0;
#pragma unroll 1
    while ((int)(ld_acquire(p) - target) < 0 && ++n < SPIN_LIMIT) {}
}
__device__ __forceinline__ float4 ld_relaxed_f4(const float4* p) {
    float4 v;
    asm volatile("ld.relaxed.gpu.global.v4.f32 {%0,%1,%2,%3}, [%4];" : "=f"(v.x), "=f"(v.y), "=f"(v.z), "=f"(v.w) : "l"(p) : "memory");
    return v;
}
__device__ __forceinline__ void st_relaxed_f4(float4* p, float4 v) {
    asm volatile("st.relaxed.gpu.global.v4.f32 [%0], {%1,%2,%3,%4};" ::"l"(p), "f"(v.x), "f"(v.y), "f"(v.z), "f"(v.w) : "memory");
}
__device__ __forceinline__ uint32_t pack_bf16(float lo, float hi) {
    uint32_t r;
    asm("cvt.rn.bf16x2.f32 %0, %1, %2;" : "=r"(r) : "f"(hi), "f"(lo));
    return r;
}
__device__ __forceinline__ uint32_t hmul2(uint32_t a, uint32_t b) {
    uint32_t r;
    asm("mul.rn.bf16x2 %0, %1, %2;" : "=r"(r) : "r"(a), "r"(b));
    return r;
}
__device__ __forceinline__ uint32_t hfma2(uint32_t a, uint32_t b, uint32_t c) {
    uint32_t r;
    asm("fma.rn.bf16x2 %0, %1, %2, %3;" : "=r"(r) : "r"(a), "r"(b), "r"(c));
    return r;
}
__device__ __forceinline__ float bf_lo(uint32_t v) { return __uint_as_float(v << 16); }
__device__ __forceinline__ float bf_hi(uint32_t v) { return __uint_as_float(v & 0xffff0000u); }
__device__ __forceinline__ void sts32(uint32_t a, uint32_t v) { asm volatile("st.shared.u32 [%0], %1;" ::"r"(a), "r"(v) : "memory"); }
__device__ __forceinline__ void sts128(uint32_t a, uint4 v) {
    asm volatile("st.shared.v4.u32 [%0], {%1,%2,%3,%4};" ::"r"(a), "r"(v.x), "r"(v.y), "r"(v.z), "r"(v.w) : "memory");
}

__device__ __forceinline__ uint64_t desc_ni(uint32_t addr, uint32_t lbo, uint32_t sbo) {
    return (uint64_t)((addr & 0x3FFFF) >> 4) | ((uint64_t)(lbo >> 4) << 16) | ((uint64_t)(sbo >> 4) << 32);
}
__device__ __forceinline__ uint64_t desc_a(uint32_t addr) { return desc_ni(addr, 128, 1024); }
template <int N> __device__ __forceinline__ uint64_t desc_b(uint32_t addr) { return desc_ni(addr, 16 * N, 128); }
__device__ __forceinline__ uint64_t desc_k(uint32_t addr) {
    return (uint64_t)((addr & 0x3FFFF) >> 4) | (1ull << 16) | (64ull << 32) | (1ull << 62);
}
__device__ __forceinline__ uint64_t desc_mn(uint32_t addr, uint32_t lbo) {
    return (uint64_t)((addr & 0x3FFFF) >> 4) | ((uint64_t)(lbo >> 4) << 16) | (64ull << 32) | (1ull << 62);
}

#define ACC8(d, o) "+f"(d[o + 0]), "+f"(d[o + 1]), "+f"(d[o + 2]), "+f"(d[o + 3]), "+f"(d[o + 4]), "+f"(d[o + 5]), "+f"(d[o + 6]), "+f"(d[o + 7])
template <int TB, int SA = 1>
__device__ __forceinline__ void wgmma_n128(float (&d)[64], uint64_t da, uint64_t db, int sd) {
    asm volatile(
        "{\n.reg .pred p;\nsetp.ne.b32 p, %66, 0;\n"
        "wgmma.mma_async.sync.aligned.m64n128k16.f32.bf16.bf16 "
        "{%0,%1,%2,%3,%4,%5,%6,%7,%8,%9,%10,%11,%12,%13,%14,%15,%16,%17,%18,%19,%20,%21,%22,%23,%24,%25,%26,%27,%28,%29,%30,%31,"
        "%32,%33,%34,%35,%36,%37,%38,%39,%40,%41,%42,%43,%44,%45,%46,%47,%48,%49,%50,%51,%52,%53,%54,%55,%56,%57,%58,%59,%60,%61,%62,%63},"
        " %64, %65, p, %68, 1, 0, %67;\n}"
        : ACC8(d, 0), ACC8(d, 8), ACC8(d, 16), ACC8(d, 24), ACC8(d, 32), ACC8(d, 40), ACC8(d, 48), ACC8(d, 56)
        : "l"(da), "l"(db), "r"(sd), "n"(TB), "n"(SA));
}
template <int N> __device__ __forceinline__ void acc_def(float (&d)[N]) {
#pragma unroll
    for (int i = 0; i < N; i++) d[i] = 0.f;
}
template <int TB>
__device__ __forceinline__ void wgmma_n64(float (&d)[32], uint64_t da, uint64_t db, int sd) {
    asm volatile(
        "{\n.reg .pred p;\nsetp.ne.b32 p, %34, 0;\n"
        "wgmma.mma_async.sync.aligned.m64n64k16.f32.bf16.bf16 "
        "{%0,%1,%2,%3,%4,%5,%6,%7,%8,%9,%10,%11,%12,%13,%14,%15,%16,%17,%18,%19,%20,%21,%22,%23,%24,%25,%26,%27,%28,%29,%30,%31},"
        " %32, %33, p, 1, 1, 0, %35;\n}"
        : ACC8(d, 0), ACC8(d, 8), ACC8(d, 16), ACC8(d, 24)
        : "l"(da), "l"(db), "r"(sd), "n"(TB));
}
template <int SA>
__device__ __forceinline__ void wgmma_n64s(float (&d)[32], uint64_t da, uint64_t db, int sd) {
    asm volatile(
        "{\n.reg .pred p;\nsetp.ne.b32 p, %34, 0;\n"
        "wgmma.mma_async.sync.aligned.m64n64k16.f32.bf16.bf16 "
        "{%0,%1,%2,%3,%4,%5,%6,%7,%8,%9,%10,%11,%12,%13,%14,%15,%16,%17,%18,%19,%20,%21,%22,%23,%24,%25,%26,%27,%28,%29,%30,%31},"
        " %32, %33, p, %35, 1, 0, 1;\n}"
        : ACC8(d, 0), ACC8(d, 8), ACC8(d, 16), ACC8(d, 24)
        : "l"(da), "l"(db), "r"(sd), "n"(SA));
}
__device__ __forceinline__ void wgmma_n64_rs(float (&d)[32], uint32_t a0, uint32_t a1, uint32_t a2, uint32_t a3, uint64_t db, int sd) {
    asm volatile(
        "{\n.reg .pred p;\nsetp.ne.b32 p, %37, 0;\n"
        "wgmma.mma_async.sync.aligned.m64n64k16.f32.bf16.bf16 "
        "{%0,%1,%2,%3,%4,%5,%6,%7,%8,%9,%10,%11,%12,%13,%14,%15,%16,%17,%18,%19,%20,%21,%22,%23,%24,%25,%26,%27,%28,%29,%30,%31},"
        " {%32,%33,%34,%35}, %36, p, 1, 1, 1;\n}"
        : ACC8(d, 0), ACC8(d, 8), ACC8(d, 16), ACC8(d, 24)
        : "r"(a0), "r"(a1), "r"(a2), "r"(a3), "l"(db), "r"(sd));
}

struct Params {
    const __nv_bfloat16* x0;
    const __nv_bfloat16* w_r;
    const __nv_bfloat16* w_i;
    const __nv_bfloat16* lam_re;
    const __nv_bfloat16* lam_im;
    const __nv_bfloat16* log_dt;
    const __nv_bfloat16* dskip;
    float* out;
    int stop;
};

__device__ __forceinline__ float ldbf(const __nv_bfloat16* p) { return __bfloat162float(*p); }

__device__ __forceinline__ void dft_fp(int j, int& f, int& ph) {
    int cs = j >> 1;
    if (j == 1) { f = 256; ph = 0; }
    else { f = cs; ph = (j & 1) ? 128 : 0; }
}

__device__ __forceinline__ void gen_col_consts(uint32_t sb, int tid) {
#pragma unroll 1
    for (int task = tid; task < 640; task += 256) {
        int f, c8;
        uint32_t a_cc, d_pi, d_po;
        if (task < 512) {
            f = task & 63; c8 = task >> 6;
            a_cc = sb + SM_X + (f >> 5) * 16384 + ((f >> 3) & 3) * 2048 + c8 * 128 + (f & 7) * 16;
            d_pi = 8192; d_po = 1024;
        } else {
            int n2 = task & 31;
            f = 2 * n2; c8 = (task >> 5) & 3;
            a_cc = sb + SM_X + 32768 + (n2 >> 3) * 1024 + c8 * 128 + (n2 & 7) * 16;
            d_pi = 4096; d_po = 512;
        }
        float cd, sd, cs, sn;
        __sincosf((float)(f >= 32 ? f - 64 : f) * (6.283185307179586f / 64.f), &sd, &cd);
        int a = (8 * c8 * f) & 63;
        __sincosf((float)(a >= 32 ? a - 64 : a) * (6.283185307179586f / 64.f), &sn, &cs);
        float cv[8], sv[8];
#pragma unroll
        for (int e = 0; e < 8; e++) {
            cv[e] = cs; sv[e] = sn;
            float t = cs * cd - sn * sd;
            sn = sn * cd + cs * sd;
            cs = t;
        }
        uint4 oc = make_uint4(pack_bf16(cv[0], cv[1]), pack_bf16(cv[2], cv[3]), pack_bf16(cv[4], cv[5]), pack_bf16(cv[6], cv[7]));
        uint4 os = make_uint4(pack_bf16(sv[0], sv[1]), pack_bf16(sv[2], sv[3]), pack_bf16(sv[4], sv[5]), pack_bf16(sv[6], sv[7]));
        sts128(a_cc, oc);
        sts128(a_cc + d_pi, os);
        sts128(a_cc + d_po, make_uint4(os.x ^ 0x80008000u, os.y ^ 0x80008000u, os.z ^ 0x80008000u, os.w ^ 0x80008000u));
        sts128(a_cc + d_pi + d_po, oc);
    }
}

__global__ void __launch_bounds__(NTHREADS, 1)
fused_kernel(const __grid_constant__ CUtensorMap tm_x, const __grid_constant__ CUtensorMap tm_bre,
             const __grid_constant__ CUtensorMap tm_bim, const __grid_constant__ CUtensorMap tm_cre,
             const __grid_constant__ CUtensorMap tm_cim, const __grid_constant__ CUtensorMap tm_col, const Params p) {
    extern __shared__ __align__(1024) uint8_t sm[];
    const uint32_t sb = s2u(sm);
    const int tid = threadIdx.x, b = blockIdx.x;
    const int c = b >> 3, r = b & 7;
    const int par = r & 1, pi_ = r >> 1, own = 4 * par + pi_;
    const int wg = __shfl_sync(~0u, tid >> 7, 0), w = __shfl_sync(~0u, (tid >> 5) & 3, 0), lane = tid & 31, g = lane >> 2, q = lane & 3;
    auto BAR = [&](int i) { return sb + SM_BAR + 8 * i; };
    unsigned* s_tgt = (unsigned*)(sm + SM_TGT);

    if (tid < NBARS) {
        int cnt = 1;
        if (tid >= B_EMPTY0 && tid < B_EMPTY0 + 4) cnt = 16;
        if (tid >= B_XEMPTY && tid < B_XEMPTY + 4) cnt = 24;
        if (tid == B_RFREE) cnt = 12;
        if (tid == B_HDONE || tid == B_WST) cnt = 2;
        if ((tid >= B_AEMPTY && tid < B_AEMPTY + 8) || tid == B_BFREE) cnt = 8;
        if (tid == B_AFREE) cnt = 4;
        mbar_init(BAR(tid), cnt);
        asm volatile("fence.mbarrier_init.release.cluster;" ::: "memory");
    }
    asm volatile("barrier.cluster.arrive.release.aligned;" ::: "memory");

    if (wg == 3) {
        asm volatile("setmaxnreg.dec.sync.aligned.u32 56;");
        if (w == 0 && lane < 6) {
            const CUtensorMap* tm = lane == 0 ? &tm_x : lane == 1 ? &tm_bre : lane == 2 ? &tm_bim : lane == 3 ? &tm_cre : lane == 4 ? &tm_cim : &tm_col;
            asm volatile("prefetch.tensormap [%0];" ::"l"(tm) : "memory");
        }
        __syncwarp();
        asm volatile("barrier.cluster.wait.acquire.aligned;" ::: "memory");
        if (w > 0) {
            if (w == 1) {
                float lr[3], li[3], ld[3];
#pragma unroll
                for (int k = 0; k < 3; k++) {
                    int ps = k < 2 ? 64 * r + 32 * k + lane : 32 * c + lane;
                    lr[k] = ldbf(p.lam_re + ps); li[k] = ldbf(p.lam_im + ps); ld[k] = ldbf(p.log_dt + ps);
                }
                if (lane < 6) s_tgt[lane] = ((ld_acquire(&g_bar[lane]) >> 7) + 1u) << 7;
#pragma unroll 1
                for (int k = 0; k < 3; k++) {
                    float a = k == 0 ? lr[0] : (k == 1 ? lr[1] : lr[2]), bq = k == 0 ? li[0] : (k == 1 ? li[1] : li[2]);
                    float dt = __bfloat162float(__float2bfloat16(expf(k == 0 ? ld[0] : (k == 1 ? ld[1] : ld[2]))));
                    float mag = expf(a * dt), t = bq * dt * 0.15915494309189535f, sn, cs;
                    t -= rintf(t);
                    sincospif(2.f * t, &sn, &cs);
                    float er = mag * cs, ei = mag * sn;
                    if (k < 2) {
                        *(float2*)(sm + SM_LAM + (32 * k + lane) * 8) = make_float2(er, ei);
                    } else {
                        er -= 1.f;
                        float inv = 1.f / (a * a + bq * bq);
                        *(float2*)(sm + SM_TAB + lane * 8) = make_float2((er * a + ei * bq) * inv, (ei * a - er * bq) * inv);
                    }
                }
                __syncwarp();
                bar_arrive(15, 160);
                if (lane == 0) mbar_arrive(BAR(B_SETUP), 1);
            }
            if (w == 2 && lane < 2) {
                const char* src = (const char*)(lane ? p.w_i : p.w_r) + (size_t)b * 8224;
                asm volatile("cp.async.bulk.prefetch.L2.global [%0], 8224;" ::"l"(src) : "memory");
            }
#pragma unroll 1
            for (int i = tid - 448; i < 96 + 128 && w > 1; i += 64) {
                if (i < 96) g_P[(uint32_t)(b * 4 + i / 24) * 1024 + 640 + ((i % 24) >> 1) * 32 + 30 + (i & 1)] = make_uint4(0, 0, 0, 0);
                else g_Ebuf[b * 128 + i - 96] = make_float4(0.f, 0.f, 0.f, 0.f);
            }
            __syncwarp();
            if (w > 1) bar_sync(0, 192);
            if (tid == 448) TX(14);
            if (w > 1) {
                if (lane < 8) {
                    const int cl = 8 * (w - 2) + lane;
                    asm volatile("cp.async.bulk.global.shared::cta.bulk_group [%0], [%1], 1024;" ::"l"(g_Wfrag + (uint32_t)((16 * (b & 7) + cl) * 1024 + (b >> 3) * 64)),
                                 "r"(sb + SM_H + cl * 1024) : "memory");
                }
                asm volatile("cp.async.bulk.commit_group;" ::: "memory");
                asm volatile("cp.async.bulk.wait_group 0;" ::: "memory");
                fence_async();
                __syncwarp();
                if (lane == 0) mbar_arrive(BAR(B_WST), 1);
                if (tid == 448) TX(15);
            }
            __syncwarp();
            if (w == 3) bar_arrive(11, 192);
            if (w == 2) {
                bar_sync(11, 192);
                if (lane == 0) { TX(7); red_release(&g_bar[4], 1);  }
            }
            if (w == 3) {
#pragma unroll 1
                for (int it = 0; it < 8; it++) {
                    const int m = 4 * c + (it >> 1), d = 64 * r + m, ch = lane + 32 * (it & 1);
                    float v[8];
#pragma unroll
                    for (int e = 0; e < 8; e++) {
                        int j = 8 * ch + e, f, ph;
                        dft_fp(j, f, ph);
                        int a = (d * f + ph) & 511;
                        a = a >= 256 ? a - 512 : a;
                        float wj = j == 0 ? 0.f : (j == 1 ? 1.f / 512.f : 2.f / 512.f);
                        v[e] = wj * __cosf((float)a * (6.283185307179586f / 512.f));
                    }
                    uint32_t off = (uint32_t)(64 + r * 8 + (ch >> 3)) * 8192 + (m >> 3) * 1024 + (ch & 7) * 128 + (m & 7) * 16;
                    *(uint4*)(g_E + off) = make_uint4(pack_bf16(v[0], v[1]), pack_bf16(v[2], v[3]), pack_bf16(v[4], v[5]), pack_bf16(v[6], v[7]));
                }
                __syncwarp();
                if (lane == 0) { fence_async(); red_release(&g_bar[6], 1); }
                return;
            }
            if (w == 2) {
#pragma unroll 1
                for (int it = 0; it < 4; it++) {
                    const int hf = it & 1;
                    __syncwarp();
                    if (hf == 0) bar_sync(13, 288); else bar_sync(6, 416);
                    if (lane == 0) {
                        const uint32_t src = sb + SM_HH + par * 32768 + hf * 16384;
                        bulk_s2peer(mapa(src, par ^ 1), src, 16384, mapa(BAR(hf ? B_HPEER1 : B_HPEER), par ^ 1));
                    }
                }
                return;
            }
            bar_sync(2, 288);
            if (lane == 0) {
                TX(5);
                fence_async();
                red_release(&g_bar[0], 1);
                TX(6);
            }
            __syncwarp();

            bar_sync(12, 160);
            if (lane == 0) {
                asm volatile("cp.async.bulk.global.shared::cta.bulk_group [%0], [%1], 8192;" ::"l"(g_A1 + (uint32_t)(((c >> 1) * 8 + r) * 16384 + (c & 1) * 8192)),
                             "r"(sb + SM_B1ST) : "memory");
                asm volatile("cp.async.bulk.commit_group;" ::: "memory");
                asm volatile("cp.async.bulk.wait_group 0;" ::: "memory");
                mbar_arrive(BAR(B_B1DONE), 1);
                fence_async();
                red_release(&g_bar[7], 1);
            }
#pragma unroll 1
            for (int layer = 0; layer < 2; layer++) {
                __syncwarp();
                bar_sync(5, 416);
                if (lane == 0) {
                    TX(0 + 8 * layer);
                    tma_store_5d(&tm_col, 32 * (b & 1), 0, b >> 1, 0, layer, sb + SM_RAW);
                    asm volatile("cp.reduce.async.bulk.global.shared::cta.bulk_group.add.f32 [%0], [%1], 8192;" ::"l"(g_ssqc + (layer * 16 + (b & 15)) * 2048),
                                 "r"(sb + SM_SSQ) : "memory");
                    asm volatile("cp.async.bulk.commit_group;" ::: "memory");
                    asm volatile("cp.async.bulk.wait_group 0;" ::: "memory");
                    TX(1 + 8 * layer);
                    fence_async();
                    red_release(&g_bar[1 + 2 * layer], 1);
                    TX(2 + 8 * layer);
                }
            }
        } else if (tid == 384) {
#pragma unroll 1
            for (int kb = 0; kb < 8; kb++) {
                uint32_t fb = BAR(B_FULL0 + kb);
                mbar_expect(fb, 16384);
                tma_5d_mc(sb + SM_A + 65536 + kb * 16384 + par * 8192, &tm_x, kb * 64, 0, 0, 8 * par, c, fb);
            }
#pragma unroll 1
            for (int k2 = 0; k2 < 8; k2++) {
                asm volatile("cp.async.bulk.prefetch.tensor.2d.L2.global [%0, {%1,%2}];" ::"l"(par ? &tm_bim : &tm_bre), "r"(k2 * 64), "r"(32 * c) : "memory");
                if ((k2 & 1) == par)
                    asm volatile("cp.async.bulk.prefetch.tensor.2d.L2.global [%0, {%1,%2}];" ::"l"((c & 1) ? &tm_cim : &tm_cre), "r"(64 * (c >> 1)), "r"(k2 * 64) : "memory");
            }
            mbar_wait(BAR(B_SETUP), 0);
#pragma unroll 1
            for (int layer = 0; layer < 2; layer++) {
                if (layer == 1) {
                    mbar_wait(BAR(B_AEMPTY + 6), 1);
                    mbar_expect(BAR(B_WRDY), 16384);
                    bulk_g2s(sb + SM_H + 16384, g_Wfrag + (uint32_t)b * 1024, 16384, BAR(B_WRDY));
                }
                wait_count(&g_bar[2 * layer], s_tgt[2 * layer]);
                TX(4 + 8 * layer);
                fence_async();
                mbar_expect(BAR(B_COL), 16384 + 8192);
                tma_5d(sb + SM_RAW, &tm_col, 32 * (b & 1), 0, b >> 1, 0, layer, BAR(B_COL));
                bulk_g2s(sb + SM_SSQ, g_ssq + layer * 2048, 8192, BAR(B_COL));
                if (layer == 0) {
                    wait_count(&g_bar[4], s_tgt[4]);
                    fence_async();
                    TX(16);
                    mbar_wait(BAR(B_B1DONE), 0);
                    TX(17);
                    mbar_expect(BAR(B_WRDY), 16384);
                    bulk_g2s(sb + SM_H + 16384, g_Wfrag + (uint32_t)b * 1024, 16384, BAR(B_WRDY));
                    wait_count(&g_bar[7], s_tgt[4]);
                    fence_async();
                }
                if (layer == 0) mbar_wait(BAR(B_AFREE), 0);
                mbar_wait(BAR(B_COL), layer);
#pragma unroll 1
                for (int s = 0; s < 8; s++) {
                    if (layer == 1) mbar_wait(BAR(B_AEMPTY + s), 1);
                    if (s >= 2) mbar_wait(BAR(B_AFULL + s - 2), 0);
                    mbar_expect(BAR(B_AFULL + s), 16384);
                    bulk_g2s(sb + SM_A + s * 16384, g_A1 + (uint32_t)(r * 8 + s) * 16384, 16384, BAR(B_AFULL + s));
                }
                if (layer == 1) wait_count(&g_bar[6], s_tgt[4]);
                wait_count(&g_bar[1 + 2 * layer], s_tgt[1 + 2 * layer]);
                TX(3 + 8 * layer);
                fence_async();
                const uint8_t* xsrc = g_X + (uint32_t)(layer * 16 + c) * 8 * 16384;
                const uint8_t* esrc = g_E + (uint32_t)(layer * 8 + own) * 8 * 8192;
                mbar_arrive(BAR(B_SSQ), 1);
                mbar_expect(BAR(B_HPEER), 16384);
                mbar_expect(BAR(B_HPEER1), 16384);
#pragma unroll 1
                for (int it = 0; it < 16; it++) {
                    if (it < 8) {
                        int st = it & 3, f = layer * 2 + (it >> 2);
                        if (f > 0) mbar_wait_cluster(BAR(B_XEMPTY + st), (f - 1) & 1);
                        mbar_expect(BAR(B_XFULL + st), 24576);
                        bulk_g2s_mc(sb + SM_X + st * 24576 + par * 8192, xsrc + (uint32_t)it * 16384 + par * 8192, 8192, BAR(B_XFULL + st));
                        bulk_g2s(sb + SM_X + st * 24576 + 16384, esrc + (uint32_t)it * 8192, 8192, BAR(B_XFULL + st));
                    }
                    if (it >= 8) {
                        if (it == 8) mbar_wait(BAR(B_AEMPTY + 5), 0);
                        int s = it - 8, tile = 4 * par + ((pi_ + 1 + (s >> 1)) & 3), sl = r ^ (s & 1);
                        mbar_wait(BAR(B_AEMPTY + s), 0);
                        uint32_t fb = BAR(B_AFULL + s), dst = sb + SM_A + s * 16384;
                        mbar_expect(fb, 16384);
                        if (layer == 1) {
                            tma_2d(dst, &tm_cre, 64 * sl, 64 * tile, fb);
                            tma_2d(dst + 8192, &tm_cim, 64 * sl, 64 * tile, fb);
                        } else {
                            bulk_g2s(dst, g_A2 + (uint32_t)(sl * 8 + tile) * 16384, 16384, fb);
                        }
                    }
                }
            }
        }
        return;
    }

    asm volatile("setmaxnreg.inc.sync.aligned.u32 152;");
    if (tid >= 96 && tid < 112) g_ssq[2048 + 16 * b + tid - 96] = 0.f;
    if (tid >= 128 && tid < 256) ((float4*)g_ssqc)[b * 128 + tid - 128] = make_float4(0.f, 0.f, 0.f, 0.f);
    TS(0);
    if (wg == 0) TC(30);
    {
        const int f = 32 * r + lane;
        float cd, sd;
        __sincosf((float)f * (6.283185307179586f / 512.f), &sd, &cd);
        const uint32_t dst = sb + SM_A + (lane >> 2) * 1024 + (lane & 3) * 32;
#pragma unroll 1
        for (int ch = tid >> 5; ch < 64; ch += 12) {
            int a = (8 * ch * f) & 511;
            a = a >= 256 ? a - 512 : a;
            float cs, sn;
            __sincosf((float)a * (6.283185307179586f / 512.f), &sn, &cs);
            float cv[8], sv[8];
#pragma unroll
            for (int e = 0; e < 8; e++) {
                cv[e] = cs; sv[e] = -sn;
                float t = cs * cd - sn * sd;
                sn = sn * cd + cs * sd;
                cs = t;
            }
            uint4 o1 = make_uint4(pack_bf16(sv[0], sv[1]), pack_bf16(sv[2], sv[3]), pack_bf16(sv[4], sv[5]), pack_bf16(sv[6], sv[7]));
            if (f == 0) o1 = make_uint4(0xbf803f80u, 0xbf803f80u, 0xbf803f80u, 0xbf803f80u);
            uint32_t a0 = dst + (ch >> 3) * 8192 + (ch & 7) * 128;
            sts128(a0, make_uint4(pack_bf16(cv[0], cv[1]), pack_bf16(cv[2], cv[3]), pack_bf16(cv[4], cv[5]), pack_bf16(cv[6], cv[7])));
            sts128(a0 + 16, o1);
        }
    }
    fence_async_smem();
    asm volatile("barrier.cluster.wait.acquire.aligned;" ::: "memory");
    bar_sync(10, 384);
    TS(1);
    if (wg < 2) {
        float acc[32];
        acc_def(acc);
        const int npos = 16 * r + 8 * wg + 2 * w;
        float sh0 = 0.f, sh1 = 0.f, s0 = 0.f, s1 = 0.f, q0 = 0.f, q1 = 0.f;
#pragma unroll 1
        for (int kb = 0; kb < 8; kb++) {
            uint32_t slot = sb + SM_A + 65536 + kb * 16384;
            mbar_wait(BAR(B_FULL0 + kb), 0);
            wg_fence();
#pragma unroll
            for (int ks = 0; ks < 4; ks++)
                wgmma_n64<0>(acc, desc_a(sb + SM_A + kb * 8192 + ks * 256), desc_k(slot + wg * 8192 + ks * 32), 1);
            wg_commit();
            {
                uint32_t v0 = lds32(slot + npos * 128 + lane * 4), v1 = lds32(slot + npos * 128 + 128 + lane * 4);
                if (kb == 0) { sh0 = __shfl_sync(~0u, bf_lo(v0), 0); sh1 = __shfl_sync(~0u, bf_lo(v1), 0); }
                float a = bf_lo(v0) - sh0, bq = bf_hi(v0) - sh0, cq = bf_lo(v1) - sh1, d = bf_hi(v1) - sh1;
                s0 += a + bq; q0 += a * a + bq * bq; s1 += cq + d; q1 += cq * cq + d * d;
            }
            wg_wait<1>();
            if (kb > 0 && kb <= 4 && lane == 0) { mbar_arrive(BAR(B_EMPTY0 + kb - 1), 1); mbar_arrive_remote(mapa(BAR(B_EMPTY0 + kb - 1), par ^ 1)); }
        }
#pragma unroll
        for (int o = 16; o; o >>= 1) {
            s0 += __shfl_xor_sync(~0u, s0, o); q0 += __shfl_xor_sync(~0u, q0, o);
            s1 += __shfl_xor_sync(~0u, s1, o); q1 += __shfl_xor_sync(~0u, q1, o);
        }
        if (lane == 0) *(float2*)(g_ssq + 128 * c + npos) = make_float2(fmaxf(q0 - s0 * s0 * (1.f / 512.f), 0.f), fmaxf(q1 - s1 * s1 * (1.f / 512.f), 0.f));
        wg_wait<0>();
        TS(2);
        uint8_t* dst = g_X + (uint32_t)((c * 8 + r) * 16384 + w * 4096 + wg * 1024 + g * 16 + 4 * q);
#pragma unroll
        for (int i = 0; i < 8; i++) {
            *(uint32_t*)(dst + i * 128) = pack_bf16(acc[4 * i], acc[4 * i + 1]);
            *(uint32_t*)(dst + 2048 + i * 128) = pack_bf16(acc[4 * i + 2], acc[4 * i + 3]);
        }
        bar_sync(2, 288);
        mbar_wait(BAR(B_SETUP), 0);
        TS(3);
    }

    if (wg == 2) {
        {
            uint4 p0 = __ldg((const uint4*)p.dskip + 2 * lane), p1 = __ldg((const uint4*)p.dskip + 2 * lane + 1);
            uint32_t u[8] = {p0.x, p0.y, p0.z, p0.w, p1.x, p1.y, p1.z, p1.w};
            int j = 64 * r + 4 * c + w, f, ph;
            dft_fp(j, f, ph);
            float s = 0.f;
            int idx = 16 * lane * f + ph;
#pragma unroll
            for (int i = 0; i < 16; i++) {
                int a = idx & 511;
                idx += f;
                a = a >= 256 ? a - 512 : a;
                s += ((i & 1) ? bf_hi(u[i >> 1]) : bf_lo(u[i >> 1])) * __cosf((float)a * (6.283185307179586f / 512.f));
            }
#pragma unroll
            for (int o = 16; o; o >>= 1) s += __shfl_xor_sync(~0u, s, o);
            if (lane == 0) g_Dh[j] = s;
        }
        mbar_wait(BAR(B_FULL0 + 7), 0);
        if (tid == 256) {
#pragma unroll 1
            for (int s = 0; s < 4; s++) mbar_wait_cluster(BAR(B_EMPTY0 + s), 0);
            mbar_expect(BAR(B_FULLB), 65536);
#pragma unroll 1
            for (int k2 = 0; k2 < 8; k2++)
                tma_2d_mc(sb + SM_A + 65536 + k2 * 8192 + par * 4096, par ? &tm_bim : &tm_bre, k2 * 64, 32 * c, BAR(B_FULLB));
        }
        __syncwarp();
        {
            const int cl = tid & 15, cb = 16 * (b & 7) + cl;
            const int c0 = cb == 0 ? 256 : 2 * cb, c1 = 2 * cb + 1;
            uint32_t wf[2][16];
#pragma unroll
            for (int h = 0; h < 2; h++) {
                const int kq = 16 * (b >> 3) + ((tid & 127) >> 4) + 8 * h, k1 = kq >> 2, qq = kq & 3;
                const unsigned short* wr_ = (const unsigned short*)p.w_r + (k1 + 128 * qq) * 257;
                const unsigned short* wi_ = (const unsigned short*)p.w_i + (k1 + 128 * qq) * 257;
#pragma unroll
                for (int i = 0; i < 4; i++) {
                    int o = 512 * i * 257;
                    wf[h][2 * i] = (uint32_t)__ldg(wr_ + o + c0) | ((uint32_t)__ldg(wr_ + o + 64 * 257 + c0) << 16);
                    wf[h][2 * i + 1] = ((uint32_t)__ldg(wi_ + o + c0) | ((uint32_t)__ldg(wi_ + o + 64 * 257 + c0) << 16)) ^ 0x80008000u;
                    wf[h][8 + 2 * i] = (uint32_t)__ldg(wr_ + o + c1) | ((uint32_t)__ldg(wr_ + o + 64 * 257 + c1) << 16);
                    wf[h][8 + 2 * i + 1] = ((uint32_t)__ldg(wi_ + o + c1) | ((uint32_t)__ldg(wi_ + o + 64 * 257 + c1) << 16)) ^ 0x80008000u;
                }
            }
#pragma unroll
            for (int h = 0; h < 2; h++)
#pragma unroll
                for (int i = 0; i < 4; i++)
                    sts128(sb + SM_H + cl * 1024 + (((tid & 127) >> 4) + 8 * h) * 64 + ((i ^ ((tid >> 5) & 3)) << 4),
                           make_uint4(wf[h][4 * i], wf[h][4 * i + 1], wf[h][4 * i + 2], wf[h][4 * i + 3]));
            fence_async_smem();
            bar_arrive(0, 192);
            bar_arrive(11, 192);
        }
        bar_sync(15, 160);
        float acc[32];
        acc_def(acc);
        mbar_wait(BAR(B_FULLB), 0);
        wg_fence();
#pragma unroll 1
        for (int kb = 0; kb < 8; kb++) {
#pragma unroll
            for (int ks = 0; ks < 4; ks++)
                wgmma_n64<0>(acc, desc_a(sb + SM_A + kb * 8192 + ks * 256), desc_k(sb + SM_A + 65536 + kb * 8192 + ks * 32), 1);
            wg_commit();
        }
        wg_wait<0>();
        if (lane == 0) { mbar_arrive(BAR(B_BFREE), 1); mbar_arrive_remote(mapa(BAR(B_BFREE), par ^ 1)); }
        if (tid == 256) {
            mbar_wait_cluster(BAR(B_BFREE), 0);
            mbar_expect(BAR(B_FULLC), 65536);
#pragma unroll 1
            for (int k2 = par; k2 < 8; k2 += 2)
                tma_2d_mc(sb + SM_A + 65536 + k2 * 8192, (c & 1) ? &tm_cim : &tm_cre, 64 * (c >> 1), k2 * 64, BAR(B_FULLC));
        }
        __syncwarp();
        {
            uint8_t* dst = sm + SM_B1ST + w * 256 + q * 32 + g * 2;
            const float wj0 = (r == 0 && w == 0 && g < 2) ? (g == 0 ? 0.f : 1.f / 512.f) : 2.f / 512.f;
#pragma unroll
            for (int i = 0; i < 4; i++) {
#pragma unroll
                for (int e = 0; e < 2; e++) {
                    float2 cf = *(const float2*)(sm + SM_TAB + (8 * i + 2 * q + e) * 8);
#pragma unroll
                    for (int h = 0; h < 2; h++) {
                        float wj = h == 0 ? wj0 : 2.f / 512.f;
                        float pr = acc[4 * i + 2 * h + e] * wj, pi = acc[16 + 4 * i + 2 * h + e] * wj;
                        uint8_t* d2 = dst + i * 2048 + h * 128 + e * 16;
                        *(__nv_bfloat16*)(d2) = __float2bfloat16(cf.x * pr - cf.y * pi);
                        *(__nv_bfloat16*)(d2 + 1024) = __float2bfloat16(cf.x * pi + cf.y * pr);
                    }
                }
            }
            fence_async_smem();
            bar_arrive(12, 160);
        }
        acc_def(acc);
        mbar_wait(BAR(B_FULLC), 0);
        wg_fence();
#pragma unroll 1
        for (int kb = 0; kb < 8; kb++) {
#pragma unroll
            for (int ks = 0; ks < 4; ks++)
                wgmma_n64<1>(acc, desc_a(sb + SM_A + kb * 8192 + ks * 256), desc_mn(sb + SM_A + 65536 + kb * 8192 + ks * 2048, 8192), 1);
            wg_commit();
        }
        wg_wait<0>();
        fence_async_smem();
        if (lane == 0) mbar_arrive(BAR(B_AFREE), 1);
        uint8_t* dst = g_A2 + (uint32_t)(((c >> 1) * 8 + r) * 16384 + (c & 1) * 8192 + w * 2048 + g * 16 + 4 * q);
#pragma unroll
        for (int i = 0; i < 8; i++) {
            *(uint32_t*)(dst + i * 128) = pack_bf16(acc[4 * i], acc[4 * i + 1]);
            *(uint32_t*)(dst + 1024 + i * 128) = pack_bf16(acc[4 * i + 2], acc[4 * i + 3]);
        }
        {
            const int m = 4 * c + w, jp = 64 * r + m;
            int fp, php;
            dft_fp(jp, fp, php);
            const __nv_bfloat16* dh = (const __nv_bfloat16*)(sm + SM_RSTD);
            if (tid == 256) wait_count(&g_bar[4], s_tgt[4]);
            bar_sync(3, 128);
            float4 d4 = __ldcg((const float4*)g_Dh + (tid - 256));
            *(uint2*)(sm + SM_RSTD + (tid - 256) * 8) = make_uint2(pack_bf16(d4.x, d4.y), pack_bf16(d4.z, d4.w));
            bar_sync(3, 128);
#pragma unroll 1
            for (int it = 0; it < 2; it++) {
                const int ch = lane + 32 * it;
                float v[8];
#pragma unroll
                for (int e = 0; e < 8; e++) {
                    int j = 8 * ch + e, f, ph;
                    dft_fp(j, f, ph);
                    float wj = j == 0 ? 0.f : (j == 1 ? 1.f / 512.f : 2.f / 512.f);
                    float gsum = 0.f;
#pragma unroll
                    for (int sgn = 0; sgn < 2; sgn++) {
                        int mm = (sgn ? f - fp : f + fp) & 511, pp = (sgn ? ph - php : ph + php) & 511;
                        if (mm > 256) { mm = 512 - mm; pp = (512 - pp) & 511; }
                        int odd = (pp >> 7) & 1;
                        float t = __bfloat162float(dh[mm == 256 ? 1 : 2 * mm + odd]);
                        if (odd && (mm & 255) == 0) t = 0.f;
                        gsum += (pp & 256) ? -t : t;
                    }
                    v[e] = 0.5f * wj * gsum;
                }
                uint32_t off = (uint32_t)(r * 8 + (ch >> 3)) * 8192 + (m >> 3) * 1024 + (ch & 7) * 128 + (m & 7) * 16;
                *(uint4*)(g_E + off) = make_uint4(pack_bf16(v[0], v[1]), pack_bf16(v[2], v[3]), pack_bf16(v[4], v[5]), pack_bf16(v[6], v[7]));
            }
        }
    }

#pragma unroll 1
    for (int layer = 0; layer < 2; layer++) {
        if (wg < 2) {
            const int n1 = 32 * wg + 8 * w + g;
            const int ct = n1 >> 2;
            gen_col_consts(sb, tid);
            uint32_t tr2[4], ti2[4], tn2[4];
#pragma unroll
            for (int i = 0; i < 4; i++) {
                float cr[2], ci[2];
#pragma unroll
                for (int e = 0; e < 2; e++) {
                    int a = (n1 * (8 * i + 2 * q + e)) & 2047;
                    a = a >= 1024 ? a - 2048 : a;
                    float ang = (float)a * (-6.283185307179586f / 2048.f);
                    cr[e] = __cosf(ang); ci[e] = __sinf(ang);
                }
                tr2[i] = pack_bf16(cr[0], cr[1]); ti2[i] = pack_bf16(ci[0], ci[1]); tn2[i] = ti2[i] ^ 0x80008000u;
            }
            mbar_wait(BAR(B_WST), 0);
            mbar_wait(BAR(B_COL), layer);
            TS(4 + 12 * layer);
            if (wg == 0) TC(0 + 10 * layer);
            const uint32_t rw0 = sb + SM_RAW + ct * 1024 + q * 64 + ((q >> 1) << 4) + (g & 3) * 4, rw1 = rw0 ^ 16;
            const int pos0 = 128 * ct + 8 * q + 2 * (g & 3);
            const int sw = b == 0 ? 1 : 0;
            uint32_t xr[4][4];
            const uint32_t st0 = sb + SM_H + (n1 >> 3) * 1024 + g * 16 + 4 * q;
#pragma unroll
            for (int i = 0; i < 4; i++) {
                float2 sq = *(const float2*)(sm + SM_SSQ + (pos0 + 32 * i) * 4);
                const uint32_t rs2 = pack_bf16(rsqrtf(sq.x * (1.f / 512.f) + 1e-5f), rsqrtf(sq.y * (1.f / 512.f) + 1e-5f));
#pragma unroll
                for (int jj = 0; jj < 4; jj++) {
                    const int K = jj ^ (2 * (i & 1));
                    uint32_t a = ((K & 1) ? rw1 : rw0) + i * 256 + (K & 2) * 16;
                    if (jj < 2) a ^= sw << 4;
                    uint32_t v = lds32(a);
                    xr[jj][i] = v;
                    uint32_t o = hmul2(v, rs2);
                    if (jj == 1 && sw) o = 0u;
                    sts32(st0 + (jj & 1) * 8192 + (4 * (jj >> 1) + i) * 128, o);
                }
            }
            if (wg == 0) TC(1 + 10 * layer);
            fence_async_smem();
            bar_sync(1, 256);
            float acc[32];
            const uint32_t s1a = sb + SM_X + wg * 16384, s2b = sb + SM_X + 32768;
            wg_fence();
#pragma unroll
            for (int ks = 0; ks < 8; ks++)
                wgmma_n64<1>(acc, desc_a(s1a + (ks >> 2) * 8192 + (ks & 3) * 256), desc_b<64>(sb + SM_H + ks * 2048), ks != 0);
            wg_commit();
            wg_wait<0>();
            if (wg == 0) TC(2 + 10 * layer);
            uint32_t are[2][4], aim[2][4];
#pragma unroll
            for (int col = 0; col < 2; col++) {
#pragma unroll
                for (int i = 0; i < 4; i++) {
                    int o = 4 * (4 * col + i);
                    uint32_t zr = pack_bf16(acc[o], acc[o + 1]), zi = pack_bf16(acc[o + 2], acc[o + 3]);
                    are[col][i] = hfma2(zr, tr2[i], hmul2(zi, tn2[i]));
                    aim[col][i] = hfma2(zr, ti2[i], hmul2(zi, tr2[i]));
                }
            }
            wg_fence();
#pragma unroll
            for (int ks = 0; ks < 2; ks++)
                wgmma_n64_rs(acc, are[0][2 * ks], are[1][2 * ks], are[0][2 * ks + 1], are[1][2 * ks + 1], desc_b<64>(s2b + ks * 2048), ks != 0);
#pragma unroll
            for (int ks = 0; ks < 2; ks++)
                wgmma_n64_rs(acc, aim[0][2 * ks], aim[1][2 * ks], aim[0][2 * ks + 1], aim[1][2 * ks + 1], desc_b<64>(s2b + 4096 + ks * 2048), 1);
            wg_commit();
            uint32_t wf[16];
            mbar_wait(BAR(B_WRDY), layer);
#pragma unroll
            for (int i = 0; i < 4; i++) {
                const int kq = n1 * 4 + q;
                uint4 v = *(const uint4*)(sm + SM_H + 16384 + kq * 64 + ((i ^ ((kq >> 1) & 3)) << 4));
                wf[4 * i] = v.x; wf[4 * i + 1] = v.y; wf[4 * i + 2] = v.z; wf[4 * i + 3] = v.w;
            }
            wg_wait<0>();
            if (wg == 0) TC(3 + 10 * layer);
#pragma unroll
            for (int col = 0; col < 2; col++) {
#pragma unroll
                for (int i = 0; i < 4; i++) {
                    uint32_t wr = wf[col * 8 + 2 * i], wn = wf[col * 8 + 2 * i + 1];
                    uint32_t zr = pack_bf16(acc[4 * i + 2 * col], acc[4 * i + 2 * col + 1]);
                    uint32_t zi = pack_bf16(acc[16 + 4 * i + 2 * col], acc[16 + 4 * i + 2 * col + 1]);
                    are[col][i] = hfma2(zr, wr, hmul2(zi, wn));
                    aim[col][i] = hfma2(zr, wn, hmul2(zi ^ 0x80008000u, wr));
                }
            }
            wg_fence();
#pragma unroll
            for (int ks = 0; ks < 2; ks++)
                wgmma_n64_rs(acc, are[0][2 * ks], are[1][2 * ks], are[0][2 * ks + 1], are[1][2 * ks + 1], desc_b<64>(s2b + ks * 2048), ks != 0);
#pragma unroll
            for (int ks = 0; ks < 2; ks++)
                wgmma_n64_rs(acc, aim[0][2 * ks], aim[1][2 * ks], aim[0][2 * ks + 1], aim[1][2 * ks + 1], desc_b<64>(s2b + 4096 + ks * 2048), 1);
            wg_commit();
            wg_wait<0>();
            if (wg == 0) TC(4 + 10 * layer);
            bar_sync(1, 256);
#pragma unroll
            for (int col = 0; col < 2; col++) {
#pragma unroll
                for (int i = 0; i < 4; i++) {
                    uint32_t zr = pack_bf16(acc[4 * i + 2 * col], acc[4 * i + 2 * col + 1]);
                    uint32_t zi = pack_bf16(acc[16 + 4 * i + 2 * col], acc[16 + 4 * i + 2 * col + 1]);
                    sts32(st0 + 16384 + (4 * col + i) * 128, hfma2(zr, tr2[i], hmul2(zi, tn2[i])));
                    sts32(st0 + 16384 + 8192 + (4 * col + i) * 128, hfma2(zr, ti2[i], hmul2(zi, tr2[i])));
                }
            }
            if (wg == 0) TC(5 + 10 * layer);
            fence_async_smem();
            bar_sync(1, 256);
            wg_fence();
#pragma unroll
            for (int ks = 0; ks < 8; ks++)
                wgmma_n64<1>(acc, desc_a(s1a + (ks >> 2) * 8192 + (ks & 3) * 256), desc_b<64>(sb + SM_H + 16384 + ks * 2048), ks != 0);
            wg_commit();
            wg_wait<0>();
            if (wg == 0) TC(6 + 10 * layer);
            const float sc = 1.f / 2048.f;
            const float sci0 = sw ? 0.f : -sc;
            const float wr0 = sw ? 0.5f : 1.f, wi0 = sw ? 0.f : 1.f;
#pragma unroll
            for (int i = 0; i < 4; i++) {
                float ss0, ss1;
#pragma unroll
                for (int col = 0; col < 2; col++) {
                    int o = 4 * (4 * col + i);
                    uint32_t vr = xr[2 * col][i], vi = xr[2 * col + 1][i];
                    float si = col == 0 ? sci0 : -sc;
                    uint32_t nr = pack_bf16(fmaf(acc[o], sc, bf_lo(vr)), fmaf(acc[o + 1], sc, bf_hi(vr)));
                    uint32_t ni = pack_bf16(fmaf(acc[o + 2], si, bf_lo(vi)), fmaf(acc[o + 3], si, bf_hi(vi)));
                    float a0 = bf_lo(nr), a1 = bf_hi(nr), b0 = bf_lo(ni), b1 = bf_hi(ni);
                    if (col == 0) {
                        ss0 = wr0 * a0 * a0 + wi0 * b0 * b0;
                        ss1 = wr0 * a1 * a1 + wi0 * b1 * b1;
                    } else {
                        ss0 += a0 * a0 + b0 * b0;
                        ss1 += a1 * a1 + b1 * b1;
                    }
                    const int K = (2 * col) ^ (2 * (i & 1));
                    uint32_t a = rw0 + i * 256 + K * 16;
                    if (col == 0) a ^= sw << 4;
                    sts32(a, nr);
                    sts32(a ^ 16, ni);
                }
                *(float2*)(sm + SM_SSQ + (pos0 + 32 * i) * 4) = make_float2(ss0 * (2.f / 512.f), ss1 * (2.f / 512.f));
            }
            fence_async_smem();
        }
        TS(5 + 12 * layer);
        if (wg == 0) TC(7 + 10 * layer);
        bar_arrive(5, 416);

        float acc[64];
        float* s_rstd = (float*)(sm + SM_RSTD);
        float* s_mean = (float*)(sm + SM_MEAN);
        const unsigned epoch = s_tgt[0] >> 7;
        const uint32_t pt3 = 1u + (2u * epoch + layer) % 3u;
        const uint32_t ptag = (pt3 & 1u) | ((pt3 & 2u) << 15);
        const uint64_t dstep = layer == 0 ? 16 : 2;
        auto c_desc = [&](int s) { return layer == 0 ? desc_a(sb + SM_A + s * 16384) : desc_k(sb + SM_A + s * 16384); };
        if (wg < 2) {
            const int prow = 32 * wg + 8 * w + g;
            const float2 l1 = *(const float2*)(sm + SM_LAM + prow * 8);
            float lr32 = l1.x, li32 = l1.y;
#pragma unroll
            for (int i = 0; i < 5; i++) { float t = lr32 * lr32 - li32 * li32; li32 = 2.f * lr32 * li32; lr32 = t; }
            float lr128 = lr32, li128 = li32;
#pragma unroll
            for (int i = 0; i < 2; i++) { float t = lr128 * lr128 - li128 * li128; li128 = 2.f * lr128 * li128; lr128 = t; }
            const float lr1 = l1.x, li1 = l1.y;
            const float l2r = lr128 * lr128 - li128 * li128, l2i = 2.f * lr128 * li128;
            const float l4r = l2r * l2r - l2i * l2i, l4i = 2.f * l2r * l2i;
            float lxr = 1.f, lxi = 0.f;
            {
                const int rho = (c - 1 - q) & 3;
                if (rho & 1) { lxr = lr128; lxi = li128; }
                if (rho & 2) { float t = lxr * l2r - lxi * l2i; lxi = lxr * l2i + lxi * l2r; lxr = t; }
            }
            acc_def(acc);
#pragma unroll 1
            for (int kb = 0; kb < 8; kb++) {
                mbar_wait(BAR(B_AFULL + kb), 0);
                mbar_wait(BAR(B_XFULL + (kb & 3)), (kb >> 2) & 1);
                wg_fence();
#pragma unroll
                for (int ks = 0; ks < 4; ks++)
                    wgmma_n128<1>(acc, desc_a(sb + SM_A + kb * 16384 + wg * 8192 + ks * 256),
                                  desc_b<128>(sb + SM_X + (kb & 3) * 24576 + ks * 4096), 1);
                wg_commit();
                wg_wait<1>();
                if (kb > 0 && lane == 0) {
                    mbar_arrive(BAR(B_AEMPTY + kb - 1), 1); mbar_arrive(BAR(B_XEMPTY + ((kb - 1) & 3)), 1);
                    mbar_arrive_remote(mapa(BAR(B_XEMPTY + ((kb - 1) & 3)), par ^ 1));
                }
            }
            wg_wait<0>();
            if (lane == 0) {
                mbar_arrive(BAR(B_AEMPTY + 7), 1); mbar_arrive(BAR(B_XEMPTY + 3), 1);
                mbar_arrive_remote(mapa(BAR(B_XEMPTY + 3), par ^ 1)); mbar_arrive_remote(mapa(BAR(B_RFREE), par ^ 1));
            }
            bar_arrive(14, 384);
            TS(6 + 12 * layer);
            bar_sync(4, 384);
            TS(7 + 12 * layer);
            float er = 0.f, ei = 0.f;
#pragma unroll
            for (int i = 0; i < 16; i++) {
                float2 rs = *(const float2*)(s_rstd + 128 + 8 * i + 2 * q);
                acc[4 * i] *= rs.x; acc[4 * i + 1] *= rs.y; acc[4 * i + 2] *= rs.x; acc[4 * i + 3] *= rs.y;
                float nr = lr1 * er - li1 * ei + acc[4 * i], ni = lr1 * ei + li1 * er + acc[4 * i + 2];
                er = lr1 * nr - li1 * ni + acc[4 * i + 1];
                ei = lr1 * ni + li1 * nr + acc[4 * i + 3];
            }
            float cr = 0.f, ci = 0.f, tr = 0.f, ti = 0.f;
#pragma unroll
            for (int qq = 0; qq < 4; qq++) {
                float xr_ = __shfl_sync(~0u, er, (lane & ~3) | qq), xi_ = __shfl_sync(~0u, ei, (lane & ~3) | qq);
                if (qq == q) { cr = tr; ci = ti; }
                float nr = lr32 * tr - li32 * ti + xr_, ni = lr32 * ti + li32 * tr + xi_;
                tr = nr; ti = ni;
            }
            float4* eb = g_Ebuf + (uint32_t)(layer * 16 * 512 + 64 * r + prow);
            if (q == 0 && c < 15) st_relaxed_f4(eb + c * 512, make_float4(tr, ti, __uint_as_float(epoch), 0.f));
            TS(8 + 12 * layer);
            float pr[4], pi[4];
            {
                unsigned n = 0;
                bool ok;
#pragma unroll 1
                do {
                    ok = true;
#pragma unroll
                    for (int k = 0; k < 4; k++) {
                        float4 v = make_float4(0.f, 0.f, __uint_as_float(epoch), 0.f);
                        if (4 * k + q < c) v = ld_relaxed_f4(eb + (4 * k + q) * 512);
                        pr[k] = v.x; pi[k] = v.y;
                        ok = ok && __float_as_uint(v.z) == epoch;
                    }
                } while (!ok && ++n < SPIN_LIMIT);
            }
            __syncwarp();
            TS(9 + 12 * layer);
            float hr = 0.f, hi = 0.f;
#pragma unroll
            for (int k = 0; k < 4; k++) {
                if (4 * k + q < c) {
                    float nr = l4r * hr - l4i * hi + pr[k], ni = l4r * hi + l4i * hr + pi[k];
                    hr = nr; hi = ni;
                }
            }
            {
                float nr = lxr * hr - lxi * hi, ni = lxr * hi + lxi * hr;
                hr = nr + __shfl_xor_sync(~0u, nr, 1); hi = ni + __shfl_xor_sync(~0u, ni, 1);
                hr += __shfl_xor_sync(~0u, hr, 2); hi += __shfl_xor_sync(~0u, hi, 2);
            }
#pragma unroll
            for (int qq = 0; qq < 3; qq++) {
                if (qq < q) { float nr = lr32 * hr - li32 * hi, ni = lr32 * hi + li32 * hr; hr = nr; hi = ni; }
            }
            er = cr + hr; ei = ci + hi;
            bar_sync(7, 384);
            mbar_wait_cluster(BAR(B_RFREE), layer);
            const uint32_t ha = sb + SM_HH + par * 32768 + (prow >> 3) * 1024 + g * 16 + 4 * q;
#pragma unroll
            for (int i = 0; i < 16; i++) {
                float nr = lr1 * er - li1 * ei + acc[4 * i], ni = lr1 * ei + li1 * er + acc[4 * i + 2];
                er = lr1 * nr - li1 * ni + acc[4 * i + 1];
                ei = lr1 * ni + li1 * nr + acc[4 * i + 3];
                sts32(ha + (i >> 3) * 16384 + (i & 7) * 128, pack_bf16(nr, er));
                sts32(ha + (i >> 3) * 16384 + 8192 + (i & 7) * 128, pack_bf16(ni, ei));
                if (i == 7) { fence_async_smem(); bar_arrive(13, 288); }
            }
            fence_async_smem();
            acc_def(acc);
            float acc2[32];
            acc_def(acc2);
            TS(10 + 12 * layer);
            bar_sync(6, 416);
            TS(11 + 12 * layer);
            float (&a0)[32] = *reinterpret_cast<float (*)[32]>(&acc[0]);
            float (&a1)[32] = *reinterpret_cast<float (*)[32]>(&acc[32]);
            auto tile_mma = [&](float (&d)[32], int u) {
#pragma unroll 1
                for (int k = 0; k < 2; k++) {
                    const uint32_t hb = sb + SM_HH + (par ^ k) * 32768 + wg * 16384;
                    if (k == 1) mbar_wait(BAR(wg ? B_HPEER1 : B_HPEER), layer);
                    mbar_wait(BAR(B_AFULL + 2 * u + k), 1);
                    const uint64_t da = c_desc(2 * u + k);
                    wg_fence();
#pragma unroll
                    for (int ks = 0; ks < 4; ks++) wgmma_n64s<1>(d, da + ks * dstep, desc_b<64>(hb + ks * 2048), 1);
#pragma unroll
                    for (int ks = 0; ks < 4; ks++) wgmma_n64s<-1>(d, da + 512 + ks * dstep, desc_b<64>(hb + 8192 + ks * 2048), 1);
                }
                wg_commit();
            };
            auto tile_ship = [&](float (&d)[32], int u) {
                uint4* dst = g_P + (uint32_t)(((c * 8 + 2 * ((pi_ + 1 + u) & 3) + par) * 4 + pi_) * 1024 + wg * 512 + (tid & 127));
#pragma unroll
                for (int i = 0; i < 4; i++)
                    dst[i * 128] = make_uint4((pack_bf16(d[8 * i], d[8 * i + 1]) & 0xfffefffeu) | ptag, pack_bf16(d[8 * i + 2], d[8 * i + 3]),
                                              pack_bf16(d[8 * i + 4], d[8 * i + 5]), pack_bf16(d[8 * i + 6], d[8 * i + 7]));
            };
            tile_mma(a0, 0);
            if ((tid & 127) == 0) mbar_arrive_remote(mapa(BAR(B_HDONE), par ^ 1));
            __syncwarp();
            tile_mma(a1, 1);
            wg_wait<1>();
            tile_ship(a0, 0);
            tile_mma(acc2, 2);
            bar_arrive(12, 384);
            wg_wait<1>();
            tile_ship(a1, 1);
            wg_wait<0>();
            tile_ship(acc2, 2);
            if (lane < 6) mbar_arrive(BAR(B_AEMPTY + lane), 1);
            TS(12 + 12 * layer);
        } else {
            const int t2 = tid - 256;
            const uint8_t* ximg = g_X + (uint32_t)layer * 16 * 8 * 16384;
            mbar_wait(BAR(B_SSQ), layer);
            TS(6 + 12 * layer);
            float sqv[16];
#pragma unroll
            for (int i = 0; i < 16; i++) sqv[i] = __ldcg(g_ssqc + (layer * 16 + i) * 2048 + 128 * c + t2);
            const unsigned short xm = __ldcg((const unsigned short*)(ximg + (uint32_t)(c * 8 * 16384 + (t2 >> 3) * 128 + (t2 & 7) * 2)));
            acc_def(acc);
#pragma unroll 1
            for (int kb = 0; kb < 8; kb++) {
                if (kb == 4) {
                    wg_wait<0>();
                    if (lane == 0) { mbar_arrive(BAR(B_XEMPTY + 3), 1); mbar_arrive_remote(mapa(BAR(B_XEMPTY + 3), par ^ 1)); }
                    float tot = 0.f;
#pragma unroll
                    for (int i = 0; i < 16; i++) tot += sqv[i];
                    float rs = rsqrtf(tot * (1.f / 512.f) + 1e-5f);
                    s_rstd[t2] = rs;
                    s_rstd[128 + t2] = 2.f * rs;
                    s_mean[t2] = layer == 0 ? 0.f : __uint_as_float((uint32_t)xm << 16) * (1.f / 512.f);
                    TS(7 + 12 * layer);
                    bar_arrive(4, 384);
                    bar_sync(14, 384);
                }
                mbar_wait(BAR(B_XFULL + (kb & 3)), (kb >> 2) & 1);
                wg_fence();
#pragma unroll
                for (int ks = 0; ks < 4; ks++)
                    wgmma_n128<1>(acc, desc_a(sb + SM_X + (kb & 3) * 24576 + 16384 + ks * 256), desc_b<128>(sb + SM_X + (kb & 3) * 24576 + ks * 4096), 1);
                wg_commit();
                wg_wait<1>();
                if ((kb & 3) != 0 && lane == 0) { mbar_arrive(BAR(B_XEMPTY + ((kb - 1) & 3)), 1); mbar_arrive_remote(mapa(BAR(B_XEMPTY + ((kb - 1) & 3)), par ^ 1)); }
            }
            wg_wait<0>();
            if (lane == 0) { mbar_arrive(BAR(B_XEMPTY + 3), 1); mbar_arrive_remote(mapa(BAR(B_XEMPTY + 3), par ^ 1)); mbar_arrive_remote(mapa(BAR(B_RFREE), par ^ 1)); }
            bar_arrive(7, 384);
            bar_sync(3, 128);
            TS(9 + 12 * layer);
            const int m0 = 16 * w + g;
            const uint32_t xoff = (uint32_t)((c * 8 + own) * 16384 + w * 4096 + g * 16 + 4 * q);
            if (layer == 0) {
                const uint8_t* xs = g_X + xoff;
#pragma unroll
                for (int i = 0; i < 16; i++) {
                    float2 rs = *(const float2*)(s_rstd + 8 * i + 2 * q);
                    uint32_t x0v = __ldcg((const uint32_t*)(xs + i * 128)), x1v = __ldcg((const uint32_t*)(xs + 2048 + i * 128));
                    acc[4 * i] = acc[4 * i] * rs.x + bf_lo(x0v);
                    acc[4 * i + 1] = acc[4 * i + 1] * rs.y + bf_hi(x0v);
                    acc[4 * i + 2] = acc[4 * i + 2] * rs.x + bf_lo(x1v);
                    acc[4 * i + 3] = acc[4 * i + 3] * rs.y + bf_hi(x1v);
                }
            } else {
                float d0 = ldbf(p.dskip + 64 * own + m0), d1 = ldbf(p.dskip + 64 * own + m0 + 8);
#pragma unroll
                for (int i = 0; i < 16; i++) {
                    float2 rs = *(const float2*)(s_rstd + 8 * i + 2 * q);
                    float2 mn = *(const float2*)(s_mean + 8 * i + 2 * q);
                    acc[4 * i] = acc[4 * i] * (1.f + rs.x * d0) + mn.x;
                    acc[4 * i + 1] = acc[4 * i + 1] * (1.f + rs.y * d0) + mn.y;
                    acc[4 * i + 2] = acc[4 * i + 2] * (1.f + rs.x * d1) + mn.x;
                    acc[4 * i + 3] = acc[4 * i + 3] * (1.f + rs.y * d1) + mn.y;
                }
            }
            TS(10 + 12 * layer);
            bar_sync(6, 416);
            TS(11 + 12 * layer);
            {
                float (&a0)[32] = *reinterpret_cast<float (*)[32]>(&acc[0]);
                float (&a1)[32] = *reinterpret_cast<float (*)[32]>(&acc[32]);
#pragma unroll 1
                for (int k = 0; k < 2; k++) {
                    const uint32_t hb = sb + SM_HH + (par ^ k) * 32768;
                    if (k == 1) {
                        mbar_wait(BAR(B_HPEER), layer);
                        mbar_wait(BAR(B_HPEER1), layer);
                        bar_sync(12, 384);
                    }
                    mbar_wait(BAR(B_AFULL + 6 + k), 1);
                    const uint64_t da = c_desc(6 + k);
                    wg_fence();
#pragma unroll
                    for (int ks = 0; ks < 4; ks++) {
                        wgmma_n64s<1>(a0, da + ks * dstep, desc_b<64>(hb + ks * 2048), 1);
                        wgmma_n64s<1>(a1, da + ks * dstep, desc_b<64>(hb + 16384 + ks * 2048), 1);
                    }
#pragma unroll
                    for (int ks = 0; ks < 4; ks++) {
                        wgmma_n64s<-1>(a0, da + 512 + ks * dstep, desc_b<64>(hb + 8192 + ks * 2048), 1);
                        wgmma_n64s<-1>(a1, da + 512 + ks * dstep, desc_b<64>(hb + 16384 + 8192 + ks * 2048), 1);
                    }
                    wg_commit();
                }
                wg_wait<0>();
            }
#pragma unroll
            for (int i = 0; i < 16; i++)
                *(float4*)(sm + SM_A + 6 * 16384 + i * 2048 + t2 * 16) = make_float4(acc[4 * i], acc[4 * i + 1], acc[4 * i + 2], acc[4 * i + 3]);
            TS(12 + 12 * layer);
        }
        {
            const int t = tid & 127;
            const int nch = wg == 2 ? 2 : 3;
            const uint4* pb = g_P + (uint32_t)((c * 8 + r) * 4 * 1024 + wg * 128 + t);
            uint4 v[3][3];
            unsigned n = 0;
#pragma unroll 1
            while (true) {
                if (lane == 31) {
#pragma unroll 1
                    while (true) {
                        uint32_t bad = 0;
#pragma unroll
                        for (int sx = 0; sx < 3; sx++) {
                            uint32_t t0;
                            asm volatile("ld.relaxed.gpu.global.u32 %0, [%1];" : "=r"(t0) : "l"(pb + ((pi_ + 1 + sx) & 3) * 1024 + (nch - 1) * 384) : "memory");
                            bad |= t0 ^ ptag;
                        }
                        if (!(bad & 0x00010001u) || ++n >= SPIN_LIMIT) break;
                    }
                }
                __syncwarp();
                uint32_t bad = 0;
#pragma unroll
                for (int k = 0; k < 3; k++)
#pragma unroll
                    for (int sx = 0; sx < 3; sx++) {
                        v[k][sx] = make_uint4(ptag, 0, 0, 0);
                        if (k < nch) v[k][sx] = ld_relaxed_u4(pb + ((pi_ + 1 + sx) & 3) * 1024 + k * 384);
                        bad |= v[k][sx].x ^ ptag;
                    }
                if (!__any_sync(~0u, bad & 0x00010001u) || ++n >= SPIN_LIMIT) break;
            }
            bar_sync(8, 384);
            TS(13 + 12 * layer);
            const int m0 = 16 * w + g;
            const float w0 = (own == 0 && m0 < 2) ? (m0 == 0 ? 0.f : 0.5f) : 1.f;
#pragma unroll
            for (int k = 0; k < 3; k++) {
                if (k < nch) {
                    const int i = wg + 3 * k;
                    float4 a = *(const float4*)(sm + SM_A + 6 * 16384 + (2 * i) * 2048 + t * 16);
                    float4 bq = *(const float4*)(sm + SM_A + 6 * 16384 + (2 * i + 1) * 2048 + t * 16);
#pragma unroll
                    for (int sx = 0; sx < 3; sx++) {
                        a.x += bf_lo(v[k][sx].x); a.y += bf_hi(v[k][sx].x); a.z += bf_lo(v[k][sx].y); a.w += bf_hi(v[k][sx].y);
                        bq.x += bf_lo(v[k][sx].z); bq.y += bf_hi(v[k][sx].z); bq.z += bf_lo(v[k][sx].w); bq.w += bf_hi(v[k][sx].w);
                    }
                    if (layer == 0) {
                        uint8_t* xd = g_X + (uint32_t)((16 * 8 + c * 8 + own) * 16384 + w * 4096 + g * 16 + 4 * q + i * 256);
                        uint32_t v0 = pack_bf16(a.x, a.y), v1 = pack_bf16(a.z, a.w), v2 = pack_bf16(bq.x, bq.y), v3 = pack_bf16(bq.z, bq.w);
                        *(uint32_t*)(xd) = v0; *(uint32_t*)(xd + 2048) = v1; *(uint32_t*)(xd + 128) = v2; *(uint32_t*)(xd + 2048 + 128) = v3;
                        float sq[4];
                        sq[0] = w0 * bf_lo(v0) * bf_lo(v0) + bf_lo(v1) * bf_lo(v1);
                        sq[1] = w0 * bf_hi(v0) * bf_hi(v0) + bf_hi(v1) * bf_hi(v1);
                        sq[2] = w0 * bf_lo(v2) * bf_lo(v2) + bf_lo(v3) * bf_lo(v3);
                        sq[3] = w0 * bf_hi(v2) * bf_hi(v2) + bf_hi(v3) * bf_hi(v3);
                        float u0 = (g & 1) ? sq[2] : sq[0], u1 = (g & 1) ? sq[3] : sq[1];
                        u0 += __shfl_xor_sync(~0u, (g & 1) ? sq[0] : sq[2], 4);
                        u1 += __shfl_xor_sync(~0u, (g & 1) ? sq[1] : sq[3], 4);
                        float z = (g & 2) ? u1 : u0;
                        z += __shfl_xor_sync(~0u, (g & 2) ? u0 : u1, 8);
                        z += __shfl_xor_sync(~0u, z, 16);
                        if (g < 4) atomicAdd(s_mean + 16 * i + 8 * (g & 1) + 2 * q + (g >> 1), z);
                    } else {
                        float* o = p.out + (uint32_t)((128 * c + 32 * q + 4 * i) * 512 + 64 * own + m0);
                        o[0] = a.x; o[512] = a.y; o[8] = a.z; o[512 + 8] = a.w;
                        o[1024] = bq.x; o[1536] = bq.y; o[1024 + 8] = bq.z; o[1536 + 8] = bq.w;
                    }
                }
            }
            if (wg < 2) mbar_wait_cluster(BAR(B_HDONE), layer);
            if (layer == 0) {
                fence_async_smem();
                bar_sync(9, 384);
                TS(14 + 12 * layer);
                if (wg == 2) {
                    atomicAdd(g_ssq + 2048 + 128 * c + t, s_mean[t] * (2.f / 512.f));
                    bar_sync(3, 128);
                    if (lane == 0) { mbar_arrive(BAR(B_AEMPTY + 6), 2); mbar_arrive(BAR(B_AEMPTY + 7), 2); }
                    if (t == 0) { fence_async(); red_release(&g_bar[2], 1); }
                }
            }
        }
        TS(15 + 12 * layer);
        if (wg == 0) TC(31);
    }
}

typedef CUresult (*EncFn)(CUtensorMap*, CUtensorMapDataType, cuuint32_t, void*, const cuuint64_t*, const cuuint64_t*,
                          const cuuint32_t*, const cuuint32_t*, CUtensorMapInterleave, CUtensorMapSwizzle,
                          CUtensorMapL2promotion, CUtensorMapFloatOOBfill);

void launch_impl(void* const* d_in, void* d_out, int stop) {
    static EncFn enc = nullptr;
    if (!enc) {
        void* fn = nullptr;
        cudaDriverEntryPointQueryResult qr;
        cudaGetDriverEntryPoint("cuTensorMapEncodeTiled", &fn, cudaEnableDefault, &qr);
        enc = (EncFn)fn;
        cudaFuncSetAttribute(fused_kernel, cudaFuncAttributeMaxDynamicSharedMemorySize, SM_TOTAL);
    }
    CUtensorMap tx, tbr, tbi, tcr, tci, tcol;
    {
        void* gx = nullptr;
        cudaGetSymbolAddress(&gx, g_X);
        cuuint64_t gd[5] = {64, 16, 64, 16, 2};
        cuuint64_t gs[4] = {128, 2048, 128 * 1024, 2048 * 1024};
        cuuint32_t bx[5] = {32, 16, 1, 16, 1};
        cuuint32_t es[5] = {1, 1, 1, 1, 1};
        enc(&tcol, CU_TENSOR_MAP_DATA_TYPE_BFLOAT16, 5, gx, gd, gs, bx, es, CU_TENSOR_MAP_INTERLEAVE_NONE,
            CU_TENSOR_MAP_SWIZZLE_64B, CU_TENSOR_MAP_L2_PROMOTION_NONE, CU_TENSOR_MAP_FLOAT_OOB_FILL_NONE);
    }
    {
        cuuint64_t gd[5] = {512, 2, 4, 16, 16};
        cuuint64_t gs[4] = {1024, 32 * 1024, 2 * 1024, 128 * 1024};
        cuuint32_t bx[5] = {64, 2, 4, 8, 1};
        cuuint32_t es[5] = {1, 1, 1, 1, 1};
        enc(&tx, CU_TENSOR_MAP_DATA_TYPE_BFLOAT16, 5, d_in[0], gd, gs, bx, es, CU_TENSOR_MAP_INTERLEAVE_NONE,
            CU_TENSOR_MAP_SWIZZLE_128B, CU_TENSOR_MAP_L2_PROMOTION_L2_128B, CU_TENSOR_MAP_FLOAT_OOB_FILL_NONE);
    }
    auto mk2 = [&](CUtensorMap* m, void* ptr, cuuint32_t rows) {
        cuuint64_t gd[2] = {512, 512};
        cuuint64_t gs[1] = {1024};
        cuuint32_t bx[2] = {64, rows};
        cuuint32_t es[2] = {1, 1};
        enc(m, CU_TENSOR_MAP_DATA_TYPE_BFLOAT16, 2, ptr, gd, gs, bx, es, CU_TENSOR_MAP_INTERLEAVE_NONE,
            CU_TENSOR_MAP_SWIZZLE_128B, CU_TENSOR_MAP_L2_PROMOTION_L2_128B, CU_TENSOR_MAP_FLOAT_OOB_FILL_NONE);
    };
    mk2(&tbr, d_in[6], 32);
    mk2(&tbi, d_in[7], 32);
    mk2(&tcr, d_in[8], 64);
    mk2(&tci, d_in[9], 64);
    Params p;
    p.x0 = (const __nv_bfloat16*)d_in[0];
    p.w_r = (const __nv_bfloat16*)d_in[1];
    p.w_i = (const __nv_bfloat16*)d_in[2];
    p.lam_re = (const __nv_bfloat16*)d_in[4];
    p.lam_im = (const __nv_bfloat16*)d_in[5];
    p.log_dt = (const __nv_bfloat16*)d_in[10];
    p.dskip = (const __nv_bfloat16*)d_in[11];
    p.out = (float*)d_out;
    p.stop = stop;
    cudaLaunchConfig_t cfg = {};
    cfg.gridDim = dim3(NCTA); cfg.blockDim = dim3(NTHREADS); cfg.dynamicSmemBytes = SM_TOTAL; cfg.stream = cudaStreamPerThread;
    cudaLaunchAttribute at[1];
    at[0].id = cudaLaunchAttributeClusterDimension;
    at[0].val.clusterDim.x = 2; at[0].val.clusterDim.y = 1; at[0].val.clusterDim.z = 1;
    cfg.attrs = at; cfg.numAttrs = 1;
    cudaLaunchKernelEx(&cfg, fused_kernel, tx, tbr, tbi, tcr, tci, tcol, p);
}

}

extern "C" void kernel_launch(void* const* d_in, const int* in_sizes, int n_in, void* d_out, int out_size) {
    (void)in_sizes; (void)n_in; (void)out_size;
    launch_impl(d_in, d_out, 100);
}
```

```cpp
#include <cuda_runtime.h>
#include <cuda_bf16.h>
#include <cuda.h>
#include <stdint.h>

namespace {

constexpr int NCTA = 128;
constexpr int NTHREADS = 512;
constexpr int SM_A = 0;
constexpr int SM_X = 131072;
constexpr int SM_H = 196608;
constexpr int SM_HH = SM_X + 32768;
constexpr int SM_M = 229376;
constexpr int SM_TOTAL = 232448;
constexpr int SM_BAR = SM_M;
constexpr int SM_TGT = SM_M + 400;
constexpr int SM_LAM = SM_M + 424;
constexpr int SM_TAB = SM_M + 944;
constexpr int SM_RSTD = SM_M + 1920;
constexpr int SM_MEAN = SM_TAB;
constexpr int SM_T64 = SM_M + 2944;
constexpr int SM_B1ST = SM_H + 24576;
constexpr int SM_RAW = SM_X + 40960;
constexpr int SM_SSQ = SM_X + 57344;
constexpr int B_FULL0 = 0;
constexpr int B_EMPTY0 = 8;
constexpr int B_FULLC = 12;
constexpr int B_AFULL = 13;
constexpr int B_AEMPTY = 21;
constexpr int B_XFULL = 29;
constexpr int B_XEMPTY = 35;
constexpr int B_AFREE = 37;
constexpr int B_COL = 38;
constexpr int B_SSQ = 39;
constexpr int B_HPEER = 40;
constexpr int B_RFREE = 41;
constexpr int B_HDONE = 42;
constexpr int B_WRDY = 43;
constexpr int B_HPEER1 = 44;
constexpr int B_FULLB = 45;
constexpr int B_BFREE = 46;
constexpr int B_SETUP = 47;
constexpr int B_B1DONE = 48;
constexpr int B_WST = 49;
constexpr int NBARS = 50;

__device__ __align__(1024) uint8_t g_X[2 * 16 * 8 * 16384];
__device__ __align__(1024) uint8_t g_A1[8 * 8 * 16384];
__device__ __align__(1024) uint8_t g_A2[8 * 8 * 16384];
__device__ __align__(1024) uint8_t g_E[2 * 8 * 8 * 8192];
__device__ __align__(16) float g_ssq[2 * 2048];
__device__ __align__(16) float g_ssqc[2 * 16 * 2048];
__device__ __align__(16) float g_Dh[512];
__device__ __align__(16) uint4 g_Wfrag[128 * 4 * 256];
__device__ __align__(16) float4 g_Ebuf[2 * 16 * 512];
__device__ __align__(16) uint4 g_P[16 * 8 * 4 * 1024];
__device__ unsigned g_bar[8];
__device__ unsigned g_err;
#define TX(i)
#define TQ(i)
#define TS(i)
#define TC(i)

constexpr unsigned SPIN_LIMIT = 1u << 22;

__device__ __forceinline__ uint32_t s2u(const void* p) { return (uint32_t)__cvta_generic_to_shared(p); }
__device__ __forceinline__ void mbar_init(uint32_t a, uint32_t c) {
    asm volatile("mbarrier.init.shared::cta.b64 [%0], %1;" ::"r"(a), "r"(c) : "memory");
}
__device__ __forceinline__ void mbar_expect(uint32_t a, uint32_t bytes) {
    asm volatile("mbarrier.arrive.expect_tx.shared::cta.b64 _, [%0], %1;" ::"r"(a), "r"(bytes) : "memory");
}
__device__ __forceinline__ void mbar_arrive(uint32_t a, uint32_t cnt) {
    asm volatile("mbarrier.arrive.shared::cta.b64 _, [%0], %1;" ::"r"(a), "r"(cnt) : "memory");
}
__device__ __forceinline__ bool mbar_try(uint32_t a, uint32_t parity) {
    uint32_t ok;
    asm volatile("{\n.reg .pred p;\nmbarrier.try_wait.parity.shared::cta.b64 p, [%1], %2;\nselp.u32 %0, 1, 0, p;\n}"
                 : "=r"(ok) : "r"(a), "r"(parity) : "memory");
    return ok != 0;
}
__device__ __forceinline__ void mbar_wait(uint32_t a, uint32_t parity) {
    asm volatile("{\n.reg .pred p, q;\n.reg .u32 n;\nmov.u32 n, 0;\n"
                 "W_%=:\nmbarrier.try_wait.parity.shared::cta.b64 p, [%0], %1;\n@p bra D_%=;\n"
                 "add.u32 n, n, 1;\nsetp.lt.u32 q, n, 4194304;\n@q bra W_%=;\nD_%=:\n}" ::"r"(a), "r"(parity) : "memory");
}
__device__ __forceinline__ void bulk_g2s(uint32_t dst, const void* src, uint32_t bytes, uint32_t bar) {
    asm volatile("cp.async.bulk.shared::cluster.global.mbarrier::complete_tx::bytes [%0], [%1], %2, [%3];" ::"r"(dst),
                 "l"(src), "r"(bytes), "r"(bar) : "memory");
}
__device__ __forceinline__ void tma_2d(uint32_t dst, const CUtensorMap* m, int c0, int c1, uint32_t bar) {
    asm volatile("cp.async.bulk.tensor.2d.shared::cluster.global.mbarrier::complete_tx::bytes [%0], [%1, {%3,%4}], [%2];" ::"r"(dst),
                 "l"(m), "r"(bar), "r"(c0), "r"(c1) : "memory");
}
__device__ __forceinline__ void tma_5d(uint32_t dst, const CUtensorMap* m, int c0, int c1, int c2, int c3, int c4, uint32_t bar) {
    asm volatile("cp.async.bulk.tensor.5d.shared::cluster.global.mbarrier::complete_tx::bytes [%0], [%1, {%3,%4,%5,%6,%7}], [%2];" ::"r"(dst),
                 "l"(m), "r"(bar), "r"(c0), "r"(c1), "r"(c2), "r"(c3), "r"(c4) : "memory");
}
__device__ __forceinline__ void tma_2d_mc(uint32_t dst, const CUtensorMap* m, int c0, int c1, uint32_t bar) {
    asm volatile("cp.async.bulk.tensor.2d.shared::cluster.global.mbarrier::complete_tx::bytes.multicast::cluster [%0], [%1, {%3,%4}], [%2], %5;" ::"r"(dst),
                 "l"(m), "r"(bar), "r"(c0), "r"(c1), "h"((unsigned short)3) : "memory");
}
__device__ __forceinline__ void tma_5d_mc(uint32_t dst, const CUtensorMap* m, int c0, int c1, int c2, int c3, int c4, uint32_t bar) {
    asm volatile("cp.async.bulk.tensor.5d.shared::cluster.global.mbarrier::complete_tx::bytes.multicast::cluster [%0], [%1, {%3,%4,%5,%6,%7}], [%2], %8;" ::"r"(dst),
                 "l"(m), "r"(bar), "r"(c0), "r"(c1), "r"(c2), "r"(c3), "r"(c4), "h"((unsigned short)3) : "memory");
}
__device__ __forceinline__ void bulk_g2s_mc(uint32_t dst, const void* src, uint32_t bytes, uint32_t bar) {
    asm volatile("cp.async.bulk.shared::cluster.global.mbarrier::complete_tx::bytes.multicast::cluster [%0], [%1], %2, [%3], %4;" ::"r"(dst),
                 "l"(src), "r"(bytes), "r"(bar), "h"((unsigned short)3) : "memory");
}
__device__ __forceinline__ void tma_store_5d(const CUtensorMap* m, int c0, int c1, int c2, int c3, int c4, uint32_t src) {
    asm volatile("cp.async.bulk.tensor.5d.global.shared::cta.bulk_group [%0, {%2,%3,%4,%5,%6}], [%1];" ::"l"(m), "r"(src),
                 "r"(c0), "r"(c1), "r"(c2), "r"(c3), "r"(c4) : "memory");
}
__device__ __forceinline__ uint32_t lds32(uint32_t a) { uint32_t v; asm volatile("ld.shared.u32 %0, [%1];" : "=r"(v) : "r"(a) : "memory"); return v; }
__device__ __forceinline__ uint4 ld_relaxed_u4(const uint4* p) {
    uint4 v;
    asm volatile("ld.relaxed.gpu.global.v4.u32 {%0,%1,%2,%3}, [%4];" : "=r"(v.x), "=r"(v.y), "=r"(v.z), "=r"(v.w) : "l"(p) : "memory");
    return v;
}
__device__ __forceinline__ void fence_async() { asm volatile("fence.proxy.async.global;" ::: "memory"); }
__device__ __forceinline__ void red_relaxed(unsigned* p, unsigned v) {
    asm volatile("red.relaxed.gpu.global.add.u32 [%0], %1;" ::"l"(p), "r"(v) : "memory");
}
__device__ __forceinline__ uint32_t mapa(uint32_t a, uint32_t rank) {
    uint32_t d;
    asm("mapa.shared::cluster.u32 %0, %1, %2;" : "=r"(d) : "r"(a), "r"(rank));
    return d;
}
__device__ __forceinline__ void mbar_arrive_remote(uint32_t ra) {
    asm volatile("mbarrier.arrive.relaxed.cluster.shared::cluster.b64 _, [%0];" ::"r"(ra) : "memory");
}
__device__ __forceinline__ void mbar_wait_cluster(uint32_t a, uint32_t parity) {
    asm volatile("{\n.reg .pred p, q;\n.reg .u32 n;\nmov.u32 n, 0;\n"
                 "W_%=:\nmbarrier.try_wait.parity.acquire.cluster.shared::cta.b64 p, [%0], %1;\n@p bra D_%=;\n"
                 "add.u32 n, n, 1;\nsetp.lt.u32 q, n, 4194304;\n@q bra W_%=;\nD_%=:\n}" ::"r"(a), "r"(parity) : "memory");
}
__device__ __forceinline__ void bulk_s2peer(uint32_t rdst, uint32_t src, uint32_t bytes, uint32_t rbar) {
    asm volatile("cp.async.bulk.shared::cluster.shared::cta.mbarrier::complete_tx::bytes [%0], [%1], %2, [%3];" ::"r"(rdst),
                 "r"(src), "r"(bytes), "r"(rbar) : "memory");
}
__device__ __forceinline__ void fence_async_smem() { asm volatile("fence.proxy.async.shared::cta;" ::: "memory"); }
__device__ __forceinline__ void wg_fence() { asm volatile("wgmma.fence.sync.aligned;" ::: "memory"); }
__device__ __forceinline__ void wg_commit() { asm volatile("wgmma.commit_group.sync.aligned;" ::: "memory"); }
template <int N> __device__ __forceinline__ void wg_wait() { asm volatile("wgmma.wait_group.sync.aligned %0;" ::"n"(N) : "memory"); }
__device__ __forceinline__ void bar_sync(int id, int n) { asm volatile("bar.sync %0, %1;" ::"r"(id), "r"(n) : "memory"); }
__device__ __forceinline__ void bar_arrive(int id, int n) { asm volatile("bar.arrive %0, %1;" ::"r"(id), "r"(n) : "memory"); }
__device__ __forceinline__ unsigned ld_acquire(const unsigned* p) {
    unsigned v;
    asm volatile("ld.acquire.gpu.global.u32 %0, [%1];" : "=r"(v) : "l"(p) : "memory");
    return v;
}
__device__ __forceinline__ void red_release(unsigned* p, unsigned v) {
    asm volatile("red.release.gpu.global.add.u32 [%0], %1;" ::"l"(p), "r"(v) : "memory");
}
__device__ __forceinline__ void wait_count(const unsigned* p, unsigned target) {
    unsigned n = 0;
#pragma unroll 1
    while ((int)(ld_acquire(p) - target) < 0 && ++n < SPIN_LIMIT) {}
}
__device__ __forceinline__ float4 ld_relaxed_f4(const float4* p) {
    float4 v;
    asm volatile("ld.relaxed.gpu.global.v4.f32 {%0,%1,%2,%3}, [%4];" : "=f"(v.x), "=f"(v.y), "=f"(v.z), "=f"(v.w) : "l"(p) : "memory");
    return v;
}
__device__ __forceinline__ void st_relaxed_f4(float4* p, float4 v) {
    asm volatile("st.relaxed.gpu.global.v4.f32 [%0], {%1,%2,%3,%4};" ::"l"(p), "f"(v.x), "f"(v.y), "f"(v.z), "f"(v.w) : "memory");
}
__device__ __forceinline__ uint32_t pack_bf16(float lo, float hi) {
    uint32_t r;
    asm("cvt.rn.bf16x2.f32 %0, %1, %2;" : "=r"(r) : "f"(hi), "f"(lo));
    return r;
}
__device__ __forceinline__ uint32_t hmul2(uint32_t a, uint32_t b) {
    uint32_t r;
    asm("mul.rn.bf16x2 %0, %1, %2;" : "=r"(r) : "r"(a), "r"(b));
    return r;
}
__device__ __forceinline__ uint32_t hfma2(uint32_t a, uint32_t b, uint32_t c) {
    uint32_t r;
    asm("fma.rn.bf16x2 %0, %1, %2, %3;" : "=r"(r) : "r"(a), "r"(b), "r"(c));
    return r;
}
__device__ __forceinline__ float bf_lo(uint32_t v) { return __uint_as_float(v << 16); }
__device__ __forceinline__ float bf_hi(uint32_t v) { return __uint_as_float(v & 0xffff0000u); }
__device__ __forceinline__ void sts32(uint32_t a, uint32_t v) { asm volatile("st.shared.u32 [%0], %1;" ::"r"(a), "r"(v) : "memory"); }
__device__ __forceinline__ void sts128(uint32_t a, uint4 v) {
    asm volatile("st.shared.v4.u32 [%0], {%1,%2,%3,%4};" ::"r"(a), "r"(v.x), "r"(v.y), "r"(v.z), "r"(v.w) : "memory");
}

__device__ __forceinline__ uint64_t desc_ni(uint32_t addr, uint32_t lbo, uint32_t sbo) {
    return (uint64_t)((addr & 0x3FFFF) >> 4) | ((uint64_t)(lbo >> 4) << 16) | ((uint64_t)(sbo >> 4) << 32);
}
__device__ __forceinline__ uint64_t desc_a(uint32_t addr) { return desc_ni(addr, 128, 1024); }
template <int N> __device__ __forceinline__ uint64_t desc_b(uint32_t addr) { return desc_ni(addr, 16 * N, 128); }
__device__ __forceinline__ uint64_t desc_k(uint32_t addr) {
    return (uint64_t)((addr & 0x3FFFF) >> 4) | (1ull << 16) | (64ull << 32) | (1ull << 62);
}
__device__ __forceinline__ uint64_t desc_mn(uint32_t addr, uint32_t lbo) {
    return (uint64_t)((addr & 0x3FFFF) >> 4) | ((uint64_t)(lbo >> 4) << 16) | (64ull << 32) | (1ull << 62);
}

#define ACC8(d, o) "+f"(d[o + 0]), "+f"(d[o + 1]), "+f"(d[o + 2]), "+f"(d[o + 3]), "+f"(d[o + 4]), "+f"(d[o + 5]), "+f"(d[o + 6]), "+f"(d[o + 7])
template <int TB, int SA = 1>
__device__ __forceinline__ void wgmma_n128(float (&d)[64], uint64_t da, uint64_t db, int sd) {
    asm volatile(
        "{\n.reg .pred p;\nsetp.ne.b32 p, %66, 0;\n"
        "wgmma.mma_async.sync.aligned.m64n128k16.f32.bf16.bf16 "
        "{%0,%1,%2,%3,%4,%5,%6,%7,%8,%9,%10,%11,%12,%13,%14,%15,%16,%17,%18,%19,%20,%21,%22,%23,%24,%25,%26,%27,%28,%29,%30,%31,"
        "%32,%33,%34,%35,%36,%37,%38,%39,%40,%41,%42,%43,%44,%45,%46,%47,%48,%49,%50,%51,%52,%53,%54,%55,%56,%57,%58,%59,%60,%61,%62,%63},"
        " %64, %65, p, %68, 1, 0, %67;\n}"
        : ACC8(d, 0), ACC8(d, 8), ACC8(d, 16), ACC8(d, 24), ACC8(d, 32), ACC8(d, 40), ACC8(d, 48), ACC8(d, 56)
        : "l"(da), "l"(db), "r"(sd), "n"(TB), "n"(SA));
}
template <int N> __device__ __forceinline__ void acc_def(float (&d)[N]) {
#pragma unroll
    for (int i = 0; i < N; i++) d[i] = 0.f;
}
template <int TB>
__device__ __forceinline__ void wgmma_n64(float (&d)[32], uint64_t da, uint64_t db, int sd) {
    asm volatile(
        "{\n.reg .pred p;\nsetp.ne.b32 p, %34, 0;\n"
        "wgmma.mma_async.sync.aligned.m64n64k16.f32.bf16.bf16 "
        "{%0,%1,%2,%3,%4,%5,%6,%7,%8,%9,%10,%11,%12,%13,%14,%15,%16,%17,%18,%19,%20,%21,%22,%23,%24,%25,%26,%27,%28,%29,%30,%31},"
        " %32, %33, p, 1, 1, 0, %35;\n}"
        : ACC8(d, 0), ACC8(d, 8), ACC8(d, 16), ACC8(d, 24)
        : "l"(da), "l"(db), "r"(sd), "n"(TB));
}
template <int SA>
__device__ __forceinline__ void wgmma_n64s(float (&d)[32], uint64_t da, uint64_t db, int sd) {
    asm volatile(
        "{\n.reg .pred p;\nsetp.ne.b32 p, %34, 0;\n"
        "wgmma.mma_async.sync.aligned.m64n64k16.f32.bf16.bf16 "
        "{%0,%1,%2,%3,%4,%5,%6,%7,%8,%9,%10,%11,%12,%13,%14,%15,%16,%17,%18,%19,%20,%21,%22,%23,%24,%25,%26,%27,%28,%29,%30,%31},"
        " %32, %33, p, %35, 1, 0, 1;\n}"
        : ACC8(d, 0), ACC8(d, 8), ACC8(d, 16), ACC8(d, 24)
        : "l"(da), "l"(db), "r"(sd), "n"(SA));
}
__device__ __forceinline__ void wgmma_n64_rs(float (&d)[32], uint32_t a0, uint32_t a1, uint32_t a2, uint32_t a3, uint64_t db, int sd) {
    asm volatile(
        "{\n.reg .pred p;\nsetp.ne.b32 p, %37, 0;\n"
        "wgmma.mma_async.sync.aligned.m64n64k16.f32.bf16.bf16 "
        "{%0,%1,%2,%3,%4,%5,%6,%7,%8,%9,%10,%11,%12,%13,%14,%15,%16,%17,%18,%19,%20,%21,%22,%23,%24,%25,%26,%27,%28,%29,%30,%31},"
        " {%32,%33,%34,%35}, %36, p, 1, 1, 1;\n}"
        : ACC8(d, 0), ACC8(d, 8), ACC8(d, 16), ACC8(d, 24)
        : "r"(a0), "r"(a1), "r"(a2), "r"(a3), "l"(db), "r"(sd));
}

struct Params {
    const __nv_bfloat16* x0;
    const __nv_bfloat16* w_r;
    const __nv_bfloat16* w_i;
    const __nv_bfloat16* lam_re;
    const __nv_bfloat16* lam_im;
    const __nv_bfloat16* log_dt;
    const __nv_bfloat16* dskip;
    float* out;
    int stop;
};

__device__ __forceinline__ uint32_t fpar(int s, int k, int L) { return s < 6 ? (uint32_t)((L + k) & 1) : (uint32_t)(k == 2); }
__device__ __forceinline__ float ldbf(const __nv_bfloat16* p) { return __bfloat162float(*p); }

__device__ __forceinline__ void dft_fp(int j, int& f, int& ph) {
    int cs = j >> 1;
    if (j == 1) { f = 256; ph = 0; }
    else { f = cs; ph = (j & 1) ? 128 : 0; }
}

__device__ __forceinline__ void gen_col_consts(uint32_t sb, int tid) {
#pragma unroll 1
    for (int task = tid; task < 640; task += 256) {
        int f, c8;
        uint32_t a_cc, d_pi, d_po;
        if (task < 512) {
            f = task & 63; c8 = task >> 6;
            a_cc = sb + SM_X + (f >> 5) * 16384 + ((f >> 3) & 3) * 2048 + c8 * 128 + (f & 7) * 16;
            d_pi = 8192; d_po = 1024;
        } else {
            int n2 = task & 31;
            f = 2 * n2; c8 = (task >> 5) & 3;
            a_cc = sb + SM_X + 32768 + (n2 >> 3) * 1024 + c8 * 128 + (n2 & 7) * 16;
            d_pi = 4096; d_po = 512;
        }
        float cd, sd, cs, sn;
        __sincosf((float)(f >= 32 ? f - 64 : f) * (6.283185307179586f / 64.f), &sd, &cd);
        int a = (8 * c8 * f) & 63;
        __sincosf((float)(a >= 32 ? a - 64 : a) * (6.283185307179586f / 64.f), &sn, &cs);
        float cv[8], sv[8];
#pragma unroll
        for (int e = 0; e < 8; e++) {
            cv[e] = cs; sv[e] = sn;
            float t = cs * cd - sn * sd;
            sn = sn * cd + cs * sd;
            cs = t;
        }
        uint4 oc = make_uint4(pack_bf16(cv[0], cv[1]), pack_bf16(cv[2], cv[3]), pack_bf16(cv[4], cv[5]), pack_bf16(cv[6], cv[7]));
        uint4 os = make_uint4(pack_bf16(sv[0], sv[1]), pack_bf16(sv[2], sv[3]), pack_bf16(sv[4], sv[5]), pack_bf16(sv[6], sv[7]));
        sts128(a_cc, oc);
        sts128(a_cc + d_pi, os);
        sts128(a_cc + d_po, make_uint4(os.x ^ 0x80008000u, os.y ^ 0x80008000u, os.z ^ 0x80008000u, os.w ^ 0x80008000u));
        sts128(a_cc + d_pi + d_po, oc);
    }
}

__global__ void __launch_bounds__(NTHREADS, 1)
fused_kernel(const __grid_constant__ CUtensorMap tm_x, const __grid_constant__ CUtensorMap tm_bre,
             const __grid_constant__ CUtensorMap tm_bim, const __grid_constant__ CUtensorMap tm_cre,
             const __grid_constant__ CUtensorMap tm_cim, const __grid_constant__ CUtensorMap tm_col, const Params p) {
    extern __shared__ __align__(1024) uint8_t sm[];
    const uint32_t sb = s2u(sm);
    const int tid = threadIdx.x, b = blockIdx.x;
    const int c = b >> 3, r = b & 7;
    const int par = r & 1, pi_ = r >> 1, own = 4 * par + pi_;
    const int wg = __shfl_sync(~0u, tid >> 7, 0), w = __shfl_sync(~0u, (tid >> 5) & 3, 0), lane = tid & 31, g = lane >> 2, q = lane & 3;
    auto BAR = [&](int i) { return sb + SM_BAR + 8 * i; };
    unsigned* s_tgt = (unsigned*)(sm + SM_TGT);

    if (tid < NBARS) {
        int cnt = 1;
        if (tid >= B_EMPTY0 && tid < B_EMPTY0 + 4) cnt = 16;
        if (tid >= B_XEMPTY && tid < B_XEMPTY + 2) cnt = 16;
        if (tid == B_RFREE) cnt = 12;
        if (tid == B_HDONE || tid == B_WST) cnt = 2;
        if ((tid >= B_AEMPTY && tid < B_AEMPTY + 8) || tid == B_BFREE) cnt = 8;
        if (tid == B_AFREE) cnt = 4;
        mbar_init(BAR(tid), cnt);
        asm volatile("fence.mbarrier_init.release.cluster;" ::: "memory");
    }
    asm volatile("barrier.cluster.arrive.release.aligned;" ::: "memory");

    if (wg == 3) {
        asm volatile("setmaxnreg.dec.sync.aligned.u32 56;");
        if (w == 0 && lane < 6) {
            const CUtensorMap* tm = lane == 0 ? &tm_x : lane == 1 ? &tm_bre : lane == 2 ? &tm_bim : lane == 3 ? &tm_cre : lane == 4 ? &tm_cim : &tm_col;
            asm volatile("prefetch.tensormap [%0];" ::"l"(tm) : "memory");
        }
        __syncwarp();
        asm volatile("barrier.cluster.wait.acquire.aligned;" ::: "memory");
        if (w > 0) {
            if (w == 1) {
                float lr[3], li[3], ld[3];
#pragma unroll
                for (int k = 0; k < 3; k++) {
                    int ps = k < 2 ? 64 * r + 32 * k + lane : 32 * c + lane;
                    lr[k] = ldbf(p.lam_re + ps); li[k] = ldbf(p.lam_im + ps); ld[k] = ldbf(p.log_dt + ps);
                }
                if (lane < 6) s_tgt[lane] = ((ld_acquire(&g_bar[lane]) >> 7) + 1u) << 7;
#pragma unroll 1
                for (int k = 0; k < 3; k++) {
                    float a = k == 0 ? lr[0] : (k == 1 ? lr[1] : lr[2]), bq = k == 0 ? li[0] : (k == 1 ? li[1] : li[2]);
                    float dt = __bfloat162float(__float2bfloat16(expf(k == 0 ? ld[0] : (k == 1 ? ld[1] : ld[2]))));
                    float mag = expf(a * dt), t = bq * dt * 0.15915494309189535f, sn, cs;
                    t -= rintf(t);
                    sincospif(2.f * t, &sn, &cs);
                    float er = mag * cs, ei = mag * sn;
                    if (k < 2) {
                        *(float2*)(sm + SM_LAM + (32 * k + lane) * 8) = make_float2(er, ei);
                    } else {
                        er -= 1.f;
                        float inv = 1.f / (a * a + bq * bq);
                        *(float2*)(sm + SM_TAB + lane * 8) = make_float2((er * a + ei * bq) * inv, (ei * a - er * bq) * inv);
                    }
                }
                __syncwarp();
                bar_arrive(15, 160);
                if (lane == 0) mbar_arrive(BAR(B_SETUP), 1);
            }
            if (w == 2 && lane < 2) {
                const char* src = (const char*)(lane ? p.w_i : p.w_r) + (size_t)b * 8224;
                asm volatile("cp.async.bulk.prefetch.L2.global [%0], 8224;" ::"l"(src) : "memory");
            }
#pragma unroll 1
            for (int i = tid - 448; i < 96 + 128 && w > 1; i += 64) {
                if (i < 96) g_P[(uint32_t)(b * 4 + i / 24) * 1024 + 640 + ((i % 24) >> 1) * 32 + 30 + (i & 1)] = make_uint4(0, 0, 0, 0);
                else g_Ebuf[b * 128 + i - 96] = make_float4(0.f, 0.f, 0.f, 0.f);
            }
            __syncwarp();
            if (w > 1) bar_sync(0, 192);
            if (tid == 448) TX(14);
            if (w > 1) {
                if (lane < 8) {
                    const int cl = 8 * (w - 2) + lane;
                    asm volatile("cp.async.bulk.global.shared::cta.bulk_group [%0], [%1], 1024;" ::"l"(g_Wfrag + (uint32_t)((16 * (b & 7) + cl) * 1024 + (b >> 3) * 64)),
                                 "r"(sb + SM_H + cl * 1024) : "memory");
                }
                asm volatile("cp.async.bulk.commit_group;" ::: "memory");
                asm volatile("cp.async.bulk.wait_group 0;" ::: "memory");
                fence_async();
                __syncwarp();
                if (lane == 0) mbar_arrive(BAR(B_WST), 1);
                if (tid == 448) TX(15);
            }
            __syncwarp();
            if (w == 3) bar_arrive(11, 192);
            if (w == 2) {
                bar_sync(11, 192);
                if (lane == 0) { TX(7); red_release(&g_bar[4], 1);  }
            }
            if (w == 3) {
#pragma unroll 1
                for (int it = 0; it < 8; it++) {
                    const int m = 4 * c + (it >> 1), d = 64 * r + m, ch = lane + 32 * (it & 1);
                    float v[8];
#pragma unroll
                    for (int e = 0; e < 8; e++) {
                        int j = 8 * ch + e, f, ph;
                        dft_fp(j, f, ph);
                        int a = (d * f + ph) & 511;
                        a = a >= 256 ? a - 512 : a;
                        float wj = j == 0 ? 0.f : (j == 1 ? 1.f / 512.f : 2.f / 512.f);
                        v[e] = wj * __cosf((float)a * (6.283185307179586f / 512.f));
                    }
                    uint32_t off = (uint32_t)(64 + r * 8 + (ch >> 3)) * 8192 + (m >> 3) * 1024 + (ch & 7) * 128 + (m & 7) * 16;
                    *(uint4*)(g_E + off) = make_uint4(pack_bf16(v[0], v[1]), pack_bf16(v[2], v[3]), pack_bf16(v[4], v[5]), pack_bf16(v[6], v[7]));
                }
                __syncwarp();
                if (lane == 0) { fence_async(); red_release(&g_bar[6], 1); }
                return;
            }
            if (w == 2) {
#pragma unroll 1
                for (int it = 0; it < 4; it++) {
                    const int hf = it & 1;
                    __syncwarp();
                    if (hf == 0) bar_sync(13, 288); else bar_sync(6, 416);
                    if (lane == 0) {
                        const uint32_t src = sb + SM_HH + par * 32768 + hf * 16384;
                        bulk_s2peer(mapa(src, par ^ 1), src, 16384, mapa(BAR(hf ? B_HPEER1 : B_HPEER), par ^ 1));
                    }
                }
                return;
            }
            bar_sync(2, 288);
            if (lane == 0) {
                TX(5);
                fence_async();
                red_release(&g_bar[0], 1);
                TX(6);
            }
            __syncwarp();

            bar_sync(12, 160);
            if (lane == 0) {
                asm volatile("cp.async.bulk.global.shared::cta.bulk_group [%0], [%1], 8192;" ::"l"(g_A1 + (uint32_t)(((c >> 1) * 8 + r) * 16384 + (c & 1) * 8192)),
                             "r"(sb + SM_B1ST) : "memory");
                asm volatile("cp.async.bulk.commit_group;" ::: "memory");
                asm volatile("cp.async.bulk.wait_group 0;" ::: "memory");
                mbar_arrive(BAR(B_B1DONE), 1);
                fence_async();
                red_release(&g_bar[7], 1);
            }
#pragma unroll 1
            for (int layer = 0; layer < 2; layer++) {
                __syncwarp();
                bar_sync(5, 416);
                if (lane == 0) {
                    TX(0 + 8 * layer);
                    tma_store_5d(&tm_col, 32 * (b & 1), 0, b >> 1, 0, layer, sb + SM_RAW);
                    asm volatile("cp.reduce.async.bulk.global.shared::cta.bulk_group.add.f32 [%0], [%1], 8192;" ::"l"(g_ssqc + (layer * 16 + (b & 15)) * 2048),
                                 "r"(sb + SM_SSQ) : "memory");
                    asm volatile("cp.async.bulk.commit_group;" ::: "memory");
                    asm volatile("cp.async.bulk.wait_group 0;" ::: "memory");
                    TX(1 + 8 * layer);
                    fence_async();
                    red_release(&g_bar[1 + 2 * layer], 1);
                    TX(2 + 8 * layer);
                }
            }
        } else if (tid == 384) {
#pragma unroll 1
            for (int kb = 0; kb < 8; kb++) {
                uint32_t fb = BAR(B_FULL0 + kb);
                mbar_expect(fb, 16384);
                tma_5d_mc(sb + SM_A + 65536 + kb * 16384 + par * 8192, &tm_x, kb * 64, 0, 0, 8 * par, c, fb);
            }
#pragma unroll 1
            for (int k2 = 0; k2 < 8; k2++) {
                asm volatile("cp.async.bulk.prefetch.tensor.2d.L2.global [%0, {%1,%2}];" ::"l"(par ? &tm_bim : &tm_bre), "r"(k2 * 64), "r"(32 * c) : "memory");
                if ((k2 & 1) == par)
                    asm volatile("cp.async.bulk.prefetch.tensor.2d.L2.global [%0, {%1,%2}];" ::"l"((c & 1) ? &tm_cim : &tm_cre), "r"(64 * (c >> 1)), "r"(k2 * 64) : "memory");
            }
            mbar_wait(BAR(B_SETUP), 0);
#pragma unroll 1
            for (int layer = 0; layer < 2; layer++) {
                if (layer == 1) {
                    mbar_wait(BAR(B_AEMPTY + 4), 0);
                    mbar_expect(BAR(B_WRDY), 16384);
                    bulk_g2s(sb + SM_H + 16384, g_Wfrag + (uint32_t)b * 1024, 16384, BAR(B_WRDY));
                }
                wait_count(&g_bar[2 * layer], s_tgt[2 * layer]);
                TX(4 + 8 * layer);
                fence_async();
                mbar_expect(BAR(B_COL), 16384 + 8192);
                tma_5d(sb + SM_RAW, &tm_col, 32 * (b & 1), 0, b >> 1, 0, layer, BAR(B_COL));
                bulk_g2s(sb + SM_SSQ, g_ssq + layer * 2048, 8192, BAR(B_COL));
                if (layer == 0) {
                    wait_count(&g_bar[4], s_tgt[4]);
                    fence_async();
                    TX(16);
                    mbar_wait(BAR(B_B1DONE), 0);
                    TX(17);
                    mbar_expect(BAR(B_WRDY), 16384);
                    bulk_g2s(sb + SM_H + 16384, g_Wfrag + (uint32_t)b * 1024, 16384, BAR(B_WRDY));
                    wait_count(&g_bar[7], s_tgt[4]);
                    fence_async();
                }
                if (layer == 0) mbar_wait(BAR(B_AFREE), 0);
                mbar_wait(BAR(B_COL), layer);
#pragma unroll 1
                for (int s = 0; s < 8; s++) {
                    if (layer == 1) mbar_wait(BAR(B_AEMPTY + s), fpar(s, 2, 0));
                    if (s >= 2) mbar_wait(BAR(B_AFULL + s - 2), fpar(s - 2, 0, layer));
                    mbar_expect(BAR(B_AFULL + s), 16384);
                    bulk_g2s(sb + SM_A + s * 16384, g_A1 + (uint32_t)(r * 8 + s) * 16384, 16384, BAR(B_AFULL + s));
                }
                if (layer == 1) wait_count(&g_bar[6], s_tgt[4]);
                wait_count(&g_bar[1 + 2 * layer], s_tgt[1 + 2 * layer]);
                TX(3 + 8 * layer);
                fence_async();
                const uint8_t* xsrc = g_X + (uint32_t)(layer * 16 + c) * 8 * 16384;
                const uint8_t* esrc = g_E + (uint32_t)(layer * 8 + own) * 8 * 8192;
                mbar_arrive(BAR(B_SSQ), 1);
                mbar_expect(BAR(B_HPEER), 16384);
                mbar_expect(BAR(B_HPEER1), 16384);
#pragma unroll 1
                for (int it = 0; it < 20; it++) {
                    if (it < 8) {
                        const int st = it < 6 ? it : it - 6;
                        if (it >= 6) mbar_wait_cluster(BAR(B_XEMPTY + st), layer);
                        mbar_expect(BAR(B_XFULL + st), 16384);
                        bulk_g2s_mc(sb + SM_X + st * 16384 + par * 8192, xsrc + (uint32_t)it * 16384 + par * 8192, 8192, BAR(B_XFULL + st));
                    }
                    if (it >= 6) {
                        const int s = it < 14 ? it - 6 : it - 14;
                        const bool isc = it >= 12;
                        mbar_wait(BAR(B_AEMPTY + s), fpar(s, it < 14 ? 0 : 1, layer));
                        uint32_t fb = BAR(B_AFULL + s), dst = sb + SM_A + s * 16384;
                        mbar_expect(fb, 16384);
                        if (!isc) {
                            bulk_g2s(dst, s < 4 ? esrc + (uint32_t)s * 16384 : xsrc + (uint32_t)(s - 4) * 16384, 16384, fb);
                        } else {
                            const int tile = 4 * par + ((pi_ + 1 + (((s + 2) & 7) >> 1)) & 3), sl = r ^ (s & 1);
                            if (layer == 1) {
                                tma_2d(dst, &tm_cre, 64 * sl, 64 * tile, fb);
                                tma_2d(dst + 8192, &tm_cim, 64 * sl, 64 * tile, fb);
                            } else {
                                bulk_g2s(dst, g_A2 + (uint32_t)(sl * 8 + tile) * 16384, 16384, fb);
                            }
                        }
                    }
                }
            }
        }
        return;
    }

    asm volatile("setmaxnreg.inc.sync.aligned.u32 152;");
    if (tid >= 96 && tid < 112) g_ssq[2048 + 16 * b + tid - 96] = 0.f;
    if (tid >= 128 && tid < 256) ((float4*)g_ssqc)[b * 128 + tid - 128] = make_float4(0.f, 0.f, 0.f, 0.f);
    TS(0);
    if (wg == 0) TC(30);
    {
        const int f = 32 * r + lane;
        float cd, sd;
        __sincosf((float)f * (6.283185307179586f / 512.f), &sd, &cd);
        const uint32_t dst = sb + SM_A + (lane >> 2) * 1024 + (lane & 3) * 32;
#pragma unroll 1
        for (int ch = tid >> 5; ch < 64; ch += 12) {
            int a = (8 * ch * f) & 511;
            a = a >= 256 ? a - 512 : a;
            float cs, sn;
            __sincosf((float)a * (6.283185307179586f / 512.f), &sn, &cs);
            float cv[8], sv[8];
#pragma unroll
            for (int e = 0; e < 8; e++) {
                cv[e] = cs; sv[e] = -sn;
                float t = cs * cd - sn * sd;
                sn = sn * cd + cs * sd;
                cs = t;
            }
            uint4 o1 = make_uint4(pack_bf16(sv[0], sv[1]), pack_bf16(sv[2], sv[3]), pack_bf16(sv[4], sv[5]), pack_bf16(sv[6], sv[7]));
            if (f == 0) o1 = make_uint4(0xbf803f80u, 0xbf803f80u, 0xbf803f80u, 0xbf803f80u);
            uint32_t a0 = dst + (ch >> 3) * 8192 + (ch & 7) * 128;
            sts128(a0, make_uint4(pack_bf16(cv[0], cv[1]), pack_bf16(cv[2], cv[3]), pack_bf16(cv[4], cv[5]), pack_bf16(cv[6], cv[7])));
            sts128(a0 + 16, o1);
        }
    }
    fence_async_smem();
    asm volatile("barrier.cluster.wait.acquire.aligned;" ::: "memory");
    bar_sync(10, 384);
    TS(1);
    if (wg < 2) {
        float acc[32];
        acc_def(acc);
        const int npos = 16 * r + 8 * wg + 2 * w;
        float sh0 = 0.f, sh1 = 0.f, s0 = 0.f, s1 = 0.f, q0 = 0.f, q1 = 0.f;
#pragma unroll 1
        for (int kb = 0; kb < 8; kb++) {
            uint32_t slot = sb + SM_A + 65536 + kb * 16384;
            mbar_wait(BAR(B_FULL0 + kb), 0);
            wg_fence();
#pragma unroll
            for (int ks = 0; ks < 4; ks++)
                wgmma_n64<0>(acc, desc_a(sb + SM_A + kb * 8192 + ks * 256), desc_k(slot + wg * 8192 + ks * 32), 1);
            wg_commit();
            {
                uint32_t v0 = lds32(slot + npos * 128 + lane * 4), v1 = lds32(slot + npos * 128 + 128 + lane * 4);
                if (kb == 0) { sh0 = __shfl_sync(~0u, bf_lo(v0), 0); sh1 = __shfl_sync(~0u, bf_lo(v1), 0); }
                float a = bf_lo(v0) - sh0, bq = bf_hi(v0) - sh0, cq = bf_lo(v1) - sh1, d = bf_hi(v1) - sh1;
                s0 += a + bq; q0 += a * a + bq * bq; s1 += cq + d; q1 += cq * cq + d * d;
            }
            wg_wait<1>();
            if (kb > 0 && kb <= 4 && lane == 0) { mbar_arrive(BAR(B_EMPTY0 + kb - 1), 1); mbar_arrive_remote(mapa(BAR(B_EMPTY0 + kb - 1), par ^ 1)); }
        }
#pragma unroll
        for (int o = 16; o; o >>= 1) {
            s0 += __shfl_xor_sync(~0u, s0, o); q0 += __shfl_xor_sync(~0u, q0, o);
            s1 += __shfl_xor_sync(~0u, s1, o); q1 += __shfl_xor_sync(~0u, q1, o);
        }
        if (lane == 0) *(float2*)(g_ssq + 128 * c + npos) = make_float2(fmaxf(q0 - s0 * s0 * (1.f / 512.f), 0.f), fmaxf(q1 - s1 * s1 * (1.f / 512.f), 0.f));
        wg_wait<0>();
        TS(2);
        uint8_t* dst = g_X + (uint32_t)((c * 8 + r) * 16384 + w * 4096 + wg * 1024 + g * 16 + 4 * q);
#pragma unroll
        for (int i = 0; i < 8; i++) {
            *(uint32_t*)(dst + i * 128) = pack_bf16(acc[4 * i], acc[4 * i + 1]);
            *(uint32_t*)(dst + 2048 + i * 128) = pack_bf16(acc[4 * i + 2], acc[4 * i + 3]);
        }
        bar_sync(2, 288);
        mbar_wait(BAR(B_SETUP), 0);
        TS(3);
    }

    if (wg == 2) {
        {
            uint4 p0 = __ldg((const uint4*)p.dskip + 2 * lane), p1 = __ldg((const uint4*)p.dskip + 2 * lane + 1);
            uint32_t u[8] = {p0.x, p0.y, p0.z, p0.w, p1.x, p1.y, p1.z, p1.w};
            int j = 64 * r + 4 * c + w, f, ph;
            dft_fp(j, f, ph);
            float s = 0.f;
            int idx = 16 * lane * f + ph;
#pragma unroll
            for (int i = 0; i < 16; i++) {
                int a = idx & 511;
                idx += f;
                a = a >= 256 ? a - 512 : a;
                s += ((i & 1) ? bf_hi(u[i >> 1]) : bf_lo(u[i >> 1])) * __cosf((float)a * (6.283185307179586f / 512.f));
            }
#pragma unroll
            for (int o = 16; o; o >>= 1) s += __shfl_xor_sync(~0u, s, o);
            if (lane == 0) g_Dh[j] = s;
        }
        mbar_wait(BAR(B_FULL0 + 7), 0);
        if (tid == 256) {
#pragma unroll 1
            for (int s = 0; s < 4; s++) mbar_wait_cluster(BAR(B_EMPTY0 + s), 0);
            mbar_expect(BAR(B_FULLB), 65536);
#pragma unroll 1
            for (int k2 = 0; k2 < 8; k2++)
                tma_2d_mc(sb + SM_A + 65536 + k2 * 8192 + par * 4096, par ? &tm_bim : &tm_bre, k2 * 64, 32 * c, BAR(B_FULLB));
        }
        __syncwarp();
        {
            const int cl = tid & 15, cb = 16 * (b & 7) + cl;
            const int c0 = cb == 0 ? 256 : 2 * cb, c1 = 2 * cb + 1;
            uint32_t wf[2][16];
#pragma unroll
            for (int h = 0; h < 2; h++) {
                const int kq = 16 * (b >> 3) + ((tid & 127) >> 4) + 8 * h, k1 = kq >> 2, qq = kq & 3;
                const unsigned short* wr_ = (const unsigned short*)p.w_r + (k1 + 128 * qq) * 257;
                const unsigned short* wi_ = (const unsigned short*)p.w_i + (k1 + 128 * qq) * 257;
#pragma unroll
                for (int i = 0; i < 4; i++) {
                    int o = 512 * i * 257;
                    wf[h][2 * i] = (uint32_t)__ldg(wr_ + o + c0) | ((uint32_t)__ldg(wr_ + o + 64 * 257 + c0) << 16);
                    wf[h][2 * i + 1] = ((uint32_t)__ldg(wi_ + o + c0) | ((uint32_t)__ldg(wi_ + o + 64 * 257 + c0) << 16)) ^ 0x80008000u;
                    wf[h][8 + 2 * i] = (uint32_t)__ldg(wr_ + o + c1) | ((uint32_t)__ldg(wr_ + o + 64 * 257 + c1) << 16);
                    wf[h][8 + 2 * i + 1] = ((uint32_t)__ldg(wi_ + o + c1) | ((uint32_t)__ldg(wi_ + o + 64 * 257 + c1) << 16)) ^ 0x80008000u;
                }
            }
#pragma unroll
            for (int h = 0; h < 2; h++)
#pragma unroll
                for (int i = 0; i < 4; i++)
                    sts128(sb + SM_H + cl * 1024 + (((tid & 127) >> 4) + 8 * h) * 64 + ((i ^ ((tid >> 5) & 3)) << 4),
                           make_uint4(wf[h][4 * i], wf[h][4 * i + 1], wf[h][4 * i + 2], wf[h][4 * i + 3]));
            fence_async_smem();
            bar_arrive(0, 192);
            bar_arrive(11, 192);
        }
        bar_sync(15, 160);
        float acc[32];
        acc_def(acc);
        mbar_wait(BAR(B_FULLB), 0);
        wg_fence();
#pragma unroll 1
        for (int kb = 0; kb < 8; kb++) {
#pragma unroll
            for (int ks = 0; ks < 4; ks++)
                wgmma_n64<0>(acc, desc_a(sb + SM_A + kb * 8192 + ks * 256), desc_k(sb + SM_A + 65536 + kb * 8192 + ks * 32), 1);
            wg_commit();
        }
        wg_wait<0>();
        if (lane == 0) { mbar_arrive(BAR(B_BFREE), 1); mbar_arrive_remote(mapa(BAR(B_BFREE), par ^ 1)); }
        if (tid == 256) {
            mbar_wait_cluster(BAR(B_BFREE), 0);
            mbar_expect(BAR(B_FULLC), 65536);
#pragma unroll 1
            for (int k2 = par; k2 < 8; k2 += 2)
                tma_2d_mc(sb + SM_A + 65536 + k2 * 8192, (c & 1) ? &tm_cim : &tm_cre, 64 * (c >> 1), k2 * 64, BAR(B_FULLC));
        }
        __syncwarp();
        {
            uint8_t* dst = sm + SM_B1ST + w * 256 + q * 32 + g * 2;
            const float wj0 = (r == 0 && w == 0 && g < 2) ? (g == 0 ? 0.f : 1.f / 512.f) : 2.f / 512.f;
#pragma unroll
            for (int i = 0; i < 4; i++) {
#pragma unroll
                for (int e = 0; e < 2; e++) {
                    float2 cf = *(const float2*)(sm + SM_TAB + (8 * i + 2 * q + e) * 8);
#pragma unroll
                    for (int h = 0; h < 2; h++) {
                        float wj = h == 0 ? wj0 : 2.f / 512.f;
                        float pr = acc[4 * i + 2 * h + e] * wj, pi = acc[16 + 4 * i + 2 * h + e] * wj;
                        uint8_t* d2 = dst + i * 2048 + h * 128 + e * 16;
                        *(__nv_bfloat16*)(d2) = __float2bfloat16(cf.x * pr - cf.y * pi);
                        *(__nv_bfloat16*)(d2 + 1024) = __float2bfloat16(cf.x * pi + cf.y * pr);
                    }
                }
            }
            fence_async_smem();
            bar_arrive(12, 160);
        }
        acc_def(acc);
        mbar_wait(BAR(B_FULLC), 0);
        wg_fence();
#pragma unroll 1
        for (int kb = 0; kb < 8; kb++) {
#pragma unroll
            for (int ks = 0; ks < 4; ks++)
                wgmma_n64<1>(acc, desc_a(sb + SM_A + kb * 8192 + ks * 256), desc_mn(sb + SM_A + 65536 + kb * 8192 + ks * 2048, 8192), 1);
            wg_commit();
        }
        wg_wait<0>();
        fence_async_smem();
        if (lane == 0) mbar_arrive(BAR(B_AFREE), 1);
        uint8_t* dst = g_A2 + (uint32_t)(((c >> 1) * 8 + r) * 16384 + (c & 1) * 8192 + w * 2048 + g * 16 + 4 * q);
#pragma unroll
        for (int i = 0; i < 8; i++) {
            *(uint32_t*)(dst + i * 128) = pack_bf16(acc[4 * i], acc[4 * i + 1]);
            *(uint32_t*)(dst + 1024 + i * 128) = pack_bf16(acc[4 * i + 2], acc[4 * i + 3]);
        }
        {
            const int m = 4 * c + w, jp = 64 * r + m;
            int fp, php;
            dft_fp(jp, fp, php);
            const __nv_bfloat16* dh = (const __nv_bfloat16*)(sm + SM_RSTD);
            if (tid == 256) wait_count(&g_bar[4], s_tgt[4]);
            bar_sync(3, 128);
            float4 d4 = __ldcg((const float4*)g_Dh + (tid - 256));
            *(uint2*)(sm + SM_RSTD + (tid - 256) * 8) = make_uint2(pack_bf16(d4.x, d4.y), pack_bf16(d4.z, d4.w));
            bar_sync(3, 128);
#pragma unroll 1
            for (int it = 0; it < 2; it++) {
                const int ch = lane + 32 * it;
                float v[8];
#pragma unroll
                for (int e = 0; e < 8; e++) {
                    int j = 8 * ch + e, f, ph;
                    dft_fp(j, f, ph);
                    float wj = j == 0 ? 0.f : (j == 1 ? 1.f / 512.f : 2.f / 512.f);
                    float gsum = 0.f;
#pragma unroll
                    for (int sgn = 0; sgn < 2; sgn++) {
                        int mm = (sgn ? f - fp : f + fp) & 511, pp = (sgn ? ph - php : ph + php) & 511;
                        if (mm > 256) { mm = 512 - mm; pp = (512 - pp) & 511; }
                        int odd = (pp >> 7) & 1;
                        float t = __bfloat162float(dh[mm == 256 ? 1 : 2 * mm + odd]);
                        if (odd && (mm & 255) == 0) t = 0.f;
                        gsum += (pp & 256) ? -t : t;
                    }
                    v[e] = 0.5f * wj * gsum;
                }
                uint32_t off = (uint32_t)(r * 8 + (ch >> 3)) * 8192 + (m >> 3) * 1024 + (ch & 7) * 128 + (m & 7) * 16;
                *(uint4*)(g_E + off) = make_uint4(pack_bf16(v[0], v[1]), pack_bf16(v[2], v[3]), pack_bf16(v[4], v[5]), pack_bf16(v[6], v[7]));
            }
        }
    }

#pragma unroll 1
    for (int layer = 0; layer < 2; layer++) {
        if (wg < 2) {
            const int n1 = 32 * wg + 8 * w + g;
            const int ct = n1 >> 2;
            gen_col_consts(sb, tid);
            uint32_t tr2[4], ti2[4], tn2[4];
#pragma unroll
            for (int i = 0; i < 4; i++) {
                float cr[2], ci[2];
#pragma unroll
                for (int e = 0; e < 2; e++) {
                    int a = (n1 * (8 * i + 2 * q + e)) & 2047;
                    a = a >= 1024 ? a - 2048 : a;
                    float ang = (float)a * (-6.283185307179586f / 2048.f);
                    cr[e] = __cosf(ang); ci[e] = __sinf(ang);
                }
                tr2[i] = pack_bf16(cr[0], cr[1]); ti2[i] = pack_bf16(ci[0], ci[1]); tn2[i] = ti2[i] ^ 0x80008000u;
            }
            mbar_wait(BAR(B_WST), 0);
            mbar_wait(BAR(B_COL), layer);
            TS(4 + 12 * layer);
            if (wg == 0) TC(0 + 10 * layer);
            const uint32_t rw0 = sb + SM_RAW + ct * 1024 + q * 64 + ((q >> 1) << 4) + (g & 3) * 4, rw1 = rw0 ^ 16;
            const int pos0 = 128 * ct + 8 * q + 2 * (g & 3);
            const int sw = b == 0 ? 1 : 0;
            uint32_t xr[4][4];
            const uint32_t st0 = sb + SM_H + (n1 >> 3) * 1024 + g * 16 + 4 * q;
#pragma unroll
            for (int i = 0; i < 4; i++) {
                float2 sq = *(const float2*)(sm + SM_SSQ + (pos0 + 32 * i) * 4);
                const uint32_t rs2 = pack_bf16(rsqrtf(sq.x * (1.f / 512.f) + 1e-5f), rsqrtf(sq.y * (1.f / 512.f) + 1e-5f));
#pragma unroll
                for (int jj = 0; jj < 4; jj++) {
                    const int K = jj ^ (2 * (i & 1));
                    uint32_t a = ((K & 1) ? rw1 : rw0) + i * 256 + (K & 2) * 16;
                    if (jj < 2) a ^= sw << 4;
                    uint32_t v = lds32(a);
                    xr[jj][i] = v;
                    uint32_t o = hmul2(v, rs2);
                    if (jj == 1 && sw) o = 0u;
                    sts32(st0 + (jj & 1) * 8192 + (4 * (jj >> 1) + i) * 128, o);
                }
            }
            if (wg == 0) TC(1 + 10 * layer);
            fence_async_smem();
            bar_sync(1, 256);
            float acc[32];
            const uint32_t s1a = sb + SM_X + wg * 16384, s2b = sb + SM_X + 32768;
            wg_fence();
#pragma unroll
            for (int ks = 0; ks < 8; ks++)
                wgmma_n64<1>(acc, desc_a(s1a + (ks >> 2) * 8192 + (ks & 3) * 256), desc_b<64>(sb + SM_H + ks * 2048), ks != 0);
            wg_commit();
            wg_wait<0>();
            if (wg == 0) TC(2 + 10 * layer);
            uint32_t are[2][4], aim[2][4];
#pragma unroll
            for (int col = 0; col < 2; col++) {
#pragma unroll
                for (int i = 0; i < 4; i++) {
                    int o = 4 * (4 * col + i);
                    uint32_t zr = pack_bf16(acc[o], acc[o + 1]), zi = pack_bf16(acc[o + 2], acc[o + 3]);
                    are[col][i] = hfma2(zr, tr2[i], hmul2(zi, tn2[i]));
                    aim[col][i] = hfma2(zr, ti2[i], hmul2(zi, tr2[i]));
                }
            }
            wg_fence();
#pragma unroll
            for (int ks = 0; ks < 2; ks++)
                wgmma_n64_rs(acc, are[0][2 * ks], are[1][2 * ks], are[0][2 * ks + 1], are[1][2 * ks + 1], desc_b<64>(s2b + ks * 2048), ks != 0);
#pragma unroll
            for (int ks = 0; ks < 2; ks++)
                wgmma_n64_rs(acc, aim[0][2 * ks], aim[1][2 * ks], aim[0][2 * ks + 1], aim[1][2 * ks + 1], desc_b<64>(s2b + 4096 + ks * 2048), 1);
            wg_commit();
            uint32_t wf[16];
            mbar_wait(BAR(B_WRDY), layer);
#pragma unroll
            for (int i = 0; i < 4; i++) {
                const int kq = n1 * 4 + q;
                uint4 v = *(const uint4*)(sm + SM_H + 16384 + kq * 64 + ((i ^ ((kq >> 1) & 3)) << 4));
                wf[4 * i] = v.x; wf[4 * i + 1] = v.y; wf[4 * i + 2] = v.z; wf[4 * i + 3] = v.w;
            }
            wg_wait<0>();
            if (wg == 0) TC(3 + 10 * layer);
#pragma unroll
            for (int col = 0; col < 2; col++) {
#pragma unroll
                for (int i = 0; i < 4; i++) {
                    uint32_t wr = wf[col * 8 + 2 * i], wn = wf[col * 8 + 2 * i + 1];
                    uint32_t zr = pack_bf16(acc[4 * i + 2 * col], acc[4 * i + 2 * col + 1]);
                    uint32_t zi = pack_bf16(acc[16 + 4 * i + 2 * col], acc[16 + 4 * i + 2 * col + 1]);
                    are[col][i] = hfma2(zr, wr, hmul2(zi, wn));
                    aim[col][i] = hfma2(zr, wn, hmul2(zi ^ 0x80008000u, wr));
                }
            }
            wg_fence();
#pragma unroll
            for (int ks = 0; ks < 2; ks++)
                wgmma_n64_rs(acc, are[0][2 * ks], are[1][2 * ks], are[0][2 * ks + 1], are[1][2 * ks + 1], desc_b<64>(s2b + ks * 2048), ks != 0);
#pragma unroll
            for (int ks = 0; ks < 2; ks++)
                wgmma_n64_rs(acc, aim[0][2 * ks], aim[1][2 * ks], aim[0][2 * ks + 1], aim[1][2 * ks + 1], desc_b<64>(s2b + 4096 + ks * 2048), 1);
            wg_commit();
            wg_wait<0>();
            if (wg == 0) TC(4 + 10 * layer);
            bar_sync(1, 256);
#pragma unroll
            for (int col = 0; col < 2; col++) {
#pragma unroll
                for (int i = 0; i < 4; i++) {
                    uint32_t zr = pack_bf16(acc[4 * i + 2 * col], acc[4 * i + 2 * col + 1]);
                    uint32_t zi = pack_bf16(acc[16 + 4 * i + 2 * col], acc[16 + 4 * i + 2 * col + 1]);
                    sts32(st0 + 16384 + (4 * col + i) * 128, hfma2(zr, tr2[i], hmul2(zi, tn2[i])));
                    sts32(st0 + 16384 + 8192 + (4 * col + i) * 128, hfma2(zr, ti2[i], hmul2(zi, tr2[i])));
                }
            }
            if (wg == 0) TC(5 + 10 * layer);
            fence_async_smem();
            bar_sync(1, 256);
            wg_fence();
#pragma unroll
            for (int ks = 0; ks < 8; ks++)
                wgmma_n64<1>(acc, desc_a(s1a + (ks >> 2) * 8192 + (ks & 3) * 256), desc_b<64>(sb + SM_H + 16384 + ks * 2048), ks != 0);
            wg_commit();
            wg_wait<0>();
            if (wg == 0) TC(6 + 10 * layer);
            const float sc = 1.f / 2048.f;
            const float sci0 = sw ? 0.f : -sc;
            const float wr0 = sw ? 0.5f : 1.f, wi0 = sw ? 0.f : 1.f;
#pragma unroll
            for (int i = 0; i < 4; i++) {
                float ss0, ss1;
#pragma unroll
                for (int col = 0; col < 2; col++) {
                    int o = 4 * (4 * col + i);
                    uint32_t vr = xr[2 * col][i], vi = xr[2 * col + 1][i];
                    float si = col == 0 ? sci0 : -sc;
                    uint32_t nr = pack_bf16(fmaf(acc[o], sc, bf_lo(vr)), fmaf(acc[o + 1], sc, bf_hi(vr)));
                    uint32_t ni = pack_bf16(fmaf(acc[o + 2], si, bf_lo(vi)), fmaf(acc[o + 3], si, bf_hi(vi)));
                    float a0 = bf_lo(nr), a1 = bf_hi(nr), b0 = bf_lo(ni), b1 = bf_hi(ni);
                    if (col == 0) {
                        ss0 = wr0 * a0 * a0 + wi0 * b0 * b0;
                        ss1 = wr0 * a1 * a1 + wi0 * b1 * b1;
                    } else {
                        ss0 += a0 * a0 + b0 * b0;
                        ss1 += a1 * a1 + b1 * b1;
                    }
                    const int K = (2 * col) ^ (2 * (i & 1));
                    uint32_t a = rw0 + i * 256 + K * 16;
                    if (col == 0) a ^= sw << 4;
                    sts32(a, nr);
                    sts32(a ^ 16, ni);
                }
                *(float2*)(sm + SM_SSQ + (pos0 + 32 * i) * 4) = make_float2(ss0 * (2.f / 512.f), ss1 * (2.f / 512.f));
            }
            fence_async_smem();
        }
        TS(5 + 12 * layer);
        if (wg == 0) TC(7 + 10 * layer);
        bar_arrive(5, 416);

        float acc[64];
        float* s_rstd = (float*)(sm + SM_RSTD);
        float* s_mean = (float*)(sm + SM_MEAN);
        const unsigned epoch = s_tgt[0] >> 7;
        const uint32_t pt3 = 1u + (2u * epoch + layer) % 3u;
        const uint32_t ptag = (pt3 & 1u) | ((pt3 & 2u) << 15);
        const uint64_t dstep = layer == 0 ? 16 : 2;
        auto c_desc = [&](int s) { return layer == 0 ? desc_a(sb + SM_A + s * 16384) : desc_k(sb + SM_A + s * 16384); };
        if (wg < 2) {
            const int prow = 32 * wg + 8 * w + g;
            const float2 l1 = *(const float2*)(sm + SM_LAM + prow * 8);
            float lr32 = l1.x, li32 = l1.y;
#pragma unroll
            for (int i = 0; i < 5; i++) { float t = lr32 * lr32 - li32 * li32; li32 = 2.f * lr32 * li32; lr32 = t; }
            float lr128 = lr32, li128 = li32;
#pragma unroll
            for (int i = 0; i < 2; i++) { float t = lr128 * lr128 - li128 * li128; li128 = 2.f * lr128 * li128; lr128 = t; }
            const float lr1 = l1.x, li1 = l1.y;
            const float l2r = lr128 * lr128 - li128 * li128, l2i = 2.f * lr128 * li128;
            const float l4r = l2r * l2r - l2i * l2i, l4i = 2.f * l2r * l2i;
            float lxr = 1.f, lxi = 0.f;
            {
                const int rho = (c - 1 - q) & 3;
                if (rho & 1) { lxr = lr128; lxi = li128; }
                if (rho & 2) { float t = lxr * l2r - lxi * l2i; lxi = lxr * l2i + lxi * l2r; lxr = t; }
            }
            acc_def(acc);
#pragma unroll 1
            for (int kb = 0; kb < 8; kb++) {
                const int st = kb < 6 ? kb : kb - 6;
                mbar_wait(BAR(B_AFULL + kb), fpar(kb, 0, layer));
                mbar_wait(BAR(B_XFULL + st), st < 2 ? (uint32_t)(kb >= 6) : (uint32_t)layer);
                wg_fence();
#pragma unroll
                for (int ks = 0; ks < 4; ks++)
                    wgmma_n128<1>(acc, desc_a(sb + SM_A + kb * 16384 + wg * 8192 + ks * 256),
                                  desc_b<128>(sb + SM_X + st * 16384 + ks * 4096), 1);
                wg_commit();
                wg_wait<1>();
                if (kb > 0 && lane == 0) {
                    mbar_arrive(BAR(B_AEMPTY + kb - 1), 1);
                    if (kb <= 2) { mbar_arrive(BAR(B_XEMPTY + kb - 1), 1); mbar_arrive_remote(mapa(BAR(B_XEMPTY + kb - 1), par ^ 1)); }
                }
            }
            wg_wait<0>();
            if (lane == 0) {
                mbar_arrive(BAR(B_AEMPTY + 7), 1);
                mbar_arrive_remote(mapa(BAR(B_RFREE), par ^ 1));
            }
            bar_arrive(14, 384);
            TS(6 + 12 * layer);
            bar_sync(4, 384);
            TS(7 + 12 * layer);
            float er = 0.f, ei = 0.f;
#pragma unroll
            for (int i = 0; i < 16; i++) {
                float2 rs = *(const float2*)(s_rstd + 128 + 8 * i + 2 * q);
                acc[4 * i] *= rs.x; acc[4 * i + 1] *= rs.y; acc[4 * i + 2] *= rs.x; acc[4 * i + 3] *= rs.y;
                float nr = lr1 * er - li1 * ei + acc[4 * i], ni = lr1 * ei + li1 * er + acc[4 * i + 2];
                er = lr1 * nr - li1 * ni + acc[4 * i + 1];
                ei = lr1 * ni + li1 * nr + acc[4 * i + 3];
            }
            float cr = 0.f, ci = 0.f, tr = 0.f, ti = 0.f;
#pragma unroll
            for (int qq = 0; qq < 4; qq++) {
                float xr_ = __shfl_sync(~0u, er, (lane & ~3) | qq), xi_ = __shfl_sync(~0u, ei, (lane & ~3) | qq);
                if (qq == q) { cr = tr; ci = ti; }
                float nr = lr32 * tr - li32 * ti + xr_, ni = lr32 * ti + li32 * tr + xi_;
                tr = nr; ti = ni;
            }
            float4* eb = g_Ebuf + (uint32_t)(layer * 16 * 512 + 64 * r + prow);
            if (q == 0 && c < 15) st_relaxed_f4(eb + c * 512, make_float4(tr, ti, __uint_as_float(epoch), 0.f));
            TS(8 + 12 * layer);
            float pr[4], pi[4];
            {
                unsigned n = 0;
                bool ok;
#pragma unroll 1
                do {
                    ok = true;
#pragma unroll
                    for (int k = 0; k < 4; k++) {
                        float4 v = make_float4(0.f, 0.f, __uint_as_float(epoch), 0.f);
                        if (4 * k + q < c) v = ld_relaxed_f4(eb + (4 * k + q) * 512);
                        pr[k] = v.x; pi[k] = v.y;
                        ok = ok && __float_as_uint(v.z) == epoch;
                    }
                } while (!ok && ++n < SPIN_LIMIT);
            }
            __syncwarp();
            TS(9 + 12 * layer);
            float hr = 0.f, hi = 0.f;
#pragma unroll
            for (int k = 0; k < 4; k++) {
                if (4 * k + q < c) {
                    float nr = l4r * hr - l4i * hi + pr[k], ni = l4r * hi + l4i * hr + pi[k];
                    hr = nr; hi = ni;
                }
            }
            {
                float nr = lxr * hr - lxi * hi, ni = lxr * hi + lxi * hr;
                hr = nr + __shfl_xor_sync(~0u, nr, 1); hi = ni + __shfl_xor_sync(~0u, ni, 1);
                hr += __shfl_xor_sync(~0u, hr, 2); hi += __shfl_xor_sync(~0u, hi, 2);
            }
#pragma unroll
            for (int qq = 0; qq < 3; qq++) {
                if (qq < q) { float nr = lr32 * hr - li32 * hi, ni = lr32 * hi + li32 * hr; hr = nr; hi = ni; }
            }
            er = cr + hr; ei = ci + hi;
            bar_sync(7, 384);
            mbar_wait_cluster(BAR(B_RFREE), layer);
            const uint32_t ha = sb + SM_HH + par * 32768 + (prow >> 3) * 1024 + g * 16 + 4 * q;
#pragma unroll
            for (int i = 0; i < 16; i++) {
                float nr = lr1 * er - li1 * ei + acc[4 * i], ni = lr1 * ei + li1 * er + acc[4 * i + 2];
                er = lr1 * nr - li1 * ni + acc[4 * i + 1];
                ei = lr1 * ni + li1 * nr + acc[4 * i + 3];
                sts32(ha + (i >> 3) * 16384 + (i & 7) * 128, pack_bf16(nr, er));
                sts32(ha + (i >> 3) * 16384 + 8192 + (i & 7) * 128, pack_bf16(ni, ei));
                if (i == 7) { fence_async_smem(); bar_arrive(13, 288); }
            }
            fence_async_smem();
            acc_def(acc);
            float acc2[32];
            acc_def(acc2);
            TS(10 + 12 * layer);
            bar_sync(6, 416);
            TS(11 + 12 * layer);
            float (&a0)[32] = *reinterpret_cast<float (*)[32]>(&acc[0]);
            float (&a1)[32] = *reinterpret_cast<float (*)[32]>(&acc[32]);
            auto tile_mma = [&](float (&d)[32], int u) {
#pragma unroll 1
                for (int k = 0; k < 2; k++) {
                    const uint32_t hb = sb + SM_HH + (par ^ k) * 32768 + wg * 16384;
                    if (k == 1) mbar_wait(BAR(wg ? B_HPEER1 : B_HPEER), layer);
                    const int cs = (2 * u + 6 + k) & 7;
                    mbar_wait(BAR(B_AFULL + cs), fpar(cs, 2, layer));
                    const uint64_t da = c_desc(cs);
                    wg_fence();
#pragma unroll
                    for (int ks = 0; ks < 4; ks++) wgmma_n64s<1>(d, da + ks * dstep, desc_b<64>(hb + ks * 2048), 1);
#pragma unroll
                    for (int ks = 0; ks < 4; ks++) wgmma_n64s<-1>(d, da + 512 + ks * dstep, desc_b<64>(hb + 8192 + ks * 2048), 1);
                }
                wg_commit();
            };
            auto tile_ship = [&](float (&d)[32], int u) {
                uint4* dst = g_P + (uint32_t)(((c * 8 + 2 * ((pi_ + 1 + u) & 3) + par) * 4 + pi_) * 1024 + wg * 512 + (tid & 127));
#pragma unroll
                for (int i = 0; i < 4; i++)
                    dst[i * 128] = make_uint4((pack_bf16(d[8 * i], d[8 * i + 1]) & 0xfffefffeu) | ptag, pack_bf16(d[8 * i + 2], d[8 * i + 3]),
                                              pack_bf16(d[8 * i + 4], d[8 * i + 5]), pack_bf16(d[8 * i + 6], d[8 * i + 7]));
            };
            tile_mma(a0, 0);
            if ((tid & 127) == 0) mbar_arrive_remote(mapa(BAR(B_HDONE), par ^ 1));
            __syncwarp();
            tile_mma(a1, 1);
            wg_wait<1>();
            tile_ship(a0, 0);
            tile_mma(acc2, 2);
            bar_arrive(12, 384);
            wg_wait<1>();
            tile_ship(a1, 1);
            wg_wait<0>();
            tile_ship(acc2, 2);
            if (lane < 6) mbar_arrive(BAR(B_AEMPTY + ((lane + 6) & 7)), 1);
            TS(12 + 12 * layer);
        } else {
            const int t2 = tid - 256;
            const uint8_t* ximg = g_X + (uint32_t)layer * 16 * 8 * 16384;
            mbar_wait(BAR(B_SSQ), layer);
            TS(6 + 12 * layer);
            float sqv[16];
#pragma unroll
            for (int i = 0; i < 16; i++) sqv[i] = __ldcg(g_ssqc + (layer * 16 + i) * 2048 + 128 * c + t2);
            const unsigned short xm = __ldcg((const unsigned short*)(ximg + (uint32_t)(c * 8 * 16384 + (t2 >> 3) * 128 + (t2 & 7) * 2)));
            {
                float tot = 0.f;
#pragma unroll
                for (int i = 0; i < 16; i++) tot += sqv[i];
                float rs = rsqrtf(tot * (1.f / 512.f) + 1e-5f);
                s_rstd[t2] = rs;
                s_rstd[128 + t2] = 2.f * rs;
                s_mean[t2] = layer == 0 ? 0.f : __uint_as_float((uint32_t)xm << 16) * (1.f / 512.f);
                TS(7 + 12 * layer);
                bar_arrive(4, 384);
            }
            acc_def(acc);
            bar_sync(14, 384);
#pragma unroll 1
            for (int it = 0; it < 8; it++) {
                const int kb = (it + 2) & 7;
                mbar_wait(BAR(B_AFULL + (kb >> 1)), fpar(0, 1, layer));
                if (kb < 2) mbar_wait(BAR(B_AFULL + 4 + kb), fpar(0, 1, layer));
                const uint32_t xb = kb < 2 ? sb + SM_A + (4 + kb) * 16384 : sb + SM_X + (kb < 6 ? kb : kb - 6) * 16384;
                wg_fence();
#pragma unroll
                for (int ks = 0; ks < 4; ks++)
                    wgmma_n128<1>(acc, desc_a(sb + SM_A + kb * 8192 + ks * 256), desc_b<128>(xb + ks * 4096), 1);
                wg_commit();
            }
            wg_wait<0>();
            if (lane < 6) mbar_arrive(BAR(B_AEMPTY + lane), 2);
            if (lane == 0) mbar_arrive_remote(mapa(BAR(B_RFREE), par ^ 1));
            bar_arrive(7, 384);
            bar_sync(3, 128);
            TS(9 + 12 * layer);
            const int m0 = 16 * w + g;
            const uint32_t xoff = (uint32_t)((c * 8 + own) * 16384 + w * 4096 + g * 16 + 4 * q);
            if (layer == 0) {
                const uint8_t* xs = g_X + xoff;
#pragma unroll
                for (int i = 0; i < 16; i++) {
                    float2 rs = *(const float2*)(s_rstd + 8 * i + 2 * q);
                    uint32_t x0v = __ldcg((const uint32_t*)(xs + i * 128)), x1v = __ldcg((const uint32_t*)(xs + 2048 + i * 128));
                    acc[4 * i] = acc[4 * i] * rs.x + bf_lo(x0v);
                    acc[4 * i + 1] = acc[4 * i + 1] * rs.y + bf_hi(x0v);
                    acc[4 * i + 2] = acc[4 * i + 2] * rs.x + bf_lo(x1v);
                    acc[4 * i + 3] = acc[4 * i + 3] * rs.y + bf_hi(x1v);
                }
            } else {
                float d0 = ldbf(p.dskip + 64 * own + m0), d1 = ldbf(p.dskip + 64 * own + m0 + 8);
#pragma unroll
                for (int i = 0; i < 16; i++) {
                    float2 rs = *(const float2*)(s_rstd + 8 * i + 2 * q);
                    float2 mn = *(const float2*)(s_mean + 8 * i + 2 * q);
                    acc[4 * i] = acc[4 * i] * (1.f + rs.x * d0) + mn.x;
                    acc[4 * i + 1] = acc[4 * i + 1] * (1.f + rs.y * d0) + mn.y;
                    acc[4 * i + 2] = acc[4 * i + 2] * (1.f + rs.x * d1) + mn.x;
                    acc[4 * i + 3] = acc[4 * i + 3] * (1.f + rs.y * d1) + mn.y;
                }
            }
            TS(10 + 12 * layer);
            bar_sync(6, 416);
            TS(11 + 12 * layer);
            {
                float (&a0)[32] = *reinterpret_cast<float (*)[32]>(&acc[0]);
                float (&a1)[32] = *reinterpret_cast<float (*)[32]>(&acc[32]);
#pragma unroll 1
                for (int k = 0; k < 2; k++) {
                    const uint32_t hb = sb + SM_HH + (par ^ k) * 32768;
                    if (k == 1) {
                        mbar_wait(BAR(B_HPEER), layer);
                        mbar_wait(BAR(B_HPEER1), layer);
                        bar_sync(12, 384);
                    }
                    mbar_wait(BAR(B_AFULL + 4 + k), fpar(4, 2, layer));
                    const uint64_t da = c_desc(4 + k);
                    wg_fence();
#pragma unroll
                    for (int ks = 0; ks < 4; ks++) {
                        wgmma_n64s<1>(a0, da + ks * dstep, desc_b<64>(hb + ks * 2048), 1);
                        wgmma_n64s<1>(a1, da + ks * dstep, desc_b<64>(hb + 16384 + ks * 2048), 1);
                    }
#pragma unroll
                    for (int ks = 0; ks < 4; ks++) {
                        wgmma_n64s<-1>(a0, da + 512 + ks * dstep, desc_b<64>(hb + 8192 + ks * 2048), 1);
                        wgmma_n64s<-1>(a1, da + 512 + ks * dstep, desc_b<64>(hb + 16384 + 8192 + ks * 2048), 1);
                    }
                    wg_commit();
                }
                wg_wait<0>();
            }
#pragma unroll
            for (int i = 0; i < 16; i++)
                *(float4*)(sm + SM_A + 4 * 16384 + i * 2048 + t2 * 16) = make_float4(acc[4 * i], acc[4 * i + 1], acc[4 * i + 2], acc[4 * i + 3]);
            TS(12 + 12 * layer);
        }
        {
            const int t = tid & 127;
            const int nch = wg == 2 ? 2 : 3;
            const uint4* pb = g_P + (uint32_t)((c * 8 + r) * 4 * 1024 + wg * 128 + t);
            uint4 v[3][3];
            unsigned n = 0;
#pragma unroll 1
            while (true) {
                if (lane == 31) {
#pragma unroll 1
                    while (true) {
                        uint32_t bad = 0;
#pragma unroll
                        for (int sx = 0; sx < 3; sx++) {
                            uint32_t t0;
                            asm volatile("ld.relaxed.gpu.global.u32 %0, [%1];" : "=r"(t0) : "l"(pb + ((pi_ + 1 + sx) & 3) * 1024 + (nch - 1) * 384) : "memory");
                            bad |= t0 ^ ptag;
                        }
                        if (!(bad & 0x00010001u) || ++n >= SPIN_LIMIT) break;
                    }
                }
                __syncwarp();
                uint32_t bad = 0;
#pragma unroll
                for (int k = 0; k < 3; k++)
#pragma unroll
                    for (int sx = 0; sx < 3; sx++) {
                        v[k][sx] = make_uint4(ptag, 0, 0, 0);
                        if (k < nch) v[k][sx] = ld_relaxed_u4(pb + ((pi_ + 1 + sx) & 3) * 1024 + k * 384);
                        bad |= v[k][sx].x ^ ptag;
                    }
                if (!__any_sync(~0u, bad & 0x00010001u) || ++n >= SPIN_LIMIT) break;
            }
            bar_sync(8, 384);
            TS(13 + 12 * layer);
            const int m0 = 16 * w + g;
            const float w0 = (own == 0 && m0 < 2) ? (m0 == 0 ? 0.f : 0.5f) : 1.f;
#pragma unroll
            for (int k = 0; k < 3; k++) {
                if (k < nch) {
                    const int i = wg + 3 * k;
                    float4 a = *(const float4*)(sm + SM_A + 4 * 16384 + (2 * i) * 2048 + t * 16);
                    float4 bq = *(const float4*)(sm + SM_A + 4 * 16384 + (2 * i + 1) * 2048 + t * 16);
#pragma unroll
                    for (int sx = 0; sx < 3; sx++) {
                        a.x += bf_lo(v[k][sx].x); a.y += bf_hi(v[k][sx].x); a.z += bf_lo(v[k][sx].y); a.w += bf_hi(v[k][sx].y);
                        bq.x += bf_lo(v[k][sx].z); bq.y += bf_hi(v[k][sx].z); bq.z += bf_lo(v[k][sx].w); bq.w += bf_hi(v[k][sx].w);
                    }
                    if (layer == 0) {
                        uint8_t* xd = g_X + (uint32_t)((16 * 8 + c * 8 + own) * 16384 + w * 4096 + g * 16 + 4 * q + i * 256);
                        uint32_t v0 = pack_bf16(a.x, a.y), v1 = pack_bf16(a.z, a.w), v2 = pack_bf16(bq.x, bq.y), v3 = pack_bf16(bq.z, bq.w);
                        *(uint32_t*)(xd) = v0; *(uint32_t*)(xd + 2048) = v1; *(uint32_t*)(xd + 128) = v2; *(uint32_t*)(xd + 2048 + 128) = v3;
                        float sq[4];
                        sq[0] = w0 * bf_lo(v0) * bf_lo(v0) + bf_lo(v1) * bf_lo(v1);
                        sq[1] = w0 * bf_hi(v0) * bf_hi(v0) + bf_hi(v1) * bf_hi(v1);
                        sq[2] = w0 * bf_lo(v2) * bf_lo(v2) + bf_lo(v3) * bf_lo(v3);
                        sq[3] = w0 * bf_hi(v2) * bf_hi(v2) + bf_hi(v3) * bf_hi(v3);
                        float u0 = (g & 1) ? sq[2] : sq[0], u1 = (g & 1) ? sq[3] : sq[1];
                        u0 += __shfl_xor_sync(~0u, (g & 1) ? sq[0] : sq[2], 4);
                        u1 += __shfl_xor_sync(~0u, (g & 1) ? sq[1] : sq[3], 4);
                        float z = (g & 2) ? u1 : u0;
                        z += __shfl_xor_sync(~0u, (g & 2) ? u0 : u1, 8);
                        z += __shfl_xor_sync(~0u, z, 16);
                        if (g < 4) atomicAdd(s_mean + 16 * i + 8 * (g & 1) + 2 * q + (g >> 1), z);
                    } else {
                        float* o = p.out + (uint32_t)((128 * c + 32 * q + 4 * i) * 512 + 64 * own + m0);
                        o[0] = a.x; o[512] = a.y; o[8] = a.z; o[512 + 8] = a.w;
                        o[1024] = bq.x; o[1536] = bq.y; o[1024 + 8] = bq.z; o[1536 + 8] = bq.w;
                    }
                }
            }
            if (wg < 2) mbar_wait_cluster(BAR(B_HDONE), layer);
            if (layer == 0) {
                fence_async_smem();
                bar_sync(9, 384);
                TS(14 + 12 * layer);
                if (wg == 2) {
                    atomicAdd(g_ssq + 2048 + 128 * c + t, s_mean[t] * (2.f / 512.f));
                    bar_sync(3, 128);
                    if (lane == 0) { mbar_arrive(BAR(B_AEMPTY + 4), 2); mbar_arrive(BAR(B_AEMPTY + 5), 2); }
                    if (t == 0) { fence_async(); red_release(&g_bar[2], 1); }
                }
            }
        }
        TS(15 + 12 * layer);
        if (wg == 0) TC(31);
    }
}

typedef CUresult (*EncFn)(CUtensorMap*, CUtensorMapDataType, cuuint32_t, void*, const cuuint64_t*, const cuuint64_t*,
                          const cuuint32_t*, const cuuint32_t*, CUtensorMapInterleave, CUtensorMapSwizzle,
                          CUtensorMapL2promotion, CUtensorMapFloatOOBfill);

void launch_impl(void* const* d_in, void* d_out, int stop) {
    static EncFn enc = nullptr;
    if (!enc) {
        void* fn = nullptr;
        cudaDriverEntryPointQueryResult qr;
        cudaGetDriverEntryPoint("cuTensorMapEncodeTiled", &fn, cudaEnableDefault, &qr);
        enc = (EncFn)fn;
        cudaFuncSetAttribute(fused_kernel, cudaFuncAttributeMaxDynamicSharedMemorySize, SM_TOTAL);
    }
    CUtensorMap tx, tbr, tbi, tcr, tci, tcol;
    {
        void* gx = nullptr;
        cudaGetSymbolAddress(&gx, g_X);
        cuuint64_t gd[5] = {64, 16, 64, 16, 2};
        cuuint64_t gs[4] = {128, 2048, 128 * 1024, 2048 * 1024};
        cuuint32_t bx[5] = {32, 16, 1, 16, 1};
        cuuint32_t es[5] = {1, 1, 1, 1, 1};
        enc(&tcol, CU_TENSOR_MAP_DATA_TYPE_BFLOAT16, 5, gx, gd, gs, bx, es, CU_TENSOR_MAP_INTERLEAVE_NONE,
            CU_TENSOR_MAP_SWIZZLE_64B, CU_TENSOR_MAP_L2_PROMOTION_NONE, CU_TENSOR_MAP_FLOAT_OOB_FILL_NONE);
    }
    {
        cuuint64_t gd[5] = {512, 2, 4, 16, 16};
        cuuint64_t gs[4] = {1024, 32 * 1024, 2 * 1024, 128 * 1024};
        cuuint32_t bx[5] = {64, 2, 4, 8, 1};
        cuuint32_t es[5] = {1, 1, 1, 1, 1};
        enc(&tx, CU_TENSOR_MAP_DATA_TYPE_BFLOAT16, 5, d_in[0], gd, gs, bx, es, CU_TENSOR_MAP_INTERLEAVE_NONE,
            CU_TENSOR_MAP_SWIZZLE_128B, CU_TENSOR_MAP_L2_PROMOTION_L2_128B, CU_TENSOR_MAP_FLOAT_OOB_FILL_NONE);
    }
    auto mk2 = [&](CUtensorMap* m, void* ptr, cuuint32_t rows) {
        cuuint64_t gd[2] = {512, 512};
        cuuint64_t gs[1] = {1024};
        cuuint32_t bx[2] = {64, rows};
        cuuint32_t es[2] = {1, 1};
        enc(m, CU_TENSOR_MAP_DATA_TYPE_BFLOAT16, 2, ptr, gd, gs, bx, es, CU_TENSOR_MAP_INTERLEAVE_NONE,
            CU_TENSOR_MAP_SWIZZLE_128B, CU_TENSOR_MAP_L2_PROMOTION_L2_128B, CU_TENSOR_MAP_FLOAT_OOB_FILL_NONE);
    };
    mk2(&tbr, d_in[6], 32);
    mk2(&tbi, d_in[7], 32);
    mk2(&tcr, d_in[8], 64);
    mk2(&tci, d_in[9], 64);
    Params p;
    p.x0 = (const __nv_bfloat16*)d_in[0];
    p.w_r = (const __nv_bfloat16*)d_in[1];
    p.w_i = (const __nv_bfloat16*)d_in[2];
    p.lam_re = (const __nv_bfloat16*)d_in[4];
    p.lam_im = (const __nv_bfloat16*)d_in[5];
    p.log_dt = (const __nv_bfloat16*)d_in[10];
    p.dskip = (const __nv_bfloat16*)d_in[11];
    p.out = (float*)d_out;
    p.stop = stop;
    cudaLaunchConfig_t cfg = {};
    cfg.gridDim = dim3(NCTA); cfg.blockDim = dim3(NTHREADS); cfg.dynamicSmemBytes = SM_TOTAL; cfg.stream = cudaStreamPerThread;
    cudaLaunchAttribute at[1];
    at[0].id = cudaLaunchAttributeClusterDimension;
    at[0].val.clusterDim.x = 2; at[0].val.clusterDim.y = 1; at[0].val.clusterDim.z = 1;
    cfg.attrs = at; cfg.numAttrs = 1;
    cudaLaunchKernelEx(&cfg, fused_kernel, tx, tbr, tbi, tcr, tci, tcol, p);
}

}

extern "C" void kernel_launch(void* const* d_in, const int* in_sizes, int n_in, void* d_out, int out_size) {
    (void)in_sizes; (void)n_in; (void)out_size;
    launch_impl(d_in, d_out, 100);
}
```

```cpp
#include <cuda_runtime.h>
#include <cuda_bf16.h>
#include <cuda.h>
#include <stdint.h>

namespace {

constexpr int NCTA = 128;
constexpr int NTHREADS = 512;
constexpr int SM_A = 0;
constexpr int SM_X = 131072;
constexpr int SM_H = 196608;
constexpr int SM_HH = SM_X + 32768;
constexpr int SM_M = 229376;
constexpr int SM_TOTAL = 232448;
constexpr int SM_BAR = SM_M;
constexpr int SM_TGT = SM_M + 400;
constexpr int SM_LAM = SM_M + 424;
constexpr int SM_TAB = SM_M + 944;
constexpr int SM_RSTD = SM_M + 1920;
constexpr int SM_MEAN = SM_TAB;
constexpr int SM_T64 = SM_M + 2944;
constexpr int SM_B1ST = SM_H + 24576;
constexpr int SM_RAW = SM_X + 40960;
constexpr int SM_SSQ = SM_X + 57344;
constexpr int B_FULL0 = 0;
constexpr int B_EMPTY0 = 8;
constexpr int B_FULLC = 12;
constexpr int B_AFULL = 13;
constexpr int B_AEMPTY = 21;
constexpr int B_XFULL = 29;
constexpr int B_XEMPTY = 35;
constexpr int B_AFREE = 37;
constexpr int B_COL = 38;
constexpr int B_SSQ = 39;
constexpr int B_HPEER = 40;
constexpr int B_RFREE = 41;
constexpr int B_HDONE = 42;
constexpr int B_WRDY = 43;
constexpr int B_HPEER1 = 44;
constexpr int B_FULLB = 45;
constexpr int B_BFREE = 46;
constexpr int B_SETUP = 47;
constexpr int B_B1DONE = 48;
constexpr int B_WST = 49;
constexpr int NBARS = 50;

__device__ __align__(1024) uint8_t g_X[2 * 16 * 8 * 16384];
__device__ __align__(1024) uint8_t g_A1[8 * 8 * 16384];
__device__ __align__(1024) uint8_t g_A2[8 * 8 * 16384];
__device__ __align__(1024) uint8_t g_E[2 * 8 * 8 * 8192];
__device__ __align__(16) float g_ssq[2 * 2048];
__device__ __align__(16) float g_ssqc[2 * 16 * 2048];
__device__ __align__(16) float g_Dh[512];
__device__ __align__(16) uint4 g_Wfrag[128 * 4 * 256];
__device__ __align__(16) float4 g_Ebuf[2 * 16 * 512];
__device__ __align__(16) uint4 g_P[16 * 8 * 4 * 1024];
__device__ unsigned g_bar[8];
__device__ unsigned g_err;
#define TX(i)
#define TQ(i)
#define TS(i)
#define TC(i)

constexpr unsigned SPIN_LIMIT = 1u << 22;

__device__ __forceinline__ uint32_t s2u(const void* p) { return (uint32_t)__cvta_generic_to_shared(p); }
__device__ __forceinline__ void mbar_init(uint32_t a, uint32_t c) {
    asm volatile("mbarrier.init.shared::cta.b64 [%0], %1;" ::"r"(a), "r"(c) : "memory");
}
__device__ __forceinline__ void mbar_expect(uint32_t a, uint32_t bytes) {
    asm volatile("mbarrier.arrive.expect_tx.shared::cta.b64 _, [%0], %1;" ::"r"(a), "r"(bytes) : "memory");
}
__device__ __forceinline__ void mbar_arrive(uint32_t a, uint32_t cnt) {
    asm volatile("mbarrier.arrive.shared::cta.b64 _, [%0], %1;" ::"r"(a), "r"(cnt) : "memory");
}
__device__ __forceinline__ bool mbar_try(uint32_t a, uint32_t parity) {
    uint32_t ok;
    asm volatile("{\n.reg .pred p;\nmbarrier.try_wait.parity.shared::cta.b64 p, [%1], %2;\nselp.u32 %0, 1, 0, p;\n}"
                 : "=r"(ok) : "r"(a), "r"(parity) : "memory");
    return ok != 0;
}
__device__ __forceinline__ void mbar_wait(uint32_t a, uint32_t parity) {
    asm volatile("{\n.reg .pred p, q;\n.reg .u32 n;\nmov.u32 n, 0;\n"
                 "W_%=:\nmbarrier.try_wait.parity.shared::cta.b64 p, [%0], %1;\n@p bra D_%=;\n"
                 "add.u32 n, n, 1;\nsetp.lt.u32 q, n, 4194304;\n@q bra W_%=;\nD_%=:\n}" ::"r"(a), "r"(parity) : "memory");
}
__device__ __forceinline__ void bulk_g2s(uint32_t dst, const void* src, uint32_t bytes, uint32_t bar) {
    asm volatile("cp.async.bulk.shared::cluster.global.mbarrier::complete_tx::bytes [%0], [%1], %2, [%3];" ::"r"(dst),
                 "l"(src), "r"(bytes), "r"(bar) : "memory");
}
__device__ __forceinline__ void tma_2d(uint32_t dst, const CUtensorMap* m, int c0, int c1, uint32_t bar) {
    asm volatile("cp.async.bulk.tensor.2d.shared::cluster.global.mbarrier::complete_tx::bytes [%0], [%1, {%3,%4}], [%2];" ::"r"(dst),
                 "l"(m), "r"(bar), "r"(c0), "r"(c1) : "memory");
}
__device__ __forceinline__ void tma_5d(uint32_t dst, const CUtensorMap* m, int c0, int c1, int c2, int c3, int c4, uint32_t bar) {
    asm volatile("cp.async.bulk.tensor.5d.shared::cluster.global.mbarrier::complete_tx::bytes [%0], [%1, {%3,%4,%5,%6,%7}], [%2];" ::"r"(dst),
                 "l"(m), "r"(bar), "r"(c0), "r"(c1), "r"(c2), "r"(c3), "r"(c4) : "memory");
}
__device__ __forceinline__ void tma_2d_mc(uint32_t dst, const CUtensorMap* m, int c0, int c1, uint32_t bar) {
    asm volatile("cp.async.bulk.tensor.2d.shared::cluster.global.mbarrier::complete_tx::bytes.multicast::cluster [%0], [%1, {%3,%4}], [%2], %5;" ::"r"(dst),
                 "l"(m), "r"(bar), "r"(c0), "r"(c1), "h"((unsigned short)3) : "memory");
}
__device__ __forceinline__ void tma_5d_mc(uint32_t dst, const CUtensorMap* m, int c0, int c1, int c2, int c3, int c4, uint32_t bar) {
    asm volatile("cp.async.bulk.tensor.5d.shared::cluster.global.mbarrier::complete_tx::bytes.multicast::cluster [%0], [%1, {%3,%4,%5,%6,%7}], [%2], %8;" ::"r"(dst),
                 "l"(m), "r"(bar), "r"(c0), "r"(c1), "r"(c2), "r"(c3), "r"(c4), "h"((unsigned short)3) : "memory");
}
__device__ __forceinline__ void bulk_g2s_mc(uint32_t dst, const void* src, uint32_t bytes, uint32_t bar) {
    asm volatile("cp.async.bulk.shared::cluster.global.mbarrier::complete_tx::bytes.multicast::cluster [%0], [%1], %2, [%3], %4;" ::"r"(dst),
                 "l"(src), "r"(bytes), "r"(bar), "h"((unsigned short)3) : "memory");
}
__device__ __forceinline__ void tma_store_5d(const CUtensorMap* m, int c0, int c1, int c2, int c3, int c4, uint32_t src) {
    asm volatile("cp.async.bulk.tensor.5d.global.shared::cta.bulk_group [%0, {%2,%3,%4,%5,%6}], [%1];" ::"l"(m), "r"(src),
                 "r"(c0), "r"(c1), "r"(c2), "r"(c3), "r"(c4) : "memory");
}
__device__ __forceinline__ uint32_t lds32(uint32_t a) { uint32_t v; asm volatile("ld.shared.u32 %0, [%1];" : "=r"(v) : "r"(a) : "memory"); return v; }
__device__ __forceinline__ uint4 ld_relaxed_u4(const uint4* p) {
    uint4 v;
    asm volatile("ld.relaxed.gpu.global.v4.u32 {%0,%1,%2,%3}, [%4];" : "=r"(v.x), "=r"(v.y), "=r"(v.z), "=r"(v.w) : "l"(p) : "memory");
    return v;
}
__device__ __forceinline__ void fence_async() { asm volatile("fence.proxy.async.global;" ::: "memory"); }
__device__ __forceinline__ void red_relaxed(unsigned* p, unsigned v) {
    asm volatile("red.relaxed.gpu.global.add.u32 [%0], %1;" ::"l"(p), "r"(v) : "memory");
}
__device__ __forceinline__ uint32_t mapa(uint32_t a, uint32_t rank) {
    uint32_t d;
    asm("mapa.shared::cluster.u32 %0, %1, %2;" : "=r"(d) : "r"(a), "r"(rank));
    return d;
}
__device__ __forceinline__ void mbar_arrive_remote(uint32_t ra) {
    asm volatile("mbarrier.arrive.relaxed.cluster.shared::cluster.b64 _, [%0];" ::"r"(ra) : "memory");
}
__device__ __forceinline__ void mbar_wait_cluster(uint32_t a, uint32_t parity) {
    asm volatile("{\n.reg .pred p, q;\n.reg .u32 n;\nmov.u32 n, 0;\n"
                 "W_%=:\nmbarrier.try_wait.parity.acquire.cluster.shared::cta.b64 p, [%0], %1;\n@p bra D_%=;\n"
                 "add.u32 n, n, 1;\nsetp.lt.u32 q, n, 4194304;\n@q bra W_%=;\nD_%=:\n}" ::"r"(a), "r"(parity) : "memory");
}
__device__ __forceinline__ void bulk_s2peer(uint32_t rdst, uint32_t src, uint32_t bytes, uint32_t rbar) {
    asm volatile("cp.async.bulk.shared::cluster.shared::cta.mbarrier::complete_tx::bytes [%0], [%1], %2, [%3];" ::"r"(rdst),
                 "r"(src), "r"(bytes), "r"(rbar) : "memory");
}
__device__ __forceinline__ void fence_async_smem() { asm volatile("fence.proxy.async.shared::cta;" ::: "memory"); }
__device__ __forceinline__ void wg_fence() { asm volatile("wgmma.fence.sync.aligned;" ::: "memory"); }
__device__ __forceinline__ void wg_commit() { asm volatile("wgmma.commit_group.sync.aligned;" ::: "memory"); }
template <int N> __device__ __forceinline__ void wg_wait() { asm volatile("wgmma.wait_group.sync.aligned %0;" ::"n"(N) : "memory"); }
__device__ __forceinline__ void bar_sync(int id, int n) { asm volatile("bar.sync %0, %1;" ::"r"(id), "r"(n) : "memory"); }
__device__ __forceinline__ void bar_arrive(int id, int n) { asm volatile("bar.arrive %0, %1;" ::"r"(id), "r"(n) : "memory"); }
__device__ __forceinline__ unsigned ld_acquire(const unsigned* p) {
    unsigned v;
    asm volatile("ld.acquire.gpu.global.u32 %0, [%1];" : "=r"(v) : "l"(p) : "memory");
    return v;
}
__device__ __forceinline__ void red_release(unsigned* p, unsigned v) {
    asm volatile("red.release.gpu.global.add.u32 [%0], %1;" ::"l"(p), "r"(v) : "memory");
}
__device__ __forceinline__ void wait_count(const unsigned* p, unsigned target) {
    unsigned n = 0;
#pragma unroll 1
    while ((int)(ld_acquire(p) - target) < 0 && ++n < SPIN_LIMIT) {}
}
__device__ __forceinline__ float4 ld_relaxed_f4(const float4* p) {
    float4 v;
    asm volatile("ld.relaxed.gpu.global.v4.f32 {%0,%1,%2,%3}, [%4];" : "=f"(v.x), "=f"(v.y), "=f"(v.z), "=f"(v.w) : "l"(p) : "memory");
    return v;
}
__device__ __forceinline__ void st_relaxed_f4(float4* p, float4 v) {
    asm volatile("st.relaxed.gpu.global.v4.f32 [%0], {%1,%2,%3,%4};" ::"l"(p), "f"(v.x), "f"(v.y), "f"(v.z), "f"(v.w) : "memory");
}
__device__ __forceinline__ uint32_t pack_bf16(float lo, float hi) {
    uint32_t r;
    asm("cvt.rn.bf16x2.f32 %0, %1, %2;" : "=r"(r) : "f"(hi), "f"(lo));
    return r;
}
__device__ __forceinline__ uint32_t hmul2(uint32_t a, uint32_t b) {
    uint32_t r;
    asm("mul.rn.bf16x2 %0, %1, %2;" : "=r"(r) : "r"(a), "r"(b));
    return r;
}
__device__ __forceinline__ uint32_t hfma2(uint32_t a, uint32_t b, uint32_t c) {
    uint32_t r;
    asm("fma.rn.bf16x2 %0, %1, %2, %3;" : "=r"(r) : "r"(a), "r"(b), "r"(c));
    return r;
}
__device__ __forceinline__ float bf_lo(uint32_t v) { return __uint_as_float(v << 16); }
__device__ __forceinline__ float bf_hi(uint32_t v) { return __uint_as_float(v & 0xffff0000u); }
__device__ __forceinline__ void sts32(uint32_t a, uint32_t v) { asm volatile("st.shared.u32 [%0], %1;" ::"r"(a), "r"(v) : "memory"); }
__device__ __forceinline__ void sts128(uint32_t a, uint4 v) {
    asm volatile("st.shared.v4.u32 [%0], {%1,%2,%3,%4};" ::"r"(a), "r"(v.x), "r"(v.y), "r"(v.z), "r"(v.w) : "memory");
}

__device__ __forceinline__ uint64_t desc_ni(uint32_t addr, uint32_t lbo, uint32_t sbo) {
    return (uint64_t)((addr & 0x3FFFF) >> 4) | ((uint64_t)(lbo >> 4) << 16) | ((uint64_t)(sbo >> 4) << 32);
}
__device__ __forceinline__ uint64_t desc_a(uint32_t addr) { return desc_ni(addr, 128, 1024); }
template <int N> __device__ __forceinline__ uint64_t desc_b(uint32_t addr) { return desc_ni(addr, 16 * N, 128); }
__device__ __forceinline__ uint64_t desc_k(uint32_t addr) {
    return (uint64_t)((addr & 0x3FFFF) >> 4) | (1ull << 16) | (64ull << 32) | (1ull << 62);
}
__device__ __forceinline__ uint64_t desc_mn(uint32_t addr, uint32_t lbo) {
    return (uint64_t)((addr & 0x3FFFF) >> 4) | ((uint64_t)(lbo >> 4) << 16) | (64ull << 32) | (1ull << 62);
}

#define ACC8(d, o) "+f"(d[o + 0]), "+f"(d[o + 1]), "+f"(d[o + 2]), "+f"(d[o + 3]), "+f"(d[o + 4]), "+f"(d[o + 5]), "+f"(d[o + 6]), "+f"(d[o + 7])
template <int TB, int SA = 1>
__device__ __forceinline__ void wgmma_n128(float (&d)[64], uint64_t da, uint64_t db, int sd) {
    asm volatile(
        "{\n.reg .pred p;\nsetp.ne.b32 p, %66, 0;\n"
        "wgmma.mma_async.sync.aligned.m64n128k16.f32.bf16.bf16 "
        "{%0,%1,%2,%3,%4,%5,%6,%7,%8,%9,%10,%11,%12,%13,%14,%15,%16,%17,%18,%19,%20,%21,%22,%23,%24,%25,%26,%27,%28,%29,%30,%31,"
        "%32,%33,%34,%35,%36,%37,%38,%39,%40,%41,%42,%43,%44,%45,%46,%47,%48,%49,%50,%51,%52,%53,%54,%55,%56,%57,%58,%59,%60,%61,%62,%63},"
        " %64, %65, p, %68, 1, 0, %67;\n}"
        : ACC8(d, 0), ACC8(d, 8), ACC8(d, 16), ACC8(d, 24), ACC8(d, 32), ACC8(d, 40), ACC8(d, 48), ACC8(d, 56)
        : "l"(da), "l"(db), "r"(sd), "n"(TB), "n"(SA));
}
template <int N> __device__ __forceinline__ void acc_def(float (&d)[N]) {
#pragma unroll
    for (int i = 0; i < N; i++) d[i] = 0.f;
}
template <int TB>
__device__ __forceinline__ void wgmma_n64(float (&d)[32], uint64_t da, uint64_t db, int sd) {
    asm volatile(
        "{\n.reg .pred p;\nsetp.ne.b32 p, %34, 0;\n"
        "wgmma.mma_async.sync.aligned.m64n64k16.f32.bf16.bf16 "
        "{%0,%1,%2,%3,%4,%5,%6,%7,%8,%9,%10,%11,%12,%13,%14,%15,%16,%17,%18,%19,%20,%21,%22,%23,%24,%25,%26,%27,%28,%29,%30,%31},"
        " %32, %33, p, 1, 1, 0, %35;\n}"
        : ACC8(d, 0), ACC8(d, 8), ACC8(d, 16), ACC8(d, 24)
        : "l"(da), "l"(db), "r"(sd), "n"(TB));
}
template <int SA>
__device__ __forceinline__ void wgmma_n64s(float (&d)[32], uint64_t da, uint64_t db, int sd) {
    asm volatile(
        "{\n.reg .pred p;\nsetp.ne.b32 p, %34, 0;\n"
        "wgmma.mma_async.sync.aligned.m64n64k16.f32.bf16.bf16 "
        "{%0,%1,%2,%3,%4,%5,%6,%7,%8,%9,%10,%11,%12,%13,%14,%15,%16,%17,%18,%19,%20,%21,%22,%23,%24,%25,%26,%27,%28,%29,%30,%31},"
        " %32, %33, p, %35, 1, 0, 1;\n}"
        : ACC8(d, 0), ACC8(d, 8), ACC8(d, 16), ACC8(d, 24)
        : "l"(da), "l"(db), "r"(sd), "n"(SA));
}
__device__ __forceinline__ void wgmma_n64_rs(float (&d)[32], uint32_t a0, uint32_t a1, uint32_t a2, uint32_t a3, uint64_t db, int sd) {
    asm volatile(
        "{\n.reg .pred p;\nsetp.ne.b32 p, %37, 0;\n"
        "wgmma.mma_async.sync.aligned.m64n64k16.f32.bf16.bf16 "
        "{%0,%1,%2,%3,%4,%5,%6,%7,%8,%9,%10,%11,%12,%13,%14,%15,%16,%17,%18,%19,%20,%21,%22,%23,%24,%25,%26,%27,%28,%29,%30,%31},"
        " {%32,%33,%34,%35}, %36, p, 1, 1, 1;\n}"
        : ACC8(d, 0), ACC8(d, 8), ACC8(d, 16), ACC8(d, 24)
        : "r"(a0), "r"(a1), "r"(a2), "r"(a3), "l"(db), "r"(sd));
}

struct Params {
    const __nv_bfloat16* x0;
    const __nv_bfloat16* w_r;
    const __nv_bfloat16* w_i;
    const __nv_bfloat16* lam_re;
    const __nv_bfloat16* lam_im;
    const __nv_bfloat16* log_dt;
    const __nv_bfloat16* dskip;
    float* out;
    int stop;
};

__device__ __forceinline__ uint32_t fpar(int s, int k, int L) { return s < 6 ? (uint32_t)((L + k) & 1) : (uint32_t)(k == 2); }
__device__ __forceinline__ int cslot(int v) { return (0x54032176u >> (4 * v)) & 7; }
__device__ __forceinline__ float ldbf(const __nv_bfloat16* p) { return __bfloat162float(*p); }

__device__ __forceinline__ void dft_fp(int j, int& f, int& ph) {
    int cs = j >> 1;
    if (j == 1) { f = 256; ph = 0; }
    else { f = cs; ph = (j & 1) ? 128 : 0; }
}

__device__ __forceinline__ void gen_col_consts(uint32_t sb, int tid) {
#pragma unroll 1
    for (int task = tid; task < 640; task += 256) {
        int f, c8;
        uint32_t a_cc, d_pi, d_po;
        if (task < 512) {
            f = task & 63; c8 = task >> 6;
            a_cc = sb + SM_X + (f >> 5) * 16384 + ((f >> 3) & 3) * 2048 + c8 * 128 + (f & 7) * 16;
            d_pi = 8192; d_po = 1024;
        } else {
            int n2 = task & 31;
            f = 2 * n2; c8 = (task >> 5) & 3;
            a_cc = sb + SM_X + 32768 + (n2 >> 3) * 1024 + c8 * 128 + (n2 & 7) * 16;
            d_pi = 4096; d_po = 512;
        }
        float cd, sd, cs, sn;
        __sincosf((float)(f >= 32 ? f - 64 : f) * (6.283185307179586f / 64.f), &sd, &cd);
        int a = (8 * c8 * f) & 63;
        __sincosf((float)(a >= 32 ? a - 64 : a) * (6.283185307179586f / 64.f), &sn, &cs);
        float cv[8], sv[8];
#pragma unroll
        for (int e = 0; e < 8; e++) {
            cv[e] = cs; sv[e] = sn;
            float t = cs * cd - sn * sd;
            sn = sn * cd + cs * sd;
            cs = t;
        }
        uint4 oc = make_uint4(pack_bf16(cv[0], cv[1]), pack_bf16(cv[2], cv[3]), pack_bf16(cv[4], cv[5]), pack_bf16(cv[6], cv[7]));
        uint4 os = make_uint4(pack_bf16(sv[0], sv[1]), pack_bf16(sv[2], sv[3]), pack_bf16(sv[4], sv[5]), pack_bf16(sv[6], sv[7]));
        sts128(a_cc, oc);
        sts128(a_cc + d_pi, os);
        sts128(a_cc + d_po, make_uint4(os.x ^ 0x80008000u, os.y ^ 0x80008000u, os.z ^ 0x80008000u, os.w ^ 0x80008000u));
        sts128(a_cc + d_pi + d_po, oc);
    }
}

__global__ void __launch_bounds__(NTHREADS, 1)
fused_kernel(const __grid_constant__ CUtensorMap tm_x, const __grid_constant__ CUtensorMap tm_bre,
             const __grid_constant__ CUtensorMap tm_bim, const __grid_constant__ CUtensorMap tm_cre,
             const __grid_constant__ CUtensorMap tm_cim, const __grid_constant__ CUtensorMap tm_col, const Params p) {
    extern __shared__ __align__(1024) uint8_t sm[];
    const uint32_t sb = s2u(sm);
    const int tid = threadIdx.x, b = blockIdx.x;
    const int c = b >> 3, r = b & 7;
    const int par = r & 1, pi_ = r >> 1, own = 4 * par + pi_;
    const int wg = __shfl_sync(~0u, tid >> 7, 0), w = __shfl_sync(~0u, (tid >> 5) & 3, 0), lane = tid & 31, g = lane >> 2, q = lane & 3;
    auto BAR = [&](int i) { return sb + SM_BAR + 8 * i; };
    unsigned* s_tgt = (unsigned*)(sm + SM_TGT);

    if (tid < NBARS) {
        int cnt = 1;
        if (tid >= B_EMPTY0 && tid < B_EMPTY0 + 4) cnt = 16;
        if (tid >= B_XEMPTY && tid < B_XEMPTY + 2) cnt = 16;
        if (tid == B_RFREE) cnt = 12;
        if (tid == B_HDONE || tid == B_WST) cnt = 2;
        if ((tid >= B_AEMPTY && tid < B_AEMPTY + 8) || tid == B_BFREE) cnt = 8;
        if (tid == B_AFREE) cnt = 4;
        mbar_init(BAR(tid), cnt);
        asm volatile("fence.mbarrier_init.release.cluster;" ::: "memory");
    }
    asm volatile("barrier.cluster.arrive.release.aligned;" ::: "memory");

    if (wg == 3) {
        asm volatile("setmaxnreg.dec.sync.aligned.u32 56;");
        if (w == 0 && lane < 6) {
            const CUtensorMap* tm = lane == 0 ? &tm_x : lane == 1 ? &tm_bre : lane == 2 ? &tm_bim : lane == 3 ? &tm_cre : lane == 4 ? &tm_cim : &tm_col;
            asm volatile("prefetch.tensormap [%0];" ::"l"(tm) : "memory");
        }
        __syncwarp();
        asm volatile("barrier.cluster.wait.acquire.aligned;" ::: "memory");
        if (w > 0) {
            if (w == 1) {
                float lr[3], li[3], ld[3];
#pragma unroll
                for (int k = 0; k < 3; k++) {
                    int ps = k < 2 ? 64 * r + 32 * k + lane : 32 * c + lane;
                    lr[k] = ldbf(p.lam_re + ps); li[k] = ldbf(p.lam_im + ps); ld[k] = ldbf(p.log_dt + ps);
                }
                if (lane < 6) s_tgt[lane] = ((ld_acquire(&g_bar[lane]) >> 7) + 1u) << 7;
#pragma unroll 1
                for (int k = 0; k < 3; k++) {
                    float a = k == 0 ? lr[0] : (k == 1 ? lr[1] : lr[2]), bq = k == 0 ? li[0] : (k == 1 ? li[1] : li[2]);
                    float dt = __bfloat162float(__float2bfloat16(expf(k == 0 ? ld[0] : (k == 1 ? ld[1] : ld[2]))));
                    float mag = expf(a * dt), t = bq * dt * 0.15915494309189535f, sn, cs;
                    t -= rintf(t);
                    sincospif(2.f * t, &sn, &cs);
                    float er = mag * cs, ei = mag * sn;
                    if (k < 2) {
                        *(float2*)(sm + SM_LAM + (32 * k + lane) * 8) = make_float2(er, ei);
                    } else {
                        er -= 1.f;
                        float inv = 1.f / (a * a + bq * bq);
                        *(float2*)(sm + SM_TAB + lane * 8) = make_float2((er * a + ei * bq) * inv, (ei * a - er * bq) * inv);
                    }
                }
                __syncwarp();
                bar_arrive(15, 160);
                if (lane == 0) mbar_arrive(BAR(B_SETUP), 1);
            }
            if (w == 2 && lane < 2) {
                const char* src = (const char*)(lane ? p.w_i : p.w_r) + (size_t)b * 8224;
                asm volatile("cp.async.bulk.prefetch.L2.global [%0], 8224;" ::"l"(src) : "memory");
            }
#pragma unroll 1
            for (int i = tid - 448; i < 96 + 128 && w > 1; i += 64) {
                if (i < 96) g_P[(uint32_t)(b * 4 + i / 24) * 1024 + 640 + ((i % 24) >> 1) * 32 + 30 + (i & 1)] = make_uint4(0, 0, 0, 0);
                else g_Ebuf[b * 128 + i - 96] = make_float4(0.f, 0.f, 0.f, 0.f);
            }
            __syncwarp();
            if (w > 1) bar_sync(0, 192);
            if (tid == 448) TX(14);
            if (w > 1) {
                if (lane < 8) {
                    const int cl = 8 * (w - 2) + lane;
                    asm volatile("cp.async.bulk.global.shared::cta.bulk_group [%0], [%1], 1024;" ::"l"(g_Wfrag + (uint32_t)((16 * (b & 7) + cl) * 1024 + (b >> 3) * 64)),
                                 "r"(sb + SM_H + cl * 1024) : "memory");
                }
                asm volatile("cp.async.bulk.commit_group;" ::: "memory");
                asm volatile("cp.async.bulk.wait_group 0;" ::: "memory");
                fence_async();
                __syncwarp();
                if (lane == 0) mbar_arrive(BAR(B_WST), 1);
                if (tid == 448) TX(15);
            }
            __syncwarp();
            if (w == 3) bar_arrive(11, 192);
            if (w == 2) {
                bar_sync(11, 192);
                if (lane == 0) { TX(7); red_release(&g_bar[4], 1);  }
            }
            if (w == 3) {
#pragma unroll 1
                for (int it = 0; it < 8; it++) {
                    const int m = 4 * c + (it >> 1), d = 64 * r + m, ch = lane + 32 * (it & 1);
                    float v[8];
#pragma unroll
                    for (int e = 0; e < 8; e++) {
                        int j = 8 * ch + e, f, ph;
                        dft_fp(j, f, ph);
                        int a = (d * f + ph) & 511;
                        a = a >= 256 ? a - 512 : a;
                        float wj = j == 0 ? 0.f : (j == 1 ? 1.f / 512.f : 2.f / 512.f);
                        v[e] = wj * __cosf((float)a * (6.283185307179586f / 512.f));
                    }
                    uint32_t off = (uint32_t)(64 + r * 8 + (ch >> 3)) * 8192 + (m >> 3) * 1024 + (ch & 7) * 128 + (m & 7) * 16;
                    *(uint4*)(g_E + off) = make_uint4(pack_bf16(v[0], v[1]), pack_bf16(v[2], v[3]), pack_bf16(v[4], v[5]), pack_bf16(v[6], v[7]));
                }
                __syncwarp();
                if (lane == 0) { fence_async(); red_release(&g_bar[6], 1); }
                return;
            }
            if (w == 2) {
#pragma unroll 1
                for (int it = 0; it < 4; it++) {
                    const int hf = it & 1;
                    __syncwarp();
                    if (hf == 0) bar_sync(13, 288); else bar_sync(6, 416);
                    if (lane == 0) {
                        const uint32_t src = sb + SM_HH + par * 32768 + hf * 16384;
                        bulk_s2peer(mapa(src, par ^ 1), src, 16384, mapa(BAR(hf ? B_HPEER1 : B_HPEER), par ^ 1));
                    }
                }
                return;
            }
            bar_sync(2, 288);
            if (lane == 0) {
                TX(5);
                fence_async();
                red_release(&g_bar[0], 1);
                TX(6);
            }
            __syncwarp();

            bar_sync(12, 160);
            if (lane == 0) {
                asm volatile("cp.async.bulk.global.shared::cta.bulk_group [%0], [%1], 8192;" ::"l"(g_A1 + (uint32_t)(((c >> 1) * 8 + r) * 16384 + (c & 1) * 8192)),
                             "r"(sb + SM_B1ST) : "memory");
                asm volatile("cp.async.bulk.commit_group;" ::: "memory");
                asm volatile("cp.async.bulk.wait_group 0;" ::: "memory");
                mbar_arrive(BAR(B_B1DONE), 1);
                fence_async();
                red_release(&g_bar[7], 1);
            }
#pragma unroll 1
            for (int layer = 0; layer < 2; layer++) {
                __syncwarp();
                bar_sync(5, 416);
                if (lane == 0) {
                    TX(0 + 8 * layer);
                    tma_store_5d(&tm_col, 32 * (b & 1), 0, b >> 1, 0, layer, sb + SM_RAW);
                    asm volatile("cp.reduce.async.bulk.global.shared::cta.bulk_group.add.f32 [%0], [%1], 8192;" ::"l"(g_ssqc + (layer * 16 + (b & 15)) * 2048),
                                 "r"(sb + SM_SSQ) : "memory");
                    asm volatile("cp.async.bulk.commit_group;" ::: "memory");
                    asm volatile("cp.async.bulk.wait_group 0;" ::: "memory");
                    TX(1 + 8 * layer);
                    fence_async();
                    red_release(&g_bar[1 + 2 * layer], 1);
                    TX(2 + 8 * layer);
                }
            }
        } else if (tid == 384) {
#pragma unroll 1
            for (int kb = 0; kb < 8; kb++) {
                uint32_t fb = BAR(B_FULL0 + kb);
                mbar_expect(fb, 16384);
                tma_5d_mc(sb + SM_A + 65536 + kb * 16384 + par * 8192, &tm_x, kb * 64, 0, 0, 8 * par, c, fb);
            }
#pragma unroll 1
            for (int k2 = 0; k2 < 8; k2++) {
                asm volatile("cp.async.bulk.prefetch.tensor.2d.L2.global [%0, {%1,%2}];" ::"l"(par ? &tm_bim : &tm_bre), "r"(k2 * 64), "r"(32 * c) : "memory");
                if ((k2 & 1) == par)
                    asm volatile("cp.async.bulk.prefetch.tensor.2d.L2.global [%0, {%1,%2}];" ::"l"((c & 1) ? &tm_cim : &tm_cre), "r"(64 * (c >> 1)), "r"(k2 * 64) : "memory");
            }
            mbar_wait(BAR(B_SETUP), 0);
#pragma unroll 1
            for (int layer = 0; layer < 2; layer++) {
                if (layer == 1) {
                    mbar_wait(BAR(B_AEMPTY + 4), 0);
                    mbar_expect(BAR(B_WRDY), 16384);
                    bulk_g2s(sb + SM_H + 16384, g_Wfrag + (uint32_t)b * 1024, 16384, BAR(B_WRDY));
                }
                wait_count(&g_bar[2 * layer], s_tgt[2 * layer]);
                TX(4 + 8 * layer);
                fence_async();
                mbar_expect(BAR(B_COL), 16384 + 8192);
                tma_5d(sb + SM_RAW, &tm_col, 32 * (b & 1), 0, b >> 1, 0, layer, BAR(B_COL));
                bulk_g2s(sb + SM_SSQ, g_ssq + layer * 2048, 8192, BAR(B_COL));
                if (layer == 0) {
                    wait_count(&g_bar[4], s_tgt[4]);
                    fence_async();
                    TX(16);
                    mbar_wait(BAR(B_B1DONE), 0);
                    TX(17);
                    mbar_expect(BAR(B_WRDY), 16384);
                    bulk_g2s(sb + SM_H + 16384, g_Wfrag + (uint32_t)b * 1024, 16384, BAR(B_WRDY));
                    wait_count(&g_bar[7], s_tgt[4]);
                    fence_async();
                }
                if (layer == 0) mbar_wait(BAR(B_AFREE), 0);
                mbar_wait(BAR(B_COL), layer);
#pragma unroll 1
                for (int s = 0; s < 8; s++) {
                    if (layer == 1) mbar_wait(BAR(B_AEMPTY + s), fpar(s, 2, 0));
                    if (s >= 2) mbar_wait(BAR(B_AFULL + s - 2), fpar(s - 2, 0, layer));
                    mbar_expect(BAR(B_AFULL + s), 16384);
                    bulk_g2s(sb + SM_A + s * 16384, g_A1 + (uint32_t)(r * 8 + s) * 16384, 16384, BAR(B_AFULL + s));
                }
                if (layer == 1) wait_count(&g_bar[6], s_tgt[4]);
                wait_count(&g_bar[1 + 2 * layer], s_tgt[1 + 2 * layer]);
                TX(3 + 8 * layer);
                fence_async();
                const uint8_t* xsrc = g_X + (uint32_t)(layer * 16 + c) * 8 * 16384;
                const uint8_t* esrc = g_E + (uint32_t)(layer * 8 + own) * 8 * 8192;
                mbar_arrive(BAR(B_SSQ), 1);
                mbar_expect(BAR(B_HPEER), 16384);
                mbar_expect(BAR(B_HPEER1), 16384);
#pragma unroll 1
                for (int it = 0; it < 20; it++) {
                    if (it < 8) {
                        const int st = it < 6 ? it : it - 6;
                        if (it >= 6) mbar_wait_cluster(BAR(B_XEMPTY + st), layer);
                        mbar_expect(BAR(B_XFULL + st), 16384);
                        bulk_g2s_mc(sb + SM_X + st * 16384 + par * 8192, xsrc + (uint32_t)it * 16384 + par * 8192, 8192, BAR(B_XFULL + st));
                    }
                    if (it >= 6) {
                        const bool isc = it >= 12;
                        const int s = isc ? cslot(it - 12) : it - 6;
                        mbar_wait(BAR(B_AEMPTY + s), fpar(s, it < 14 ? 0 : 1, layer));
                        uint32_t fb = BAR(B_AFULL + s), dst = sb + SM_A + s * 16384;
                        mbar_expect(fb, 16384);
                        if (!isc) {
                            bulk_g2s(dst, s < 4 ? esrc + (uint32_t)s * 16384 : xsrc + (uint32_t)(s - 4) * 16384, 16384, fb);
                        } else {
                            const int tile = 4 * par + ((pi_ + 1 + ((it - 12) >> 1)) & 3), sl = r ^ (it & 1);
                            if (layer == 1) {
                                tma_2d(dst, &tm_cre, 64 * sl, 64 * tile, fb);
                                tma_2d(dst + 8192, &tm_cim, 64 * sl, 64 * tile, fb);
                            } else {
                                bulk_g2s(dst, g_A2 + (uint32_t)(sl * 8 + tile) * 16384, 16384, fb);
                            }
                        }
                    }
                }
            }
        }
        return;
    }

    asm volatile("setmaxnreg.inc.sync.aligned.u32 152;");
    if (tid >= 96 && tid < 112) g_ssq[2048 + 16 * b + tid - 96] = 0.f;
    if (tid >= 128 && tid < 256) ((float4*)g_ssqc)[b * 128 + tid - 128] = make_float4(0.f, 0.f, 0.f, 0.f);
    TS(0);
    if (wg == 0) TC(30);
    {
        const int f = 32 * r + lane;
        float cd, sd;
        __sincosf((float)f * (6.283185307179586f / 512.f), &sd, &cd);
        const uint32_t dst = sb + SM_A + (lane >> 2) * 1024 + (lane & 3) * 32;
#pragma unroll 1
        for (int ch = tid >> 5; ch < 64; ch += 12) {
            int a = (8 * ch * f) & 511;
            a = a >= 256 ? a - 512 : a;
            float cs, sn;
            __sincosf((float)a * (6.283185307179586f / 512.f), &sn, &cs);
            float cv[8], sv[8];
#pragma unroll
            for (int e = 0; e < 8; e++) {
                cv[e] = cs; sv[e] = -sn;
                float t = cs * cd - sn * sd;
                sn = sn * cd + cs * sd;
                cs = t;
            }
            uint4 o1 = make_uint4(pack_bf16(sv[0], sv[1]), pack_bf16(sv[2], sv[3]), pack_bf16(sv[4], sv[5]), pack_bf16(sv[6], sv[7]));
            if (f == 0) o1 = make_uint4(0xbf803f80u, 0xbf803f80u, 0xbf803f80u, 0xbf803f80u);
            uint32_t a0 = dst + (ch >> 3) * 8192 + (ch & 7) * 128;
            sts128(a0, make_uint4(pack_bf16(cv[0], cv[1]), pack_bf16(cv[2], cv[3]), pack_bf16(cv[4], cv[5]), pack_bf16(cv[6], cv[7])));
            sts128(a0 + 16, o1);
        }
    }
    fence_async_smem();
    asm volatile("barrier.cluster.wait.acquire.aligned;" ::: "memory");
    bar_sync(10, 384);
    TS(1);
    if (wg < 2) {
        float acc[32];
        acc_def(acc);
        const int npos = 16 * r + 8 * wg + 2 * w;
        float sh0 = 0.f, sh1 = 0.f, s0 = 0.f, s1 = 0.f, q0 = 0.f, q1 = 0.f;
#pragma unroll 1
        for (int kb = 0; kb < 8; kb++) {
            uint32_t slot = sb + SM_A + 65536 + kb * 16384;
            mbar_wait(BAR(B_FULL0 + kb), 0);
            wg_fence();
#pragma unroll
            for (int ks = 0; ks < 4; ks++)
                wgmma_n64<0>(acc, desc_a(sb + SM_A + kb * 8192 + ks * 256), desc_k(slot + wg * 8192 + ks * 32), 1);
            wg_commit();
            {
                uint32_t v0 = lds32(slot + npos * 128 + lane * 4), v1 = lds32(slot + npos * 128 + 128 + lane * 4);
                if (kb == 0) { sh0 = __shfl_sync(~0u, bf_lo(v0), 0); sh1 = __shfl_sync(~0u, bf_lo(v1), 0); }
                float a = bf_lo(v0) - sh0, bq = bf_hi(v0) - sh0, cq = bf_lo(v1) - sh1, d = bf_hi(v1) - sh1;
                s0 += a + bq; q0 += a * a + bq * bq; s1 += cq + d; q1 += cq * cq + d * d;
            }
            wg_wait<1>();
            if (kb > 0 && kb <= 4 && lane == 0) { mbar_arrive(BAR(B_EMPTY0 + kb - 1), 1); mbar_arrive_remote(mapa(BAR(B_EMPTY0 + kb - 1), par ^ 1)); }
        }
#pragma unroll
        for (int o = 16; o; o >>= 1) {
            s0 += __shfl_xor_sync(~0u, s0, o); q0 += __shfl_xor_sync(~0u, q0, o);
            s1 += __shfl_xor_sync(~0u, s1, o); q1 += __shfl_xor_sync(~0u, q1, o);
        }
        if (lane == 0) *(float2*)(g_ssq + 128 * c + npos) = make_float2(fmaxf(q0 - s0 * s0 * (1.f / 512.f), 0.f), fmaxf(q1 - s1 * s1 * (1.f / 512.f), 0.f));
        wg_wait<0>();
        TS(2);
        uint8_t* dst = g_X + (uint32_t)((c * 8 + r) * 16384 + w * 4096 + wg * 1024 + g * 16 + 4 * q);
#pragma unroll
        for (int i = 0; i < 8; i++) {
            *(uint32_t*)(dst + i * 128) = pack_bf16(acc[4 * i], acc[4 * i + 1]);
            *(uint32_t*)(dst + 2048 + i * 128) = pack_bf16(acc[4 * i + 2], acc[4 * i + 3]);
        }
        bar_sync(2, 288);
        mbar_wait(BAR(B_SETUP), 0);
        TS(3);
    }

    if (wg == 2) {
        {
            uint4 p0 = __ldg((const uint4*)p.dskip + 2 * lane), p1 = __ldg((const uint4*)p.dskip + 2 * lane + 1);
            uint32_t u[8] = {p0.x, p0.y, p0.z, p0.w, p1.x, p1.y, p1.z, p1.w};
            int j = 64 * r + 4 * c + w, f, ph;
            dft_fp(j, f, ph);
            float s = 0.f;
            int idx = 16 * lane * f + ph;
#pragma unroll
            for (int i = 0; i < 16; i++) {
                int a = idx & 511;
                idx += f;
                a = a >= 256 ? a - 512 : a;
                s += ((i & 1) ? bf_hi(u[i >> 1]) : bf_lo(u[i >> 1])) * __cosf((float)a * (6.283185307179586f / 512.f));
            }
#pragma unroll
            for (int o = 16; o; o >>= 1) s += __shfl_xor_sync(~0u, s, o);
            if (lane == 0) g_Dh[j] = s;
        }
        mbar_wait(BAR(B_FULL0 + 7), 0);
        if (tid == 256) {
#pragma unroll 1
            for (int s = 0; s < 4; s++) mbar_wait_cluster(BAR(B_EMPTY0 + s), 0);
            mbar_expect(BAR(B_FULLB), 65536);
#pragma unroll 1
            for (int k2 = 0; k2 < 8; k2++)
                tma_2d_mc(sb + SM_A + 65536 + k2 * 8192 + par * 4096, par ? &tm_bim : &tm_bre, k2 * 64, 32 * c, BAR(B_FULLB));
        }
        __syncwarp();
        {
            const int cl = tid & 15, cb = 16 * (b & 7) + cl;
            const int c0 = cb == 0 ? 256 : 2 * cb, c1 = 2 * cb + 1;
            uint32_t wf[2][16];
#pragma unroll
            for (int h = 0; h < 2; h++) {
                const int kq = 16 * (b >> 3) + ((tid & 127) >> 4) + 8 * h, k1 = kq >> 2, qq = kq & 3;
                const unsigned short* wr_ = (const unsigned short*)p.w_r + (k1 + 128 * qq) * 257;
                const unsigned short* wi_ = (const unsigned short*)p.w_i + (k1 + 128 * qq) * 257;
#pragma unroll
                for (int i = 0; i < 4; i++) {
                    int o = 512 * i * 257;
                    wf[h][2 * i] = (uint32_t)__ldg(wr_ + o + c0) | ((uint32_t)__ldg(wr_ + o + 64 * 257 + c0) << 16);
                    wf[h][2 * i + 1] = ((uint32_t)__ldg(wi_ + o + c0) | ((uint32_t)__ldg(wi_ + o + 64 * 257 + c0) << 16)) ^ 0x80008000u;
                    wf[h][8 + 2 * i] = (uint32_t)__ldg(wr_ + o + c1) | ((uint32_t)__ldg(wr_ + o + 64 * 257 + c1) << 16);
                    wf[h][8 + 2 * i + 1] = ((uint32_t)__ldg(wi_ + o + c1) | ((uint32_t)__ldg(wi_ + o + 64 * 257 + c1) << 16)) ^ 0x80008000u;
                }
            }
#pragma unroll
            for (int h = 0; h < 2; h++)
#pragma unroll
                for (int i = 0; i < 4; i++)
                    sts128(sb + SM_H + cl * 1024 + (((tid & 127) >> 4) + 8 * h) * 64 + ((i ^ ((tid >> 5) & 3)) << 4),
                           make_uint4(wf[h][4 * i], wf[h][4 * i + 1], wf[h][4 * i + 2], wf[h][4 * i + 3]));
            fence_async_smem();
            bar_arrive(0, 192);
            bar_arrive(11, 192);
        }
        bar_sync(15, 160);
        float acc[32];
        acc_def(acc);
        mbar_wait(BAR(B_FULLB), 0);
        wg_fence();
#pragma unroll 1
        for (int kb = 0; kb < 8; kb++) {
#pragma unroll
            for (int ks = 0; ks < 4; ks++)
                wgmma_n64<0>(acc, desc_a(sb + SM_A + kb * 8192 + ks * 256), desc_k(sb + SM_A + 65536 + kb * 8192 + ks * 32), 1);
            wg_commit();
        }
        wg_wait<0>();
        if (lane == 0) { mbar_arrive(BAR(B_BFREE), 1); mbar_arrive_remote(mapa(BAR(B_BFREE), par ^ 1)); }
        if (tid == 256) {
            mbar_wait_cluster(BAR(B_BFREE), 0);
            mbar_expect(BAR(B_FULLC), 65536);
#pragma unroll 1
            for (int k2 = par; k2 < 8; k2 += 2)
                tma_2d_mc(sb + SM_A + 65536 + k2 * 8192, (c & 1) ? &tm_cim : &tm_cre, 64 * (c >> 1), k2 * 64, BAR(B_FULLC));
        }
        __syncwarp();
        {
            uint8_t* dst = sm + SM_B1ST + w * 256 + q * 32 + g * 2;
            const float wj0 = (r == 0 && w == 0 && g < 2) ? (g == 0 ? 0.f : 1.f / 512.f) : 2.f / 512.f;
#pragma unroll
            for (int i = 0; i < 4; i++) {
#pragma unroll
                for (int e = 0; e < 2; e++) {
                    float2 cf = *(const float2*)(sm + SM_TAB + (8 * i + 2 * q + e) * 8);
#pragma unroll
                    for (int h = 0; h < 2; h++) {
                        float wj = h == 0 ? wj0 : 2.f / 512.f;
                        float pr = acc[4 * i + 2 * h + e] * wj, pi = acc[16 + 4 * i + 2 * h + e] * wj;
                        uint8_t* d2 = dst + i * 2048 + h * 128 + e * 16;
                        *(__nv_bfloat16*)(d2) = __float2bfloat16(cf.x * pr - cf.y * pi);
                        *(__nv_bfloat16*)(d2 + 1024) = __float2bfloat16(cf.x * pi + cf.y * pr);
                    }
                }
            }
            fence_async_smem();
            bar_arrive(12, 160);
        }
        acc_def(acc);
        mbar_wait(BAR(B_FULLC), 0);
        wg_fence();
#pragma unroll 1
        for (int kb = 0; kb < 8; kb++) {
#pragma unroll
            for (int ks = 0; ks < 4; ks++)
                wgmma_n64<1>(acc, desc_a(sb + SM_A + kb * 8192 + ks * 256), desc_mn(sb + SM_A + 65536 + kb * 8192 + ks * 2048, 8192), 1);
            wg_commit();
        }
        wg_wait<0>();
        fence_async_smem();
        if (lane == 0) mbar_arrive(BAR(B_AFREE), 1);
        uint8_t* dst = g_A2 + (uint32_t)(((c >> 1) * 8 + r) * 16384 + (c & 1) * 8192 + w * 2048 + g * 16 + 4 * q);
#pragma unroll
        for (int i = 0; i < 8; i++) {
            *(uint32_t*)(dst + i * 128) = pack_bf16(acc[4 * i], acc[4 * i + 1]);
            *(uint32_t*)(dst + 1024 + i * 128) = pack_bf16(acc[4 * i + 2], acc[4 * i + 3]);
        }
        {
            const int m = 4 * c + w, jp = 64 * r + m;
            int fp, php;
            dft_fp(jp, fp, php);
            const __nv_bfloat16* dh = (const __nv_bfloat16*)(sm + SM_RSTD);
            if (tid == 256) wait_count(&g_bar[4], s_tgt[4]);
            bar_sync(3, 128);
            float4 d4 = __ldcg((const float4*)g_Dh + (tid - 256));
            *(uint2*)(sm + SM_RSTD + (tid - 256) * 8) = make_uint2(pack_bf16(d4.x, d4.y), pack_bf16(d4.z, d4.w));
            bar_sync(3, 128);
#pragma unroll 1
            for (int it = 0; it < 2; it++) {
                const int ch = lane + 32 * it;
                float v[8];
#pragma unroll
                for (int e = 0; e < 8; e++) {
                    int j = 8 * ch + e, f, ph;
                    dft_fp(j, f, ph);
                    float wj = j == 0 ? 0.f : (j == 1 ? 1.f / 512.f : 2.f / 512.f);
                    float gsum = 0.f;
#pragma unroll
                    for (int sgn = 0; sgn < 2; sgn++) {
                        int mm = (sgn ? f - fp : f + fp) & 511, pp = (sgn ? ph - php : ph + php) & 511;
                        if (mm > 256) { mm = 512 - mm; pp = (512 - pp) & 511; }
                        int odd = (pp >> 7) & 1;
                        float t = __bfloat162float(dh[mm == 256 ? 1 : 2 * mm + odd]);
                        if (odd && (mm & 255) == 0) t = 0.f;
                        gsum += (pp & 256) ? -t : t;
                    }
                    v[e] = 0.5f * wj * gsum;
                }
                uint32_t off = (uint32_t)(r * 8 + (ch >> 3)) * 8192 + (m >> 3) * 1024 + (ch & 7) * 128 + (m & 7) * 16;
                *(uint4*)(g_E + off) = make_uint4(pack_bf16(v[0], v[1]), pack_bf16(v[2], v[3]), pack_bf16(v[4], v[5]), pack_bf16(v[6], v[7]));
            }
        }
    }

#pragma unroll 1
    for (int layer = 0; layer < 2; layer++) {
        if (wg < 2) {
            const int n1 = 32 * wg + 8 * w + g;
            const int ct = n1 >> 2;
            gen_col_consts(sb, tid);
            uint32_t tr2[4], ti2[4], tn2[4];
#pragma unroll
            for (int i = 0; i < 4; i++) {
                float cr[2], ci[2];
#pragma unroll
                for (int e = 0; e < 2; e++) {
                    int a = (n1 * (8 * i + 2 * q + e)) & 2047;
                    a = a >= 1024 ? a - 2048 : a;
                    float ang = (float)a * (-6.283185307179586f / 2048.f);
                    cr[e] = __cosf(ang); ci[e] = __sinf(ang);
                }
                tr2[i] = pack_bf16(cr[0], cr[1]); ti2[i] = pack_bf16(ci[0], ci[1]); tn2[i] = ti2[i] ^ 0x80008000u;
            }
            mbar_wait(BAR(B_WST), 0);
            mbar_wait(BAR(B_COL), layer);
            TS(4 + 12 * layer);
            if (wg == 0) TC(0 + 10 * layer);
            const uint32_t rw0 = sb + SM_RAW + ct * 1024 + q * 64 + ((q >> 1) << 4) + (g & 3) * 4, rw1 = rw0 ^ 16;
            const int pos0 = 128 * ct + 8 * q + 2 * (g & 3);
            const int sw = b == 0 ? 1 : 0;
            uint32_t xr[4][4];
            const uint32_t st0 = sb + SM_H + (n1 >> 3) * 1024 + g * 16 + 4 * q;
#pragma unroll
            for (int i = 0; i < 4; i++) {
                float2 sq = *(const float2*)(sm + SM_SSQ + (pos0 + 32 * i) * 4);
                const uint32_t rs2 = pack_bf16(rsqrtf(sq.x * (1.f / 512.f) + 1e-5f), rsqrtf(sq.y * (1.f / 512.f) + 1e-5f));
#pragma unroll
                for (int jj = 0; jj < 4; jj++) {
                    const int K = jj ^ (2 * (i & 1));
                    uint32_t a = ((K & 1) ? rw1 : rw0) + i * 256 + (K & 2) * 16;
                    if (jj < 2) a ^= sw << 4;
                    uint32_t v = lds32(a);
                    xr[jj][i] = v;
                    uint32_t o = hmul2(v, rs2);
                    if (jj == 1 && sw) o = 0u;
                    sts32(st0 + (jj & 1) * 8192 + (4 * (jj >> 1) + i) * 128, o);
                }
            }
            if (wg == 0) TC(1 + 10 * layer);
            fence_async_smem();
            bar_sync(1, 256);
            float acc[32];
            const uint32_t s1a = sb + SM_X + wg * 16384, s2b = sb + SM_X + 32768;
            wg_fence();
#pragma unroll
            for (int ks = 0; ks < 8; ks++)
                wgmma_n64<1>(acc, desc_a(s1a + (ks >> 2) * 8192 + (ks & 3) * 256), desc_b<64>(sb + SM_H + ks * 2048), ks != 0);
            wg_commit();
            wg_wait<0>();
            if (wg == 0) TC(2 + 10 * layer);
            uint32_t are[2][4], aim[2][4];
#pragma unroll
            for (int col = 0; col < 2; col++) {
#pragma unroll
                for (int i = 0; i < 4; i++) {
                    int o = 4 * (4 * col + i);
                    uint32_t zr = pack_bf16(acc[o], acc[o + 1]), zi = pack_bf16(acc[o + 2], acc[o + 3]);
                    are[col][i] = hfma2(zr, tr2[i], hmul2(zi, tn2[i]));
                    aim[col][i] = hfma2(zr, ti2[i], hmul2(zi, tr2[i]));
                }
            }
            wg_fence();
#pragma unroll
            for (int ks = 0; ks < 2; ks++)
                wgmma_n64_rs(acc, are[0][2 * ks], are[1][2 * ks], are[0][2 * ks + 1], are[1][2 * ks + 1], desc_b<64>(s2b + ks * 2048), ks != 0);
#pragma unroll
            for (int ks = 0; ks < 2; ks++)
                wgmma_n64_rs(acc, aim[0][2 * ks], aim[1][2 * ks], aim[0][2 * ks + 1], aim[1][2 * ks + 1], desc_b<64>(s2b + 4096 + ks * 2048), 1);
            wg_commit();
            uint32_t wf[16];
            mbar_wait(BAR(B_WRDY), layer);
#pragma unroll
            for (int i = 0; i < 4; i++) {
                const int kq = n1 * 4 + q;
                uint4 v = *(const uint4*)(sm + SM_H + 16384 + kq * 64 + ((i ^ ((kq >> 1) & 3)) << 4));
                wf[4 * i] = v.x; wf[4 * i + 1] = v.y; wf[4 * i + 2] = v.z; wf[4 * i + 3] = v.w;
            }
            wg_wait<0>();
            if (wg == 0) TC(3 + 10 * layer);
#pragma unroll
            for (int col = 0; col < 2; col++) {
#pragma unroll
                for (int i = 0; i < 4; i++) {
                    uint32_t wr = wf[col * 8 + 2 * i], wn = wf[col * 8 + 2 * i + 1];
                    uint32_t zr = pack_bf16(acc[4 * i + 2 * col], acc[4 * i + 2 * col + 1]);
                    uint32_t zi = pack_bf16(acc[16 + 4 * i + 2 * col], acc[16 + 4 * i + 2 * col + 1]);
                    are[col][i] = hfma2(zr, wr, hmul2(zi, wn));
                    aim[col][i] = hfma2(zr, wn, hmul2(zi ^ 0x80008000u, wr));
                }
            }
            wg_fence();
#pragma unroll
            for (int ks = 0; ks < 2; ks++)
                wgmma_n64_rs(acc, are[0][2 * ks], are[1][2 * ks], are[0][2 * ks + 1], are[1][2 * ks + 1], desc_b<64>(s2b + ks * 2048), ks != 0);
#pragma unroll
            for (int ks = 0; ks < 2; ks++)
                wgmma_n64_rs(acc, aim[0][2 * ks], aim[1][2 * ks], aim[0][2 * ks + 1], aim[1][2 * ks + 1], desc_b<64>(s2b + 4096 + ks * 2048), 1);
            wg_commit();
            wg_wait<0>();
            if (wg == 0) TC(4 + 10 * layer);
            bar_sync(1, 256);
#pragma unroll
            for (int col = 0; col < 2; col++) {
#pragma unroll
                for (int i = 0; i < 4; i++) {
                    uint32_t zr = pack_bf16(acc[4 * i + 2 * col], acc[4 * i + 2 * col + 1]);
                    uint32_t zi = pack_bf16(acc[16 + 4 * i + 2 * col], acc[16 + 4 * i + 2 * col + 1]);
                    sts32(st0 + 16384 + (4 * col + i) * 128, hfma2(zr, tr2[i], hmul2(zi, tn2[i])));
                    sts32(st0 + 16384 + 8192 + (4 * col + i) * 128, hfma2(zr, ti2[i], hmul2(zi, tr2[i])));
                }
            }
            if (wg == 0) TC(5 + 10 * layer);
            fence_async_smem();
            bar_sync(1, 256);
            wg_fence();
#pragma unroll
            for (int ks = 0; ks < 8; ks++)
                wgmma_n64<1>(acc, desc_a(s1a + (ks >> 2) * 8192 + (ks & 3) * 256), desc_b<64>(sb + SM_H + 16384 + ks * 2048), ks != 0);
            wg_commit();
            wg_wait<0>();
            if (wg == 0) TC(6 + 10 * layer);
            const float sc = 1.f / 2048.f;
            const float sci0 = sw ? 0.f : -sc;
            const float wr0 = sw ? 0.5f : 1.f, wi0 = sw ? 0.f : 1.f;
#pragma unroll
            for (int i = 0; i < 4; i++) {
                float ss0, ss1;
#pragma unroll
                for (int col = 0; col < 2; col++) {
                    int o = 4 * (4 * col + i);
                    uint32_t vr = xr[2 * col][i], vi = xr[2 * col + 1][i];
                    float si = col == 0 ? sci0 : -sc;
                    uint32_t nr = pack_bf16(fmaf(acc[o], sc, bf_lo(vr)), fmaf(acc[o + 1], sc, bf_hi(vr)));
                    uint32_t ni = pack_bf16(fmaf(acc[o + 2], si, bf_lo(vi)), fmaf(acc[o + 3], si, bf_hi(vi)));
                    float a0 = bf_lo(nr), a1 = bf_hi(nr), b0 = bf_lo(ni), b1 = bf_hi(ni);
                    if (col == 0) {
                        ss0 = wr0 * a0 * a0 + wi0 * b0 * b0;
                        ss1 = wr0 * a1 * a1 + wi0 * b1 * b1;
                    } else {
                        ss0 += a0 * a0 + b0 * b0;
                        ss1 += a1 * a1 + b1 * b1;
                    }
                    const int K = (2 * col) ^ (2 * (i & 1));
                    uint32_t a = rw0 + i * 256 + K * 16;
                    if (col == 0) a ^= sw << 4;
                    sts32(a, nr);
                    sts32(a ^ 16, ni);
                }
                *(float2*)(sm + SM_SSQ + (pos0 + 32 * i) * 4) = make_float2(ss0 * (2.f / 512.f), ss1 * (2.f / 512.f));
            }
            fence_async_smem();
        }
        TS(5 + 12 * layer);
        if (wg == 0) TC(7 + 10 * layer);
        bar_arrive(5, 416);

        float acc[64];
        float* s_rstd = (float*)(sm + SM_RSTD);
        float* s_mean = (float*)(sm + SM_MEAN);
        const unsigned epoch = s_tgt[0] >> 7;
        const uint32_t pt3 = 1u + (2u * epoch + layer) % 3u;
        const uint32_t ptag = (pt3 & 1u) | ((pt3 & 2u) << 15);
        const uint64_t dstep = layer == 0 ? 16 : 2;
        auto c_desc = [&](int s) { return layer == 0 ? desc_a(sb + SM_A + s * 16384) : desc_k(sb + SM_A + s * 16384); };
        if (wg < 2) {
            const int prow = 32 * wg + 8 * w + g;
            const float2 l1 = *(const float2*)(sm + SM_LAM + prow * 8);
            float lr32 = l1.x, li32 = l1.y;
#pragma unroll
            for (int i = 0; i < 5; i++) { float t = lr32 * lr32 - li32 * li32; li32 = 2.f * lr32 * li32; lr32 = t; }
            float lr128 = lr32, li128 = li32;
#pragma unroll
            for (int i = 0; i < 2; i++) { float t = lr128 * lr128 - li128 * li128; li128 = 2.f * lr128 * li128; lr128 = t; }
            const float lr1 = l1.x, li1 = l1.y;
            const float l2r = lr128 * lr128 - li128 * li128, l2i = 2.f * lr128 * li128;
            const float l4r = l2r * l2r - l2i * l2i, l4i = 2.f * l2r * l2i;
            float lxr = 1.f, lxi = 0.f;
            {
                const int rho = (c - 1 - q) & 3;
                if (rho & 1) { lxr = lr128; lxi = li128; }
                if (rho & 2) { float t = lxr * l2r - lxi * l2i; lxi = lxr * l2i + lxi * l2r; lxr = t; }
            }
            acc_def(acc);
#pragma unroll 1
            for (int kb = 0; kb < 8; kb++) {
                const int st = kb < 6 ? kb : kb - 6;
                mbar_wait(BAR(B_AFULL + kb), fpar(kb, 0, layer));
                mbar_wait(BAR(B_XFULL + st), st < 2 ? (uint32_t)(kb >= 6) : (uint32_t)layer);
                wg_fence();
#pragma unroll
                for (int ks = 0; ks < 4; ks++)
                    wgmma_n128<1>(acc, desc_a(sb + SM_A + kb * 16384 + wg * 8192 + ks * 256),
                                  desc_b<128>(sb + SM_X + st * 16384 + ks * 4096), 1);
                wg_commit();
                wg_wait<1>();
                if (kb > 0 && lane == 0) {
                    mbar_arrive(BAR(B_AEMPTY + kb - 1), 1);
                    if (kb <= 2) { mbar_arrive(BAR(B_XEMPTY + kb - 1), 1); mbar_arrive_remote(mapa(BAR(B_XEMPTY + kb - 1), par ^ 1)); }
                }
            }
            wg_wait<0>();
            if (lane == 0) {
                mbar_arrive(BAR(B_AEMPTY + 7), 1);
                mbar_arrive_remote(mapa(BAR(B_RFREE), par ^ 1));
            }
            bar_arrive(14, 384);
            TS(6 + 12 * layer);
            bar_sync(4, 384);
            TS(7 + 12 * layer);
            float er = 0.f, ei = 0.f;
#pragma unroll
            for (int i = 0; i < 16; i++) {
                float2 rs = *(const float2*)(s_rstd + 128 + 8 * i + 2 * q);
                acc[4 * i] *= rs.x; acc[4 * i + 1] *= rs.y; acc[4 * i + 2] *= rs.x; acc[4 * i + 3] *= rs.y;
                float nr = lr1 * er - li1 * ei + acc[4 * i], ni = lr1 * ei + li1 * er + acc[4 * i + 2];
                er = lr1 * nr - li1 * ni + acc[4 * i + 1];
                ei = lr1 * ni + li1 * nr + acc[4 * i + 3];
            }
            float cr = 0.f, ci = 0.f, tr = 0.f, ti = 0.f;
#pragma unroll
            for (int qq = 0; qq < 4; qq++) {
                float xr_ = __shfl_sync(~0u, er, (lane & ~3) | qq), xi_ = __shfl_sync(~0u, ei, (lane & ~3) | qq);
                if (qq == q) { cr = tr; ci = ti; }
                float nr = lr32 * tr - li32 * ti + xr_, ni = lr32 * ti + li32 * tr + xi_;
                tr = nr; ti = ni;
            }
            float4* eb = g_Ebuf + (uint32_t)(layer * 16 * 512 + 64 * r + prow);
            if (q == 0 && c < 15) st_relaxed_f4(eb + c * 512, make_float4(tr, ti, __uint_as_float(epoch), 0.f));
            TS(8 + 12 * layer);
            float pr[4], pi[4];
            {
                unsigned n = 0;
                bool ok;
#pragma unroll 1
                do {
                    ok = true;
#pragma unroll
                    for (int k = 0; k < 4; k++) {
                        float4 v = make_float4(0.f, 0.f, __uint_as_float(epoch), 0.f);
                        if (4 * k + q < c) v = ld_relaxed_f4(eb + (4 * k + q) * 512);
                        pr[k] = v.x; pi[k] = v.y;
                        ok = ok && __float_as_uint(v.z) == epoch;
                    }
                } while (!ok && ++n < SPIN_LIMIT);
            }
            __syncwarp();
            TS(9 + 12 * layer);
            float hr = 0.f, hi = 0.f;
#pragma unroll
            for (int k = 0; k < 4; k++) {
                if (4 * k + q < c) {
                    float nr = l4r * hr - l4i * hi + pr[k], ni = l4r * hi + l4i * hr + pi[k];
                    hr = nr; hi = ni;
                }
            }
            {
                float nr = lxr * hr - lxi * hi, ni = lxr * hi + lxi * hr;
                hr = nr + __shfl_xor_sync(~0u, nr, 1); hi = ni + __shfl_xor_sync(~0u, ni, 1);
                hr += __shfl_xor_sync(~0u, hr, 2); hi += __shfl_xor_sync(~0u, hi, 2);
            }
#pragma unroll
            for (int qq = 0; qq < 3; qq++) {
                if (qq < q) { float nr = lr32 * hr - li32 * hi, ni = lr32 * hi + li32 * hr; hr = nr; hi = ni; }
            }
            er = cr + hr; ei = ci + hi;
            bar_sync(7, 384);
            mbar_wait_cluster(BAR(B_RFREE), layer);
            const uint32_t ha = sb + SM_HH + par * 32768 + (prow >> 3) * 1024 + g * 16 + 4 * q;
#pragma unroll
            for (int i = 0; i < 16; i++) {
                float nr = lr1 * er - li1 * ei + acc[4 * i], ni = lr1 * ei + li1 * er + acc[4 * i + 2];
                er = lr1 * nr - li1 * ni + acc[4 * i + 1];
                ei = lr1 * ni + li1 * nr + acc[4 * i + 3];
                sts32(ha + (i >> 3) * 16384 + (i & 7) * 128, pack_bf16(nr, er));
                sts32(ha + (i >> 3) * 16384 + 8192 + (i & 7) * 128, pack_bf16(ni, ei));
                if (i == 7) { fence_async_smem(); bar_arrive(13, 288); }
            }
            fence_async_smem();
            acc_def(acc);
            float acc2[32];
            acc_def(acc2);
            TS(10 + 12 * layer);
            bar_sync(6, 416);
            TS(11 + 12 * layer);
            float (&a0)[32] = *reinterpret_cast<float (*)[32]>(&acc[0]);
            float (&a1)[32] = *reinterpret_cast<float (*)[32]>(&acc[32]);
            auto tile_mma = [&](float (&d)[32], int u) {
#pragma unroll 1
                for (int k = 0; k < 2; k++) {
                    const uint32_t hb = sb + SM_HH + (par ^ k) * 32768 + wg * 16384;
                    if (k == 1) mbar_wait(BAR(wg ? B_HPEER1 : B_HPEER), layer);
                    const int cs = cslot(2 * u + k);
                    mbar_wait(BAR(B_AFULL + cs), fpar(cs, 2, layer));
                    const uint64_t da = c_desc(cs);
                    wg_fence();
#pragma unroll
                    for (int ks = 0; ks < 4; ks++) wgmma_n64s<1>(d, da + ks * dstep, desc_b<64>(hb + ks * 2048), 1);
#pragma unroll
                    for (int ks = 0; ks < 4; ks++) wgmma_n64s<-1>(d, da + 512 + ks * dstep, desc_b<64>(hb + 8192 + ks * 2048), 1);
                }
                wg_commit();
            };
            auto tile_ship = [&](float (&d)[32], int u) {
                uint4* dst = g_P + (uint32_t)(((c * 8 + 2 * ((pi_ + 1 + u) & 3) + par) * 4 + pi_) * 1024 + wg * 512 + (tid & 127));
#pragma unroll
                for (int i = 0; i < 4; i++)
                    dst[i * 128] = make_uint4((pack_bf16(d[8 * i], d[8 * i + 1]) & 0xfffefffeu) | ptag, pack_bf16(d[8 * i + 2], d[8 * i + 3]),
                                              pack_bf16(d[8 * i + 4], d[8 * i + 5]), pack_bf16(d[8 * i + 6], d[8 * i + 7]));
            };
            tile_mma(a0, 0);
            if ((tid & 127) == 0) mbar_arrive_remote(mapa(BAR(B_HDONE), par ^ 1));
            __syncwarp();
            tile_mma(a1, 1);
            wg_wait<1>();
            tile_ship(a0, 0);
            tile_mma(acc2, 2);
            bar_arrive(12, 384);
            wg_wait<1>();
            tile_ship(a1, 1);
            wg_wait<0>();
            tile_ship(acc2, 2);
            if (lane < 6) mbar_arrive(BAR(B_AEMPTY + ((lane + 6) & 7)), 1);
            TS(12 + 12 * layer);
        } else {
            const int t2 = tid - 256;
            const uint8_t* ximg = g_X + (uint32_t)layer * 16 * 8 * 16384;
            mbar_wait(BAR(B_SSQ), layer);
            TS(6 + 12 * layer);
            float sqv[16];
#pragma unroll
            for (int i = 0; i < 16; i++) sqv[i] = __ldcg(g_ssqc + (layer * 16 + i) * 2048 + 128 * c + t2);
            const unsigned short xm = __ldcg((const unsigned short*)(ximg + (uint32_t)(c * 8 * 16384 + (t2 >> 3) * 128 + (t2 & 7) * 2)));
            {
                float tot = 0.f;
#pragma unroll
                for (int i = 0; i < 16; i++) tot += sqv[i];
                float rs = rsqrtf(tot * (1.f / 512.f) + 1e-5f);
                s_rstd[t2] = rs;
                s_rstd[128 + t2] = 2.f * rs;
                s_mean[t2] = layer == 0 ? 0.f : __uint_as_float((uint32_t)xm << 16) * (1.f / 512.f);
                TS(7 + 12 * layer);
                bar_arrive(4, 384);
            }
            acc_def(acc);
            bar_sync(14, 384);
#pragma unroll 1
            for (int it = 0; it < 8; it++) {
                const int kb = (it + 2) & 7;
                mbar_wait(BAR(B_AFULL + (kb >> 1)), fpar(0, 1, layer));
                if (kb < 2) mbar_wait(BAR(B_AFULL + 4 + kb), fpar(0, 1, layer));
                const uint32_t xb = kb < 2 ? sb + SM_A + (4 + kb) * 16384 : sb + SM_X + (kb < 6 ? kb : kb - 6) * 16384;
                wg_fence();
#pragma unroll
                for (int ks = 0; ks < 4; ks++)
                    wgmma_n128<1>(acc, desc_a(sb + SM_A + kb * 8192 + ks * 256), desc_b<128>(xb + ks * 4096), 1);
                wg_commit();
                wg_wait<1>();
                if (it >= 2 && (it & 1) == 0 && lane == 0) mbar_arrive(BAR(B_AEMPTY + (it >> 1)), 2);
            }
            wg_wait<0>();
            if (lane < 3) mbar_arrive(BAR(B_AEMPTY + (lane == 0 ? 0 : lane + 3)), 2);
            if (lane == 0) mbar_arrive_remote(mapa(BAR(B_RFREE), par ^ 1));
            bar_arrive(7, 384);
            bar_sync(3, 128);
            TS(9 + 12 * layer);
            const int m0 = 16 * w + g;
            const uint32_t xoff = (uint32_t)((c * 8 + own) * 16384 + w * 4096 + g * 16 + 4 * q);
            if (layer == 0) {
                const uint8_t* xs = g_X + xoff;
#pragma unroll
                for (int i = 0; i < 16; i++) {
                    float2 rs = *(const float2*)(s_rstd + 8 * i + 2 * q);
                    uint32_t x0v = __ldcg((const uint32_t*)(xs + i * 128)), x1v = __ldcg((const uint32_t*)(xs + 2048 + i * 128));
                    acc[4 * i] = acc[4 * i] * rs.x + bf_lo(x0v);
                    acc[4 * i + 1] = acc[4 * i + 1] * rs.y + bf_hi(x0v);
                    acc[4 * i + 2] = acc[4 * i + 2] * rs.x + bf_lo(x1v);
                    acc[4 * i + 3] = acc[4 * i + 3] * rs.y + bf_hi(x1v);
                }
            } else {
                float d0 = ldbf(p.dskip + 64 * own + m0), d1 = ldbf(p.dskip + 64 * own + m0 + 8);
#pragma unroll
                for (int i = 0; i < 16; i++) {
                    float2 rs = *(const float2*)(s_rstd + 8 * i + 2 * q);
                    float2 mn = *(const float2*)(s_mean + 8 * i + 2 * q);
                    acc[4 * i] = acc[4 * i] * (1.f + rs.x * d0) + mn.x;
                    acc[4 * i + 1] = acc[4 * i + 1] * (1.f + rs.y * d0) + mn.y;
                    acc[4 * i + 2] = acc[4 * i + 2] * (1.f + rs.x * d1) + mn.x;
                    acc[4 * i + 3] = acc[4 * i + 3] * (1.f + rs.y * d1) + mn.y;
                }
            }
            TS(10 + 12 * layer);
            bar_sync(6, 416);
            TS(11 + 12 * layer);
            {
                float (&a0)[32] = *reinterpret_cast<float (*)[32]>(&acc[0]);
                float (&a1)[32] = *reinterpret_cast<float (*)[32]>(&acc[32]);
#pragma unroll 1
                for (int k = 0; k < 2; k++) {
                    const uint32_t hb = sb + SM_HH + (par ^ k) * 32768;
                    if (k == 1) {
                        mbar_wait(BAR(B_HPEER), layer);
                        mbar_wait(BAR(B_HPEER1), layer);
                        bar_sync(12, 384);
                    }
                    mbar_wait(BAR(B_AFULL + 4 + k), fpar(4, 2, layer));
                    const uint64_t da = c_desc(4 + k);
                    wg_fence();
#pragma unroll
                    for (int ks = 0; ks < 4; ks++) {
                        wgmma_n64s<1>(a0, da + ks * dstep, desc_b<64>(hb + ks * 2048), 1);
                        wgmma_n64s<1>(a1, da + ks * dstep, desc_b<64>(hb + 16384 + ks * 2048), 1);
                    }
#pragma unroll
                    for (int ks = 0; ks < 4; ks++) {
                        wgmma_n64s<-1>(a0, da + 512 + ks * dstep, desc_b<64>(hb + 8192 + ks * 2048), 1);
                        wgmma_n64s<-1>(a1, da + 512 + ks * dstep, desc_b<64>(hb + 16384 + 8192 + ks * 2048), 1);
                    }
                    wg_commit();
                }
                wg_wait<0>();
            }
#pragma unroll
            for (int i = 0; i < 16; i++)
                *(float4*)(sm + SM_A + 4 * 16384 + i * 2048 + t2 * 16) = make_float4(acc[4 * i], acc[4 * i + 1], acc[4 * i + 2], acc[4 * i + 3]);
            TS(12 + 12 * layer);
        }
        {
            const int t = tid & 127;
            const int nch = wg == 2 ? 2 : 3;
            const uint4* pb = g_P + (uint32_t)((c * 8 + r) * 4 * 1024 + wg * 128 + t);
            uint4 v[3][3];
            unsigned n = 0;
#pragma unroll 1
            while (true) {
                if (lane == 31) {
#pragma unroll 1
                    while (true) {
                        uint32_t bad = 0;
#pragma unroll
                        for (int sx = 0; sx < 3; sx++) {
                            uint32_t t0;
                            asm volatile("ld.relaxed.gpu.global.u32 %0, [%1];" : "=r"(t0) : "l"(pb + ((pi_ + 1 + sx) & 3) * 1024 + (nch - 1) * 384) : "memory");
                            bad |= t0 ^ ptag;
                        }
                        if (!(bad & 0x00010001u) || ++n >= SPIN_LIMIT) break;
                    }
                }
                __syncwarp();
                uint32_t bad = 0;
#pragma unroll
                for (int k = 0; k < 3; k++)
#pragma unroll
                    for (int sx = 0; sx < 3; sx++) {
                        v[k][sx] = make_uint4(ptag, 0, 0, 0);
                        if (k < nch) v[k][sx] = ld_relaxed_u4(pb + ((pi_ + 1 + sx) & 3) * 1024 + k * 384);
                        bad |= v[k][sx].x ^ ptag;
                    }
                if (!__any_sync(~0u, bad & 0x00010001u) || ++n >= SPIN_LIMIT) break;
            }
            bar_sync(8, 384);
            TS(13 + 12 * layer);
            const int m0 = 16 * w + g;
            const float w0 = (own == 0 && m0 < 2) ? (m0 == 0 ? 0.f : 0.5f) : 1.f;
#pragma unroll
            for (int k = 0; k < 3; k++) {
                if (k < nch) {
                    const int i = wg + 3 * k;
                    float4 a = *(const float4*)(sm + SM_A + 4 * 16384 + (2 * i) * 2048 + t * 16);
                    float4 bq = *(const float4*)(sm + SM_A + 4 * 16384 + (2 * i + 1) * 2048 + t * 16);
#pragma unroll
                    for (int sx = 0; sx < 3; sx++) {
                        a.x += bf_lo(v[k][sx].x); a.y += bf_hi(v[k][sx].x); a.z += bf_lo(v[k][sx].y); a.w += bf_hi(v[k][sx].y);
                        bq.x += bf_lo(v[k][sx].z); bq.y += bf_hi(v[k][sx].z); bq.z += bf_lo(v[k][sx].w); bq.w += bf_hi(v[k][sx].w);
                    }
                    if (layer == 0) {
                        uint8_t* xd = g_X + (uint32_t)((16 * 8 + c * 8 + own) * 16384 + w * 4096 + g * 16 + 4 * q + i * 256);
                        uint32_t v0 = pack_bf16(a.x, a.y), v1 = pack_bf16(a.z, a.w), v2 = pack_bf16(bq.x, bq.y), v3 = pack_bf16(bq.z, bq.w);
                        *(uint32_t*)(xd) = v0; *(uint32_t*)(xd + 2048) = v1; *(uint32_t*)(xd + 128) = v2; *(uint32_t*)(xd + 2048 + 128) = v3;
                        float sq[4];
                        sq[0] = w0 * bf_lo(v0) * bf_lo(v0) + bf_lo(v1) * bf_lo(v1);
                        sq[1] = w0 * bf_hi(v0) * bf_hi(v0) + bf_hi(v1) * bf_hi(v1);
                        sq[2] = w0 * bf_lo(v2) * bf_lo(v2) + bf_lo(v3) * bf_lo(v3);
                        sq[3] = w0 * bf_hi(v2) * bf_hi(v2) + bf_hi(v3) * bf_hi(v3);
                        float u0 = (g & 1) ? sq[2] : sq[0], u1 = (g & 1) ? sq[3] : sq[1];
                        u0 += __shfl_xor_sync(~0u, (g & 1) ? sq[0] : sq[2], 4);
                        u1 += __shfl_xor_sync(~0u, (g & 1) ? sq[1] : sq[3], 4);
                        float z = (g & 2) ? u1 : u0;
                        z += __shfl_xor_sync(~0u, (g & 2) ? u0 : u1, 8);
                        z += __shfl_xor_sync(~0u, z, 16);
                        if (g < 4) atomicAdd(s_mean + 16 * i + 8 * (g & 1) + 2 * q + (g >> 1), z);
                    } else {
                        float* o = p.out + (uint32_t)((128 * c + 32 * q + 4 * i) * 512 + 64 * own + m0);
                        o[0] = a.x; o[512] = a.y; o[8] = a.z; o[512 + 8] = a.w;
                        o[1024] = bq.x; o[1536] = bq.y; o[1024 + 8] = bq.z; o[1536 + 8] = bq.w;
                    }
                }
            }
            if (wg < 2) mbar_wait_cluster(BAR(B_HDONE), layer);
            if (layer == 0) {
                fence_async_smem();
                bar_sync(9, 384);
                TS(14 + 12 * layer);
                if (wg == 2) {
                    atomicAdd(g_ssq + 2048 + 128 * c + t, s_mean[t] * (2.f / 512.f));
                    bar_sync(3, 128);
                    if (lane == 0) { mbar_arrive(BAR(B_AEMPTY + 4), 2); mbar_arrive(BAR(B_AEMPTY + 5), 2); }
                    if (t == 0) { fence_async(); red_release(&g_bar[2], 1); }
                }
            }
        }
        TS(15 + 12 * layer);
        if (wg == 0) TC(31);
    }
}

typedef CUresult (*EncFn)(CUtensorMap*, CUtensorMapDataType, cuuint32_t, void*, const cuuint64_t*, const cuuint64_t*,
                          const cuuint32_t*, const cuuint32_t*, CUtensorMapInterleave, CUtensorMapSwizzle,
                          CUtensorMapL2promotion, CUtensorMapFloatOOBfill);

void launch_impl(void* const* d_in, void* d_out, int stop) {
    static EncFn enc = nullptr;
    if (!enc) {
        void* fn = nullptr;
        cudaDriverEntryPointQueryResult qr;
        cudaGetDriverEntryPoint("cuTensorMapEncodeTiled", &fn, cudaEnableDefault, &qr);
        enc = (EncFn)fn;
        cudaFuncSetAttribute(fused_kernel, cudaFuncAttributeMaxDynamicSharedMemorySize, SM_TOTAL);
    }
    CUtensorMap tx, tbr, tbi, tcr, tci, tcol;
    {
        void* gx = nullptr;
        cudaGetSymbolAddress(&gx, g_X);
        cuuint64_t gd[5] = {64, 16, 64, 16, 2};
        cuuint64_t gs[4] = {128, 2048, 128 * 1024, 2048 * 1024};
        cuuint32_t bx[5] = {32, 16, 1, 16, 1};
        cuuint32_t es[5] = {1, 1, 1, 1, 1};
        enc(&tcol, CU_TENSOR_MAP_DATA_TYPE_BFLOAT16, 5, gx, gd, gs, bx, es, CU_TENSOR_MAP_INTERLEAVE_NONE,
            CU_TENSOR_MAP_SWIZZLE_64B, CU_TENSOR_MAP_L2_PROMOTION_NONE, CU_TENSOR_MAP_FLOAT_OOB_FILL_NONE);
    }
    {
        cuuint64_t gd[5] = {512, 2, 4, 16, 16};
        cuuint64_t gs[4] = {1024, 32 * 1024, 2 * 1024, 128 * 1024};
        cuuint32_t bx[5] = {64, 2, 4, 8, 1};
        cuuint32_t es[5] = {1, 1, 1, 1, 1};
        enc(&tx, CU_TENSOR_MAP_DATA_TYPE_BFLOAT16, 5, d_in[0], gd, gs, bx, es, CU_TENSOR_MAP_INTERLEAVE_NONE,
            CU_TENSOR_MAP_SWIZZLE_128B, CU_TENSOR_MAP_L2_PROMOTION_L2_128B, CU_TENSOR_MAP_FLOAT_OOB_FILL_NONE);
    }
    auto mk2 = [&](CUtensorMap* m, void* ptr, cuuint32_t rows) {
        cuuint64_t gd[2] = {512, 512};
        cuuint64_t gs[1] = {1024};
        cuuint32_t bx[2] = {64, rows};
        cuuint32_t es[2] = {1, 1};
        enc(m, CU_TENSOR_MAP_DATA_TYPE_BFLOAT16, 2, ptr, gd, gs, bx, es, CU_TENSOR_MAP_INTERLEAVE_NONE,
            CU_TENSOR_MAP_SWIZZLE_128B, CU_TENSOR_MAP_L2_PROMOTION_L2_128B, CU_TENSOR_MAP_FLOAT_OOB_FILL_NONE);
    };
    mk2(&tbr, d_in[6], 32);
    mk2(&tbi, d_in[7], 32);
    mk2(&tcr, d_in[8], 64);
    mk2(&tci, d_in[9], 64);
    Params p;
    p.x0 = (const __nv_bfloat16*)d_in[0];
    p.w_r = (const __nv_bfloat16*)d_in[1];
    p.w_i = (const __nv_bfloat16*)d_in[2];
    p.lam_re = (const __nv_bfloat16*)d_in[4];
    p.lam_im = (const __nv_bfloat16*)d_in[5];
    p.log_dt = (const __nv_bfloat16*)d_in[10];
    p.dskip = (const __nv_bfloat16*)d_in[11];
    p.out = (float*)d_out;
    p.stop = stop;
    cudaLaunchConfig_t cfg = {};
    cfg.gridDim = dim3(NCTA); cfg.blockDim = dim3(NTHREADS); cfg.dynamicSmemBytes = SM_TOTAL; cfg.stream = cudaStreamPerThread;
    cudaLaunchAttribute at[1];
    at[0].id = cudaLaunchAttributeClusterDimension;
    at[0].val.clusterDim.x = 2; at[0].val.clusterDim.y = 1; at[0].val.clusterDim.z = 1;
    cfg.attrs = at; cfg.numAttrs = 1;
    cudaLaunchKernelEx(&cfg, fused_kernel, tx, tbr, tbi, tcr, tci, tcol, p);
}

}

extern "C" void kernel_launch(void* const* d_in, const int* in_sizes, int n_in, void* d_out, int out_size) {
    (void)in_sizes; (void)n_in; (void)out_size;
    launch_impl(d_in, d_out, 100);
}
```

```cpp
#include <cuda_runtime.h>
#include <cuda_bf16.h>
#include <cuda.h>
#include <stdint.h>

namespace {

constexpr int NCTA = 128;
constexpr int NTHREADS = 512;
constexpr int SM_A = 0;
constexpr int SM_X = 131072;
constexpr int SM_H = 196608;
constexpr int SM_HH = SM_X + 32768;
constexpr int SM_M = 229376;
constexpr int SM_TOTAL = 232448;
constexpr int SM_BAR = SM_M;
constexpr int SM_TGT = SM_M + 400;
constexpr int SM_LAM = SM_M + 424;
constexpr int SM_TAB = SM_M + 944;
constexpr int SM_RSTD = SM_M + 1920;
constexpr int SM_MEAN = SM_TAB;
constexpr int SM_T64 = SM_M + 2944;
constexpr int SM_B1ST = SM_H + 24576;
constexpr int SM_RAW = SM_X + 40960;
constexpr int SM_SSQ = SM_X + 57344;
constexpr int B_FULL0 = 0;
constexpr int B_EMPTY0 = 8;
constexpr int B_FULLC = 12;
constexpr int B_AFULL = 13;
constexpr int B_AEMPTY = 21;
constexpr int B_XFULL = 29;
constexpr int B_XEMPTY = 35;
constexpr int B_AFREE = 37;
constexpr int B_COL = 38;
constexpr int B_SSQ = 39;
constexpr int B_HPEER = 40;
constexpr int B_RFREE = 41;
constexpr int B_HDONE = 42;
constexpr int B_WRDY = 43;
constexpr int B_HPEER1 = 44;
constexpr int B_FULLB = 45;
constexpr int B_BFREE = 46;
constexpr int B_SETUP = 47;
constexpr int B_B1DONE = 48;
constexpr int B_WST = 49;
constexpr int NBARS = 50;

__device__ __align__(1024) uint8_t g_X[2 * 16 * 8 * 16384];
__device__ __align__(1024) uint8_t g_A1[8 * 8 * 16384];
__device__ __align__(1024) uint8_t g_A2[8 * 8 * 16384];
__device__ __align__(1024) uint8_t g_E[2 * 8 * 8 * 8192];
__device__ __align__(16) float g_ssq[2 * 2048];
__device__ __align__(16) float g_ssqc[2 * 16 * 2048];
__device__ __align__(16) float g_Dh[512];
__device__ __align__(16) uint4 g_Wfrag[128 * 4 * 256];
__device__ __align__(16) float4 g_Ebuf[2 * 16 * 512];
__device__ __align__(16) uint4 g_P[16 * 8 * 4 * 1024];
__device__ unsigned g_bar[8];
__device__ unsigned g_err;
#define TX(i)
#define TQ(i)
#define TS(i)
#define TC(i)

constexpr unsigned SPIN_LIMIT = 1u << 22;

__device__ __forceinline__ uint32_t s2u(const void* p) { return (uint32_t)__cvta_generic_to_shared(p); }
__device__ __forceinline__ void mbar_init(uint32_t a, uint32_t c) {
    asm volatile("mbarrier.init.shared::cta.b64 [%0], %1;" ::"r"(a), "r"(c) : "memory");
}
__device__ __forceinline__ void mbar_expect(uint32_t a, uint32_t bytes) {
    asm volatile("mbarrier.arrive.expect_tx.shared::cta.b64 _, [%0], %1;" ::"r"(a), "r"(bytes) : "memory");
}
__device__ __forceinline__ void mbar_arrive(uint32_t a, uint32_t cnt) {
    asm volatile("mbarrier.arrive.shared::cta.b64 _, [%0], %1;" ::"r"(a), "r"(cnt) : "memory");
}
__device__ __forceinline__ bool mbar_try(uint32_t a, uint32_t parity) {
    uint32_t ok;
    asm volatile("{\n.reg .pred p;\nmbarrier.try_wait.parity.shared::cta.b64 p, [%1], %2;\nselp.u32 %0, 1, 0, p;\n}"
                 : "=r"(ok) : "r"(a), "r"(parity) : "memory");
    return ok != 0;
}
__device__ __forceinline__ void mbar_wait(uint32_t a, uint32_t parity) {
    asm volatile("{\n.reg .pred p, q;\n.reg .u32 n;\nmov.u32 n, 0;\n"
                 "W_%=:\nmbarrier.try_wait.parity.shared::cta.b64 p, [%0], %1;\n@p bra D_%=;\n"
                 "add.u32 n, n, 1;\nsetp.lt.u32 q, n, 4194304;\n@q bra W_%=;\nD_%=:\n}" ::"r"(a), "r"(parity) : "memory");
}
__device__ __forceinline__ void bulk_g2s(uint32_t dst, const void* src, uint32_t bytes, uint32_t bar) {
    asm volatile("cp.async.bulk.shared::cluster.global.mbarrier::complete_tx::bytes [%0], [%1], %2, [%3];" ::"r"(dst),
                 "l"(src), "r"(bytes), "r"(bar) : "memory");
}
__device__ __forceinline__ void tma_2d(uint32_t dst, const CUtensorMap* m, int c0, int c1, uint32_t bar) {
    asm volatile("cp.async.bulk.tensor.2d.shared::cluster.global.mbarrier::complete_tx::bytes [%0], [%1, {%3,%4}], [%2];" ::"r"(dst),
                 "l"(m), "r"(bar), "r"(c0), "r"(c1) : "memory");
}
__device__ __forceinline__ void tma_5d(uint32_t dst, const CUtensorMap* m, int c0, int c1, int c2, int c3, int c4, uint32_t bar) {
    asm volatile("cp.async.bulk.tensor.5d.shared::cluster.global.mbarrier::complete_tx::bytes [%0], [%1, {%3,%4,%5,%6,%7}], [%2];" ::"r"(dst),
                 "l"(m), "r"(bar), "r"(c0), "r"(c1), "r"(c2), "r"(c3), "r"(c4) : "memory");
}
__device__ __forceinline__ void tma_2d_mc(uint32_t dst, const CUtensorMap* m, int c0, int c1, uint32_t bar) {
    asm volatile("cp.async.bulk.tensor.2d.shared::cluster.global.mbarrier::complete_tx::bytes.multicast::cluster [%0], [%1, {%3,%4}], [%2], %5;" ::"r"(dst),
                 "l"(m), "r"(bar), "r"(c0), "r"(c1), "h"((unsigned short)3) : "memory");
}
__device__ __forceinline__ void tma_5d_mc(uint32_t dst, const CUtensorMap* m, int c0, int c1, int c2, int c3, int c4, uint32_t bar) {
    asm volatile("cp.async.bulk.tensor.5d.shared::cluster.global.mbarrier::complete_tx::bytes.multicast::cluster [%0], [%1, {%3,%4,%5,%6,%7}], [%2], %8;" ::"r"(dst),
                 "l"(m), "r"(bar), "r"(c0), "r"(c1), "r"(c2), "r"(c3), "r"(c4), "h"((unsigned short)3) : "memory");
}
__device__ __forceinline__ void bulk_g2s_mc(uint32_t dst, const void* src, uint32_t bytes, uint32_t bar) {
    asm volatile("cp.async.bulk.shared::cluster.global.mbarrier::complete_tx::bytes.multicast::cluster [%0], [%1], %2, [%3], %4;" ::"r"(dst),
                 "l"(src), "r"(bytes), "r"(bar), "h"((unsigned short)3) : "memory");
}
__device__ __forceinline__ void tma_store_5d(const CUtensorMap* m, int c0, int c1, int c2, int c3, int c4, uint32_t src) {
    asm volatile("cp.async.bulk.tensor.5d.global.shared::cta.bulk_group [%0, {%2,%3,%4,%5,%6}], [%1];" ::"l"(m), "r"(src),
                 "r"(c0), "r"(c1), "r"(c2), "r"(c3), "r"(c4) : "memory");
}
__device__ __forceinline__ uint32_t lds32(uint32_t a) { uint32_t v; asm volatile("ld.shared.u32 %0, [%1];" : "=r"(v) : "r"(a) : "memory"); return v; }
__device__ __forceinline__ uint4 ld_relaxed_u4(const uint4* p) {
    uint4 v;
    asm volatile("ld.relaxed.gpu.global.v4.u32 {%0,%1,%2,%3}, [%4];" : "=r"(v.x), "=r"(v.y), "=r"(v.z), "=r"(v.w) : "l"(p) : "memory");
    return v;
}
__device__ __forceinline__ void fence_async() { asm volatile("fence.proxy.async.global;" ::: "memory"); }
__device__ __forceinline__ void red_relaxed(unsigned* p, unsigned v) {
    asm volatile("red.relaxed.gpu.global.add.u32 [%0], %1;" ::"l"(p), "r"(v) : "memory");
}
__device__ __forceinline__ uint32_t mapa(uint32_t a, uint32_t rank) {
    uint32_t d;
    asm("mapa.shared::cluster.u32 %0, %1, %2;" : "=r"(d) : "r"(a), "r"(rank));
    return d;
}
__device__ __forceinline__ void mbar_arrive_remote(uint32_t ra) {
    asm volatile("mbarrier.arrive.relaxed.cluster.shared::cluster.b64 _, [%0];" ::"r"(ra) : "memory");
}
__device__ __forceinline__ void mbar_wait_cluster(uint32_t a, uint32_t parity) {
    asm volatile("{\n.reg .pred p, q;\n.reg .u32 n;\nmov.u32 n, 0;\n"
                 "W_%=:\nmbarrier.try_wait.parity.acquire.cluster.shared::cta.b64 p, [%0], %1;\n@p bra D_%=;\n"
                 "add.u32 n, n, 1;\nsetp.lt.u32 q, n, 4194304;\n@q bra W_%=;\nD_%=:\n}" ::"r"(a), "r"(parity) : "memory");
}
__device__ __forceinline__ void bulk_s2peer(uint32_t rdst, uint32_t src, uint32_t bytes, uint32_t rbar) {
    asm volatile("cp.async.bulk.shared::cluster.shared::cta.mbarrier::complete_tx::bytes [%0], [%1], %2, [%3];" ::"r"(rdst),
                 "r"(src), "r"(bytes), "r"(rbar) : "memory");
}
__device__ __forceinline__ void fence_async_smem() { asm volatile("fence.proxy.async.shared::cta;" ::: "memory"); }
__device__ __forceinline__ void wg_fence() { asm volatile("wgmma.fence.sync.aligned;" ::: "memory"); }
__device__ __forceinline__ void wg_commit() { asm volatile("wgmma.commit_group.sync.aligned;" ::: "memory"); }
template <int N> __device__ __forceinline__ void wg_wait() { asm volatile("wgmma.wait_group.sync.aligned %0;" ::"n"(N) : "memory"); }
__device__ __forceinline__ void bar_sync(int id, int n) { asm volatile("bar.sync %0, %1;" ::"r"(id), "r"(n) : "memory"); }
__device__ __forceinline__ void bar_arrive(int id, int n) { asm volatile("bar.arrive %0, %1;" ::"r"(id), "r"(n) : "memory"); }
__device__ __forceinline__ unsigned ld_acquire(const unsigned* p) {
    unsigned v;
    asm volatile("ld.acquire.gpu.global.u32 %0, [%1];" : "=r"(v) : "l"(p) : "memory");
    return v;
}
__device__ __forceinline__ void red_release(unsigned* p, unsigned v) {
    asm volatile("red.release.gpu.global.add.u32 [%0], %1;" ::"l"(p), "r"(v) : "memory");
}
__device__ __forceinline__ void wait_count(const unsigned* p, unsigned target) {
    unsigned n = 0;
#pragma unroll 1
    while ((int)(ld_acquire(p) - target) < 0 && ++n < SPIN_LIMIT) {}
}
__device__ __forceinline__ float4 ld_relaxed_f4(const float4* p) {
    float4 v;
    asm volatile("ld.relaxed.gpu.global.v4.f32 {%0,%1,%2,%3}, [%4];" : "=f"(v.x), "=f"(v.y), "=f"(v.z), "=f"(v.w) : "l"(p) : "memory");
    return v;
}
__device__ __forceinline__ void st_relaxed_f4(float4* p, float4 v) {
    asm volatile("st.relaxed.gpu.global.v4.f32 [%0], {%1,%2,%3,%4};" ::"l"(p), "f"(v.x), "f"(v.y), "f"(v.z), "f"(v.w) : "memory");
}
__device__ __forceinline__ uint32_t pack_bf16(float lo, float hi) {
    uint32_t r;
    asm("cvt.rn.bf16x2.f32 %0, %1, %2;" : "=r"(r) : "f"(hi), "f"(lo));
    return r;
}
__device__ __forceinline__ uint32_t hmul2(uint32_t a, uint32_t b) {
    uint32_t r;
    asm("mul.rn.bf16x2 %0, %1, %2;" : "=r"(r) : "r"(a), "r"(b));
    return r;
}
__device__ __forceinline__ uint32_t hfma2(uint32_t a, uint32_t b, uint32_t c) {
    uint32_t r;
    asm("fma.rn.bf16x2 %0, %1, %2, %3;" : "=r"(r) : "r"(a), "r"(b), "r"(c));
    return r;
}
__device__ __forceinline__ float bf_lo(uint32_t v) { return __uint_as_float(v << 16); }
__device__ __forceinline__ float bf_hi(uint32_t v) { return __uint_as_float(v & 0xffff0000u); }
__device__ __forceinline__ void sts32(uint32_t a, uint32_t v) { asm volatile("st.shared.u32 [%0], %1;" ::"r"(a), "r"(v) : "memory"); }
__device__ __forceinline__ void sts128(uint32_t a, uint4 v) {
    asm volatile("st.shared.v4.u32 [%0], {%1,%2,%3,%4};" ::"r"(a), "r"(v.x), "r"(v.y), "r"(v.z), "r"(v.w) : "memory");
}

__device__ __forceinline__ uint64_t desc_ni(uint32_t addr, uint32_t lbo, uint32_t sbo) {
    return (uint64_t)((addr & 0x3FFFF) >> 4) | ((uint64_t)(lbo >> 4) << 16) | ((uint64_t)(sbo >> 4) << 32);
}
__device__ __forceinline__ uint64_t desc_a(uint32_t addr) { return desc_ni(addr, 128, 1024); }
template <int N> __device__ __forceinline__ uint64_t desc_b(uint32_t addr) { return desc_ni(addr, 16 * N, 128); }
__device__ __forceinline__ uint64_t desc_k(uint32_t addr) {
    return (uint64_t)((addr & 0x3FFFF) >> 4) | (1ull << 16) | (64ull << 32) | (1ull << 62);
}
__device__ __forceinline__ uint64_t desc_mn(uint32_t addr, uint32_t lbo) {
    return (uint64_t)((addr & 0x3FFFF) >> 4) | ((uint64_t)(lbo >> 4) << 16) | (64ull << 32) | (1ull << 62);
}

#define ACC8(d, o) "+f"(d[o + 0]), "+f"(d[o + 1]), "+f"(d[o + 2]), "+f"(d[o + 3]), "+f"(d[o + 4]), "+f"(d[o + 5]), "+f"(d[o + 6]), "+f"(d[o + 7])
template <int TB, int SA = 1>
__device__ __forceinline__ void wgmma_n128(float (&d)[64], uint64_t da, uint64_t db, int sd) {
    asm volatile(
        "{\n.reg .pred p;\nsetp.ne.b32 p, %66, 0;\n"
        "wgmma.mma_async.sync.aligned.m64n128k16.f32.bf16.bf16 "
        "{%0,%1,%2,%3,%4,%5,%6,%7,%8,%9,%10,%11,%12,%13,%14,%15,%16,%17,%18,%19,%20,%21,%22,%23,%24,%25,%26,%27,%28,%29,%30,%31,"
        "%32,%33,%34,%35,%36,%37,%38,%39,%40,%41,%42,%43,%44,%45,%46,%47,%48,%49,%50,%51,%52,%53,%54,%55,%56,%57,%58,%59,%60,%61,%62,%63},"
        " %64, %65, p, %68, 1, 0, %67;\n}"
        : ACC8(d, 0), ACC8(d, 8), ACC8(d, 16), ACC8(d, 24), ACC8(d, 32), ACC8(d, 40), ACC8(d, 48), ACC8(d, 56)
        : "l"(da), "l"(db), "r"(sd), "n"(TB), "n"(SA));
}
template <int N> __device__ __forceinline__ void acc_def(float (&d)[N]) {
#pragma unroll
    for (int i = 0; i < N; i++) d[i] = 0.f;
}
template <int TB>
__device__ __forceinline__ void wgmma_n64(float (&d)[32], uint64_t da, uint64_t db, int sd) {
    asm volatile(
        "{\n.reg .pred p;\nsetp.ne.b32 p, %34, 0;\n"
        "wgmma.mma_async.sync.aligned.m64n64k16.f32.bf16.bf16 "
        "{%0,%1,%2,%3,%4,%5,%6,%7,%8,%9,%10,%11,%12,%13,%14,%15,%16,%17,%18,%19,%20,%21,%22,%23,%24,%25,%26,%27,%28,%29,%30,%31},"
        " %32, %33, p, 1, 1, 0, %35;\n}"
        : ACC8(d, 0), ACC8(d, 8), ACC8(d, 16), ACC8(d, 24)
        : "l"(da), "l"(db), "r"(sd), "n"(TB));
}
template <int SA>
__device__ __forceinline__ void wgmma_n64s(float (&d)[32], uint64_t da, uint64_t db, int sd) {
    asm volatile(
        "{\n.reg .pred p;\nsetp.ne.b32 p, %34, 0;\n"
        "wgmma.mma_async.sync.aligned.m64n64k16.f32.bf16.bf16 "
        "{%0,%1,%2,%3,%4,%5,%6,%7,%8,%9,%10,%11,%12,%13,%14,%15,%16,%17,%18,%19,%20,%21,%22,%23,%24,%25,%26,%27,%28,%29,%30,%31},"
        " %32, %33, p, %35, 1, 0, 1;\n}"
        : ACC8(d, 0), ACC8(d, 8), ACC8(d, 16), ACC8(d, 24)
        : "l"(da), "l"(db), "r"(sd), "n"(SA));
}
__device__ __forceinline__ void wgmma_n64_rs(float (&d)[32], uint32_t a0, uint32_t a1, uint32_t a2, uint32_t a3, uint64_t db, int sd) {
    asm volatile(
        "{\n.reg .pred p;\nsetp.ne.b32 p, %37, 0;\n"
        "wgmma.mma_async.sync.aligned.m64n64k16.f32.bf16.bf16 "
        "{%0,%1,%2,%3,%4,%5,%6,%7,%8,%9,%10,%11,%12,%13,%14,%15,%16,%17,%18,%19,%20,%21,%22,%23,%24,%25,%26,%27,%28,%29,%30,%31},"
        " {%32,%33,%34,%35}, %36, p, 1, 1, 1;\n}"
        : ACC8(d, 0), ACC8(d, 8), ACC8(d, 16), ACC8(d, 24)
        : "r"(a0), "r"(a1), "r"(a2), "r"(a3), "l"(db), "r"(sd));
}

struct Params {
    const __nv_bfloat16* x0;
    const __nv_bfloat16* w_r;
    const __nv_bfloat16* w_i;
    const __nv_bfloat16* lam_re;
    const __nv_bfloat16* lam_im;
    const __nv_bfloat16* log_dt;
    const __nv_bfloat16* dskip;
    float* out;
    int stop;
};

__device__ __forceinline__ uint32_t fpar(int s, int k, int L) { return s < 6 ? (uint32_t)((L + k) & 1) : (uint32_t)(k == 2); }
__device__ __forceinline__ int cslot(int v) { return (0x54032176u >> (4 * v)) & 7; }
__device__ __forceinline__ float ldbf(const __nv_bfloat16* p) { return __bfloat162float(*p); }

__device__ __forceinline__ void dft_fp(int j, int& f, int& ph) {
    int cs = j >> 1;
    if (j == 1) { f = 256; ph = 0; }
    else { f = cs; ph = (j & 1) ? 128 : 0; }
}

__device__ __forceinline__ void gen_col_consts(uint32_t sb, int tid) {
#pragma unroll 1
    for (int task = tid; task < 640; task += 256) {
        int f, c8;
        uint32_t a_cc, d_pi, d_po;
        if (task < 512) {
            f = task & 63; c8 = task >> 6;
            a_cc = sb + SM_X + (f >> 5) * 16384 + ((f >> 3) & 3) * 2048 + c8 * 128 + (f & 7) * 16;
            d_pi = 8192; d_po = 1024;
        } else {
            int n2 = task & 31;
            f = 2 * n2; c8 = (task >> 5) & 3;
            a_cc = sb + SM_X + 32768 + (n2 >> 3) * 1024 + c8 * 128 + (n2 & 7) * 16;
            d_pi = 4096; d_po = 512;
        }
        float cd, sd, cs, sn;
        __sincosf((float)(f >= 32 ? f - 64 : f) * (6.283185307179586f / 64.f), &sd, &cd);
        int a = (8 * c8 * f) & 63;
        __sincosf((float)(a >= 32 ? a - 64 : a) * (6.283185307179586f / 64.f), &sn, &cs);
        float cv[8], sv[8];
#pragma unroll
        for (int e = 0; e < 8; e++) {
            cv[e] = cs; sv[e] = sn;
            float t = cs * cd - sn * sd;
            sn = sn * cd + cs * sd;
            cs = t;
        }
        uint4 oc = make_uint4(pack_bf16(cv[0], cv[1]), pack_bf16(cv[2], cv[3]), pack_bf16(cv[4], cv[5]), pack_bf16(cv[6], cv[7]));
        uint4 os = make_uint4(pack_bf16(sv[0], sv[1]), pack_bf16(sv[2], sv[3]), pack_bf16(sv[4], sv[5]), pack_bf16(sv[6], sv[7]));
        sts128(a_cc, oc);
        sts128(a_cc + d_pi, os);
        sts128(a_cc + d_po, make_uint4(os.x ^ 0x80008000u, os.y ^ 0x80008000u, os.z ^ 0x80008000u, os.w ^ 0x80008000u));
        sts128(a_cc + d_pi + d_po, oc);
    }
}

__global__ void __launch_bounds__(NTHREADS, 1)
fused_kernel(const __grid_constant__ CUtensorMap tm_x, const __grid_constant__ CUtensorMap tm_bre,
             const __grid_constant__ CUtensorMap tm_bim, const __grid_constant__ CUtensorMap tm_cre,
             const __grid_constant__ CUtensorMap tm_cim, const __grid_constant__ CUtensorMap tm_col, const Params p) {
    extern __shared__ __align__(1024) uint8_t sm[];
    const uint32_t sb = s2u(sm);
    const int tid = threadIdx.x, b = blockIdx.x;
    const int c = b >> 3, r = b & 7;
    const int par = r & 1, pi_ = r >> 1, own = 4 * par + pi_;
    const int wg = __shfl_sync(~0u, tid >> 7, 0), w = __shfl_sync(~0u, (tid >> 5) & 3, 0), lane = tid & 31, g = lane >> 2, q = lane & 3;
    auto BAR = [&](int i) { return sb + SM_BAR + 8 * i; };
    unsigned* s_tgt = (unsigned*)(sm + SM_TGT);

    if (tid < NBARS) {
        int cnt = 1;
        if (tid >= B_EMPTY0 && tid < B_EMPTY0 + 4) cnt = 16;
        if (tid >= B_XEMPTY && tid < B_XEMPTY + 2) cnt = 16;
        if (tid == B_RFREE) cnt = 12;
        if (tid == B_HDONE || tid == B_WST) cnt = 2;
        if ((tid >= B_AEMPTY && tid < B_AEMPTY + 8) || tid == B_BFREE) cnt = 8;
        if (tid == B_AFREE) cnt = 4;
        mbar_init(BAR(tid), cnt);
        asm volatile("fence.mbarrier_init.release.cluster;" ::: "memory");
    }
    asm volatile("barrier.cluster.arrive.release.aligned;" ::: "memory");

    if (wg == 3) {
        asm volatile("setmaxnreg.dec.sync.aligned.u32 56;");
        if (w == 0 && lane < 6) {
            const CUtensorMap* tm = lane == 0 ? &tm_x : lane == 1 ? &tm_bre : lane == 2 ? &tm_bim : lane == 3 ? &tm_cre : lane == 4 ? &tm_cim : &tm_col;
            asm volatile("prefetch.tensormap [%0];" ::"l"(tm) : "memory");
        }
        __syncwarp();
        asm volatile("barrier.cluster.wait.acquire.aligned;" ::: "memory");
        if (w > 0) {
            if (w == 1) {
                float lr[3], li[3], ld[3];
#pragma unroll
                for (int k = 0; k < 3; k++) {
                    int ps = k < 2 ? 64 * r + 32 * k + lane : 32 * c + lane;
                    lr[k] = ldbf(p.lam_re + ps); li[k] = ldbf(p.lam_im + ps); ld[k] = ldbf(p.log_dt + ps);
                }
                if (lane < 6) s_tgt[lane] = ((ld_acquire(&g_bar[lane]) >> 7) + 1u) << 7;
#pragma unroll 1
                for (int k = 0; k < 3; k++) {
                    float a = k == 0 ? lr[0] : (k == 1 ? lr[1] : lr[2]), bq = k == 0 ? li[0] : (k == 1 ? li[1] : li[2]);
                    float dt = __bfloat162float(__float2bfloat16(expf(k == 0 ? ld[0] : (k == 1 ? ld[1] : ld[2]))));
                    float mag = expf(a * dt), t = bq * dt * 0.15915494309189535f, sn, cs;
                    t -= rintf(t);
                    sincospif(2.f * t, &sn, &cs);
                    float er = mag * cs, ei = mag * sn;
                    if (k < 2) {
                        *(float2*)(sm + SM_LAM + (32 * k + lane) * 8) = make_float2(er, ei);
                    } else {
                        er -= 1.f;
                        float inv = 1.f / (a * a + bq * bq);
                        *(float2*)(sm + SM_TAB + lane * 8) = make_float2((er * a + ei * bq) * inv, (ei * a - er * bq) * inv);
                    }
                }
                __syncwarp();
                bar_arrive(15, 160);
                if (lane == 0) mbar_arrive(BAR(B_SETUP), 1);
            }
            if (w == 2 && lane < 2) {
                const char* src = (const char*)(lane ? p.w_i : p.w_r) + (size_t)b * 8224;
                asm volatile("cp.async.bulk.prefetch.L2.global [%0], 8224;" ::"l"(src) : "memory");
            }
#pragma unroll 1
            for (int i = tid - 448; i < 96 + 128 && w > 1; i += 64) {
                if (i < 96) g_P[(uint32_t)(b * 4 + i / 24) * 1024 + 640 + ((i % 24) >> 1) * 32 + 30 + (i & 1)] = make_uint4(0, 0, 0, 0);
                else g_Ebuf[b * 128 + i - 96] = make_float4(0.f, 0.f, 0.f, 0.f);
            }
            __syncwarp();
            if (w > 1) bar_sync(0, 192);
            if (tid == 448) TX(14);
            if (w > 1) {
                if (lane < 8) {
                    const int cl = 8 * (w - 2) + lane;
                    asm volatile("cp.async.bulk.global.shared::cta.bulk_group [%0], [%1], 1024;" ::"l"(g_Wfrag + (uint32_t)((16 * (b & 7) + cl) * 1024 + (b >> 3) * 64)),
                                 "r"(sb + SM_H + cl * 1024) : "memory");
                }
                asm volatile("cp.async.bulk.commit_group;" ::: "memory");
                asm volatile("cp.async.bulk.wait_group 0;" ::: "memory");
                fence_async();
                __syncwarp();
                if (lane == 0) mbar_arrive(BAR(B_WST), 1);
                if (tid == 448) TX(15);
            }
            __syncwarp();
            if (w == 3) bar_arrive(11, 192);
            if (w == 2) {
                bar_sync(11, 192);
                if (lane == 0) { TX(7); red_release(&g_bar[4], 1);  }
            }
            if (w == 3) {
#pragma unroll 1
                for (int it = 0; it < 8; it++) {
                    const int m = 4 * c + (it >> 1), d = 64 * r + m, ch = lane + 32 * (it & 1);
                    float v[8];
#pragma unroll
                    for (int e = 0; e < 8; e++) {
                        int j = 8 * ch + e, f, ph;
                        dft_fp(j, f, ph);
                        int a = (d * f + ph) & 511;
                        a = a >= 256 ? a - 512 : a;
                        float wj = j == 0 ? 0.f : (j == 1 ? 1.f / 512.f : 2.f / 512.f);
                        v[e] = wj * __cosf((float)a * (6.283185307179586f / 512.f));
                    }
                    uint32_t off = (uint32_t)(64 + r * 8 + (ch >> 3)) * 8192 + (m >> 3) * 1024 + (ch & 7) * 128 + (m & 7) * 16;
                    *(uint4*)(g_E + off) = make_uint4(pack_bf16(v[0], v[1]), pack_bf16(v[2], v[3]), pack_bf16(v[4], v[5]), pack_bf16(v[6], v[7]));
                }
                __syncwarp();
                if (lane == 0) { fence_async(); red_release(&g_bar[6], 1); }
                return;
            }
            if (w == 2) {
#pragma unroll 1
                for (int it = 0; it < 4; it++) {
                    const int hf = it & 1;
                    __syncwarp();
                    if (hf == 0) bar_sync(13, 288); else bar_sync(6, 288);
                    if (lane == 0) {
                        const uint32_t src = sb + SM_HH + par * 32768 + hf * 16384;
                        bulk_s2peer(mapa(src, par ^ 1), src, 16384, mapa(BAR(hf ? B_HPEER1 : B_HPEER), par ^ 1));
                    }
                }
                return;
            }
            bar_sync(2, 288);
            if (lane == 0) {
                TX(5);
                fence_async();
                red_release(&g_bar[0], 1);
                TX(6);
            }
            __syncwarp();

            bar_sync(12, 160);
            if (lane == 0) {
                asm volatile("cp.async.bulk.global.shared::cta.bulk_group [%0], [%1], 8192;" ::"l"(g_A1 + (uint32_t)(((c >> 1) * 8 + r) * 16384 + (c & 1) * 8192)),
                             "r"(sb + SM_B1ST) : "memory");
                asm volatile("cp.async.bulk.commit_group;" ::: "memory");
                asm volatile("cp.async.bulk.wait_group 0;" ::: "memory");
                mbar_arrive(BAR(B_B1DONE), 1);
                fence_async();
                red_release(&g_bar[7], 1);
            }
#pragma unroll 1
            for (int layer = 0; layer < 2; layer++) {
                __syncwarp();
                bar_sync(5, 416);
                if (lane == 0) {
                    TX(0 + 8 * layer);
                    tma_store_5d(&tm_col, 32 * (b & 1), 0, b >> 1, 0, layer, sb + SM_RAW);
                    asm volatile("cp.reduce.async.bulk.global.shared::cta.bulk_group.add.f32 [%0], [%1], 8192;" ::"l"(g_ssqc + (layer * 16 + (b & 15)) * 2048),
                                 "r"(sb + SM_SSQ) : "memory");
                    asm volatile("cp.async.bulk.commit_group;" ::: "memory");
                    asm volatile("cp.async.bulk.wait_group 0;" ::: "memory");
                    TX(1 + 8 * layer);
                    fence_async();
                    red_release(&g_bar[1 + 2 * layer], 1);
                    TX(2 + 8 * layer);
                }
            }
        } else if (tid == 384) {
#pragma unroll 1
            for (int kb = 0; kb < 8; kb++) {
                uint32_t fb = BAR(B_FULL0 + kb);
                mbar_expect(fb, 16384);
                tma_5d_mc(sb + SM_A + 65536 + kb * 16384 + par * 8192, &tm_x, kb * 64, 0, 0, 8 * par, c, fb);
            }
#pragma unroll 1
            for (int k2 = 0; k2 < 8; k2++) {
                asm volatile("cp.async.bulk.prefetch.tensor.2d.L2.global [%0, {%1,%2}];" ::"l"(par ? &tm_bim : &tm_bre), "r"(k2 * 64), "r"(32 * c) : "memory");
                if ((k2 & 1) == par)
                    asm volatile("cp.async.bulk.prefetch.tensor.2d.L2.global [%0, {%1,%2}];" ::"l"((c & 1) ? &tm_cim : &tm_cre), "r"(64 * (c >> 1)), "r"(k2 * 64) : "memory");
            }
            mbar_wait(BAR(B_SETUP), 0);
#pragma unroll 1
            for (int layer = 0; layer < 2; layer++) {
                if (layer == 1) {
                    mbar_wait(BAR(B_AEMPTY + 4), 0);
                    mbar_expect(BAR(B_WRDY), 16384);
                    bulk_g2s(sb + SM_H + 16384, g_Wfrag + (uint32_t)b * 1024, 16384, BAR(B_WRDY));
                }
                wait_count(&g_bar[2 * layer], s_tgt[2 * layer]);
                TX(4 + 8 * layer);
                fence_async();
                mbar_expect(BAR(B_COL), 16384 + 8192);
                tma_5d(sb + SM_RAW, &tm_col, 32 * (b & 1), 0, b >> 1, 0, layer, BAR(B_COL));
                bulk_g2s(sb + SM_SSQ, g_ssq + layer * 2048, 8192, BAR(B_COL));
                if (layer == 0) {
                    wait_count(&g_bar[4], s_tgt[4]);
                    fence_async();
                    TX(16);
                    mbar_wait(BAR(B_B1DONE), 0);
                    TX(17);
                    mbar_expect(BAR(B_WRDY), 16384);
                    bulk_g2s(sb + SM_H + 16384, g_Wfrag + (uint32_t)b * 1024, 16384, BAR(B_WRDY));
                    wait_count(&g_bar[7], s_tgt[4]);
                    fence_async();
                }
                if (layer == 0) mbar_wait(BAR(B_AFREE), 0);
                mbar_wait(BAR(B_COL), layer);
#pragma unroll 1
                for (int s = 0; s < 8; s++) {
                    if (layer == 1) mbar_wait(BAR(B_AEMPTY + s), fpar(s, 2, 0));
                    if (s >= 2) mbar_wait(BAR(B_AFULL + s - 2), fpar(s - 2, 0, layer));
                    mbar_expect(BAR(B_AFULL + s), 16384);
                    bulk_g2s(sb + SM_A + s * 16384, g_A1 + (uint32_t)(r * 8 + s) * 16384, 16384, BAR(B_AFULL + s));
                }
                if (layer == 1) wait_count(&g_bar[6], s_tgt[4]);
                wait_count(&g_bar[1 + 2 * layer], s_tgt[1 + 2 * layer]);
                TX(3 + 8 * layer);
                fence_async();
                const uint8_t* xsrc = g_X + (uint32_t)(layer * 16 + c) * 8 * 16384;
                const uint8_t* esrc = g_E + (uint32_t)(layer * 8 + own) * 8 * 8192;
                mbar_arrive(BAR(B_SSQ), 1);
                mbar_expect(BAR(B_HPEER), 16384);
                mbar_expect(BAR(B_HPEER1), 16384);
#pragma unroll 1
                for (int it = 0; it < 20; it++) {
                    if (it < 8) {
                        const int st = it < 6 ? it : it - 6;
                        if (it >= 6) mbar_wait_cluster(BAR(B_XEMPTY + st), layer);
                        mbar_expect(BAR(B_XFULL + st), 16384);
                        bulk_g2s_mc(sb + SM_X + st * 16384 + par * 8192, xsrc + (uint32_t)it * 16384 + par * 8192, 8192, BAR(B_XFULL + st));
                    }
                    if (it >= 6) {
                        const bool isc = it >= 12;
                        const int s = isc ? cslot(it - 12) : it - 6;
                        mbar_wait(BAR(B_AEMPTY + s), fpar(s, it < 14 ? 0 : 1, layer));
                        uint32_t fb = BAR(B_AFULL + s), dst = sb + SM_A + s * 16384;
                        mbar_expect(fb, 16384);
                        if (!isc) {
                            bulk_g2s(dst, s < 4 ? esrc + (uint32_t)s * 16384 : xsrc + (uint32_t)(s - 4) * 16384, 16384, fb);
                        } else {
                            const int tile = 4 * par + ((pi_ + 1 + ((it - 12) >> 1)) & 3), sl = r ^ (it & 1);
                            if (layer == 1) {
                                tma_2d(dst, &tm_cre, 64 * sl, 64 * tile, fb);
                                tma_2d(dst + 8192, &tm_cim, 64 * sl, 64 * tile, fb);
                            } else {
                                bulk_g2s(dst, g_A2 + (uint32_t)(sl * 8 + tile) * 16384, 16384, fb);
                            }
                        }
                    }
                }
            }
        }
        return;
    }

    asm volatile("setmaxnreg.inc.sync.aligned.u32 152;");
    if (tid >= 96 && tid < 112) g_ssq[2048 + 16 * b + tid - 96] = 0.f;
    if (tid >= 128 && tid < 256) ((float4*)g_ssqc)[b * 128 + tid - 128] = make_float4(0.f, 0.f, 0.f, 0.f);
    TS(0);
    if (wg == 0) TC(30);
    {
        const int f = 32 * r + lane;
        float cd, sd;
        __sincosf((float)f * (6.283185307179586f / 512.f), &sd, &cd);
        const uint32_t dst = sb + SM_A + (lane >> 2) * 1024 + (lane & 3) * 32;
#pragma unroll 1
        for (int ch = tid >> 5; ch < 64; ch += 12) {
            int a = (8 * ch * f) & 511;
            a = a >= 256 ? a - 512 : a;
            float cs, sn;
            __sincosf((float)a * (6.283185307179586f / 512.f), &sn, &cs);
            float cv[8], sv[8];
#pragma unroll
            for (int e = 0; e < 8; e++) {
                cv[e] = cs; sv[e] = -sn;
                float t = cs * cd - sn * sd;
                sn = sn * cd + cs * sd;
                cs = t;
            }
            uint4 o1 = make_uint4(pack_bf16(sv[0], sv[1]), pack_bf16(sv[2], sv[3]), pack_bf16(sv[4], sv[5]), pack_bf16(sv[6], sv[7]));
            if (f == 0) o1 = make_uint4(0xbf803f80u, 0xbf803f80u, 0xbf803f80u, 0xbf803f80u);
            uint32_t a0 = dst + (ch >> 3) * 8192 + (ch & 7) * 128;
            sts128(a0, make_uint4(pack_bf16(cv[0], cv[1]), pack_bf16(cv[2], cv[3]), pack_bf16(cv[4], cv[5]), pack_bf16(cv[6], cv[7])));
            sts128(a0 + 16, o1);
        }
    }
    fence_async_smem();
    asm volatile("barrier.cluster.wait.acquire.aligned;" ::: "memory");
    bar_sync(10, 384);
    TS(1);
    if (wg < 2) {
        float acc[32];
        acc_def(acc);
        const int npos = 16 * r + 8 * wg + 2 * w;
        float sh0 = 0.f, sh1 = 0.f, s0 = 0.f, s1 = 0.f, q0 = 0.f, q1 = 0.f;
#pragma unroll 1
        for (int kb = 0; kb < 8; kb++) {
            uint32_t slot = sb + SM_A + 65536 + kb * 16384;
            mbar_wait(BAR(B_FULL0 + kb), 0);
            wg_fence();
#pragma unroll
            for (int ks = 0; ks < 4; ks++)
                wgmma_n64<0>(acc, desc_a(sb + SM_A + kb * 8192 + ks * 256), desc_k(slot + wg * 8192 + ks * 32), 1);
            wg_commit();
            {
                uint32_t v0 = lds32(slot + npos * 128 + lane * 4), v1 = lds32(slot + npos * 128 + 128 + lane * 4);
                if (kb == 0) { sh0 = __shfl_sync(~0u, bf_lo(v0), 0); sh1 = __shfl_sync(~0u, bf_lo(v1), 0); }
                float a = bf_lo(v0) - sh0, bq = bf_hi(v0) - sh0, cq = bf_lo(v1) - sh1, d = bf_hi(v1) - sh1;
                s0 += a + bq; q0 += a * a + bq * bq; s1 += cq + d; q1 += cq * cq + d * d;
            }
            wg_wait<1>();
            if (kb > 0 && kb <= 4 && lane == 0) { mbar_arrive(BAR(B_EMPTY0 + kb - 1), 1); mbar_arrive_remote(mapa(BAR(B_EMPTY0 + kb - 1), par ^ 1)); }
        }
#pragma unroll
        for (int o = 16; o; o >>= 1) {
            s0 += __shfl_xor_sync(~0u, s0, o); q0 += __shfl_xor_sync(~0u, q0, o);
            s1 += __shfl_xor_sync(~0u, s1, o); q1 += __shfl_xor_sync(~0u, q1, o);
        }
        if (lane == 0) *(float2*)(g_ssq + 128 * c + npos) = make_float2(fmaxf(q0 - s0 * s0 * (1.f / 512.f), 0.f), fmaxf(q1 - s1 * s1 * (1.f / 512.f), 0.f));
        wg_wait<0>();
        TS(2);
        uint8_t* dst = g_X + (uint32_t)((c * 8 + r) * 16384 + w * 4096 + wg * 1024 + g * 16 + 4 * q);
#pragma unroll
        for (int i = 0; i < 8; i++) {
            *(uint32_t*)(dst + i * 128) = pack_bf16(acc[4 * i], acc[4 * i + 1]);
            *(uint32_t*)(dst + 2048 + i * 128) = pack_bf16(acc[4 * i + 2], acc[4 * i + 3]);
        }
        bar_sync(2, 288);
        mbar_wait(BAR(B_SETUP), 0);
        TS(3);
    }

    if (wg == 2) {
        {
            uint4 p0 = __ldg((const uint4*)p.dskip + 2 * lane), p1 = __ldg((const uint4*)p.dskip + 2 * lane + 1);
            uint32_t u[8] = {p0.x, p0.y, p0.z, p0.w, p1.x, p1.y, p1.z, p1.w};
            int j = 64 * r + 4 * c + w, f, ph;
            dft_fp(j, f, ph);
            float s = 0.f;
            int idx = 16 * lane * f + ph;
#pragma unroll
            for (int i = 0; i < 16; i++) {
                int a = idx & 511;
                idx += f;
                a = a >= 256 ? a - 512 : a;
                s += ((i & 1) ? bf_hi(u[i >> 1]) : bf_lo(u[i >> 1])) * __cosf((float)a * (6.283185307179586f / 512.f));
            }
#pragma unroll
            for (int o = 16; o; o >>= 1) s += __shfl_xor_sync(~0u, s, o);
            if (lane == 0) g_Dh[j] = s;
        }
        mbar_wait(BAR(B_FULL0 + 7), 0);
        if (tid == 256) {
#pragma unroll 1
            for (int s = 0; s < 4; s++) mbar_wait_cluster(BAR(B_EMPTY0 + s), 0);
            mbar_expect(BAR(B_FULLB), 65536);
#pragma unroll 1
            for (int k2 = 0; k2 < 8; k2++)
                tma_2d_mc(sb + SM_A + 65536 + k2 * 8192 + par * 4096, par ? &tm_bim : &tm_bre, k2 * 64, 32 * c, BAR(B_FULLB));
        }
        __syncwarp();
        {
            const int cl = tid & 15, cb = 16 * (b & 7) + cl;
            const int c0 = cb == 0 ? 256 : 2 * cb, c1 = 2 * cb + 1;
            uint32_t wf[2][16];
#pragma unroll
            for (int h = 0; h < 2; h++) {
                const int kq = 16 * (b >> 3) + ((tid & 127) >> 4) + 8 * h, k1 = kq >> 2, qq = kq & 3;
                const unsigned short* wr_ = (const unsigned short*)p.w_r + (k1 + 128 * qq) * 257;
                const unsigned short* wi_ = (const unsigned short*)p.w_i + (k1 + 128 * qq) * 257;
#pragma unroll
                for (int i = 0; i < 4; i++) {
                    int o = 512 * i * 257;
                    wf[h][2 * i] = (uint32_t)__ldg(wr_ + o + c0) | ((uint32_t)__ldg(wr_ + o + 64 * 257 + c0) << 16);
                    wf[h][2 * i + 1] = ((uint32_t)__ldg(wi_ + o + c0) | ((uint32_t)__ldg(wi_ + o + 64 * 257 + c0) << 16)) ^ 0x80008000u;
                    wf[h][8 + 2 * i] = (uint32_t)__ldg(wr_ + o + c1) | ((uint32_t)__ldg(wr_ + o + 64 * 257 + c1) << 16);
                    wf[h][8 + 2 * i + 1] = ((uint32_t)__ldg(wi_ + o + c1) | ((uint32_t)__ldg(wi_ + o + 64 * 257 + c1) << 16)) ^ 0x80008000u;
                }
            }
#pragma unroll
            for (int h = 0; h < 2; h++)
#pragma unroll
                for (int i = 0; i < 4; i++)
                    sts128(sb + SM_H + cl * 1024 + (((tid & 127) >> 4) + 8 * h) * 64 + ((i ^ ((tid >> 5) & 3)) << 4),
                           make_uint4(wf[h][4 * i], wf[h][4 * i + 1], wf[h][4 * i + 2], wf[h][4 * i + 3]));
            fence_async_smem();
            bar_arrive(0, 192);
            bar_arrive(11, 192);
        }
        bar_sync(15, 160);
        float acc[32];
        acc_def(acc);
        mbar_wait(BAR(B_FULLB), 0);
        wg_fence();
#pragma unroll 1
        for (int kb = 0; kb < 8; kb++) {
#pragma unroll
            for (int ks = 0; ks < 4; ks++)
                wgmma_n64<0>(acc, desc_a(sb + SM_A + kb * 8192 + ks * 256), desc_k(sb + SM_A + 65536 + kb * 8192 + ks * 32), 1);
            wg_commit();
        }
        wg_wait<0>();
        if (lane == 0) { mbar_arrive(BAR(B_BFREE), 1); mbar_arrive_remote(mapa(BAR(B_BFREE), par ^ 1)); }
        if (tid == 256) {
            mbar_wait_cluster(BAR(B_BFREE), 0);
            mbar_expect(BAR(B_FULLC), 65536);
#pragma unroll 1
            for (int k2 = par; k2 < 8; k2 += 2)
                tma_2d_mc(sb + SM_A + 65536 + k2 * 8192, (c & 1) ? &tm_cim : &tm_cre, 64 * (c >> 1), k2 * 64, BAR(B_FULLC));
        }
        __syncwarp();
        {
            uint8_t* dst = sm + SM_B1ST + w * 256 + q * 32 + g * 2;
            const float wj0 = (r == 0 && w == 0 && g < 2) ? (g == 0 ? 0.f : 1.f / 512.f) : 2.f / 512.f;
#pragma unroll
            for (int i = 0; i < 4; i++) {
#pragma unroll
                for (int e = 0; e < 2; e++) {
                    float2 cf = *(const float2*)(sm + SM_TAB + (8 * i + 2 * q + e) * 8);
#pragma unroll
                    for (int h = 0; h < 2; h++) {
                        float wj = h == 0 ? wj0 : 2.f / 512.f;
                        float pr = acc[4 * i + 2 * h + e] * wj, pi = acc[16 + 4 * i + 2 * h + e] * wj;
                        uint8_t* d2 = dst + i * 2048 + h * 128 + e * 16;
                        *(__nv_bfloat16*)(d2) = __float2bfloat16(cf.x * pr - cf.y * pi);
                        *(__nv_bfloat16*)(d2 + 1024) = __float2bfloat16(cf.x * pi + cf.y * pr);
                    }
                }
            }
            fence_async_smem();
            bar_arrive(12, 160);
        }
        acc_def(acc);
        mbar_wait(BAR(B_FULLC), 0);
        wg_fence();
#pragma unroll 1
        for (int kb = 0; kb < 8; kb++) {
#pragma unroll
            for (int ks = 0; ks < 4; ks++)
                wgmma_n64<1>(acc, desc_a(sb + SM_A + kb * 8192 + ks * 256), desc_mn(sb + SM_A + 65536 + kb * 8192 + ks * 2048, 8192), 1);
            wg_commit();
        }
        wg_wait<0>();
        fence_async_smem();
        if (lane == 0) mbar_arrive(BAR(B_AFREE), 1);
        uint8_t* dst = g_A2 + (uint32_t)(((c >> 1) * 8 + r) * 16384 + (c & 1) * 8192 + w * 2048 + g * 16 + 4 * q);
#pragma unroll
        for (int i = 0; i < 8; i++) {
            *(uint32_t*)(dst + i * 128) = pack_bf16(acc[4 * i], acc[4 * i + 1]);
            *(uint32_t*)(dst + 1024 + i * 128) = pack_bf16(acc[4 * i + 2], acc[4 * i + 3]);
        }
        {
            const int m = 4 * c + w, jp = 64 * r + m;
            int fp, php;
            dft_fp(jp, fp, php);
            const __nv_bfloat16* dh = (const __nv_bfloat16*)(sm + SM_RSTD);
            if (tid == 256) wait_count(&g_bar[4], s_tgt[4]);
            bar_sync(3, 128);
            float4 d4 = __ldcg((const float4*)g_Dh + (tid - 256));
            *(uint2*)(sm + SM_RSTD + (tid - 256) * 8) = make_uint2(pack_bf16(d4.x, d4.y), pack_bf16(d4.z, d4.w));
            bar_sync(3, 128);
#pragma unroll 1
            for (int it = 0; it < 2; it++) {
                const int ch = lane + 32 * it;
                float v[8];
#pragma unroll
                for (int e = 0; e < 8; e++) {
                    int j = 8 * ch + e, f, ph;
                    dft_fp(j, f, ph);
                    float wj = j == 0 ? 0.f : (j == 1 ? 1.f / 512.f : 2.f / 512.f);
                    float gsum = 0.f;
#pragma unroll
                    for (int sgn = 0; sgn < 2; sgn++) {
                        int mm = (sgn ? f - fp : f + fp) & 511, pp = (sgn ? ph - php : ph + php) & 511;
                        if (mm > 256) { mm = 512 - mm; pp = (512 - pp) & 511; }
                        int odd = (pp >> 7) & 1;
                        float t = __bfloat162float(dh[mm == 256 ? 1 : 2 * mm + odd]);
                        if (odd && (mm & 255) == 0) t = 0.f;
                        gsum += (pp & 256) ? -t : t;
                    }
                    v[e] = 0.5f * wj * gsum;
                }
                uint32_t off = (uint32_t)(r * 8 + (ch >> 3)) * 8192 + (m >> 3) * 1024 + (ch & 7) * 128 + (m & 7) * 16;
                *(uint4*)(g_E + off) = make_uint4(pack_bf16(v[0], v[1]), pack_bf16(v[2], v[3]), pack_bf16(v[4], v[5]), pack_bf16(v[6], v[7]));
            }
        }
    }

#pragma unroll 1
    for (int layer = 0; layer < 2; layer++) {
        if (wg < 2) {
            const int n1 = 32 * wg + 8 * w + g;
            const int ct = n1 >> 2;
            gen_col_consts(sb, tid);
            uint32_t tr2[4], ti2[4], tn2[4];
#pragma unroll
            for (int i = 0; i < 4; i++) {
                float cr[2], ci[2];
#pragma unroll
                for (int e = 0; e < 2; e++) {
                    int a = (n1 * (8 * i + 2 * q + e)) & 2047;
                    a = a >= 1024 ? a - 2048 : a;
                    float ang = (float)a * (-6.283185307179586f / 2048.f);
                    cr[e] = __cosf(ang); ci[e] = __sinf(ang);
                }
                tr2[i] = pack_bf16(cr[0], cr[1]); ti2[i] = pack_bf16(ci[0], ci[1]); tn2[i] = ti2[i] ^ 0x80008000u;
            }
            mbar_wait(BAR(B_WST), 0);
            mbar_wait(BAR(B_COL), layer);
            TS(4 + 12 * layer);
            if (wg == 0) TC(0 + 10 * layer);
            const uint32_t rw0 = sb + SM_RAW + ct * 1024 + q * 64 + ((q >> 1) << 4) + (g & 3) * 4, rw1 = rw0 ^ 16;
            const int pos0 = 128 * ct + 8 * q + 2 * (g & 3);
            const int sw = b == 0 ? 1 : 0;
            uint32_t xr[4][4];
            const uint32_t st0 = sb + SM_H + (n1 >> 3) * 1024 + g * 16 + 4 * q;
#pragma unroll
            for (int i = 0; i < 4; i++) {
                float2 sq = *(const float2*)(sm + SM_SSQ + (pos0 + 32 * i) * 4);
                const uint32_t rs2 = pack_bf16(rsqrtf(sq.x * (1.f / 512.f) + 1e-5f), rsqrtf(sq.y * (1.f / 512.f) + 1e-5f));
#pragma unroll
                for (int jj = 0; jj < 4; jj++) {
                    const int K = jj ^ (2 * (i & 1));
                    uint32_t a = ((K & 1) ? rw1 : rw0) + i * 256 + (K & 2) * 16;
                    if (jj < 2) a ^= sw << 4;
                    uint32_t v = lds32(a);
                    xr[jj][i] = v;
                    uint32_t o = hmul2(v, rs2);
                    if (jj == 1 && sw) o = 0u;
                    sts32(st0 + (jj & 1) * 8192 + (4 * (jj >> 1) + i) * 128, o);
                }
            }
            if (wg == 0) TC(1 + 10 * layer);
            fence_async_smem();
            bar_sync(1, 256);
            float acc[32];
            const uint32_t s1a = sb + SM_X + wg * 16384, s2b = sb + SM_X + 32768;
            wg_fence();
#pragma unroll
            for (int ks = 0; ks < 8; ks++)
                wgmma_n64<1>(acc, desc_a(s1a + (ks >> 2) * 8192 + (ks & 3) * 256), desc_b<64>(sb + SM_H + ks * 2048), ks != 0);
            wg_commit();
            wg_wait<0>();
            if (wg == 0) TC(2 + 10 * layer);
            uint32_t are[2][4], aim[2][4];
#pragma unroll
            for (int col = 0; col < 2; col++) {
#pragma unroll
                for (int i = 0; i < 4; i++) {
                    int o = 4 * (4 * col + i);
                    uint32_t zr = pack_bf16(acc[o], acc[o + 1]), zi = pack_bf16(acc[o + 2], acc[o + 3]);
                    are[col][i] = hfma2(zr, tr2[i], hmul2(zi, tn2[i]));
                    aim[col][i] = hfma2(zr, ti2[i], hmul2(zi, tr2[i]));
                }
            }
            wg_fence();
#pragma unroll
            for (int ks = 0; ks < 2; ks++)
                wgmma_n64_rs(acc, are[0][2 * ks], are[1][2 * ks], are[0][2 * ks + 1], are[1][2 * ks + 1], desc_b<64>(s2b + ks * 2048), ks != 0);
#pragma unroll
            for (int ks = 0; ks < 2; ks++)
                wgmma_n64_rs(acc, aim[0][2 * ks], aim[1][2 * ks], aim[0][2 * ks + 1], aim[1][2 * ks + 1], desc_b<64>(s2b + 4096 + ks * 2048), 1);
            wg_commit();
            uint32_t wf[16];
            mbar_wait(BAR(B_WRDY), layer);
#pragma unroll
            for (int i = 0; i < 4; i++) {
                const int kq = n1 * 4 + q;
                uint4 v = *(const uint4*)(sm + SM_H + 16384 + kq * 64 + ((i ^ ((kq >> 1) & 3)) << 4));
                wf[4 * i] = v.x; wf[4 * i + 1] = v.y; wf[4 * i + 2] = v.z; wf[4 * i + 3] = v.w;
            }
            wg_wait<0>();
            if (wg == 0) TC(3 + 10 * layer);
#pragma unroll
            for (int col = 0; col < 2; col++) {
#pragma unroll
                for (int i = 0; i < 4; i++) {
                    uint32_t wr = wf[col * 8 + 2 * i], wn = wf[col * 8 + 2 * i + 1];
                    uint32_t zr = pack_bf16(acc[4 * i + 2 * col], acc[4 * i + 2 * col + 1]);
                    uint32_t zi = pack_bf16(acc[16 + 4 * i + 2 * col], acc[16 + 4 * i + 2 * col + 1]);
                    are[col][i] = hfma2(zr, wr, hmul2(zi, wn));
                    aim[col][i] = hfma2(zr, wn, hmul2(zi ^ 0x80008000u, wr));
                }
            }
            wg_fence();
#pragma unroll
            for (int ks = 0; ks < 2; ks++)
                wgmma_n64_rs(acc, are[0][2 * ks], are[1][2 * ks], are[0][2 * ks + 1], are[1][2 * ks + 1], desc_b<64>(s2b + ks * 2048), ks != 0);
#pragma unroll
            for (int ks = 0; ks < 2; ks++)
                wgmma_n64_rs(acc, aim[0][2 * ks], aim[1][2 * ks], aim[0][2 * ks + 1], aim[1][2 * ks + 1], desc_b<64>(s2b + 4096 + ks * 2048), 1);
            wg_commit();
            wg_wait<0>();
            if (wg == 0) TC(4 + 10 * layer);
            bar_sync(1, 256);
#pragma unroll
            for (int col = 0; col < 2; col++) {
#pragma unroll
                for (int i = 0; i < 4; i++) {
                    uint32_t zr = pack_bf16(acc[4 * i + 2 * col], acc[4 * i + 2 * col + 1]);
                    uint32_t zi = pack_bf16(acc[16 + 4 * i + 2 * col], acc[16 + 4 * i + 2 * col + 1]);
                    sts32(st0 + 16384 + (4 * col + i) * 128, hfma2(zr, tr2[i], hmul2(zi, tn2[i])));
                    sts32(st0 + 16384 + 8192 + (4 * col + i) * 128, hfma2(zr, ti2[i], hmul2(zi, tr2[i])));
                }
            }
            if (wg == 0) TC(5 + 10 * layer);
            fence_async_smem();
            bar_sync(1, 256);
            wg_fence();
#pragma unroll
            for (int ks = 0; ks < 8; ks++)
                wgmma_n64<1>(acc, desc_a(s1a + (ks >> 2) * 8192 + (ks & 3) * 256), desc_b<64>(sb + SM_H + 16384 + ks * 2048), ks != 0);
            wg_commit();
            wg_wait<0>();
            if (wg == 0) TC(6 + 10 * layer);
            const float sc = 1.f / 2048.f;
            const float sci0 = sw ? 0.f : -sc;
            const float wr0 = sw ? 0.5f : 1.f, wi0 = sw ? 0.f : 1.f;
#pragma unroll
            for (int i = 0; i < 4; i++) {
                float ss0, ss1;
#pragma unroll
                for (int col = 0; col < 2; col++) {
                    int o = 4 * (4 * col + i);
                    uint32_t vr = xr[2 * col][i], vi = xr[2 * col + 1][i];
                    float si = col == 0 ? sci0 : -sc;
                    uint32_t nr = pack_bf16(fmaf(acc[o], sc, bf_lo(vr)), fmaf(acc[o + 1], sc, bf_hi(vr)));
                    uint32_t ni = pack_bf16(fmaf(acc[o + 2], si, bf_lo(vi)), fmaf(acc[o + 3], si, bf_hi(vi)));
                    float a0 = bf_lo(nr), a1 = bf_hi(nr), b0 = bf_lo(ni), b1 = bf_hi(ni);
                    if (col == 0) {
                        ss0 = wr0 * a0 * a0 + wi0 * b0 * b0;
                        ss1 = wr0 * a1 * a1 + wi0 * b1 * b1;
                    } else {
                        ss0 += a0 * a0 + b0 * b0;
                        ss1 += a1 * a1 + b1 * b1;
                    }
                    const int K = (2 * col) ^ (2 * (i & 1));
                    uint32_t a = rw0 + i * 256 + K * 16;
                    if (col == 0) a ^= sw << 4;
                    sts32(a, nr);
                    sts32(a ^ 16, ni);
                }
                *(float2*)(sm + SM_SSQ + (pos0 + 32 * i) * 4) = make_float2(ss0 * (2.f / 512.f), ss1 * (2.f / 512.f));
            }
            fence_async_smem();
        }
        TS(5 + 12 * layer);
        if (wg == 0) TC(7 + 10 * layer);
        bar_arrive(5, 416);

        float acc[64];
        float* s_rstd = (float*)(sm + SM_RSTD);
        float* s_mean = (float*)(sm + SM_MEAN);
        const unsigned epoch = s_tgt[0] >> 7;
        const uint32_t pt3 = 1u + (2u * epoch + layer) % 3u;
        const uint32_t ptag = (pt3 & 1u) | ((pt3 & 2u) << 15);
        const uint64_t dstep = layer == 0 ? 16 : 2;
        auto c_desc = [&](int s) { return layer == 0 ? desc_a(sb + SM_A + s * 16384) : desc_k(sb + SM_A + s * 16384); };
        if (wg < 2) {
            const int prow = 32 * wg + 8 * w + g;
            const float2 l1 = *(const float2*)(sm + SM_LAM + prow * 8);
            float lr32 = l1.x, li32 = l1.y;
#pragma unroll
            for (int i = 0; i < 5; i++) { float t = lr32 * lr32 - li32 * li32; li32 = 2.f * lr32 * li32; lr32 = t; }
            float lr128 = lr32, li128 = li32;
#pragma unroll
            for (int i = 0; i < 2; i++) { float t = lr128 * lr128 - li128 * li128; li128 = 2.f * lr128 * li128; lr128 = t; }
            const float lr1 = l1.x, li1 = l1.y;
            const float l2r = lr128 * lr128 - li128 * li128, l2i = 2.f * lr128 * li128;
            const float l4r = l2r * l2r - l2i * l2i, l4i = 2.f * l2r * l2i;
            float lxr = 1.f, lxi = 0.f;
            {
                const int rho = (c - 1 - q) & 3;
                if (rho & 1) { lxr = lr128; lxi = li128; }
                if (rho & 2) { float t = lxr * l2r - lxi * l2i; lxi = lxr * l2i + lxi * l2r; lxr = t; }
            }
            acc_def(acc);
#pragma unroll 1
            for (int kb = 0; kb < 8; kb++) {
                const int st = kb < 6 ? kb : kb - 6;
                mbar_wait(BAR(B_AFULL + kb), fpar(kb, 0, layer));
                mbar_wait(BAR(B_XFULL + st), st < 2 ? (uint32_t)(kb >= 6) : (uint32_t)layer);
                wg_fence();
#pragma unroll
                for (int ks = 0; ks < 4; ks++)
                    wgmma_n128<1>(acc, desc_a(sb + SM_A + kb * 16384 + wg * 8192 + ks * 256),
                                  desc_b<128>(sb + SM_X + st * 16384 + ks * 4096), 1);
                wg_commit();
                wg_wait<1>();
                if (kb > 0 && lane == 0) {
                    mbar_arrive(BAR(B_AEMPTY + kb - 1), 1);
                    if (kb <= 2) { mbar_arrive(BAR(B_XEMPTY + kb - 1), 1); mbar_arrive_remote(mapa(BAR(B_XEMPTY + kb - 1), par ^ 1)); }
                }
            }
            wg_wait<0>();
            if (lane == 0) {
                mbar_arrive(BAR(B_AEMPTY + 7), 1);
                mbar_arrive_remote(mapa(BAR(B_RFREE), par ^ 1));
            }
            bar_arrive(14, 384);
            TS(6 + 12 * layer);
            bar_sync(4, 384);
            TS(7 + 12 * layer);
            float er = 0.f, ei = 0.f;
#pragma unroll
            for (int i = 0; i < 16; i++) {
                float2 rs = *(const float2*)(s_rstd + 128 + 8 * i + 2 * q);
                acc[4 * i] *= rs.x; acc[4 * i + 1] *= rs.y; acc[4 * i + 2] *= rs.x; acc[4 * i + 3] *= rs.y;
                float nr = lr1 * er - li1 * ei + acc[4 * i], ni = lr1 * ei + li1 * er + acc[4 * i + 2];
                er = lr1 * nr - li1 * ni + acc[4 * i + 1];
                ei = lr1 * ni + li1 * nr + acc[4 * i + 3];
            }
            float cr = 0.f, ci = 0.f, tr = 0.f, ti = 0.f;
#pragma unroll
            for (int qq = 0; qq < 4; qq++) {
                float xr_ = __shfl_sync(~0u, er, (lane & ~3) | qq), xi_ = __shfl_sync(~0u, ei, (lane & ~3) | qq);
                if (qq == q) { cr = tr; ci = ti; }
                float nr = lr32 * tr - li32 * ti + xr_, ni = lr32 * ti + li32 * tr + xi_;
                tr = nr; ti = ni;
            }
            float4* eb = g_Ebuf + (uint32_t)(layer * 16 * 512 + 64 * r + prow);
            if (q == 0 && c < 15) st_relaxed_f4(eb + c * 512, make_float4(tr, ti, __uint_as_float(epoch), 0.f));
            TS(8 + 12 * layer);
            float acc2[32];
            acc_def(acc2);
            float pr[4], pi[4];
            {
                unsigned n = 0;
                bool ok;
#pragma unroll 1
                do {
                    ok = true;
#pragma unroll
                    for (int k = 0; k < 4; k++) {
                        float4 v = make_float4(0.f, 0.f, __uint_as_float(epoch), 0.f);
                        if (4 * k + q < c) v = ld_relaxed_f4(eb + (4 * k + q) * 512);
                        pr[k] = v.x; pi[k] = v.y;
                        ok = ok && __float_as_uint(v.z) == epoch;
                    }
                } while (!ok && ++n < SPIN_LIMIT);
            }
            __syncwarp();
            TS(9 + 12 * layer);
            float hr = 0.f, hi = 0.f;
#pragma unroll
            for (int k = 0; k < 4; k++) {
                if (4 * k + q < c) {
                    float nr = l4r * hr - l4i * hi + pr[k], ni = l4r * hi + l4i * hr + pi[k];
                    hr = nr; hi = ni;
                }
            }
            {
                float nr = lxr * hr - lxi * hi, ni = lxr * hi + lxi * hr;
                hr = nr + __shfl_xor_sync(~0u, nr, 1); hi = ni + __shfl_xor_sync(~0u, ni, 1);
                hr += __shfl_xor_sync(~0u, hr, 2); hi += __shfl_xor_sync(~0u, hi, 2);
            }
#pragma unroll
            for (int qq = 0; qq < 3; qq++) {
                if (qq < q) { float nr = lr32 * hr - li32 * hi, ni = lr32 * hi + li32 * hr; hr = nr; hi = ni; }
            }
            er = cr + hr; ei = ci + hi;
            bar_sync(7, 384);
            mbar_wait_cluster(BAR(B_RFREE), layer);
            const uint32_t ha = sb + SM_HH + par * 32768 + (prow >> 3) * 1024 + g * 16 + 4 * q;
#pragma unroll
            for (int i = 0; i < 16; i++) {
                float nr = lr1 * er - li1 * ei + acc[4 * i], ni = lr1 * ei + li1 * er + acc[4 * i + 2];
                er = lr1 * nr - li1 * ni + acc[4 * i + 1];
                ei = lr1 * ni + li1 * nr + acc[4 * i + 3];
                sts32(ha + (i >> 3) * 16384 + (i & 7) * 128, pack_bf16(nr, er));
                sts32(ha + (i >> 3) * 16384 + 8192 + (i & 7) * 128, pack_bf16(ni, ei));
                if (i == 7) { fence_async_smem(); bar_arrive(13, 288); }
            }
            fence_async_smem();
            TS(10 + 12 * layer);
            bar_arrive(10, 384);
            bar_sync(6, 288);
            TS(11 + 12 * layer);
            float (&a0)[32] = *reinterpret_cast<float (*)[32]>(&acc[0]);
            float (&a1)[32] = *reinterpret_cast<float (*)[32]>(&acc[32]);
            auto tile_mma = [&](float (&d)[32], int u) {
#pragma unroll 1
                for (int k = 0; k < 2; k++) {
                    const uint32_t hb = sb + SM_HH + (par ^ k) * 32768 + wg * 16384;
                    if (k == 1) mbar_wait(BAR(wg ? B_HPEER1 : B_HPEER), layer);
                    const int cs = cslot(2 * u + k);
                    mbar_wait(BAR(B_AFULL + cs), fpar(cs, 2, layer));
                    const uint64_t da = c_desc(cs);
                    wg_fence();
#pragma unroll
                    for (int ks = 0; ks < 4; ks++) wgmma_n64s<1>(d, da + ks * dstep, desc_b<64>(hb + ks * 2048), (ks | k) != 0);
#pragma unroll
                    for (int ks = 0; ks < 4; ks++) wgmma_n64s<-1>(d, da + 512 + ks * dstep, desc_b<64>(hb + 8192 + ks * 2048), 1);
                }
                wg_commit();
            };
            auto tile_ship = [&](float (&d)[32], int u) {
                uint4* dst = g_P + (uint32_t)(((c * 8 + 2 * ((pi_ + 1 + u) & 3) + par) * 4 + pi_) * 1024 + wg * 512 + (tid & 127));
#pragma unroll
                for (int i = 0; i < 4; i++)
                    dst[i * 128] = make_uint4((pack_bf16(d[8 * i], d[8 * i + 1]) & 0xfffefffeu) | ptag, pack_bf16(d[8 * i + 2], d[8 * i + 3]),
                                              pack_bf16(d[8 * i + 4], d[8 * i + 5]), pack_bf16(d[8 * i + 6], d[8 * i + 7]));
            };
            tile_mma(a0, 0);
            if ((tid & 127) == 0) mbar_arrive_remote(mapa(BAR(B_HDONE), par ^ 1));
            __syncwarp();
            tile_mma(a1, 1);
            wg_wait<1>();
            tile_ship(a0, 0);
            tile_mma(acc2, 2);
            bar_arrive(12, 384);
            wg_wait<1>();
            tile_ship(a1, 1);
            wg_wait<0>();
            tile_ship(acc2, 2);
            if (lane < 6) mbar_arrive(BAR(B_AEMPTY + ((lane + 6) & 7)), 1);
            TS(12 + 12 * layer);
        } else {
            const int t2 = tid - 256;
            const uint8_t* ximg = g_X + (uint32_t)layer * 16 * 8 * 16384;
            mbar_wait(BAR(B_SSQ), layer);
            TS(6 + 12 * layer);
            float sqv[16];
#pragma unroll
            for (int i = 0; i < 16; i++) sqv[i] = __ldcg(g_ssqc + (layer * 16 + i) * 2048 + 128 * c + t2);
            const unsigned short xm = __ldcg((const unsigned short*)(ximg + (uint32_t)(c * 8 * 16384 + (t2 >> 3) * 128 + (t2 & 7) * 2)));
            {
                float tot = 0.f;
#pragma unroll
                for (int i = 0; i < 16; i++) tot += sqv[i];
                float rs = rsqrtf(tot * (1.f / 512.f) + 1e-5f);
                s_rstd[t2] = rs;
                s_rstd[128 + t2] = 2.f * rs;
                s_mean[t2] = layer == 0 ? 0.f : __uint_as_float((uint32_t)xm << 16) * (1.f / 512.f);
                TS(7 + 12 * layer);
                bar_arrive(4, 384);
            }
            acc_def(acc);
            bar_sync(14, 384);
#pragma unroll 1
            for (int it = 0; it < 8; it++) {
                const int kb = (it + 2) & 7;
                mbar_wait(BAR(B_AFULL + (kb >> 1)), fpar(0, 1, layer));
                if (kb < 2) mbar_wait(BAR(B_AFULL + 4 + kb), fpar(0, 1, layer));
                const uint32_t xb = kb < 2 ? sb + SM_A + (4 + kb) * 16384 : sb + SM_X + (kb < 6 ? kb : kb - 6) * 16384;
                wg_fence();
#pragma unroll
                for (int ks = 0; ks < 4; ks++)
                    wgmma_n128<1>(acc, desc_a(sb + SM_A + kb * 8192 + ks * 256), desc_b<128>(xb + ks * 4096), 1);
                wg_commit();
                wg_wait<1>();
                if (it >= 2 && (it & 1) == 0 && lane == 0) mbar_arrive(BAR(B_AEMPTY + (it >> 1)), 2);
                if (it == 4) {
                    if (lane == 0) mbar_arrive_remote(mapa(BAR(B_RFREE), par ^ 1));
                    bar_arrive(7, 384);
                }
            }
            wg_wait<0>();
            if (lane < 3) mbar_arrive(BAR(B_AEMPTY + (lane == 0 ? 0 : lane + 3)), 2);
            bar_sync(3, 128);
            TS(9 + 12 * layer);
            const int m0 = 16 * w + g;
            const uint32_t xoff = (uint32_t)((c * 8 + own) * 16384 + w * 4096 + g * 16 + 4 * q);
            if (layer == 0) {
                const uint8_t* xs = g_X + xoff;
#pragma unroll
                for (int i = 0; i < 16; i++) {
                    float2 rs = *(const float2*)(s_rstd + 8 * i + 2 * q);
                    uint32_t x0v = __ldcg((const uint32_t*)(xs + i * 128)), x1v = __ldcg((const uint32_t*)(xs + 2048 + i * 128));
                    acc[4 * i] = acc[4 * i] * rs.x + bf_lo(x0v);
                    acc[4 * i + 1] = acc[4 * i + 1] * rs.y + bf_hi(x0v);
                    acc[4 * i + 2] = acc[4 * i + 2] * rs.x + bf_lo(x1v);
                    acc[4 * i + 3] = acc[4 * i + 3] * rs.y + bf_hi(x1v);
                }
            } else {
                float d0 = ldbf(p.dskip + 64 * own + m0), d1 = ldbf(p.dskip + 64 * own + m0 + 8);
#pragma unroll
                for (int i = 0; i < 16; i++) {
                    float2 rs = *(const float2*)(s_rstd + 8 * i + 2 * q);
                    float2 mn = *(const float2*)(s_mean + 8 * i + 2 * q);
                    acc[4 * i] = acc[4 * i] * (1.f + rs.x * d0) + mn.x;
                    acc[4 * i + 1] = acc[4 * i + 1] * (1.f + rs.y * d0) + mn.y;
                    acc[4 * i + 2] = acc[4 * i + 2] * (1.f + rs.x * d1) + mn.x;
                    acc[4 * i + 3] = acc[4 * i + 3] * (1.f + rs.y * d1) + mn.y;
                }
            }
            TS(10 + 12 * layer);
            bar_sync(10, 384);
            TS(11 + 12 * layer);
            {
                float (&a0)[32] = *reinterpret_cast<float (*)[32]>(&acc[0]);
                float (&a1)[32] = *reinterpret_cast<float (*)[32]>(&acc[32]);
#pragma unroll 1
                for (int k = 0; k < 2; k++) {
                    const uint32_t hb = sb + SM_HH + (par ^ k) * 32768;
                    if (k == 1) {
                        mbar_wait(BAR(B_HPEER), layer);
                        mbar_wait(BAR(B_HPEER1), layer);
                        bar_sync(12, 384);
                    }
                    mbar_wait(BAR(B_AFULL + 4 + k), fpar(4, 2, layer));
                    const uint64_t da = c_desc(4 + k);
                    wg_fence();
#pragma unroll
                    for (int ks = 0; ks < 4; ks++) {
                        wgmma_n64s<1>(a0, da + ks * dstep, desc_b<64>(hb + ks * 2048), 1);
                        wgmma_n64s<1>(a1, da + ks * dstep, desc_b<64>(hb + 16384 + ks * 2048), 1);
                    }
#pragma unroll
                    for (int ks = 0; ks < 4; ks++) {
                        wgmma_n64s<-1>(a0, da + 512 + ks * dstep, desc_b<64>(hb + 8192 + ks * 2048), 1);
                        wgmma_n64s<-1>(a1, da + 512 + ks * dstep, desc_b<64>(hb + 16384 + 8192 + ks * 2048), 1);
                    }
                    wg_commit();
                }
                wg_wait<0>();
            }
#pragma unroll
            for (int i = 0; i < 16; i++)
                *(float4*)(sm + SM_A + 4 * 16384 + i * 2048 + t2 * 16) = make_float4(acc[4 * i], acc[4 * i + 1], acc[4 * i + 2], acc[4 * i + 3]);
            TS(12 + 12 * layer);
        }
        {
            const int t = tid & 127;
            const int nch = wg == 2 ? 2 : 3;
            const uint4* pb = g_P + (uint32_t)((c * 8 + r) * 4 * 1024 + wg * 128 + t);
            uint4 v[3][3];
            unsigned n = 0;
#pragma unroll 1
            while (true) {
                if (lane == 31) {
#pragma unroll 1
                    while (true) {
                        uint32_t bad = 0;
#pragma unroll
                        for (int sx = 0; sx < 3; sx++) {
                            uint32_t t0;
                            asm volatile("ld.relaxed.gpu.global.u32 %0, [%1];" : "=r"(t0) : "l"(pb + ((pi_ + 1 + sx) & 3) * 1024 + (nch - 1) * 384) : "memory");
                            bad |= t0 ^ ptag;
                        }
                        if (!(bad & 0x00010001u) || ++n >= SPIN_LIMIT) break;
                    }
                }
                __syncwarp();
                uint32_t bad = 0;
#pragma unroll
                for (int k = 0; k < 3; k++)
#pragma unroll
                    for (int sx = 0; sx < 3; sx++) {
                        v[k][sx] = make_uint4(ptag, 0, 0, 0);
                        if (k < nch) v[k][sx] = ld_relaxed_u4(pb + ((pi_ + 1 + sx) & 3) * 1024 + k * 384);
                        bad |= v[k][sx].x ^ ptag;
                    }
                if (!__any_sync(~0u, bad & 0x00010001u) || ++n >= SPIN_LIMIT) break;
            }
            bar_sync(8, 384);
            TS(13 + 12 * layer);
            const int m0 = 16 * w + g;
            const float w0 = (own == 0 && m0 < 2) ? (m0 == 0 ? 0.f : 0.5f) : 1.f;
#pragma unroll
            for (int k = 0; k < 3; k++) {
                if (k < nch) {
                    const int i = wg + 3 * k;
                    float4 a = *(const float4*)(sm + SM_A + 4 * 16384 + (2 * i) * 2048 + t * 16);
                    float4 bq = *(const float4*)(sm + SM_A + 4 * 16384 + (2 * i + 1) * 2048 + t * 16);
#pragma unroll
                    for (int sx = 0; sx < 3; sx++) {
                        a.x += bf_lo(v[k][sx].x); a.y += bf_hi(v[k][sx].x); a.z += bf_lo(v[k][sx].y); a.w += bf_hi(v[k][sx].y);
                        bq.x += bf_lo(v[k][sx].z); bq.y += bf_hi(v[k][sx].z); bq.z += bf_lo(v[k][sx].w); bq.w += bf_hi(v[k][sx].w);
                    }
                    if (layer == 0) {
                        uint8_t* xd = g_X + (uint32_t)((16 * 8 + c * 8 + own) * 16384 + w * 4096 + g * 16 + 4 * q + i * 256);
                        uint32_t v0 = pack_bf16(a.x, a.y), v1 = pack_bf16(a.z, a.w), v2 = pack_bf16(bq.x, bq.y), v3 = pack_bf16(bq.z, bq.w);
                        *(uint32_t*)(xd) = v0; *(uint32_t*)(xd + 2048) = v1; *(uint32_t*)(xd + 128) = v2; *(uint32_t*)(xd + 2048 + 128) = v3;
                        float sq[4];
                        sq[0] = w0 * bf_lo(v0) * bf_lo(v0) + bf_lo(v1) * bf_lo(v1);
                        sq[1] = w0 * bf_hi(v0) * bf_hi(v0) + bf_hi(v1) * bf_hi(v1);
                        sq[2] = w0 * bf_lo(v2) * bf_lo(v2) + bf_lo(v3) * bf_lo(v3);
                        sq[3] = w0 * bf_hi(v2) * bf_hi(v2) + bf_hi(v3) * bf_hi(v3);
                        float u0 = (g & 1) ? sq[2] : sq[0], u1 = (g & 1) ? sq[3] : sq[1];
                        u0 += __shfl_xor_sync(~0u, (g & 1) ? sq[0] : sq[2], 4);
                        u1 += __shfl_xor_sync(~0u, (g & 1) ? sq[1] : sq[3], 4);
                        float z = (g & 2) ? u1 : u0;
                        z += __shfl_xor_sync(~0u, (g & 2) ? u0 : u1, 8);
                        z += __shfl_xor_sync(~0u, z, 16);
                        if (g < 4) atomicAdd(s_mean + 16 * i + 8 * (g & 1) + 2 * q + (g >> 1), z);
                    } else {
                        float* o = p.out + (uint32_t)((128 * c + 32 * q + 4 * i) * 512 + 64 * own + m0);
                        o[0] = a.x; o[512] = a.y; o[8] = a.z; o[512 + 8] = a.w;
                        o[1024] = bq.x; o[1536] = bq.y; o[1024 + 8] = bq.z; o[1536 + 8] = bq.w;
                    }
                }
            }
            if (wg < 2) mbar_wait_cluster(BAR(B_HDONE), layer);
            if (layer == 0) {
                fence_async_smem();
                bar_sync(9, 384);
                TS(14 + 12 * layer);
                if (wg == 2) {
                    atomicAdd(g_ssq + 2048 + 128 * c + t, s_mean[t] * (2.f / 512.f));
                    bar_sync(3, 128);
                    if (lane == 0) { mbar_arrive(BAR(B_AEMPTY + 4), 2); mbar_arrive(BAR(B_AEMPTY + 5), 2); }
                    if (t == 0) { fence_async(); red_release(&g_bar[2], 1); }
                }
            }
        }
        TS(15 + 12 * layer);
        if (wg == 0) TC(31);
    }
}

typedef CUresult (*EncFn)(CUtensorMap*, CUtensorMapDataType, cuuint32_t, void*, const cuuint64_t*, const cuuint64_t*,
                          const cuuint32_t*, const cuuint32_t*, CUtensorMapInterleave, CUtensorMapSwizzle,
                          CUtensorMapL2promotion, CUtensorMapFloatOOBfill);

void launch_impl(void* const* d_in, void* d_out, int stop) {
    static EncFn enc = nullptr;
    if (!enc) {
        void* fn = nullptr;
        cudaDriverEntryPointQueryResult qr;
        cudaGetDriverEntryPoint("cuTensorMapEncodeTiled", &fn, cudaEnableDefault, &qr);
        enc = (EncFn)fn;
        cudaFuncSetAttribute(fused_kernel, cudaFuncAttributeMaxDynamicSharedMemorySize, SM_TOTAL);
    }
    CUtensorMap tx, tbr, tbi, tcr, tci, tcol;
    {
        void* gx = nullptr;
        cudaGetSymbolAddress(&gx, g_X);
        cuuint64_t gd[5] = {64, 16, 64, 16, 2};
        cuuint64_t gs[4] = {128, 2048, 128 * 1024, 2048 * 1024};
        cuuint32_t bx[5] = {32, 16, 1, 16, 1};
        cuuint32_t es[5] = {1, 1, 1, 1, 1};
        enc(&tcol, CU_TENSOR_MAP_DATA_TYPE_BFLOAT16, 5, gx, gd, gs, bx, es, CU_TENSOR_MAP_INTERLEAVE_NONE,
            CU_TENSOR_MAP_SWIZZLE_64B, CU_TENSOR_MAP_L2_PROMOTION_NONE, CU_TENSOR_MAP_FLOAT_OOB_FILL_NONE);
    }
    {
        cuuint64_t gd[5] = {512, 2, 4, 16, 16};
        cuuint64_t gs[4] = {1024, 32 * 1024, 2 * 1024, 128 * 1024};
        cuuint32_t bx[5] = {64, 2, 4, 8, 1};
        cuuint32_t es[5] = {1, 1, 1, 1, 1};
        enc(&tx, CU_TENSOR_MAP_DATA_TYPE_BFLOAT16, 5, d_in[0], gd, gs, bx, es, CU_TENSOR_MAP_INTERLEAVE_NONE,
            CU_TENSOR_MAP_SWIZZLE_128B, CU_TENSOR_MAP_L2_PROMOTION_L2_128B, CU_TENSOR_MAP_FLOAT_OOB_FILL_NONE);
    }
    auto mk2 = [&](CUtensorMap* m, void* ptr, cuuint32_t rows) {
        cuuint64_t gd[2] = {512, 512};
        cuuint64_t gs[1] = {1024};
        cuuint32_t bx[2] = {64, rows};
        cuuint32_t es[2] = {1, 1};
        enc(m, CU_TENSOR_MAP_DATA_TYPE_BFLOAT16, 2, ptr, gd, gs, bx, es, CU_TENSOR_MAP_INTERLEAVE_NONE,
            CU_TENSOR_MAP_SWIZZLE_128B, CU_TENSOR_MAP_L2_PROMOTION_L2_128B, CU_TENSOR_MAP_FLOAT_OOB_FILL_NONE);
    };
    mk2(&tbr, d_in[6], 32);
    mk2(&tbi, d_in[7], 32);
    mk2(&tcr, d_in[8], 64);
    mk2(&tci, d_in[9], 64);
    Params p;
    p.x0 = (const __nv_bfloat16*)d_in[0];
    p.w_r = (const __nv_bfloat16*)d_in[1];
    p.w_i = (const __nv_bfloat16*)d_in[2];
    p.lam_re = (const __nv_bfloat16*)d_in[4];
    p.lam_im = (const __nv_bfloat16*)d_in[5];
    p.log_dt = (const __nv_bfloat16*)d_in[10];
    p.dskip = (const __nv_bfloat16*)d_in[11];
    p.out = (float*)d_out;
    p.stop = stop;
    cudaLaunchConfig_t cfg = {};
    cfg.gridDim = dim3(NCTA); cfg.blockDim = dim3(NTHREADS); cfg.dynamicSmemBytes = SM_TOTAL; cfg.stream = cudaStreamPerThread;
    cudaLaunchAttribute at[1];
    at[0].id = cudaLaunchAttributeClusterDimension;
    at[0].val.clusterDim.x = 2; at[0].val.clusterDim.y = 1; at[0].val.clusterDim.z = 1;
    cfg.attrs = at; cfg.numAttrs = 1;
    cudaLaunchKernelEx(&cfg, fused_kernel, tx, tbr, tbi, tcr, tci, tcol, p);
}

}

extern "C" void kernel_launch(void* const* d_in, const int* in_sizes, int n_in, void* d_out, int out_size) {
    (void)in_sizes; (void)n_in; (void)out_size;
    launch_impl(d_in, d_out, 100);
}
```

```cpp
#include <cuda_runtime.h>
#include <cuda_bf16.h>
#include <cuda.h>
#include <stdint.h>

namespace {

constexpr int NCTA = 128;
constexpr int NTHREADS = 512;
constexpr int SM_A = 0;
constexpr int SM_X = 131072;
constexpr int SM_H = 196608;
constexpr int SM_HH = SM_X + 32768;
constexpr int SM_M = 229376;
constexpr int SM_TOTAL = 232448;
constexpr int SM_BAR = SM_M;
constexpr int SM_TGT = SM_M + 400;
constexpr int SM_LAM = SM_M + 424;
constexpr int SM_TAB = SM_M + 944;
constexpr int SM_RSTD = SM_M + 1920;
constexpr int SM_MEAN = SM_TAB;
constexpr int SM_T64 = SM_M + 2944;
constexpr int SM_B1ST = SM_H + 24576;
constexpr int SM_RAW = SM_X + 40960;
constexpr int SM_SSQ = SM_X + 57344;
constexpr int B_FULL0 = 0;
constexpr int B_EMPTY0 = 8;
constexpr int B_FULLC = 12;
constexpr int B_AFULL = 13;
constexpr int B_AEMPTY = 21;
constexpr int B_XFULL = 29;
constexpr int B_XEMPTY = 35;
constexpr int B_AFREE = 37;
constexpr int B_COL = 38;
constexpr int B_SSQ = 39;
constexpr int B_HPEER = 40;
constexpr int B_RFREE = 41;
constexpr int B_HDONE = 42;
constexpr int B_WRDY = 43;
constexpr int B_HPEER1 = 44;
constexpr int B_FULLB = 45;
constexpr int B_BFREE = 46;
constexpr int B_SETUP = 47;
constexpr int B_B1DONE = 48;
constexpr int B_WST = 49;
constexpr int NBARS = 50;

__device__ __align__(1024) uint8_t g_X[2 * 16 * 8 * 16384];
__device__ __align__(1024) uint8_t g_A1[8 * 8 * 16384];
__device__ __align__(1024) uint8_t g_A2[8 * 8 * 16384];
__device__ __align__(1024) uint8_t g_E[2 * 8 * 8 * 8192];
__device__ __align__(16) float g_ssq[2 * 2048];
__device__ __align__(16) float g_ssqc[2 * 16 * 2048];
__device__ __align__(16) float g_Dh[512];
__device__ __align__(16) uint4 g_Wfrag[128 * 4 * 256];
__device__ __align__(16) float4 g_Ebuf[2 * 16 * 512];
__device__ __align__(16) uint4 g_P[16 * 8 * 4 * 1024];
__device__ unsigned g_bar[8];
__device__ unsigned g_err;
#define TX(i)
#define TQ(i)
#define TS(i)
#define TC(i)

constexpr unsigned SPIN_LIMIT = 1u << 22;

__device__ __forceinline__ uint32_t s2u(const void* p) { return (uint32_t)__cvta_generic_to_shared(p); }
__device__ __forceinline__ void mbar_init(uint32_t a, uint32_t c) {
    asm volatile("mbarrier.init.shared::cta.b64 [%0], %1;" ::"r"(a), "r"(c) : "memory");
}
__device__ __forceinline__ void mbar_expect(uint32_t a, uint32_t bytes) {
    asm volatile("mbarrier.arrive.expect_tx.shared::cta.b64 _, [%0], %1;" ::"r"(a), "r"(bytes) : "memory");
}
__device__ __forceinline__ void mbar_arrive(uint32_t a, uint32_t cnt) {
    asm volatile("mbarrier.arrive.shared::cta.b64 _, [%0], %1;" ::"r"(a), "r"(cnt) : "memory");
}
__device__ __forceinline__ bool mbar_try(uint32_t a, uint32_t parity) {
    uint32_t ok;
    asm volatile("{\n.reg .pred p;\nmbarrier.try_wait.parity.shared::cta.b64 p, [%1], %2;\nselp.u32 %0, 1, 0, p;\n}"
                 : "=r"(ok) : "r"(a), "r"(parity) : "memory");
    return ok != 0;
}
__device__ __forceinline__ void mbar_wait(uint32_t a, uint32_t parity) {
    asm volatile("{\n.reg .pred p, q;\n.reg .u32 n;\nmov.u32 n, 0;\n"
                 "W_%=:\nmbarrier.try_wait.parity.shared::cta.b64 p, [%0], %1;\n@p bra D_%=;\n"
                 "add.u32 n, n, 1;\nsetp.lt.u32 q, n, 4194304;\n@q bra W_%=;\nD_%=:\n}" ::"r"(a), "r"(parity) : "memory");
}
__device__ __forceinline__ void bulk_g2s(uint32_t dst, const void* src, uint32_t bytes, uint32_t bar) {
    asm volatile("cp.async.bulk.shared::cluster.global.mbarrier::complete_tx::bytes [%0], [%1], %2, [%3];" ::"r"(dst),
                 "l"(src), "r"(bytes), "r"(bar) : "memory");
}
__device__ __forceinline__ void tma_2d(uint32_t dst, const CUtensorMap* m, int c0, int c1, uint32_t bar) {
    asm volatile("cp.async.bulk.tensor.2d.shared::cluster.global.mbarrier::complete_tx::bytes [%0], [%1, {%3,%4}], [%2];" ::"r"(dst),
                 "l"(m), "r"(bar), "r"(c0), "r"(c1) : "memory");
}
__device__ __forceinline__ void tma_5d(uint32_t dst, const CUtensorMap* m, int c0, int c1, int c2, int c3, int c4, uint32_t bar) {
    asm volatile("cp.async.bulk.tensor.5d.shared::cluster.global.mbarrier::complete_tx::bytes [%0], [%1, {%3,%4,%5,%6,%7}], [%2];" ::"r"(dst),
                 "l"(m), "r"(bar), "r"(c0), "r"(c1), "r"(c2), "r"(c3), "r"(c4) : "memory");
}
__device__ __forceinline__ void tma_2d_mc(uint32_t dst, const CUtensorMap* m, int c0, int c1, uint32_t bar) {
    asm volatile("cp.async.bulk.tensor.2d.shared::cluster.global.mbarrier::complete_tx::bytes.multicast::cluster [%0], [%1, {%3,%4}], [%2], %5;" ::"r"(dst),
                 "l"(m), "r"(bar), "r"(c0), "r"(c1), "h"((unsigned short)3) : "memory");
}
__device__ __forceinline__ void tma_5d_mc(uint32_t dst, const CUtensorMap* m, int c0, int c1, int c2, int c3, int c4, uint32_t bar) {
    asm volatile("cp.async.bulk.tensor.5d.shared::cluster.global.mbarrier::complete_tx::bytes.multicast::cluster [%0], [%1, {%3,%4,%5,%6,%7}], [%2], %8;" ::"r"(dst),
                 "l"(m), "r"(bar), "r"(c0), "r"(c1), "r"(c2), "r"(c3), "r"(c4), "h"((unsigned short)3) : "memory");
}
__device__ __forceinline__ void bulk_g2s_mc(uint32_t dst, const void* src, uint32_t bytes, uint32_t bar) {
    asm volatile("cp.async.bulk.shared::cluster.global.mbarrier::complete_tx::bytes.multicast::cluster [%0], [%1], %2, [%3], %4;" ::"r"(dst),
                 "l"(src), "r"(bytes), "r"(bar), "h"((unsigned short)3) : "memory");
}
__device__ __forceinline__ void tma_store_5d(const CUtensorMap* m, int c0, int c1, int c2, int c3, int c4, uint32_t src) {
    asm volatile("cp.async.bulk.tensor.5d.global.shared::cta.bulk_group [%0, {%2,%3,%4,%5,%6}], [%1];" ::"l"(m), "r"(src),
                 "r"(c0), "r"(c1), "r"(c2), "r"(c3), "r"(c4) : "memory");
}
__device__ __forceinline__ uint32_t lds32(uint32_t a) { uint32_t v; asm volatile("ld.shared.u32 %0, [%1];" : "=r"(v) : "r"(a) : "memory"); return v; }
__device__ __forceinline__ uint4 ld_relaxed_u4(const uint4* p) {
    uint4 v;
    asm volatile("ld.relaxed.gpu.global.v4.u32 {%0,%1,%2,%3}, [%4];" : "=r"(v.x), "=r"(v.y), "=r"(v.z), "=r"(v.w) : "l"(p) : "memory");
    return v;
}
__device__ __forceinline__ void fence_async() { asm volatile("fence.proxy.async.global;" ::: "memory"); }
__device__ __forceinline__ void red_relaxed(unsigned* p, unsigned v) {
    asm volatile("red.relaxed.gpu.global.add.u32 [%0], %1;" ::"l"(p), "r"(v) : "memory");
}
__device__ __forceinline__ uint32_t mapa(uint32_t a, uint32_t rank) {
    uint32_t d;
    asm("mapa.shared::cluster.u32 %0, %1, %2;" : "=r"(d) : "r"(a), "r"(rank));
    return d;
}
__device__ __forceinline__ void mbar_arrive_remote(uint32_t ra) {
    asm volatile("mbarrier.arrive.relaxed.cluster.shared::cluster.b64 _, [%0];" ::"r"(ra) : "memory");
}
__device__ __forceinline__ void mbar_wait_cluster(uint32_t a, uint32_t parity) {
    asm volatile("{\n.reg .pred p, q;\n.reg .u32 n;\nmov.u32 n, 0;\n"
                 "W_%=:\nmbarrier.try_wait.parity.acquire.cluster.shared::cta.b64 p, [%0], %1;\n@p bra D_%=;\n"
                 "add.u32 n, n, 1;\nsetp.lt.u32 q, n, 4194304;\n@q bra W_%=;\nD_%=:\n}" ::"r"(a), "r"(parity) : "memory");
}
__device__ __forceinline__ void bulk_s2peer(uint32_t rdst, uint32_t src, uint32_t bytes, uint32_t rbar) {
    asm volatile("cp.async.bulk.shared::cluster.shared::cta.mbarrier::complete_tx::bytes [%0], [%1], %2, [%3];" ::"r"(rdst),
                 "r"(src), "r"(bytes), "r"(rbar) : "memory");
}
__device__ __forceinline__ void fence_async_smem() { asm volatile("fence.proxy.async.shared::cta;" ::: "memory"); }
__device__ __forceinline__ void wg_fence() { asm volatile("wgmma.fence.sync.aligned;" ::: "memory"); }
__device__ __forceinline__ void wg_commit() { asm volatile("wgmma.commit_group.sync.aligned;" ::: "memory"); }
template <int N> __device__ __forceinline__ void wg_wait() { asm volatile("wgmma.wait_group.sync.aligned %0;" ::"n"(N) : "memory"); }
__device__ __forceinline__ void bar_sync(int id, int n) { asm volatile("bar.sync %0, %1;" ::"r"(id), "r"(n) : "memory"); }
__device__ __forceinline__ void bar_arrive(int id, int n) { asm volatile("bar.arrive %0, %1;" ::"r"(id), "r"(n) : "memory"); }
__device__ __forceinline__ unsigned ld_acquire(const unsigned* p) {
    unsigned v;
    asm volatile("ld.acquire.gpu.global.u32 %0, [%1];" : "=r"(v) : "l"(p) : "memory");
    return v;
}
__device__ __forceinline__ void red_release(unsigned* p, unsigned v) {
    asm volatile("red.release.gpu.global.add.u32 [%0], %1;" ::"l"(p), "r"(v) : "memory");
}
__device__ __forceinline__ void wait_count(const unsigned* p, unsigned target) {
    unsigned n = 0;
#pragma unroll 1
    while ((int)(ld_acquire(p) - target) < 0 && ++n < SPIN_LIMIT) {}
}
__device__ __forceinline__ float4 ld_relaxed_f4(const float4* p) {
    float4 v;
    asm volatile("ld.relaxed.gpu.global.v4.f32 {%0,%1,%2,%3}, [%4];" : "=f"(v.x), "=f"(v.y), "=f"(v.z), "=f"(v.w) : "l"(p) : "memory");
    return v;
}
__device__ __forceinline__ void st_relaxed_f4(float4* p, float4 v) {
    asm volatile("st.relaxed.gpu.global.v4.f32 [%0], {%1,%2,%3,%4};" ::"l"(p), "f"(v.x), "f"(v.y), "f"(v.z), "f"(v.w) : "memory");
}
__device__ __forceinline__ uint32_t pack_bf16(float lo, float hi) {
    uint32_t r;
    asm("cvt.rn.bf16x2.f32 %0, %1, %2;" : "=r"(r) : "f"(hi), "f"(lo));
    return r;
}
__device__ __forceinline__ uint32_t hmul2(uint32_t a, uint32_t b) {
    uint32_t r;
    asm("mul.rn.bf16x2 %0, %1, %2;" : "=r"(r) : "r"(a), "r"(b));
    return r;
}
__device__ __forceinline__ uint32_t hfma2(uint32_t a, uint32_t b, uint32_t c) {
    uint32_t r;
    asm("fma.rn.bf16x2 %0, %1, %2, %3;" : "=r"(r) : "r"(a), "r"(b), "r"(c));
    return r;
}
__device__ __forceinline__ float bf_lo(uint32_t v) { return __uint_as_float(v << 16); }
__device__ __forceinline__ float bf_hi(uint32_t v) { return __uint_as_float(v & 0xffff0000u); }
__device__ __forceinline__ void sts32(uint32_t a, uint32_t v) { asm volatile("st.shared.u32 [%0], %1;" ::"r"(a), "r"(v) : "memory"); }
__device__ __forceinline__ void sts128(uint32_t a, uint4 v) {
    asm volatile("st.shared.v4.u32 [%0], {%1,%2,%3,%4};" ::"r"(a), "r"(v.x), "r"(v.y), "r"(v.z), "r"(v.w) : "memory");
}

__device__ __forceinline__ uint64_t desc_ni(uint32_t addr, uint32_t lbo, uint32_t sbo) {
    return (uint64_t)((addr & 0x3FFFF) >> 4) | ((uint64_t)(lbo >> 4) << 16) | ((uint64_t)(sbo >> 4) << 32);
}
__device__ __forceinline__ uint64_t desc_a(uint32_t addr) { return desc_ni(addr, 128, 1024); }
template <int N> __device__ __forceinline__ uint64_t desc_b(uint32_t addr) { return desc_ni(addr, 16 * N, 128); }
__device__ __forceinline__ uint64_t desc_k(uint32_t addr) {
    return (uint64_t)((addr & 0x3FFFF) >> 4) | (1ull << 16) | (64ull << 32) | (1ull << 62);
}
__device__ __forceinline__ uint64_t desc_mn(uint32_t addr, uint32_t lbo) {
    return (uint64_t)((addr & 0x3FFFF) >> 4) | ((uint64_t)(lbo >> 4) << 16) | (64ull << 32) | (1ull << 62);
}

#define ACC8(d, o) "+f"(d[o + 0]), "+f"(d[o + 1]), "+f"(d[o + 2]), "+f"(d[o + 3]), "+f"(d[o + 4]), "+f"(d[o + 5]), "+f"(d[o + 6]), "+f"(d[o + 7])
template <int TB, int SA = 1>
__device__ __forceinline__ void wgmma_n128(float (&d)[64], uint64_t da, uint64_t db, int sd) {
    asm volatile(
        "{\n.reg .pred p;\nsetp.ne.b32 p, %66, 0;\n"
        "wgmma.mma_async.sync.aligned.m64n128k16.f32.bf16.bf16 "
        "{%0,%1,%2,%3,%4,%5,%6,%7,%8,%9,%10,%11,%12,%13,%14,%15,%16,%17,%18,%19,%20,%21,%22,%23,%24,%25,%26,%27,%28,%29,%30,%31,"
        "%32,%33,%34,%35,%36,%37,%38,%39,%40,%41,%42,%43,%44,%45,%46,%47,%48,%49,%50,%51,%52,%53,%54,%55,%56,%57,%58,%59,%60,%61,%62,%63},"
        " %64, %65, p, %68, 1, 0, %67;\n}"
        : ACC8(d, 0), ACC8(d, 8), ACC8(d, 16), ACC8(d, 24), ACC8(d, 32), ACC8(d, 40), ACC8(d, 48), ACC8(d, 56)
        : "l"(da), "l"(db), "r"(sd), "n"(TB), "n"(SA));
}
template <int N> __device__ __forceinline__ void acc_def(float (&d)[N]) {
#pragma unroll
    for (int i = 0; i < N; i++) d[i] = 0.f;
}
template <int TB>
__device__ __forceinline__ void wgmma_n64(float (&d)[32], uint64_t da, uint64_t db, int sd) {
    asm volatile(
        "{\n.reg .pred p;\nsetp.ne.b32 p, %34, 0;\n"
        "wgmma.mma_async.sync.aligned.m64n64k16.f32.bf16.bf16 "
        "{%0,%1,%2,%3,%4,%5,%6,%7,%8,%9,%10,%11,%12,%13,%14,%15,%16,%17,%18,%19,%20,%21,%22,%23,%24,%25,%26,%27,%28,%29,%30,%31},"
        " %32, %33, p, 1, 1, 0, %35;\n}"
        : ACC8(d, 0), ACC8(d, 8), ACC8(d, 16), ACC8(d, 24)
        : "l"(da), "l"(db), "r"(sd), "n"(TB));
}
template <int SA>
__device__ __forceinline__ void wgmma_n64s(float (&d)[32], uint64_t da, uint64_t db, int sd) {
    asm volatile(
        "{\n.reg .pred p;\nsetp.ne.b32 p, %34, 0;\n"
        "wgmma.mma_async.sync.aligned.m64n64k16.f32.bf16.bf16 "
        "{%0,%1,%2,%3,%4,%5,%6,%7,%8,%9,%10,%11,%12,%13,%14,%15,%16,%17,%18,%19,%20,%21,%22,%23,%24,%25,%26,%27,%28,%29,%30,%31},"
        " %32, %33, p, %35, 1, 0, 1;\n}"
        : ACC8(d, 0), ACC8(d, 8), ACC8(d, 16), ACC8(d, 24)
        : "l"(da), "l"(db), "r"(sd), "n"(SA));
}
__device__ __forceinline__ void wgmma_n64_rs(float (&d)[32], uint32_t a0, uint32_t a1, uint32_t a2, uint32_t a3, uint64_t db, int sd) {
    asm volatile(
        "{\n.reg .pred p;\nsetp.ne.b32 p, %37, 0;\n"
        "wgmma.mma_async.sync.aligned.m64n64k16.f32.bf16.bf16 "
        "{%0,%1,%2,%3,%4,%5,%6,%7,%8,%9,%10,%11,%12,%13,%14,%15,%16,%17,%18,%19,%20,%21,%22,%23,%24,%25,%26,%27,%28,%29,%30,%31},"
        " {%32,%33,%34,%35}, %36, p, 1, 1, 1;\n}"
        : ACC8(d, 0), ACC8(d, 8), ACC8(d, 16), ACC8(d, 24)
        : "r"(a0), "r"(a1), "r"(a2), "r"(a3), "l"(db), "r"(sd));
}

struct Params {
    const __nv_bfloat16* x0;
    const __nv_bfloat16* w_r;
    const __nv_bfloat16* w_i;
    const __nv_bfloat16* lam_re;
    const __nv_bfloat16* lam_im;
    const __nv_bfloat16* log_dt;
    const __nv_bfloat16* dskip;
    float* out;
    int stop;
};

__device__ __forceinline__ uint32_t fpar(int s, int k, int L) { return s < 6 ? (uint32_t)((L + k) & 1) : (uint32_t)(k == 2); }
__device__ __forceinline__ int cslot(int v) { return (0x54032176u >> (4 * v)) & 7; }
__device__ __forceinline__ float ldbf(const __nv_bfloat16* p) { return __bfloat162float(*p); }

__device__ __forceinline__ void dft_fp(int j, int& f, int& ph) {
    int cs = j >> 1;
    if (j == 1) { f = 256; ph = 0; }
    else { f = cs; ph = (j & 1) ? 128 : 0; }
}

__device__ __forceinline__ void gen_col_consts(uint32_t sb, int tid) {
#pragma unroll 1
    for (int task = tid; task < 640; task += 256) {
        int f, c8;
        uint32_t a_cc, d_pi, d_po;
        if (task < 512) {
            f = task & 63; c8 = task >> 6;
            a_cc = sb + SM_X + (f >> 5) * 16384 + ((f >> 3) & 3) * 2048 + c8 * 128 + (f & 7) * 16;
            d_pi = 8192; d_po = 1024;
        } else {
            int n2 = task & 31;
            f = 2 * n2; c8 = (task >> 5) & 3;
            a_cc = sb + SM_X + 32768 + (n2 >> 3) * 1024 + c8 * 128 + (n2 & 7) * 16;
            d_pi = 4096; d_po = 512;
        }
        float cd, sd, cs, sn;
        __sincosf((float)(f >= 32 ? f - 64 : f) * (6.283185307179586f / 64.f), &sd, &cd);
        int a = (8 * c8 * f) & 63;
        __sincosf((float)(a >= 32 ? a - 64 : a) * (6.283185307179586f / 64.f), &sn, &cs);
        float cv[8], sv[8];
#pragma unroll
        for (int e = 0; e < 8; e++) {
            cv[e] = cs; sv[e] = sn;
            float t = cs * cd - sn * sd;
            sn = sn * cd + cs * sd;
            cs = t;
        }
        uint4 oc = make_uint4(pack_bf16(cv[0], cv[1]), pack_bf16(cv[2], cv[3]), pack_bf16(cv[4], cv[5]), pack_bf16(cv[6], cv[7]));
        uint4 os = make_uint4(pack_bf16(sv[0], sv[1]), pack_bf16(sv[2], sv[3]), pack_bf16(sv[4], sv[5]), pack_bf16(sv[6], sv[7]));
        sts128(a_cc, oc);
        sts128(a_cc + d_pi, os);
        sts128(a_cc + d_po, make_uint4(os.x ^ 0x80008000u, os.y ^ 0x80008000u, os.z ^ 0x80008000u, os.w ^ 0x80008000u));
        sts128(a_cc + d_pi + d_po, oc);
    }
}

__global__ void __launch_bounds__(NTHREADS, 1)
fused_kernel(const __grid_constant__ CUtensorMap tm_x, const __grid_constant__ CUtensorMap tm_bre,
             const __grid_constant__ CUtensorMap tm_bim, const __grid_constant__ CUtensorMap tm_cre,
             const __grid_constant__ CUtensorMap tm_cim, const __grid_constant__ CUtensorMap tm_col, const Params p) {
    extern __shared__ __align__(1024) uint8_t sm[];
    const uint32_t sb = s2u(sm);
    const int tid = threadIdx.x, b = blockIdx.x;
    const int c = b >> 3, r = b & 7;
    const int par = r & 1, pi_ = r >> 1, own = 4 * par + pi_;
    const int wg = __shfl_sync(~0u, tid >> 7, 0), w = __shfl_sync(~0u, (tid >> 5) & 3, 0), lane = tid & 31, g = lane >> 2, q = lane & 3;
    auto BAR = [&](int i) { return sb + SM_BAR + 8 * i; };
    unsigned* s_tgt = (unsigned*)(sm + SM_TGT);

    if (tid < NBARS) {
        int cnt = 1;
        if (tid >= B_EMPTY0 && tid < B_EMPTY0 + 4) cnt = 16;
        if (tid >= B_XEMPTY && tid < B_XEMPTY + 2) cnt = 16;
        if (tid == B_RFREE) cnt = 12;
        if (tid == B_HDONE || tid == B_WST) cnt = 2;
        if ((tid >= B_AEMPTY && tid < B_AEMPTY + 8) || tid == B_BFREE) cnt = 8;
        if (tid == B_AFREE) cnt = 4;
        mbar_init(BAR(tid), cnt);
        asm volatile("fence.mbarrier_init.release.cluster;" ::: "memory");
    }
    asm volatile("barrier.cluster.arrive.release.aligned;" ::: "memory");

    if (wg == 3) {
        asm volatile("setmaxnreg.dec.sync.aligned.u32 56;");
        if (w == 0 && lane < 6) {
            const CUtensorMap* tm = lane == 0 ? &tm_x : lane == 1 ? &tm_bre : lane == 2 ? &tm_bim : lane == 3 ? &tm_cre : lane == 4 ? &tm_cim : &tm_col;
            asm volatile("prefetch.tensormap [%0];" ::"l"(tm) : "memory");
        }
        __syncwarp();
        asm volatile("barrier.cluster.wait.acquire.aligned;" ::: "memory");
        if (w > 0) {
            if (w == 1) {
                float lr[3], li[3], ld[3];
#pragma unroll
                for (int k = 0; k < 3; k++) {
                    int ps = k < 2 ? 64 * r + 32 * k + lane : 32 * c + lane;
                    lr[k] = ldbf(p.lam_re + ps); li[k] = ldbf(p.lam_im + ps); ld[k] = ldbf(p.log_dt + ps);
                }
                if (lane < 6) s_tgt[lane] = ((ld_acquire(&g_bar[lane]) >> 7) + 1u) << 7;
#pragma unroll 1
                for (int k = 0; k < 3; k++) {
                    float a = k == 0 ? lr[0] : (k == 1 ? lr[1] : lr[2]), bq = k == 0 ? li[0] : (k == 1 ? li[1] : li[2]);
                    float dt = __bfloat162float(__float2bfloat16(expf(k == 0 ? ld[0] : (k == 1 ? ld[1] : ld[2]))));
                    float mag = expf(a * dt), t = bq * dt * 0.15915494309189535f, sn, cs;
                    t -= rintf(t);
                    sincospif(2.f * t, &sn, &cs);
                    float er = mag * cs, ei = mag * sn;
                    if (k < 2) {
                        *(float2*)(sm + SM_LAM + (32 * k + lane) * 8) = make_float2(er, ei);
                    } else {
                        er -= 1.f;
                        float inv = 1.f / (a * a + bq * bq);
                        *(float2*)(sm + SM_TAB + lane * 8) = make_float2((er * a + ei * bq) * inv, (ei * a - er * bq) * inv);
                    }
                }
                __syncwarp();
                bar_arrive(15, 160);
                if (lane == 0) mbar_arrive(BAR(B_SETUP), 1);
            }
            if (w == 2 && lane < 2) {
                const char* src = (const char*)(lane ? p.w_i : p.w_r) + (size_t)b * 8224;
                asm volatile("cp.async.bulk.prefetch.L2.global [%0], 8224;" ::"l"(src) : "memory");
            }
#pragma unroll 1
            for (int i = tid - 448; i < 96 + 128 && w > 1; i += 64) {
                if (i < 96) g_P[(uint32_t)(b * 4 + i / 24) * 1024 + 640 + ((i % 24) >> 1) * 32 + 30 + (i & 1)] = make_uint4(0, 0, 0, 0);
                else g_Ebuf[b * 128 + i - 96] = make_float4(0.f, 0.f, 0.f, 0.f);
            }
            __syncwarp();
            if (w > 1) bar_sync(0, 192);
            if (tid == 448) TX(14);
            if (w > 1) {
                if (lane < 8) {
                    const int cl = 8 * (w - 2) + lane;
                    asm volatile("cp.async.bulk.global.shared::cta.bulk_group [%0], [%1], 1024;" ::"l"(g_Wfrag + (uint32_t)((16 * (b & 7) + cl) * 1024 + (b >> 3) * 64)),
                                 "r"(sb + SM_H + cl * 1024) : "memory");
                }
                asm volatile("cp.async.bulk.commit_group;" ::: "memory");
                asm volatile("cp.async.bulk.wait_group 0;" ::: "memory");
                fence_async();
                __syncwarp();
                if (lane == 0) mbar_arrive(BAR(B_WST), 1);
                if (tid == 448) TX(15);
            }
            __syncwarp();
            if (w == 3) bar_arrive(11, 192);
            if (w == 2) {
                bar_sync(11, 192);
                if (lane == 0) { TX(7); red_release(&g_bar[4], 1);  }
            }
            if (w == 3) {
#pragma unroll 1
                for (int it = 0; it < 8; it++) {
                    const int m = 4 * c + (it >> 1), d = 64 * r + m, ch = lane + 32 * (it & 1);
                    float v[8];
#pragma unroll
                    for (int e = 0; e < 8; e++) {
                        int j = 8 * ch + e, f, ph;
                        dft_fp(j, f, ph);
                        int a = (d * f + ph) & 511;
                        a = a >= 256 ? a - 512 : a;
                        float wj = j == 0 ? 0.f : (j == 1 ? 1.f / 512.f : 2.f / 512.f);
                        v[e] = wj * __cosf((float)a * (6.283185307179586f / 512.f));
                    }
                    uint32_t off = (uint32_t)(64 + r * 8 + (ch >> 3)) * 8192 + (m >> 3) * 1024 + (ch & 7) * 128 + (m & 7) * 16;
                    *(uint4*)(g_E + off) = make_uint4(pack_bf16(v[0], v[1]), pack_bf16(v[2], v[3]), pack_bf16(v[4], v[5]), pack_bf16(v[6], v[7]));
                }
                __syncwarp();
                if (lane == 0) { fence_async(); red_release(&g_bar[6], 1); }
                return;
            }
            if (w == 2) {
#pragma unroll 1
                for (int it = 0; it < 4; it++) {
                    const int hf = it & 1;
                    __syncwarp();
                    if (hf == 0) bar_sync(13, 288); else bar_sync(6, 288);
                    if (lane == 0) {
                        const uint32_t src = sb + SM_HH + par * 32768 + hf * 16384;
                        bulk_s2peer(mapa(src, par ^ 1), src, 16384, mapa(BAR(hf ? B_HPEER1 : B_HPEER), par ^ 1));
                    }
                }
                return;
            }
            bar_sync(2, 288);
            if (lane == 0) {
                TX(5);
                fence_async();
                red_release(&g_bar[0], 1);
                TX(6);
            }
            __syncwarp();

            bar_sync(12, 160);
            if (lane == 0) {
                asm volatile("cp.async.bulk.global.shared::cta.bulk_group [%0], [%1], 8192;" ::"l"(g_A1 + (uint32_t)(((c >> 1) * 8 + r) * 16384 + (c & 1) * 8192)),
                             "r"(sb + SM_B1ST) : "memory");
                asm volatile("cp.async.bulk.commit_group;" ::: "memory");
                asm volatile("cp.async.bulk.wait_group 0;" ::: "memory");
                mbar_arrive(BAR(B_B1DONE), 1);
                fence_async();
                red_release(&g_bar[7], 1);
            }
#pragma unroll 1
            for (int layer = 0; layer < 2; layer++) {
                __syncwarp();
                bar_sync(5, 416);
                if (lane == 0) {
                    TX(0 + 8 * layer);
                    tma_store_5d(&tm_col, 32 * (b & 1), 0, b >> 1, 0, layer, sb + SM_RAW);
                    asm volatile("cp.reduce.async.bulk.global.shared::cta.bulk_group.add.f32 [%0], [%1], 8192;" ::"l"(g_ssqc + (layer * 16 + (b & 15)) * 2048),
                                 "r"(sb + SM_SSQ) : "memory");
                    asm volatile("cp.async.bulk.commit_group;" ::: "memory");
                    asm volatile("cp.async.bulk.wait_group 0;" ::: "memory");
                    TX(1 + 8 * layer);
                    fence_async();
                    red_release(&g_bar[1 + 2 * layer], 1);
                    TX(2 + 8 * layer);
                }
            }
        } else if (tid == 384) {
#pragma unroll 1
            for (int kb = 0; kb < 8; kb++) {
                uint32_t fb = BAR(B_FULL0 + kb);
                mbar_expect(fb, 16384);
                tma_5d_mc(sb + SM_A + 65536 + kb * 16384 + par * 8192, &tm_x, kb * 64, 0, 0, 8 * par, c, fb);
            }
#pragma unroll 1
            for (int k2 = 0; k2 < 8; k2++) {
                asm volatile("cp.async.bulk.prefetch.tensor.2d.L2.global [%0, {%1,%2}];" ::"l"(par ? &tm_bim : &tm_bre), "r"(k2 * 64), "r"(32 * c) : "memory");
                if ((k2 & 1) == par)
                    asm volatile("cp.async.bulk.prefetch.tensor.2d.L2.global [%0, {%1,%2}];" ::"l"((c & 1) ? &tm_cim : &tm_cre), "r"(64 * (c >> 1)), "r"(k2 * 64) : "memory");
            }
            mbar_wait(BAR(B_SETUP), 0);
#pragma unroll 1
            for (int layer = 0; layer < 2; layer++) {
                if (layer == 1) {
                    mbar_wait(BAR(B_AEMPTY + 4), 0);
                    mbar_expect(BAR(B_WRDY), 16384);
                    bulk_g2s(sb + SM_H + 16384, g_Wfrag + (uint32_t)b * 1024, 16384, BAR(B_WRDY));
                }
                wait_count(&g_bar[2 * layer], s_tgt[2 * layer]);
                TX(4 + 8 * layer);
                fence_async();
                mbar_expect(BAR(B_COL), 16384 + 8192);
                tma_5d(sb + SM_RAW, &tm_col, 32 * (b & 1), 0, b >> 1, 0, layer, BAR(B_COL));
                bulk_g2s(sb + SM_SSQ, g_ssq + layer * 2048, 8192, BAR(B_COL));
                if (layer == 0) {
                    wait_count(&g_bar[4], s_tgt[4]);
                    fence_async();
                    TX(16);
                    mbar_wait(BAR(B_B1DONE), 0);
                    TX(17);
                    mbar_expect(BAR(B_WRDY), 16384);
                    bulk_g2s(sb + SM_H + 16384, g_Wfrag + (uint32_t)b * 1024, 16384, BAR(B_WRDY));
                    wait_count(&g_bar[7], s_tgt[4]);
                    fence_async();
                }
                if (layer == 0) mbar_wait(BAR(B_AFREE), 0);
                mbar_wait(BAR(B_COL), layer);
#pragma unroll 1
                for (int s = 0; s < 8; s++) {
                    if (layer == 1) mbar_wait(BAR(B_AEMPTY + s), fpar(s, 2, 0));
                    if (s >= 2) mbar_wait(BAR(B_AFULL + s - 2), fpar(s - 2, 0, layer));
                    mbar_expect(BAR(B_AFULL + s), 16384);
                    bulk_g2s(sb + SM_A + s * 16384, g_A1 + (uint32_t)(r * 8 + s) * 16384, 16384, BAR(B_AFULL + s));
                }
                if (layer == 1) wait_count(&g_bar[6], s_tgt[4]);
                wait_count(&g_bar[1 + 2 * layer], s_tgt[1 + 2 * layer]);
                TX(3 + 8 * layer);
                fence_async();
                const uint8_t* xsrc = g_X + (uint32_t)(layer * 16 + c) * 8 * 16384;
                const uint8_t* esrc = g_E + (uint32_t)(layer * 8 + own) * 8 * 8192;
                mbar_arrive(BAR(B_SSQ), 1);
                mbar_expect(BAR(B_HPEER), 16384);
                mbar_expect(BAR(B_HPEER1), 16384);
#pragma unroll 1
                for (int it = 0; it < 20; it++) {
                    if (it < 8) {
                        const int st = it < 6 ? it : it - 6;
                        if (it >= 6) mbar_wait_cluster(BAR(B_XEMPTY + st), layer);
                        mbar_expect(BAR(B_XFULL + st), 16384);
                        bulk_g2s_mc(sb + SM_X + st * 16384 + par * 8192, xsrc + (uint32_t)it * 16384 + par * 8192, 8192, BAR(B_XFULL + st));
                    }
                    if (it >= 6) {
                        const bool isc = it >= 12;
                        const int s = isc ? cslot(it - 12) : it - 6;
                        mbar_wait(BAR(B_AEMPTY + s), fpar(s, it < 14 ? 0 : 1, layer));
                        uint32_t fb = BAR(B_AFULL + s), dst = sb + SM_A + s * 16384;
                        mbar_expect(fb, 16384);
                        if (!isc) {
                            bulk_g2s(dst, s < 4 ? esrc + (uint32_t)s * 16384 : xsrc + (uint32_t)(s - 4) * 16384, 16384, fb);
                        } else {
                            const int tile = 4 * par + ((pi_ + 1 + ((it - 12) >> 1)) & 3), sl = r ^ (it & 1);
                            if (layer == 1) {
                                tma_2d(dst, &tm_cre, 64 * sl, 64 * tile, fb);
                                tma_2d(dst + 8192, &tm_cim, 64 * sl, 64 * tile, fb);
                            } else {
                                bulk_g2s(dst, g_A2 + (uint32_t)(sl * 8 + tile) * 16384, 16384, fb);
                            }
                        }
                    }
                }
            }
        }
        return;
    }

    asm volatile("setmaxnreg.inc.sync.aligned.u32 152;");
    if (tid >= 96 && tid < 112) g_ssq[2048 + 16 * b + tid - 96] = 0.f;
    if (tid >= 128 && tid < 256) ((float4*)g_ssqc)[b * 128 + tid - 128] = make_float4(0.f, 0.f, 0.f, 0.f);
    TS(0);
    if (wg == 0) TC(30);
    {
        const int f = 32 * r + lane;
        float cd, sd;
        __sincosf((float)f * (6.283185307179586f / 512.f), &sd, &cd);
        const uint32_t dst = sb + SM_A + (lane >> 2) * 1024 + (lane & 3) * 32;
#pragma unroll 1
        for (int ch = tid >> 5; ch < 64; ch += 12) {
            int a = (8 * ch * f) & 511;
            a = a >= 256 ? a - 512 : a;
            float cs, sn;
            __sincosf((float)a * (6.283185307179586f / 512.f), &sn, &cs);
            float cv[8], sv[8];
#pragma unroll
            for (int e = 0; e < 8; e++) {
                cv[e] = cs; sv[e] = -sn;
                float t = cs * cd - sn * sd;
                sn = sn * cd + cs * sd;
                cs = t;
            }
            uint4 o1 = make_uint4(pack_bf16(sv[0], sv[1]), pack_bf16(sv[2], sv[3]), pack_bf16(sv[4], sv[5]), pack_bf16(sv[6], sv[7]));
            if (f == 0) o1 = make_uint4(0xbf803f80u, 0xbf803f80u, 0xbf803f80u, 0xbf803f80u);
            uint32_t a0 = dst + (ch >> 3) * 8192 + (ch & 7) * 128;
            sts128(a0, make_uint4(pack_bf16(cv[0], cv[1]), pack_bf16(cv[2], cv[3]), pack_bf16(cv[4], cv[5]), pack_bf16(cv[6], cv[7])));
            sts128(a0 + 16, o1);
        }
    }
    fence_async_smem();
    asm volatile("barrier.cluster.wait.acquire.aligned;" ::: "memory");
    bar_sync(10, 384);
    TS(1);
    if (wg < 2) {
        float acc[32];
        acc_def(acc);
        const int npos = 16 * r + 8 * wg + 2 * w;
        float sh0 = 0.f, sh1 = 0.f, s0 = 0.f, s1 = 0.f, q0 = 0.f, q1 = 0.f;
#pragma unroll 1
        for (int kb = 0; kb < 8; kb++) {
            uint32_t slot = sb + SM_A + 65536 + kb * 16384;
            mbar_wait(BAR(B_FULL0 + kb), 0);
            wg_fence();
#pragma unroll
            for (int ks = 0; ks < 4; ks++)
                wgmma_n64<0>(acc, desc_a(sb + SM_A + kb * 8192 + ks * 256), desc_k(slot + wg * 8192 + ks * 32), 1);
            wg_commit();
            {
                uint32_t v0 = lds32(slot + npos * 128 + lane * 4), v1 = lds32(slot + npos * 128 + 128 + lane * 4);
                if (kb == 0) { sh0 = __shfl_sync(~0u, bf_lo(v0), 0); sh1 = __shfl_sync(~0u, bf_lo(v1), 0); }
                float a = bf_lo(v0) - sh0, bq = bf_hi(v0) - sh0, cq = bf_lo(v1) - sh1, d = bf_hi(v1) - sh1;
                s0 += a + bq; q0 += a * a + bq * bq; s1 += cq + d; q1 += cq * cq + d * d;
            }
            wg_wait<1>();
            if (kb > 0 && kb <= 4 && lane == 0) { mbar_arrive(BAR(B_EMPTY0 + kb - 1), 1); mbar_arrive_remote(mapa(BAR(B_EMPTY0 + kb - 1), par ^ 1)); }
        }
#pragma unroll
        for (int o = 16; o; o >>= 1) {
            s0 += __shfl_xor_sync(~0u, s0, o); q0 += __shfl_xor_sync(~0u, q0, o);
            s1 += __shfl_xor_sync(~0u, s1, o); q1 += __shfl_xor_sync(~0u, q1, o);
        }
        if (lane == 0) *(float2*)(g_ssq + 128 * c + npos) = make_float2(fmaxf(q0 - s0 * s0 * (1.f / 512.f), 0.f), fmaxf(q1 - s1 * s1 * (1.f / 512.f), 0.f));
        wg_wait<0>();
        TS(2);
        uint8_t* dst = g_X + (uint32_t)((c * 8 + r) * 16384 + w * 4096 + wg * 1024 + g * 16 + 4 * q);
#pragma unroll
        for (int i = 0; i < 8; i++) {
            *(uint32_t*)(dst + i * 128) = pack_bf16(acc[4 * i], acc[4 * i + 1]);
            *(uint32_t*)(dst + 2048 + i * 128) = pack_bf16(acc[4 * i + 2], acc[4 * i + 3]);
        }
        bar_sync(2, 288);
        mbar_wait(BAR(B_SETUP), 0);
        TS(3);
    }

    if (wg == 2) {
        {
            uint4 p0 = __ldg((const uint4*)p.dskip + 2 * lane), p1 = __ldg((const uint4*)p.dskip + 2 * lane + 1);
            uint32_t u[8] = {p0.x, p0.y, p0.z, p0.w, p1.x, p1.y, p1.z, p1.w};
            int j = 64 * r + 4 * c + w, f, ph;
            dft_fp(j, f, ph);
            float s = 0.f;
            int idx = 16 * lane * f + ph;
#pragma unroll
            for (int i = 0; i < 16; i++) {
                int a = idx & 511;
                idx += f;
                a = a >= 256 ? a - 512 : a;
                s += ((i & 1) ? bf_hi(u[i >> 1]) : bf_lo(u[i >> 1])) * __cosf((float)a * (6.283185307179586f / 512.f));
            }
#pragma unroll
            for (int o = 16; o; o >>= 1) s += __shfl_xor_sync(~0u, s, o);
            if (lane == 0) g_Dh[j] = s;
        }
        mbar_wait(BAR(B_FULL0 + 7), 0);
        if (tid == 256) {
#pragma unroll 1
            for (int s = 0; s < 4; s++) mbar_wait_cluster(BAR(B_EMPTY0 + s), 0);
            mbar_expect(BAR(B_FULLB), 65536);
#pragma unroll 1
            for (int k2 = 0; k2 < 8; k2++)
                tma_2d_mc(sb + SM_A + 65536 + k2 * 8192 + par * 4096, par ? &tm_bim : &tm_bre, k2 * 64, 32 * c, BAR(B_FULLB));
        }
        __syncwarp();
        {
            const int cl = tid & 15, cb = 16 * (b & 7) + cl;
            const int c0 = cb == 0 ? 256 : 2 * cb, c1 = 2 * cb + 1;
            uint32_t wf[2][16];
#pragma unroll
            for (int h = 0; h < 2; h++) {
                const int kq = 16 * (b >> 3) + ((tid & 127) >> 4) + 8 * h, k1 = kq >> 2, qq = kq & 3;
                const unsigned short* wr_ = (const unsigned short*)p.w_r + (k1 + 128 * qq) * 257;
                const unsigned short* wi_ = (const unsigned short*)p.w_i + (k1 + 128 * qq) * 257;
#pragma unroll
                for (int i = 0; i < 4; i++) {
                    int o = 512 * i * 257;
                    wf[h][2 * i] = (uint32_t)__ldg(wr_ + o + c0) | ((uint32_t)__ldg(wr_ + o + 64 * 257 + c0) << 16);
                    wf[h][2 * i + 1] = ((uint32_t)__ldg(wi_ + o + c0) | ((uint32_t)__ldg(wi_ + o + 64 * 257 + c0) << 16)) ^ 0x80008000u;
                    wf[h][8 + 2 * i] = (uint32_t)__ldg(wr_ + o + c1) | ((uint32_t)__ldg(wr_ + o + 64 * 257 + c1) << 16);
                    wf[h][8 + 2 * i + 1] = ((uint32_t)__ldg(wi_ + o + c1) | ((uint32_t)__ldg(wi_ + o + 64 * 257 + c1) << 16)) ^ 0x80008000u;
                }
            }
#pragma unroll
            for (int h = 0; h < 2; h++)
#pragma unroll
                for (int i = 0; i < 4; i++)
                    sts128(sb + SM_H + cl * 1024 + (((tid & 127) >> 4) + 8 * h) * 64 + ((i ^ ((tid >> 5) & 3)) << 4),
                           make_uint4(wf[h][4 * i], wf[h][4 * i + 1], wf[h][4 * i + 2], wf[h][4 * i + 3]));
            fence_async_smem();
            bar_arrive(0, 192);
            bar_arrive(11, 192);
        }
        bar_sync(15, 160);
        float acc[32];
        acc_def(acc);
        mbar_wait(BAR(B_FULLB), 0);
        wg_fence();
#pragma unroll 1
        for (int kb = 0; kb < 8; kb++) {
#pragma unroll
            for (int ks = 0; ks < 4; ks++)
                wgmma_n64<0>(acc, desc_a(sb + SM_A + kb * 8192 + ks * 256), desc_k(sb + SM_A + 65536 + kb * 8192 + ks * 32), 1);
            wg_commit();
        }
        wg_wait<0>();
        if (lane == 0) { mbar_arrive(BAR(B_BFREE), 1); mbar_arrive_remote(mapa(BAR(B_BFREE), par ^ 1)); }
        if (tid == 256) {
            mbar_wait_cluster(BAR(B_BFREE), 0);
            mbar_expect(BAR(B_FULLC), 65536);
#pragma unroll 1
            for (int k2 = par; k2 < 8; k2 += 2)
                tma_2d_mc(sb + SM_A + 65536 + k2 * 8192, (c & 1) ? &tm_cim : &tm_cre, 64 * (c >> 1), k2 * 64, BAR(B_FULLC));
        }
        __syncwarp();
        {
            uint8_t* dst = sm + SM_B1ST + w * 256 + q * 32 + g * 2;
            const float wj0 = (r == 0 && w == 0 && g < 2) ? (g == 0 ? 0.f : 1.f / 512.f) : 2.f / 512.f;
#pragma unroll
            for (int i = 0; i < 4; i++) {
#pragma unroll
                for (int e = 0; e < 2; e++) {
                    float2 cf = *(const float2*)(sm + SM_TAB + (8 * i + 2 * q + e) * 8);
#pragma unroll
                    for (int h = 0; h < 2; h++) {
                        float wj = h == 0 ? wj0 : 2.f / 512.f;
                        float pr = acc[4 * i + 2 * h + e] * wj, pi = acc[16 + 4 * i + 2 * h + e] * wj;
                        uint8_t* d2 = dst + i * 2048 + h * 128 + e * 16;
                        *(__nv_bfloat16*)(d2) = __float2bfloat16(cf.x * pr - cf.y * pi);
                        *(__nv_bfloat16*)(d2 + 1024) = __float2bfloat16(cf.x * pi + cf.y * pr);
                    }
                }
            }
            fence_async_smem();
            bar_arrive(12, 160);
        }
        acc_def(acc);
        mbar_wait(BAR(B_FULLC), 0);
        wg_fence();
#pragma unroll 1
        for (int kb = 0; kb < 8; kb++) {
#pragma unroll
            for (int ks = 0; ks < 4; ks++)
                wgmma_n64<1>(acc, desc_a(sb + SM_A + kb * 8192 + ks * 256), desc_mn(sb + SM_A + 65536 + kb * 8192 + ks * 2048, 8192), 1);
            wg_commit();
        }
        wg_wait<0>();
        fence_async_smem();
        if (lane == 0) mbar_arrive(BAR(B_AFREE), 1);
        uint8_t* dst = g_A2 + (uint32_t)(((c >> 1) * 8 + r) * 16384 + (c & 1) * 8192 + w * 2048 + g * 16 + 4 * q);
#pragma unroll
        for (int i = 0; i < 8; i++) {
            *(uint32_t*)(dst + i * 128) = pack_bf16(acc[4 * i], acc[4 * i + 1]);
            *(uint32_t*)(dst + 1024 + i * 128) = pack_bf16(acc[4 * i + 2], acc[4 * i + 3]);
        }
        {
            const int m = 4 * c + w, jp = 64 * r + m;
            int fp, php;
            dft_fp(jp, fp, php);
            const __nv_bfloat16* dh = (const __nv_bfloat16*)(sm + SM_RSTD);
            if (tid == 256) wait_count(&g_bar[4], s_tgt[4]);
            bar_sync(3, 128);
            float4 d4 = __ldcg((const float4*)g_Dh + (tid - 256));
            *(uint2*)(sm + SM_RSTD + (tid - 256) * 8) = make_uint2(pack_bf16(d4.x, d4.y), pack_bf16(d4.z, d4.w));
            bar_sync(3, 128);
#pragma unroll 1
            for (int it = 0; it < 2; it++) {
                const int ch = lane + 32 * it;
                float v[8];
#pragma unroll
                for (int e = 0; e < 8; e++) {
                    int j = 8 * ch + e, f, ph;
                    dft_fp(j, f, ph);
                    float wj = j == 0 ? 0.f : (j == 1 ? 1.f / 512.f : 2.f / 512.f);
                    float gsum = 0.f;
#pragma unroll
                    for (int sgn = 0; sgn < 2; sgn++) {
                        int mm = (sgn ? f - fp : f + fp) & 511, pp = (sgn ? ph - php : ph + php) & 511;
                        if (mm > 256) { mm = 512 - mm; pp = (512 - pp) & 511; }
                        int odd = (pp >> 7) & 1;
                        float t = __bfloat162float(dh[mm == 256 ? 1 : 2 * mm + odd]);
                        if (odd && (mm & 255) == 0) t = 0.f;
                        gsum += (pp & 256) ? -t : t;
                    }
                    v[e] = 0.5f * wj * gsum;
                }
                uint32_t off = (uint32_t)(r * 8 + (ch >> 3)) * 8192 + (m >> 3) * 1024 + (ch & 7) * 128 + (m & 7) * 16;
                *(uint4*)(g_E + off) = make_uint4(pack_bf16(v[0], v[1]), pack_bf16(v[2], v[3]), pack_bf16(v[4], v[5]), pack_bf16(v[6], v[7]));
            }
        }
    }

#pragma unroll 1
    for (int layer = 0; layer < 2; layer++) {
        if (wg < 2) {
            const int n1 = 32 * wg + 8 * w + g;
            const int ct = n1 >> 2;
            gen_col_consts(sb, tid);
            uint32_t tr2[4], ti2[4], tn2[4];
#pragma unroll
            for (int i = 0; i < 4; i++) {
                float cr[2], ci[2];
#pragma unroll
                for (int e = 0; e < 2; e++) {
                    int a = (n1 * (8 * i + 2 * q + e)) & 2047;
                    a = a >= 1024 ? a - 2048 : a;
                    float ang = (float)a * (-6.283185307179586f / 2048.f);
                    cr[e] = __cosf(ang); ci[e] = __sinf(ang);
                }
                tr2[i] = pack_bf16(cr[0], cr[1]); ti2[i] = pack_bf16(ci[0], ci[1]); tn2[i] = ti2[i] ^ 0x80008000u;
            }
            mbar_wait(BAR(B_WST), 0);
            mbar_wait(BAR(B_COL), layer);
            TS(4 + 12 * layer);
            if (wg == 0) TC(0 + 10 * layer);
            const uint32_t rw0 = sb + SM_RAW + ct * 1024 + q * 64 + ((q >> 1) << 4) + (g & 3) * 4, rw1 = rw0 ^ 16;
            const int pos0 = 128 * ct + 8 * q + 2 * (g & 3);
            const int sw = b == 0 ? 1 : 0;
            uint32_t xr[4][4];
            const uint32_t st0 = sb + SM_H + (n1 >> 3) * 1024 + g * 16 + 4 * q;
#pragma unroll
            for (int i = 0; i < 4; i++) {
                float2 sq = *(const float2*)(sm + SM_SSQ + (pos0 + 32 * i) * 4);
                const uint32_t rs2 = pack_bf16(rsqrtf(sq.x * (1.f / 512.f) + 1e-5f), rsqrtf(sq.y * (1.f / 512.f) + 1e-5f));
#pragma unroll
                for (int jj = 0; jj < 4; jj++) {
                    const int K = jj ^ (2 * (i & 1));
                    uint32_t a = ((K & 1) ? rw1 : rw0) + i * 256 + (K & 2) * 16;
                    if (jj < 2) a ^= sw << 4;
                    uint32_t v = lds32(a);
                    xr[jj][i] = v;
                    uint32_t o = hmul2(v, rs2);
                    if (jj == 1 && sw) o = 0u;
                    sts32(st0 + (jj & 1) * 8192 + (4 * (jj >> 1) + i) * 128, o);
                }
            }
            if (wg == 0) TC(1 + 10 * layer);
            fence_async_smem();
            bar_sync(1, 256);
            float acc[32];
            const uint32_t s1a = sb + SM_X + wg * 16384, s2b = sb + SM_X + 32768;
            wg_fence();
#pragma unroll
            for (int ks = 0; ks < 8; ks++)
                wgmma_n64<1>(acc, desc_a(s1a + (ks >> 2) * 8192 + (ks & 3) * 256), desc_b<64>(sb + SM_H + ks * 2048), ks != 0);
            wg_commit();
            wg_wait<0>();
            if (wg == 0) TC(2 + 10 * layer);
            uint32_t are[2][4], aim[2][4];
#pragma unroll
            for (int col = 0; col < 2; col++) {
#pragma unroll
                for (int i = 0; i < 4; i++) {
                    int o = 4 * (4 * col + i);
                    uint32_t zr = pack_bf16(acc[o], acc[o + 1]), zi = pack_bf16(acc[o + 2], acc[o + 3]);
                    are[col][i] = hfma2(zr, tr2[i], hmul2(zi, tn2[i]));
                    aim[col][i] = hfma2(zr, ti2[i], hmul2(zi, tr2[i]));
                }
            }
            wg_fence();
#pragma unroll
            for (int ks = 0; ks < 2; ks++)
                wgmma_n64_rs(acc, are[0][2 * ks], are[1][2 * ks], are[0][2 * ks + 1], are[1][2 * ks + 1], desc_b<64>(s2b + ks * 2048), ks != 0);
#pragma unroll
            for (int ks = 0; ks < 2; ks++)
                wgmma_n64_rs(acc, aim[0][2 * ks], aim[1][2 * ks], aim[0][2 * ks + 1], aim[1][2 * ks + 1], desc_b<64>(s2b + 4096 + ks * 2048), 1);
            wg_commit();
            uint32_t wf[16];
            mbar_wait(BAR(B_WRDY), layer);
#pragma unroll
            for (int i = 0; i < 4; i++) {
                const int kq = n1 * 4 + q;
                uint4 v = *(const uint4*)(sm + SM_H + 16384 + kq * 64 + ((i ^ ((kq >> 1) & 3)) << 4));
                wf[4 * i] = v.x; wf[4 * i + 1] = v.y; wf[4 * i + 2] = v.z; wf[4 * i + 3] = v.w;
            }
            wg_wait<0>();
            if (wg == 0) TC(3 + 10 * layer);
#pragma unroll
            for (int col = 0; col < 2; col++) {
#pragma unroll
                for (int i = 0; i < 4; i++) {
                    uint32_t wr = wf[col * 8 + 2 * i], wn = wf[col * 8 + 2 * i + 1];
                    uint32_t zr = pack_bf16(acc[4 * i + 2 * col], acc[4 * i + 2 * col + 1]);
                    uint32_t zi = pack_bf16(acc[16 + 4 * i + 2 * col], acc[16 + 4 * i + 2 * col + 1]);
                    are[col][i] = hfma2(zr, wr, hmul2(zi, wn));
                    aim[col][i] = hfma2(zr, wn, hmul2(zi ^ 0x80008000u, wr));
                }
            }
            wg_fence();
#pragma unroll
            for (int ks = 0; ks < 2; ks++)
                wgmma_n64_rs(acc, are[0][2 * ks], are[1][2 * ks], are[0][2 * ks + 1], are[1][2 * ks + 1], desc_b<64>(s2b + ks * 2048), ks != 0);
#pragma unroll
            for (int ks = 0; ks < 2; ks++)
                wgmma_n64_rs(acc, aim[0][2 * ks], aim[1][2 * ks], aim[0][2 * ks + 1], aim[1][2 * ks + 1], desc_b<64>(s2b + 4096 + ks * 2048), 1);
            wg_commit();
            wg_wait<0>();
            if (wg == 0) TC(4 + 10 * layer);
            bar_sync(1, 256);
#pragma unroll
            for (int col = 0; col < 2; col++) {
#pragma unroll
                for (int i = 0; i < 4; i++) {
                    uint32_t zr = pack_bf16(acc[4 * i + 2 * col], acc[4 * i + 2 * col + 1]);
                    uint32_t zi = pack_bf16(acc[16 + 4 * i + 2 * col], acc[16 + 4 * i + 2 * col + 1]);
                    sts32(st0 + 16384 + (4 * col + i) * 128, hfma2(zr, tr2[i], hmul2(zi, tn2[i])));
                    sts32(st0 + 16384 + 8192 + (4 * col + i) * 128, hfma2(zr, ti2[i], hmul2(zi, tr2[i])));
                }
            }
            if (wg == 0) TC(5 + 10 * layer);
            fence_async_smem();
            bar_sync(1, 256);
            wg_fence();
#pragma unroll
            for (int ks = 0; ks < 8; ks++)
                wgmma_n64<1>(acc, desc_a(s1a + (ks >> 2) * 8192 + (ks & 3) * 256), desc_b<64>(sb + SM_H + 16384 + ks * 2048), ks != 0);
            wg_commit();
            wg_wait<0>();
            if (wg == 0) TC(6 + 10 * layer);
            const float sc = 1.f / 2048.f;
            const float sci0 = sw ? 0.f : -sc;
            const float wr0 = sw ? 0.5f : 1.f, wi0 = sw ? 0.f : 1.f;
#pragma unroll
            for (int i = 0; i < 4; i++) {
                float ss0, ss1;
#pragma unroll
                for (int col = 0; col < 2; col++) {
                    int o = 4 * (4 * col + i);
                    uint32_t vr = xr[2 * col][i], vi = xr[2 * col + 1][i];
                    float si = col == 0 ? sci0 : -sc;
                    uint32_t nr = pack_bf16(fmaf(acc[o], sc, bf_lo(vr)), fmaf(acc[o + 1], sc, bf_hi(vr)));
                    uint32_t ni = pack_bf16(fmaf(acc[o + 2], si, bf_lo(vi)), fmaf(acc[o + 3], si, bf_hi(vi)));
                    float a0 = bf_lo(nr), a1 = bf_hi(nr), b0 = bf_lo(ni), b1 = bf_hi(ni);
                    if (col == 0) {
                        ss0 = wr0 * a0 * a0 + wi0 * b0 * b0;
                        ss1 = wr0 * a1 * a1 + wi0 * b1 * b1;
                    } else {
                        ss0 += a0 * a0 + b0 * b0;
                        ss1 += a1 * a1 + b1 * b1;
                    }
                    const int K = (2 * col) ^ (2 * (i & 1));
                    uint32_t a = rw0 + i * 256 + K * 16;
                    if (col == 0) a ^= sw << 4;
                    sts32(a, nr);
                    sts32(a ^ 16, ni);
                }
                *(float2*)(sm + SM_SSQ + (pos0 + 32 * i) * 4) = make_float2(ss0 * (2.f / 512.f), ss1 * (2.f / 512.f));
            }
            fence_async_smem();
        }
        TS(5 + 12 * layer);
        if (wg == 0) TC(7 + 10 * layer);
        bar_arrive(5, 416);

        float acc[64];
        float* s_rstd = (float*)(sm + SM_RSTD);
        float* s_mean = (float*)(sm + SM_MEAN);
        const unsigned epoch = s_tgt[0] >> 7;
        const uint32_t pt3 = 1u + (2u * epoch + layer) % 3u;
        const uint32_t ptag = (pt3 & 1u) | ((pt3 & 2u) << 15);
        const uint64_t dstep = layer == 0 ? 16 : 2;
        auto c_desc = [&](int s) { return layer == 0 ? desc_a(sb + SM_A + s * 16384) : desc_k(sb + SM_A + s * 16384); };
        if (wg < 2) {
            const int prow = 32 * wg + 8 * w + g;
            const float2 l1 = *(const float2*)(sm + SM_LAM + prow * 8);
            float lr32 = l1.x, li32 = l1.y;
#pragma unroll
            for (int i = 0; i < 5; i++) { float t = lr32 * lr32 - li32 * li32; li32 = 2.f * lr32 * li32; lr32 = t; }
            float lr128 = lr32, li128 = li32;
#pragma unroll
            for (int i = 0; i < 2; i++) { float t = lr128 * lr128 - li128 * li128; li128 = 2.f * lr128 * li128; lr128 = t; }
            const float lr1 = l1.x, li1 = l1.y;
            const float l2r = lr128 * lr128 - li128 * li128, l2i = 2.f * lr128 * li128;
            const float l4r = l2r * l2r - l2i * l2i, l4i = 2.f * l2r * l2i;
            float lxr = 1.f, lxi = 0.f;
            {
                const int rho = (c - 1 - q) & 3;
                if (rho & 1) { lxr = lr128; lxi = li128; }
                if (rho & 2) { float t = lxr * l2r - lxi * l2i; lxi = lxr * l2i + lxi * l2r; lxr = t; }
            }
            acc_def(acc);
#pragma unroll 1
            for (int kb = 0; kb < 8; kb++) {
                const int st = kb < 6 ? kb : kb - 6;
                mbar_wait(BAR(B_AFULL + kb), fpar(kb, 0, layer));
                mbar_wait(BAR(B_XFULL + st), st < 2 ? (uint32_t)(kb >= 6) : (uint32_t)layer);
                wg_fence();
#pragma unroll
                for (int ks = 0; ks < 4; ks++)
                    wgmma_n128<1>(acc, desc_a(sb + SM_A + kb * 16384 + wg * 8192 + ks * 256),
                                  desc_b<128>(sb + SM_X + st * 16384 + ks * 4096), 1);
                wg_commit();
                wg_wait<1>();
                if (kb > 0 && lane == 0) {
                    mbar_arrive(BAR(B_AEMPTY + kb - 1), 1);
                    if (kb <= 2) { mbar_arrive(BAR(B_XEMPTY + kb - 1), 1); mbar_arrive_remote(mapa(BAR(B_XEMPTY + kb - 1), par ^ 1)); }
                }
            }
            wg_wait<0>();
            if (lane == 0) {
                mbar_arrive(BAR(B_AEMPTY + 7), 1);
                mbar_arrive_remote(mapa(BAR(B_RFREE), par ^ 1));
            }
            bar_arrive(14, 384);
            TS(6 + 12 * layer);
            bar_sync(4, 384);
            TS(7 + 12 * layer);
            float er = 0.f, ei = 0.f;
#pragma unroll
            for (int i = 0; i < 16; i++) {
                float2 rs = *(const float2*)(s_rstd + 128 + 8 * i + 2 * q);
                acc[4 * i] *= rs.x; acc[4 * i + 1] *= rs.y; acc[4 * i + 2] *= rs.x; acc[4 * i + 3] *= rs.y;
                float nr = lr1 * er - li1 * ei + acc[4 * i], ni = lr1 * ei + li1 * er + acc[4 * i + 2];
                er = lr1 * nr - li1 * ni + acc[4 * i + 1];
                ei = lr1 * ni + li1 * nr + acc[4 * i + 3];
            }
            float cr = 0.f, ci = 0.f, tr = 0.f, ti = 0.f;
#pragma unroll
            for (int qq = 0; qq < 4; qq++) {
                float xr_ = __shfl_sync(~0u, er, (lane & ~3) | qq), xi_ = __shfl_sync(~0u, ei, (lane & ~3) | qq);
                if (qq == q) { cr = tr; ci = ti; }
                float nr = lr32 * tr - li32 * ti + xr_, ni = lr32 * ti + li32 * tr + xi_;
                tr = nr; ti = ni;
            }
            float4* eb = g_Ebuf + (uint32_t)(layer * 16 * 512 + 64 * r + prow);
            if (q == 0 && c < 15) st_relaxed_f4(eb + c * 512, make_float4(tr, ti, __uint_as_float(epoch), 0.f));
            TS(8 + 12 * layer);
            float acc2[32];
            acc_def(acc2);
            float pr[4], pi[4];
            {
                unsigned n = 0;
                bool ok;
#pragma unroll 1
                do {
                    ok = true;
#pragma unroll
                    for (int k = 0; k < 4; k++) {
                        float4 v = make_float4(0.f, 0.f, __uint_as_float(epoch), 0.f);
                        if (4 * k + q < c) v = ld_relaxed_f4(eb + (4 * k + q) * 512);
                        pr[k] = v.x; pi[k] = v.y;
                        ok = ok && __float_as_uint(v.z) == epoch;
                    }
                } while (!ok && ++n < SPIN_LIMIT);
            }
            __syncwarp();
            TS(9 + 12 * layer);
            float hr = 0.f, hi = 0.f;
#pragma unroll
            for (int k = 0; k < 4; k++) {
                if (4 * k + q < c) {
                    float nr = l4r * hr - l4i * hi + pr[k], ni = l4r * hi + l4i * hr + pi[k];
                    hr = nr; hi = ni;
                }
            }
            {
                float nr = lxr * hr - lxi * hi, ni = lxr * hi + lxi * hr;
                hr = nr + __shfl_xor_sync(~0u, nr, 1); hi = ni + __shfl_xor_sync(~0u, ni, 1);
                hr += __shfl_xor_sync(~0u, hr, 2); hi += __shfl_xor_sync(~0u, hi, 2);
            }
#pragma unroll
            for (int qq = 0; qq < 3; qq++) {
                if (qq < q) { float nr = lr32 * hr - li32 * hi, ni = lr32 * hi + li32 * hr; hr = nr; hi = ni; }
            }
            er = cr + hr; ei = ci + hi;
            bar_sync(7, 384);
            mbar_wait_cluster(BAR(B_RFREE), layer);
            const uint32_t ha = sb + SM_HH + par * 32768 + (prow >> 3) * 1024 + g * 16 + 4 * q;
#pragma unroll
            for (int i = 0; i < 16; i++) {
                float nr = lr1 * er - li1 * ei + acc[4 * i], ni = lr1 * ei + li1 * er + acc[4 * i + 2];
                er = lr1 * nr - li1 * ni + acc[4 * i + 1];
                ei = lr1 * ni + li1 * nr + acc[4 * i + 3];
                sts32(ha + (i >> 3) * 16384 + (i & 7) * 128, pack_bf16(nr, er));
                sts32(ha + (i >> 3) * 16384 + 8192 + (i & 7) * 128, pack_bf16(ni, ei));
                if (i == 7) { fence_async_smem(); bar_arrive(13, 288); }
            }
            fence_async_smem();
            TS(10 + 12 * layer);
            bar_arrive(10, 384);
            bar_sync(6, 288);
            TS(11 + 12 * layer);
            float (&a0)[32] = *reinterpret_cast<float (*)[32]>(&acc[0]);
            float (&a1)[32] = *reinterpret_cast<float (*)[32]>(&acc[32]);
            auto tile_mma = [&](float (&d)[32], int u) {
#pragma unroll 1
                for (int k = 0; k < 2; k++) {
                    const uint32_t hb = sb + SM_HH + (par ^ k) * 32768 + wg * 16384;
                    if (k == 1) mbar_wait(BAR(wg ? B_HPEER1 : B_HPEER), layer);
                    const int cs = cslot(2 * u + k);
                    mbar_wait(BAR(B_AFULL + cs), fpar(cs, 2, layer));
                    const uint64_t da = c_desc(cs);
                    wg_fence();
#pragma unroll
                    for (int ks = 0; ks < 4; ks++) wgmma_n64s<1>(d, da + ks * dstep, desc_b<64>(hb + ks * 2048), (ks | k) != 0);
#pragma unroll
                    for (int ks = 0; ks < 4; ks++) wgmma_n64s<-1>(d, da + 512 + ks * dstep, desc_b<64>(hb + 8192 + ks * 2048), 1);
                }
                wg_commit();
            };
            auto tile_ship = [&](float (&d)[32], int u) {
                uint4* dst = g_P + (uint32_t)(((c * 8 + 2 * ((pi_ + 1 + u) & 3) + par) * 4 + pi_) * 1024 + wg * 512 + (tid & 127));
#pragma unroll
                for (int i = 0; i < 4; i++)
                    dst[i * 128] = make_uint4((pack_bf16(d[8 * i], d[8 * i + 1]) & 0xfffefffeu) | ptag, pack_bf16(d[8 * i + 2], d[8 * i + 3]),
                                              pack_bf16(d[8 * i + 4], d[8 * i + 5]), pack_bf16(d[8 * i + 6], d[8 * i + 7]));
            };
            tile_mma(a0, 0);
            if ((tid & 127) == 0) mbar_arrive_remote(mapa(BAR(B_HDONE), par ^ 1));
            __syncwarp();
            tile_mma(a1, 1);
            wg_wait<1>();
            tile_ship(a0, 0);
            tile_mma(acc2, 2);
            bar_arrive(12, 384);
            wg_wait<1>();
            tile_ship(a1, 1);
            wg_wait<0>();
            tile_ship(acc2, 2);
            if (lane < 6) mbar_arrive(BAR(B_AEMPTY + ((lane + 6) & 7)), 1);
            TS(12 + 12 * layer);
        } else {
            const int t2 = tid - 256;
            const uint8_t* ximg = g_X + (uint32_t)layer * 16 * 8 * 16384;
            mbar_wait(BAR(B_SSQ), layer);
            TS(6 + 12 * layer);
            float sqv[16];
#pragma unroll
            for (int i = 0; i < 16; i++) sqv[i] = __ldcg(g_ssqc + (layer * 16 + i) * 2048 + 128 * c + t2);
            const unsigned short xm = __ldcg((const unsigned short*)(ximg + (uint32_t)(c * 8 * 16384 + (t2 >> 3) * 128 + (t2 & 7) * 2)));
            {
                float tot = 0.f;
#pragma unroll
                for (int i = 0; i < 16; i++) tot += sqv[i];
                float rs = rsqrtf(tot * (1.f / 512.f) + 1e-5f);
                s_rstd[t2] = rs;
                s_rstd[128 + t2] = 2.f * rs;
                s_mean[t2] = layer == 0 ? 0.f : __uint_as_float((uint32_t)xm << 16) * (1.f / 512.f);
                TS(7 + 12 * layer);
                bar_arrive(4, 384);
            }
            acc_def(acc);
            bar_sync(14, 384);
#pragma unroll 1
            for (int it = 0; it < 4; it++) {
                const int sl = (it + 1) & 3;
                mbar_wait(BAR(B_AFULL + sl), fpar(0, 1, layer));
                if (sl == 0) { mbar_wait(BAR(B_AFULL + 4), fpar(0, 1, layer)); mbar_wait(BAR(B_AFULL + 5), fpar(0, 1, layer)); }
                const uint32_t xb = sl == 0 ? sb + SM_A + 4 * 16384 : sb + SM_X + (sl < 3 ? 2 * sl : 0) * 16384;
                wg_fence();
#pragma unroll
                for (int ks = 0; ks < 8; ks++)
                    wgmma_n128<1>(acc, desc_a(sb + SM_A + sl * 16384 + (ks >> 2) * 8192 + (ks & 3) * 256), desc_b<128>(xb + ks * 4096), 1);
                wg_commit();
                wg_wait<1>();
                if (it >= 1 && lane == 0) mbar_arrive(BAR(B_AEMPTY + it), 2);
                if (it == 2) {
                    if (lane == 0) mbar_arrive_remote(mapa(BAR(B_RFREE), par ^ 1));
                    bar_arrive(7, 384);
                }
            }
            wg_wait<0>();
            if (lane < 3) mbar_arrive(BAR(B_AEMPTY + (lane == 0 ? 0 : lane + 3)), 2);
            bar_sync(3, 128);
            TS(9 + 12 * layer);
            const int m0 = 16 * w + g;
            const uint32_t xoff = (uint32_t)((c * 8 + own) * 16384 + w * 4096 + g * 16 + 4 * q);
            if (layer == 0) {
                const uint8_t* xs = g_X + xoff;
#pragma unroll
                for (int i = 0; i < 16; i++) {
                    float2 rs = *(const float2*)(s_rstd + 8 * i + 2 * q);
                    uint32_t x0v = __ldcg((const uint32_t*)(xs + i * 128)), x1v = __ldcg((const uint32_t*)(xs + 2048 + i * 128));
                    acc[4 * i] = acc[4 * i] * rs.x + bf_lo(x0v);
                    acc[4 * i + 1] = acc[4 * i + 1] * rs.y + bf_hi(x0v);
                    acc[4 * i + 2] = acc[4 * i + 2] * rs.x + bf_lo(x1v);
                    acc[4 * i + 3] = acc[4 * i + 3] * rs.y + bf_hi(x1v);
                }
            } else {
                float d0 = ldbf(p.dskip + 64 * own + m0), d1 = ldbf(p.dskip + 64 * own + m0 + 8);
#pragma unroll
                for (int i = 0; i < 16; i++) {
                    float2 rs = *(const float2*)(s_rstd + 8 * i + 2 * q);
                    float2 mn = *(const float2*)(s_mean + 8 * i + 2 * q);
                    acc[4 * i] = acc[4 * i] * (1.f + rs.x * d0) + mn.x;
                    acc[4 * i + 1] = acc[4 * i + 1] * (1.f + rs.y * d0) + mn.y;
                    acc[4 * i + 2] = acc[4 * i + 2] * (1.f + rs.x * d1) + mn.x;
                    acc[4 * i + 3] = acc[4 * i + 3] * (1.f + rs.y * d1) + mn.y;
                }
            }
            TS(10 + 12 * layer);
            bar_sync(10, 384);
            TS(11 + 12 * layer);
            {
                float (&a0)[32] = *reinterpret_cast<float (*)[32]>(&acc[0]);
                float (&a1)[32] = *reinterpret_cast<float (*)[32]>(&acc[32]);
#pragma unroll 1
                for (int k = 0; k < 2; k++) {
                    const uint32_t hb = sb + SM_HH + (par ^ k) * 32768;
                    if (k == 1) {
                        mbar_wait(BAR(B_HPEER), layer);
                        mbar_wait(BAR(B_HPEER1), layer);
                        bar_sync(12, 384);
                    }
                    mbar_wait(BAR(B_AFULL + 4 + k), fpar(4, 2, layer));
                    const uint64_t da = c_desc(4 + k);
                    wg_fence();
#pragma unroll
                    for (int ks = 0; ks < 4; ks++) {
                        wgmma_n64s<1>(a0, da + ks * dstep, desc_b<64>(hb + ks * 2048), 1);
                        wgmma_n64s<1>(a1, da + ks * dstep, desc_b<64>(hb + 16384 + ks * 2048), 1);
                    }
#pragma unroll
                    for (int ks = 0; ks < 4; ks++) {
                        wgmma_n64s<-1>(a0, da + 512 + ks * dstep, desc_b<64>(hb + 8192 + ks * 2048), 1);
                        wgmma_n64s<-1>(a1, da + 512 + ks * dstep, desc_b<64>(hb + 16384 + 8192 + ks * 2048), 1);
                    }
                    wg_commit();
                }
                wg_wait<0>();
            }
#pragma unroll
            for (int i = 0; i < 16; i++)
                *(float4*)(sm + SM_A + 4 * 16384 + i * 2048 + t2 * 16) = make_float4(acc[4 * i], acc[4 * i + 1], acc[4 * i + 2], acc[4 * i + 3]);
            TS(12 + 12 * layer);
        }
        {
            const int t = tid & 127;
            const int nch = wg == 2 ? 2 : 3;
            const uint4* pb = g_P + (uint32_t)((c * 8 + r) * 4 * 1024 + wg * 128 + t);
            uint4 v[3][3];
            unsigned n = 0;
#pragma unroll 1
            while (true) {
                if (lane == 31) {
#pragma unroll 1
                    while (true) {
                        uint32_t bad = 0;
#pragma unroll
                        for (int sx = 0; sx < 3; sx++) {
                            uint32_t t0;
                            asm volatile("ld.relaxed.gpu.global.u32 %0, [%1];" : "=r"(t0) : "l"(pb + ((pi_ + 1 + sx) & 3) * 1024 + (nch - 1) * 384) : "memory");
                            bad |= t0 ^ ptag;
                        }
                        if (!(bad & 0x00010001u) || ++n >= SPIN_LIMIT) break;
                    }
                }
                __syncwarp();
                uint32_t bad = 0;
#pragma unroll
                for (int k = 0; k < 3; k++)
#pragma unroll
                    for (int sx = 0; sx < 3; sx++) {
                        v[k][sx] = make_uint4(ptag, 0, 0, 0);
                        if (k < nch) v[k][sx] = ld_relaxed_u4(pb + ((pi_ + 1 + sx) & 3) * 1024 + k * 384);
                        bad |= v[k][sx].x ^ ptag;
                    }
                if (!__any_sync(~0u, bad & 0x00010001u) || ++n >= SPIN_LIMIT) break;
            }
            bar_sync(8, 384);
            TS(13 + 12 * layer);
            const int m0 = 16 * w + g;
            const float w0 = (own == 0 && m0 < 2) ? (m0 == 0 ? 0.f : 0.5f) : 1.f;
#pragma unroll
            for (int k = 0; k < 3; k++) {
                if (k < nch) {
                    const int i = wg + 3 * k;
                    float4 a = *(const float4*)(sm + SM_A + 4 * 16384 + (2 * i) * 2048 + t * 16);
                    float4 bq = *(const float4*)(sm + SM_A + 4 * 16384 + (2 * i + 1) * 2048 + t * 16);
#pragma unroll
                    for (int sx = 0; sx < 3; sx++) {
                        a.x += bf_lo(v[k][sx].x); a.y += bf_hi(v[k][sx].x); a.z += bf_lo(v[k][sx].y); a.w += bf_hi(v[k][sx].y);
                        bq.x += bf_lo(v[k][sx].z); bq.y += bf_hi(v[k][sx].z); bq.z += bf_lo(v[k][sx].w); bq.w += bf_hi(v[k][sx].w);
                    }
                    if (layer == 0) {
                        uint8_t* xd = g_X + (uint32_t)((16 * 8 + c * 8 + own) * 16384 + w * 4096 + g * 16 + 4 * q + i * 256);
                        uint32_t v0 = pack_bf16(a.x, a.y), v1 = pack_bf16(a.z, a.w), v2 = pack_bf16(bq.x, bq.y), v3 = pack_bf16(bq.z, bq.w);
                        *(uint32_t*)(xd) = v0; *(uint32_t*)(xd + 2048) = v1; *(uint32_t*)(xd + 128) = v2; *(uint32_t*)(xd + 2048 + 128) = v3;
                        float sq[4];
                        sq[0] = w0 * bf_lo(v0) * bf_lo(v0) + bf_lo(v1) * bf_lo(v1);
                        sq[1] = w0 * bf_hi(v0) * bf_hi(v0) + bf_hi(v1) * bf_hi(v1);
                        sq[2] = w0 * bf_lo(v2) * bf_lo(v2) + bf_lo(v3) * bf_lo(v3);
                        sq[3] = w0 * bf_hi(v2) * bf_hi(v2) + bf_hi(v3) * bf_hi(v3);
                        float u0 = (g & 1) ? sq[2] : sq[0], u1 = (g & 1) ? sq[3] : sq[1];
                        u0 += __shfl_xor_sync(~0u, (g & 1) ? sq[0] : sq[2], 4);
                        u1 += __shfl_xor_sync(~0u, (g & 1) ? sq[1] : sq[3], 4);
                        float z = (g & 2) ? u1 : u0;
                        z += __shfl_xor_sync(~0u, (g & 2) ? u0 : u1, 8);
                        z += __shfl_xor_sync(~0u, z, 16);
                        if (g < 4) atomicAdd(s_mean + 16 * i + 8 * (g & 1) + 2 * q + (g >> 1), z);
                    } else {
                        float* o = p.out + (uint32_t)((128 * c + 32 * q + 4 * i) * 512 + 64 * own + m0);
                        o[0] = a.x; o[512] = a.y; o[8] = a.z; o[512 + 8] = a.w;
                        o[1024] = bq.x; o[1536] = bq.y; o[1024 + 8] = bq.z; o[1536 + 8] = bq.w;
                    }
                }
            }
            if (wg < 2) mbar_wait_cluster(BAR(B_HDONE), layer);
            if (layer == 0) {
                fence_async_smem();
                bar_sync(9, 384);
                TS(14 + 12 * layer);
                if (wg == 2) {
                    atomicAdd(g_ssq + 2048 + 128 * c + t, s_mean[t] * (2.f / 512.f));
                    bar_sync(3, 128);
                    if (lane == 0) { mbar_arrive(BAR(B_AEMPTY + 4), 2); mbar_arrive(BAR(B_AEMPTY + 5), 2); }
                    if (t == 0) { fence_async(); red_release(&g_bar[2], 1); }
                }
            }
        }
        TS(15 + 12 * layer);
        if (wg == 0) TC(31);
    }
}

typedef CUresult (*EncFn)(CUtensorMap*, CUtensorMapDataType, cuuint32_t, void*, const cuuint64_t*, const cuuint64_t*,
                          const cuuint32_t*, const cuuint32_t*, CUtensorMapInterleave, CUtensorMapSwizzle,
                          CUtensorMapL2promotion, CUtensorMapFloatOOBfill);

void launch_impl(void* const* d_in, void* d_out, int stop) {
    static EncFn enc = nullptr;
    if (!enc) {
        void* fn = nullptr;
        cudaDriverEntryPointQueryResult qr;
        cudaGetDriverEntryPoint("cuTensorMapEncodeTiled", &fn, cudaEnableDefault, &qr);
        enc = (EncFn)fn;
        cudaFuncSetAttribute(fused_kernel, cudaFuncAttributeMaxDynamicSharedMemorySize, SM_TOTAL);
    }
    CUtensorMap tx, tbr, tbi, tcr, tci, tcol;
    {
        void* gx = nullptr;
        cudaGetSymbolAddress(&gx, g_X);
        cuuint64_t gd[5] = {64, 16, 64, 16, 2};
        cuuint64_t gs[4] = {128, 2048, 128 * 1024, 2048 * 1024};
        cuuint32_t bx[5] = {32, 16, 1, 16, 1};
        cuuint32_t es[5] = {1, 1, 1, 1, 1};
        enc(&tcol, CU_TENSOR_MAP_DATA_TYPE_BFLOAT16, 5, gx, gd, gs, bx, es, CU_TENSOR_MAP_INTERLEAVE_NONE,
            CU_TENSOR_MAP_SWIZZLE_64B, CU_TENSOR_MAP_L2_PROMOTION_NONE, CU_TENSOR_MAP_FLOAT_OOB_FILL_NONE);
    }
    {
        cuuint64_t gd[5] = {512, 2, 4, 16, 16};
        cuuint64_t gs[4] = {1024, 32 * 1024, 2 * 1024, 128 * 1024};
        cuuint32_t bx[5] = {64, 2, 4, 8, 1};
        cuuint32_t es[5] = {1, 1, 1, 1, 1};
        enc(&tx, CU_TENSOR_MAP_DATA_TYPE_BFLOAT16, 5, d_in[0], gd, gs, bx, es, CU_TENSOR_MAP_INTERLEAVE_NONE,
            CU_TENSOR_MAP_SWIZZLE_128B, CU_TENSOR_MAP_L2_PROMOTION_L2_128B, CU_TENSOR_MAP_FLOAT_OOB_FILL_NONE);
    }
    auto mk2 = [&](CUtensorMap* m, void* ptr, cuuint32_t rows) {
        cuuint64_t gd[2] = {512, 512};
        cuuint64_t gs[1] = {1024};
        cuuint32_t bx[2] = {64, rows};
        cuuint32_t es[2] = {1, 1};
        enc(m, CU_TENSOR_MAP_DATA_TYPE_BFLOAT16, 2, ptr, gd, gs, bx, es, CU_TENSOR_MAP_INTERLEAVE_NONE,
            CU_TENSOR_MAP_SWIZZLE_128B, CU_TENSOR_MAP_L2_PROMOTION_L2_128B, CU_TENSOR_MAP_FLOAT_OOB_FILL_NONE);
    };
    mk2(&tbr, d_in[6], 32);
    mk2(&tbi, d_in[7], 32);
    mk2(&tcr, d_in[8], 64);
    mk2(&tci, d_in[9], 64);
    Params p;
    p.x0 = (const __nv_bfloat16*)d_in[0];
    p.w_r = (const __nv_bfloat16*)d_in[1];
    p.w_i = (const __nv_bfloat16*)d_in[2];
    p.lam_re = (const __nv_bfloat16*)d_in[4];
    p.lam_im = (const __nv_bfloat16*)d_in[5];
    p.log_dt = (const __nv_bfloat16*)d_in[10];
    p.dskip = (const __nv_bfloat16*)d_in[11];
    p.out = (float*)d_out;
    p.stop = stop;
    cudaLaunchConfig_t cfg = {};
    cfg.gridDim = dim3(NCTA); cfg.blockDim = dim3(NTHREADS); cfg.dynamicSmemBytes = SM_TOTAL; cfg.stream = cudaStreamPerThread;
    cudaLaunchAttribute at[1];
    at[0].id = cudaLaunchAttributeClusterDimension;
    at[0].val.clusterDim.x = 2; at[0].val.clusterDim.y = 1; at[0].val.clusterDim.z = 1;
    cfg.attrs = at; cfg.numAttrs = 1;
    cudaLaunchKernelEx(&cfg, fused_kernel, tx, tbr, tbi, tcr, tci, tcol, p);
}

}

extern "C" void kernel_launch(void* const* d_in, const int* in_sizes, int n_in, void* d_out, int out_size) {
    (void)in_sizes; (void)n_in; (void)out_size;
    launch_impl(d_in, d_out, 100);
}
```

```cpp
#include <cuda_runtime.h>
#include <cuda_bf16.h>
#include <cuda.h>
#include <stdint.h>

namespace {

constexpr int NCTA = 128;
constexpr int NTHREADS = 512;
constexpr int SM_A = 0;
constexpr int SM_X = 131072;
constexpr int SM_H = 196608;
constexpr int SM_HH = SM_X + 32768;
constexpr int SM_M = 229376;
constexpr int SM_TOTAL = 232448;
constexpr int SM_BAR = SM_M;
constexpr int SM_TGT = SM_M + 400;
constexpr int SM_LAM = SM_M + 424;
constexpr int SM_TAB = SM_M + 944;
constexpr int SM_RSTD = SM_M + 1920;
constexpr int SM_MEAN = SM_TAB;
constexpr int SM_T64 = SM_M + 2944;
constexpr int SM_B1ST = SM_H + 24576;
constexpr int SM_RAW = SM_X + 40960;
constexpr int SM_SSQ = SM_X + 57344;
constexpr int B_FULL0 = 0;
constexpr int B_EMPTY0 = 8;
constexpr int B_FULLC = 12;
constexpr int B_AFULL = 13;
constexpr int B_AEMPTY = 21;
constexpr int B_XFULL = 29;
constexpr int B_XEMPTY = 35;
constexpr int B_AFREE = 37;
constexpr int B_COL = 38;
constexpr int B_SSQ = 39;
constexpr int B_HPEER = 40;
constexpr int B_RFREE = 41;
constexpr int B_HDONE = 42;
constexpr int B_WRDY = 43;
constexpr int B_HPEER1 = 44;
constexpr int B_FULLB = 45;
constexpr int B_BFREE = 46;
constexpr int B_SETUP = 47;
constexpr int B_B1DONE = 48;
constexpr int B_WST = 49;
constexpr int NBARS = 50;

__device__ __align__(1024) uint8_t g_X[2 * 16 * 8 * 16384];
__device__ __align__(1024) uint8_t g_A1[8 * 8 * 16384];
__device__ __align__(1024) uint8_t g_A2[8 * 8 * 16384];
__device__ __align__(1024) uint8_t g_E[2 * 8 * 8 * 8192];
__device__ __align__(16) float g_ssq[2 * 2048];
__device__ __align__(16) float g_ssqc[2 * 16 * 2048];
__device__ __align__(16) float g_Dh[512];
__device__ __align__(16) uint4 g_Wfrag[128 * 4 * 256];
__device__ __align__(16) float4 g_Ebuf[2 * 16 * 512];
__device__ __align__(16) uint4 g_P[16 * 8 * 4 * 1024];
__device__ unsigned g_bar[8];
__device__ unsigned g_err;
#define TX(i)
#define TQ(i)
#define TS(i)
#define TC(i)

constexpr unsigned SPIN_LIMIT = 1u << 22;

__device__ __forceinline__ uint32_t s2u(const void* p) { return (uint32_t)__cvta_generic_to_shared(p); }
__device__ __forceinline__ void mbar_init(uint32_t a, uint32_t c) {
    asm volatile("mbarrier.init.shared::cta.b64 [%0], %1;" ::"r"(a), "r"(c) : "memory");
}
__device__ __forceinline__ void mbar_expect(uint32_t a, uint32_t bytes) {
    asm volatile("mbarrier.arrive.expect_tx.shared::cta.b64 _, [%0], %1;" ::"r"(a), "r"(bytes) : "memory");
}
__device__ __forceinline__ void mbar_arrive(uint32_t a, uint32_t cnt) {
    asm volatile("mbarrier.arrive.shared::cta.b64 _, [%0], %1;" ::"r"(a), "r"(cnt) : "memory");
}
__device__ __forceinline__ bool mbar_try(uint32_t a, uint32_t parity) {
    uint32_t ok;
    asm volatile("{\n.reg .pred p;\nmbarrier.try_wait.parity.shared::cta.b64 p, [%1], %2;\nselp.u32 %0, 1, 0, p;\n}"
                 : "=r"(ok) : "r"(a), "r"(parity) : "memory");
    return ok != 0;
}
__device__ __forceinline__ void mbar_wait(uint32_t a, uint32_t parity) {
    asm volatile("{\n.reg .pred p, q;\n.reg .u32 n;\nmov.u32 n, 0;\n"
                 "W_%=:\nmbarrier.try_wait.parity.shared::cta.b64 p, [%0], %1;\n@p bra D_%=;\n"
                 "add.u32 n, n, 1;\nsetp.lt.u32 q, n, 4194304;\n@q bra W_%=;\nD_%=:\n}" ::"r"(a), "r"(parity) : "memory");
}
__device__ __forceinline__ void bulk_g2s(uint32_t dst, const void* src, uint32_t bytes, uint32_t bar) {
    asm volatile("cp.async.bulk.shared::cluster.global.mbarrier::complete_tx::bytes [%0], [%1], %2, [%3];" ::"r"(dst),
                 "l"(src), "r"(bytes), "r"(bar) : "memory");
}
__device__ __forceinline__ void tma_2d(uint32_t dst, const CUtensorMap* m, int c0, int c1, uint32_t bar) {
    asm volatile("cp.async.bulk.tensor.2d.shared::cluster.global.mbarrier::complete_tx::bytes [%0], [%1, {%3,%4}], [%2];" ::"r"(dst),
                 "l"(m), "r"(bar), "r"(c0), "r"(c1) : "memory");
}
__device__ __forceinline__ void tma_5d(uint32_t dst, const CUtensorMap* m, int c0, int c1, int c2, int c3, int c4, uint32_t bar) {
    asm volatile("cp.async.bulk.tensor.5d.shared::cluster.global.mbarrier::complete_tx::bytes [%0], [%1, {%3,%4,%5,%6,%7}], [%2];" ::"r"(dst),
                 "l"(m), "r"(bar), "r"(c0), "r"(c1), "r"(c2), "r"(c3), "r"(c4) : "memory");
}
__device__ __forceinline__ void tma_2d_mc(uint32_t dst, const CUtensorMap* m, int c0, int c1, uint32_t bar) {
    asm volatile("cp.async.bulk.tensor.2d.shared::cluster.global.mbarrier::complete_tx::bytes.multicast::cluster [%0], [%1, {%3,%4}], [%2], %5;" ::"r"(dst),
                 "l"(m), "r"(bar), "r"(c0), "r"(c1), "h"((unsigned short)3) : "memory");
}
__device__ __forceinline__ void tma_5d_mc(uint32_t dst, const CUtensorMap* m, int c0, int c1, int c2, int c3, int c4, uint32_t bar) {
    asm volatile("cp.async.bulk.tensor.5d.shared::cluster.global.mbarrier::complete_tx::bytes.multicast::cluster [%0], [%1, {%3,%4,%5,%6,%7}], [%2], %8;" ::"r"(dst),
                 "l"(m), "r"(bar), "r"(c0), "r"(c1), "r"(c2), "r"(c3), "r"(c4), "h"((unsigned short)3) : "memory");
}
__device__ __forceinline__ void bulk_g2s_mc(uint32_t dst, const void* src, uint32_t bytes, uint32_t bar) {
    asm volatile("cp.async.bulk.shared::cluster.global.mbarrier::complete_tx::bytes.multicast::cluster [%0], [%1], %2, [%3], %4;" ::"r"(dst),
                 "l"(src), "r"(bytes), "r"(bar), "h"((unsigned short)3) : "memory");
}
__device__ __forceinline__ void tma_store_5d(const CUtensorMap* m, int c0, int c1, int c2, int c3, int c4, uint32_t src) {
    asm volatile("cp.async.bulk.tensor.5d.global.shared::cta.bulk_group [%0, {%2,%3,%4,%5,%6}], [%1];" ::"l"(m), "r"(src),
                 "r"(c0), "r"(c1), "r"(c2), "r"(c3), "r"(c4) : "memory");
}
__device__ __forceinline__ uint32_t lds32(uint32_t a) { uint32_t v; asm volatile("ld.shared.u32 %0, [%1];" : "=r"(v) : "r"(a) : "memory"); return v; }
__device__ __forceinline__ uint4 ld_relaxed_u4(const uint4* p) {
    uint4 v;
    asm volatile("ld.relaxed.gpu.global.v4.u32 {%0,%1,%2,%3}, [%4];" : "=r"(v.x), "=r"(v.y), "=r"(v.z), "=r"(v.w) : "l"(p) : "memory");
    return v;
}
__device__ __forceinline__ void fence_async() { asm volatile("fence.proxy.async.global;" ::: "memory"); }
__device__ __forceinline__ void red_relaxed(unsigned* p, unsigned v) {
    asm volatile("red.relaxed.gpu.global.add.u32 [%0], %1;" ::"l"(p), "r"(v) : "memory");
}
__device__ __forceinline__ uint32_t mapa(uint32_t a, uint32_t rank) {
    uint32_t d;
    asm("mapa.shared::cluster.u32 %0, %1, %2;" : "=r"(d) : "r"(a), "r"(rank));
    return d;
}
__device__ __forceinline__ void mbar_arrive_remote(uint32_t ra) {
    asm volatile("mbarrier.arrive.relaxed.cluster.shared::cluster.b64 _, [%0];" ::"r"(ra) : "memory");
}
__device__ __forceinline__ void mbar_wait_cluster(uint32_t a, uint32_t parity) {
    asm volatile("{\n.reg .pred p, q;\n.reg .u32 n;\nmov.u32 n, 0;\n"
                 "W_%=:\nmbarrier.try_wait.parity.acquire.cluster.shared::cta.b64 p, [%0], %1;\n@p bra D_%=;\n"
                 "add.u32 n, n, 1;\nsetp.lt.u32 q, n, 4194304;\n@q bra W_%=;\nD_%=:\n}" ::"r"(a), "r"(parity) : "memory");
}
__device__ __forceinline__ void bulk_s2peer(uint32_t rdst, uint32_t src, uint32_t bytes, uint32_t rbar) {
    asm volatile("cp.async.bulk.shared::cluster.shared::cta.mbarrier::complete_tx::bytes [%0], [%1], %2, [%3];" ::"r"(rdst),
                 "r"(src), "r"(bytes), "r"(rbar) : "memory");
}
__device__ __forceinline__ void fence_async_smem() { asm volatile("fence.proxy.async.shared::cta;" ::: "memory"); }
__device__ __forceinline__ void wg_fence() { asm volatile("wgmma.fence.sync.aligned;" ::: "memory"); }
__device__ __forceinline__ void wg_commit() { asm volatile("wgmma.commit_group.sync.aligned;" ::: "memory"); }
template <int N> __device__ __forceinline__ void wg_wait() { asm volatile("wgmma.wait_group.sync.aligned %0;" ::"n"(N) : "memory"); }
__device__ __forceinline__ void bar_sync(int id, int n) { asm volatile("bar.sync %0, %1;" ::"r"(id), "r"(n) : "memory"); }
__device__ __forceinline__ void bar_arrive(int id, int n) { asm volatile("bar.arrive %0, %1;" ::"r"(id), "r"(n) : "memory"); }
__device__ __forceinline__ unsigned ld_acquire(const unsigned* p) {
    unsigned v;
    asm volatile("ld.acquire.gpu.global.u32 %0, [%1];" : "=r"(v) : "l"(p) : "memory");
    return v;
}
__device__ __forceinline__ void red_release(unsigned* p, unsigned v) {
    asm volatile("red.release.gpu.global.add.u32 [%0], %1;" ::"l"(p), "r"(v) : "memory");
}
__device__ __forceinline__ void wait_count(const unsigned* p, unsigned target) {
    unsigned n = 0;
#pragma unroll 1
    while ((int)(ld_acquire(p) - target) < 0 && ++n < SPIN_LIMIT) {}
}
__device__ __forceinline__ float4 ld_relaxed_f4(const float4* p) {
    float4 v;
    asm volatile("ld.relaxed.gpu.global.v4.f32 {%0,%1,%2,%3}, [%4];" : "=f"(v.x), "=f"(v.y), "=f"(v.z), "=f"(v.w) : "l"(p) : "memory");
    return v;
}
__device__ __forceinline__ void st_relaxed_f4(float4* p, float4 v) {
    asm volatile("st.relaxed.gpu.global.v4.f32 [%0], {%1,%2,%3,%4};" ::"l"(p), "f"(v.x), "f"(v.y), "f"(v.z), "f"(v.w) : "memory");
}
__device__ __forceinline__ uint32_t pack_bf16(float lo, float hi) {
    uint32_t r;
    asm("cvt.rn.bf16x2.f32 %0, %1, %2;" : "=r"(r) : "f"(hi), "f"(lo));
    return r;
}
__device__ __forceinline__ uint32_t hmul2(uint32_t a, uint32_t b) {
    uint32_t r;
    asm("mul.rn.bf16x2 %0, %1, %2;" : "=r"(r) : "r"(a), "r"(b));
    return r;
}
__device__ __forceinline__ uint32_t hfma2(uint32_t a, uint32_t b, uint32_t c) {
    uint32_t r;
    asm("fma.rn.bf16x2 %0, %1, %2, %3;" : "=r"(r) : "r"(a), "r"(b), "r"(c));
    return r;
}
__device__ __forceinline__ float bf_lo(uint32_t v) { return __uint_as_float(v << 16); }
__device__ __forceinline__ float bf_hi(uint32_t v) { return __uint_as_float(v & 0xffff0000u); }
__device__ __forceinline__ void sts32(uint32_t a, uint32_t v) { asm volatile("st.shared.u32 [%0], %1;" ::"r"(a), "r"(v) : "memory"); }
__device__ __forceinline__ void sts128(uint32_t a, uint4 v) {
    asm volatile("st.shared.v4.u32 [%0], {%1,%2,%3,%4};" ::"r"(a), "r"(v.x), "r"(v.y), "r"(v.z), "r"(v.w) : "memory");
}

__device__ __forceinline__ uint64_t mkdesc(uint32_t lo, uint32_t hi) { return ((uint64_t)hi << 32) | lo; }
#define DOFF(addr) (sb4 + (((addr) - sb) >> 4))
#define desc_a(addr) mkdesc(DOFF(addr) + (8u << 16), 64u)
#define desc_b64(addr) mkdesc(DOFF(addr) + (64u << 16), 8u)
#define desc_b128(addr) mkdesc(DOFF(addr) + (128u << 16), 8u)
#define desc_k(addr) mkdesc(DOFF(addr) + (1u << 16), 64u | (1u << 30))
#define desc_mn(addr) mkdesc(DOFF(addr) + (512u << 16), 64u | (1u << 30))

#define ACC8(d, o) "+f"(d[o + 0]), "+f"(d[o + 1]), "+f"(d[o + 2]), "+f"(d[o + 3]), "+f"(d[o + 4]), "+f"(d[o + 5]), "+f"(d[o + 6]), "+f"(d[o + 7])
template <int TB, int SA = 1>
__device__ __forceinline__ void wgmma_n128(float (&d)[64], uint64_t da, uint64_t db, int sd) {
    asm volatile(
        "{\n.reg .pred p;\nsetp.ne.b32 p, %66, 0;\n"
        "wgmma.mma_async.sync.aligned.m64n128k16.f32.bf16.bf16 "
        "{%0,%1,%2,%3,%4,%5,%6,%7,%8,%9,%10,%11,%12,%13,%14,%15,%16,%17,%18,%19,%20,%21,%22,%23,%24,%25,%26,%27,%28,%29,%30,%31,"
        "%32,%33,%34,%35,%36,%37,%38,%39,%40,%41,%42,%43,%44,%45,%46,%47,%48,%49,%50,%51,%52,%53,%54,%55,%56,%57,%58,%59,%60,%61,%62,%63},"
        " %64, %65, p, %68, 1, 0, %67;\n}"
        : ACC8(d, 0), ACC8(d, 8), ACC8(d, 16), ACC8(d, 24), ACC8(d, 32), ACC8(d, 40), ACC8(d, 48), ACC8(d, 56)
        : "l"(da), "l"(db), "r"(sd), "n"(TB), "n"(SA));
}
template <int N> __device__ __forceinline__ void acc_def(float (&d)[N]) {
#pragma unroll
    for (int i = 0; i < N; i++) d[i] = 0.f;
}
template <int TB>
__device__ __forceinline__ void wgmma_n64(float (&d)[32], uint64_t da, uint64_t db, int sd) {
    asm volatile(
        "{\n.reg .pred p;\nsetp.ne.b32 p, %34, 0;\n"
        "wgmma.mma_async.sync.aligned.m64n64k16.f32.bf16.bf16 "
        "{%0,%1,%2,%3,%4,%5,%6,%7,%8,%9,%10,%11,%12,%13,%14,%15,%16,%17,%18,%19,%20,%21,%22,%23,%24,%25,%26,%27,%28,%29,%30,%31},"
        " %32, %33, p, 1, 1, 0, %35;\n}"
        : ACC8(d, 0), ACC8(d, 8), ACC8(d, 16), ACC8(d, 24)
        : "l"(da), "l"(db), "r"(sd), "n"(TB));
}
template <int SA>
__device__ __forceinline__ void wgmma_n64s(float (&d)[32], uint64_t da, uint64_t db, int sd) {
    asm volatile(
        "{\n.reg .pred p;\nsetp.ne.b32 p, %34, 0;\n"
        "wgmma.mma_async.sync.aligned.m64n64k16.f32.bf16.bf16 "
        "{%0,%1,%2,%3,%4,%5,%6,%7,%8,%9,%10,%11,%12,%13,%14,%15,%16,%17,%18,%19,%20,%21,%22,%23,%24,%25,%26,%27,%28,%29,%30,%31},"
        " %32, %33, p, %35, 1, 0, 1;\n}"
        : ACC8(d, 0), ACC8(d, 8), ACC8(d, 16), ACC8(d, 24)
        : "l"(da), "l"(db), "r"(sd), "n"(SA));
}
__device__ __forceinline__ void wgmma_n64_rs(float (&d)[32], uint32_t a0, uint32_t a1, uint32_t a2, uint32_t a3, uint64_t db, int sd) {
    asm volatile(
        "{\n.reg .pred p;\nsetp.ne.b32 p, %37, 0;\n"
        "wgmma.mma_async.sync.aligned.m64n64k16.f32.bf16.bf16 "
        "{%0,%1,%2,%3,%4,%5,%6,%7,%8,%9,%10,%11,%12,%13,%14,%15,%16,%17,%18,%19,%20,%21,%22,%23,%24,%25,%26,%27,%28,%29,%30,%31},"
        " {%32,%33,%34,%35}, %36, p, 1, 1, 1;\n}"
        : ACC8(d, 0), ACC8(d, 8), ACC8(d, 16), ACC8(d, 24)
        : "r"(a0), "r"(a1), "r"(a2), "r"(a3), "l"(db), "r"(sd));
}

struct Params {
    const __nv_bfloat16* x0;
    const __nv_bfloat16* w_r;
    const __nv_bfloat16* w_i;
    const __nv_bfloat16* lam_re;
    const __nv_bfloat16* lam_im;
    const __nv_bfloat16* log_dt;
    const __nv_bfloat16* dskip;
    float* out;
    int stop;
};

__device__ __forceinline__ uint32_t fpar(int s, int k, int L) { return s < 6 ? (uint32_t)((L + k) & 1) : (uint32_t)(k == 2); }
__device__ __forceinline__ int cslot(int v) { return (0x54032176u >> (4 * v)) & 7; }
__device__ __forceinline__ float ldbf(const __nv_bfloat16* p) { return __bfloat162float(*p); }

__device__ __forceinline__ void dft_fp(int j, int& f, int& ph) {
    int cs = j >> 1;
    if (j == 1) { f = 256; ph = 0; }
    else { f = cs; ph = (j & 1) ? 128 : 0; }
}

__device__ __forceinline__ void gen_col_consts(uint32_t sb, int tid) {
#pragma unroll 1
    for (int task = tid; task < 640; task += 256) {
        int f, c8;
        uint32_t a_cc, d_pi, d_po;
        if (task < 512) {
            f = task & 63; c8 = task >> 6;
            a_cc = sb + SM_X + (f >> 5) * 16384 + ((f >> 3) & 3) * 2048 + c8 * 128 + (f & 7) * 16;
            d_pi = 8192; d_po = 1024;
        } else {
            int n2 = task & 31;
            f = 2 * n2; c8 = (task >> 5) & 3;
            a_cc = sb + SM_X + 32768 + (n2 >> 3) * 1024 + c8 * 128 + (n2 & 7) * 16;
            d_pi = 4096; d_po = 512;
        }
        float cd, sd, cs, sn;
        __sincosf((float)(f >= 32 ? f - 64 : f) * (6.283185307179586f / 64.f), &sd, &cd);
        int a = (8 * c8 * f) & 63;
        __sincosf((float)(a >= 32 ? a - 64 : a) * (6.283185307179586f / 64.f), &sn, &cs);
        float cv[8], sv[8];
#pragma unroll
        for (int e = 0; e < 8; e++) {
            cv[e] = cs; sv[e] = sn;
            float t = cs * cd - sn * sd;
            sn = sn * cd + cs * sd;
            cs = t;
        }
        uint4 oc = make_uint4(pack_bf16(cv[0], cv[1]), pack_bf16(cv[2], cv[3]), pack_bf16(cv[4], cv[5]), pack_bf16(cv[6], cv[7]));
        uint4 os = make_uint4(pack_bf16(sv[0], sv[1]), pack_bf16(sv[2], sv[3]), pack_bf16(sv[4], sv[5]), pack_bf16(sv[6], sv[7]));
        sts128(a_cc, oc);
        sts128(a_cc + d_pi, os);
        sts128(a_cc + d_po, make_uint4(os.x ^ 0x80008000u, os.y ^ 0x80008000u, os.z ^ 0x80008000u, os.w ^ 0x80008000u));
        sts128(a_cc + d_pi + d_po, oc);
    }
}

__global__ void __launch_bounds__(NTHREADS, 1)
fused_kernel(const __grid_constant__ CUtensorMap tm_x, const __grid_constant__ CUtensorMap tm_bre,
             const __grid_constant__ CUtensorMap tm_bim, const __grid_constant__ CUtensorMap tm_cre,
             const __grid_constant__ CUtensorMap tm_cim, const __grid_constant__ CUtensorMap tm_col, const Params p) {
    extern __shared__ __align__(1024) uint8_t sm[];
    const uint32_t sb = s2u(sm);
    const uint32_t sb4 = (sb & 0x3FFFF) >> 4;
    const int tid = threadIdx.x, b = blockIdx.x;
    const int c = b >> 3, r = b & 7;
    const int par = r & 1, pi_ = r >> 1, own = 4 * par + pi_;
    const int wg = __shfl_sync(~0u, tid >> 7, 0), w = __shfl_sync(~0u, (tid >> 5) & 3, 0), lane = tid & 31, g = lane >> 2, q = lane & 3;
    auto BAR = [&](int i) { return sb + SM_BAR + 8 * i; };
    unsigned* s_tgt = (unsigned*)(sm + SM_TGT);

    if (tid < NBARS) {
        int cnt = 1;
        if (tid >= B_EMPTY0 && tid < B_EMPTY0 + 4) cnt = 16;
        if (tid >= B_XEMPTY && tid < B_XEMPTY + 2) cnt = 16;
        if (tid == B_RFREE) cnt = 12;
        if (tid == B_HDONE || tid == B_WST) cnt = 2;
        if ((tid >= B_AEMPTY && tid < B_AEMPTY + 8) || tid == B_BFREE) cnt = 8;
        if (tid == B_AFREE) cnt = 4;
        mbar_init(BAR(tid), cnt);
        asm volatile("fence.mbarrier_init.release.cluster;" ::: "memory");
    }
    asm volatile("barrier.cluster.arrive.release.aligned;" ::: "memory");

    if (wg == 3) {
        asm volatile("setmaxnreg.dec.sync.aligned.u32 56;");
        if (w == 0 && lane < 6) {
            const CUtensorMap* tm = lane == 0 ? &tm_x : lane == 1 ? &tm_bre : lane == 2 ? &tm_bim : lane == 3 ? &tm_cre : lane == 4 ? &tm_cim : &tm_col;
            asm volatile("prefetch.tensormap [%0];" ::"l"(tm) : "memory");
        }
        __syncwarp();
        asm volatile("barrier.cluster.wait.acquire.aligned;" ::: "memory");
        if (w > 0) {
            if (w == 1) {
                float lr[3], li[3], ld[3];
#pragma unroll
                for (int k = 0; k < 3; k++) {
                    int ps = k < 2 ? 64 * r + 32 * k + lane : 32 * c + lane;
                    lr[k] = ldbf(p.lam_re + ps); li[k] = ldbf(p.lam_im + ps); ld[k] = ldbf(p.log_dt + ps);
                }
                if (lane < 6) s_tgt[lane] = ((ld_acquire(&g_bar[lane]) >> 7) + 1u) << 7;
#pragma unroll 1
                for (int k = 0; k < 3; k++) {
                    float a = k == 0 ? lr[0] : (k == 1 ? lr[1] : lr[2]), bq = k == 0 ? li[0] : (k == 1 ? li[1] : li[2]);
                    float dt = __bfloat162float(__float2bfloat16(expf(k == 0 ? ld[0] : (k == 1 ? ld[1] : ld[2]))));
                    float mag = expf(a * dt), t = bq * dt * 0.15915494309189535f, sn, cs;
                    t -= rintf(t);
                    sincospif(2.f * t, &sn, &cs);
                    float er = mag * cs, ei = mag * sn;
                    if (k < 2) {
                        *(float2*)(sm + SM_LAM + (32 * k + lane) * 8) = make_float2(er, ei);
                    } else {
                        er -= 1.f;
                        float inv = 1.f / (a * a + bq * bq);
                        *(float2*)(sm + SM_TAB + lane * 8) = make_float2((er * a + ei * bq) * inv, (ei * a - er * bq) * inv);
                    }
                }
                __syncwarp();
                bar_arrive(15, 160);
                if (lane == 0) mbar_arrive(BAR(B_SETUP), 1);
            }
            if (w == 2 && lane < 2) {
                const char* src = (const char*)(lane ? p.w_i : p.w_r) + (size_t)b * 8224;
                asm volatile("cp.async.bulk.prefetch.L2.global [%0], 8224;" ::"l"(src) : "memory");
            }
#pragma unroll 1
            for (int i = tid - 448; i < 96 + 128 && w > 1; i += 64) {
                if (i < 96) g_P[(uint32_t)(b * 4 + i / 24) * 1024 + 640 + ((i % 24) >> 1) * 32 + 30 + (i & 1)] = make_uint4(0, 0, 0, 0);
                else g_Ebuf[b * 128 + i - 96] = make_float4(0.f, 0.f, 0.f, 0.f);
            }
            __syncwarp();
            if (w > 1) bar_sync(0, 192);
            if (tid == 448) TX(14);
            if (w > 1) {
                if (lane < 8) {
                    const int cl = 8 * (w - 2) + lane;
                    asm volatile("cp.async.bulk.global.shared::cta.bulk_group [%0], [%1], 1024;" ::"l"(g_Wfrag + (uint32_t)((16 * (b & 7) + cl) * 1024 + (b >> 3) * 64)),
                                 "r"(sb + SM_H + cl * 1024) : "memory");
                }
                asm volatile("cp.async.bulk.commit_group;" ::: "memory");
                asm volatile("cp.async.bulk.wait_group 0;" ::: "memory");
                fence_async();
                __syncwarp();
                if (lane == 0) mbar_arrive(BAR(B_WST), 1);
                if (tid == 448) TX(15);
            }
            __syncwarp();
            if (w == 3) bar_arrive(11, 192);
            if (w == 2) {
                bar_sync(11, 192);
                if (lane == 0) { TX(7); red_release(&g_bar[4], 1);  }
            }
            if (w == 3) {
#pragma unroll 1
                for (int it = 0; it < 8; it++) {
                    const int m = 4 * c + (it >> 1), d = 64 * r + m, ch = lane + 32 * (it & 1);
                    float v[8];
#pragma unroll
                    for (int e = 0; e < 8; e++) {
                        int j = 8 * ch + e, f, ph;
                        dft_fp(j, f, ph);
                        int a = (d * f + ph) & 511;
                        a = a >= 256 ? a - 512 : a;
                        float wj = j == 0 ? 0.f : (j == 1 ? 1.f / 512.f : 2.f / 512.f);
                        v[e] = wj * __cosf((float)a * (6.283185307179586f / 512.f));
                    }
                    uint32_t off = (uint32_t)(64 + r * 8 + (ch >> 3)) * 8192 + (m >> 3) * 1024 + (ch & 7) * 128 + (m & 7) * 16;
                    *(uint4*)(g_E + off) = make_uint4(pack_bf16(v[0], v[1]), pack_bf16(v[2], v[3]), pack_bf16(v[4], v[5]), pack_bf16(v[6], v[7]));
                }
                __syncwarp();
                if (lane == 0) { fence_async(); red_release(&g_bar[6], 1); }
                return;
            }
            if (w == 2) {
#pragma unroll 1
                for (int it = 0; it < 4; it++) {
                    const int hf = it & 1;
                    __syncwarp();
                    if (hf == 0) bar_sync(13, 288); else bar_sync(6, 288);
                    if (lane == 0) {
                        const uint32_t src = sb + SM_HH + par * 32768 + hf * 16384;
                        bulk_s2peer(mapa(src, par ^ 1), src, 16384, mapa(BAR(hf ? B_HPEER1 : B_HPEER), par ^ 1));
                    }
                }
                return;
            }
            bar_sync(2, 288);
            if (lane == 0) {
                TX(5);
                fence_async();
                red_release(&g_bar[0], 1);
                TX(6);
            }
            __syncwarp();

            bar_sync(12, 160);
            if (lane == 0) {
                asm volatile("cp.async.bulk.global.shared::cta.bulk_group [%0], [%1], 8192;" ::"l"(g_A1 + (uint32_t)(((c >> 1) * 8 + r) * 16384 + (c & 1) * 8192)),
                             "r"(sb + SM_B1ST) : "memory");
                asm volatile("cp.async.bulk.commit_group;" ::: "memory");
                asm volatile("cp.async.bulk.wait_group 0;" ::: "memory");
                mbar_arrive(BAR(B_B1DONE), 1);
                fence_async();
                red_release(&g_bar[7], 1);
            }
#pragma unroll 1
            for (int layer = 0; layer < 2; layer++) {
                __syncwarp();
                bar_sync(5, 416);
                if (lane == 0) {
                    TX(0 + 8 * layer);
                    tma_store_5d(&tm_col, 32 * (b & 1), 0, b >> 1, 0, layer, sb + SM_RAW);
                    asm volatile("cp.reduce.async.bulk.global.shared::cta.bulk_group.add.f32 [%0], [%1], 8192;" ::"l"(g_ssqc + (layer * 16 + (b & 15)) * 2048),
                                 "r"(sb + SM_SSQ) : "memory");
                    asm volatile("cp.async.bulk.commit_group;" ::: "memory");
                    asm volatile("cp.async.bulk.wait_group 0;" ::: "memory");
                    TX(1 + 8 * layer);
                    fence_async();
                    red_release(&g_bar[1 + 2 * layer], 1);
                    TX(2 + 8 * layer);
                }
            }
        } else if (tid == 384) {
#pragma unroll 1
            for (int kb = 0; kb < 8; kb++) {
                uint32_t fb = BAR(B_FULL0 + kb);
                mbar_expect(fb, 16384);
                tma_5d_mc(sb + SM_A + 65536 + kb * 16384 + par * 8192, &tm_x, kb * 64, 0, 0, 8 * par, c, fb);
            }
#pragma unroll 1
            for (int k2 = 0; k2 < 8; k2++) {
                asm volatile("cp.async.bulk.prefetch.tensor.2d.L2.global [%0, {%1,%2}];" ::"l"(par ? &tm_bim : &tm_bre), "r"(k2 * 64), "r"(32 * c) : "memory");
                if ((k2 & 1) == par)
                    asm volatile("cp.async.bulk.prefetch.tensor.2d.L2.global [%0, {%1,%2}];" ::"l"((c & 1) ? &tm_cim : &tm_cre), "r"(64 * (c >> 1)), "r"(k2 * 64) : "memory");
            }
            mbar_wait(BAR(B_SETUP), 0);
#pragma unroll 1
            for (int layer = 0; layer < 2; layer++) {
                if (layer == 1) {
                    mbar_wait(BAR(B_AEMPTY + 4), 0);
                    mbar_expect(BAR(B_WRDY), 16384);
                    bulk_g2s(sb + SM_H + 16384, g_Wfrag + (uint32_t)b * 1024, 16384, BAR(B_WRDY));
                }
                wait_count(&g_bar[2 * layer], s_tgt[2 * layer]);
                TX(4 + 8 * layer);
                fence_async();
                mbar_expect(BAR(B_COL), 16384 + 8192);
                tma_5d(sb + SM_RAW, &tm_col, 32 * (b & 1), 0, b >> 1, 0, layer, BAR(B_COL));
                bulk_g2s(sb + SM_SSQ, g_ssq + layer * 2048, 8192, BAR(B_COL));
                if (layer == 0) {
                    wait_count(&g_bar[4], s_tgt[4]);
                    fence_async();
                    TX(16);
                    mbar_wait(BAR(B_B1DONE), 0);
                    TX(17);
                    mbar_expect(BAR(B_WRDY), 16384);
                    bulk_g2s(sb + SM_H + 16384, g_Wfrag + (uint32_t)b * 1024, 16384, BAR(B_WRDY));
                    wait_count(&g_bar[7], s_tgt[4]);
                    fence_async();
                }
                if (layer == 0) mbar_wait(BAR(B_AFREE), 0);
                mbar_wait(BAR(B_COL), layer);
#pragma unroll 1
                for (int s = 0; s < 8; s++) {
                    if (layer == 1) mbar_wait(BAR(B_AEMPTY + s), fpar(s, 2, 0));
                    if (s >= 2) mbar_wait(BAR(B_AFULL + s - 2), fpar(s - 2, 0, layer));
                    mbar_expect(BAR(B_AFULL + s), 16384);
                    bulk_g2s(sb + SM_A + s * 16384, g_A1 + (uint32_t)(r * 8 + s) * 16384, 16384, BAR(B_AFULL + s));
                }
                if (layer == 1) wait_count(&g_bar[6], s_tgt[4]);
                wait_count(&g_bar[1 + 2 * layer], s_tgt[1 + 2 * layer]);
                TX(3 + 8 * layer);
                fence_async();
                const uint8_t* xsrc = g_X + (uint32_t)(layer * 16 + c) * 8 * 16384;
                const uint8_t* esrc = g_E + (uint32_t)(layer * 8 + own) * 8 * 8192;
                mbar_arrive(BAR(B_SSQ), 1);
                mbar_expect(BAR(B_HPEER), 16384);
                mbar_expect(BAR(B_HPEER1), 16384);
#pragma unroll 1
                for (int it = 0; it < 20; it++) {
                    if (it < 8) {
                        const int st = it < 6 ? it : it - 6;
                        if (it >= 6) mbar_wait_cluster(BAR(B_XEMPTY + st), layer);
                        mbar_expect(BAR(B_XFULL + st), 16384);
                        bulk_g2s_mc(sb + SM_X + st * 16384 + par * 8192, xsrc + (uint32_t)it * 16384 + par * 8192, 8192, BAR(B_XFULL + st));
                    }
                    if (it >= 6) {
                        const bool isc = it >= 12;
                        const int s = isc ? cslot(it - 12) : it - 6;
                        mbar_wait(BAR(B_AEMPTY + s), fpar(s, it < 14 ? 0 : 1, layer));
                        uint32_t fb = BAR(B_AFULL + s), dst = sb + SM_A + s * 16384;
                        mbar_expect(fb, 16384);
                        if (!isc) {
                            bulk_g2s(dst, s < 4 ? esrc + (uint32_t)s * 16384 : xsrc + (uint32_t)(s - 4) * 16384, 16384, fb);
                        } else {
                            const int tile = 4 * par + ((pi_ + 1 + ((it - 12) >> 1)) & 3), sl = r ^ (it & 1);
                            if (layer == 1) {
                                tma_2d(dst, &tm_cre, 64 * sl, 64 * tile, fb);
                                tma_2d(dst + 8192, &tm_cim, 64 * sl, 64 * tile, fb);
                            } else {
                                bulk_g2s(dst, g_A2 + (uint32_t)(sl * 8 + tile) * 16384, 16384, fb);
                            }
                        }
                    }
                }
            }
        }
        return;
    }

    asm volatile("setmaxnreg.inc.sync.aligned.u32 152;");
    if (tid >= 96 && tid < 112) g_ssq[2048 + 16 * b + tid - 96] = 0.f;
    if (tid >= 128 && tid < 256) ((float4*)g_ssqc)[b * 128 + tid - 128] = make_float4(0.f, 0.f, 0.f, 0.f);
    TS(0);
    if (wg == 0) TC(30);
    {
        const int f = 32 * r + lane;
        float cd, sd;
        __sincosf((float)f * (6.283185307179586f / 512.f), &sd, &cd);
        const uint32_t dst = sb + SM_A + (lane >> 2) * 1024 + (lane & 3) * 32;
#pragma unroll 1
        for (int ch = tid >> 5; ch < 64; ch += 12) {
            int a = (8 * ch * f) & 511;
            a = a >= 256 ? a - 512 : a;
            float cs, sn;
            __sincosf((float)a * (6.283185307179586f / 512.f), &sn, &cs);
            float cv[8], sv[8];
#pragma unroll
            for (int e = 0; e < 8; e++) {
                cv[e] = cs; sv[e] = -sn;
                float t = cs * cd - sn * sd;
                sn = sn * cd + cs * sd;
                cs = t;
            }
            uint4 o1 = make_uint4(pack_bf16(sv[0], sv[1]), pack_bf16(sv[2], sv[3]), pack_bf16(sv[4], sv[5]), pack_bf16(sv[6], sv[7]));
            if (f == 0) o1 = make_uint4(0xbf803f80u, 0xbf803f80u, 0xbf803f80u, 0xbf803f80u);
            uint32_t a0 = dst + (ch >> 3) * 8192 + (ch & 7) * 128;
            sts128(a0, make_uint4(pack_bf16(cv[0], cv[1]), pack_bf16(cv[2], cv[3]), pack_bf16(cv[4], cv[5]), pack_bf16(cv[6], cv[7])));
            sts128(a0 + 16, o1);
        }
    }
    fence_async_smem();
    asm volatile("barrier.cluster.wait.acquire.aligned;" ::: "memory");
    bar_sync(10, 384);
    TS(1);
    if (wg < 2) {
        float acc[32];
        acc_def(acc);
        const int npos = 16 * r + 8 * wg + 2 * w;
        float sh0 = 0.f, sh1 = 0.f, s0 = 0.f, s1 = 0.f, q0 = 0.f, q1 = 0.f;
#pragma unroll 1
        for (int kb = 0; kb < 8; kb++) {
            uint32_t slot = sb + SM_A + 65536 + kb * 16384;
            mbar_wait(BAR(B_FULL0 + kb), 0);
            wg_fence();
#pragma unroll
            for (int ks = 0; ks < 4; ks++)
                wgmma_n64<0>(acc, desc_a(sb + SM_A + kb * 8192 + ks * 256), desc_k(slot + wg * 8192 + ks * 32), 1);
            wg_commit();
            {
                uint32_t v0 = lds32(slot + npos * 128 + lane * 4), v1 = lds32(slot + npos * 128 + 128 + lane * 4);
                if (kb == 0) { sh0 = __shfl_sync(~0u, bf_lo(v0), 0); sh1 = __shfl_sync(~0u, bf_lo(v1), 0); }
                float a = bf_lo(v0) - sh0, bq = bf_hi(v0) - sh0, cq = bf_lo(v1) - sh1, d = bf_hi(v1) - sh1;
                s0 += a + bq; q0 += a * a + bq * bq; s1 += cq + d; q1 += cq * cq + d * d;
            }
            wg_wait<1>();
            if (kb > 0 && kb <= 4 && lane == 0) { mbar_arrive(BAR(B_EMPTY0 + kb - 1), 1); mbar_arrive_remote(mapa(BAR(B_EMPTY0 + kb - 1), par ^ 1)); }
        }
#pragma unroll
        for (int o = 16; o; o >>= 1) {
            s0 += __shfl_xor_sync(~0u, s0, o); q0 += __shfl_xor_sync(~0u, q0, o);
            s1 += __shfl_xor_sync(~0u, s1, o); q1 += __shfl_xor_sync(~0u, q1, o);
        }
        if (lane == 0) *(float2*)(g_ssq + 128 * c + npos) = make_float2(fmaxf(q0 - s0 * s0 * (1.f / 512.f), 0.f), fmaxf(q1 - s1 * s1 * (1.f / 512.f), 0.f));
        wg_wait<0>();
        TS(2);
        uint8_t* dst = g_X + (uint32_t)((c * 8 + r) * 16384 + w * 4096 + wg * 1024 + g * 16 + 4 * q);
#pragma unroll
        for (int i = 0; i < 8; i++) {
            *(uint32_t*)(dst + i * 128) = pack_bf16(acc[4 * i], acc[4 * i + 1]);
            *(uint32_t*)(dst + 2048 + i * 128) = pack_bf16(acc[4 * i + 2], acc[4 * i + 3]);
        }
        bar_sync(2, 288);
        mbar_wait(BAR(B_SETUP), 0);
        TS(3);
    }

    if (wg == 2) {
        {
            uint4 p0 = __ldg((const uint4*)p.dskip + 2 * lane), p1 = __ldg((const uint4*)p.dskip + 2 * lane + 1);
            uint32_t u[8] = {p0.x, p0.y, p0.z, p0.w, p1.x, p1.y, p1.z, p1.w};
            int j = 64 * r + 4 * c + w, f, ph;
            dft_fp(j, f, ph);
            float s = 0.f;
            int idx = 16 * lane * f + ph;
#pragma unroll
            for (int i = 0; i < 16; i++) {
                int a = idx & 511;
                idx += f;
                a = a >= 256 ? a - 512 : a;
                s += ((i & 1) ? bf_hi(u[i >> 1]) : bf_lo(u[i >> 1])) * __cosf((float)a * (6.283185307179586f / 512.f));
            }
#pragma unroll
            for (int o = 16; o; o >>= 1) s += __shfl_xor_sync(~0u, s, o);
            if (lane == 0) g_Dh[j] = s;
        }
        mbar_wait(BAR(B_FULL0 + 7), 0);
        if (tid == 256) {
#pragma unroll 1
            for (int s = 0; s < 4; s++) mbar_wait_cluster(BAR(B_EMPTY0 + s), 0);
            mbar_expect(BAR(B_FULLB), 65536);
#pragma unroll 1
            for (int k2 = 0; k2 < 8; k2++)
                tma_2d_mc(sb + SM_A + 65536 + k2 * 8192 + par * 4096, par ? &tm_bim : &tm_bre, k2 * 64, 32 * c, BAR(B_FULLB));
        }
        __syncwarp();
        {
            const int cl = tid & 15, cb = 16 * (b & 7) + cl;
            const int c0 = cb == 0 ? 256 : 2 * cb, c1 = 2 * cb + 1;
            uint32_t wf[2][16];
#pragma unroll
            for (int h = 0; h < 2; h++) {
                const int kq = 16 * (b >> 3) + ((tid & 127) >> 4) + 8 * h, k1 = kq >> 2, qq = kq & 3;
                const unsigned short* wr_ = (const unsigned short*)p.w_r + (k1 + 128 * qq) * 257;
                const unsigned short* wi_ = (const unsigned short*)p.w_i + (k1 + 128 * qq) * 257;
#pragma unroll
                for (int i = 0; i < 4; i++) {
                    int o = 512 * i * 257;
                    wf[h][2 * i] = (uint32_t)__ldg(wr_ + o + c0) | ((uint32_t)__ldg(wr_ + o + 64 * 257 + c0) << 16);
                    wf[h][2 * i + 1] = ((uint32_t)__ldg(wi_ + o + c0) | ((uint32_t)__ldg(wi_ + o + 64 * 257 + c0) << 16)) ^ 0x80008000u;
                    wf[h][8 + 2 * i] = (uint32_t)__ldg(wr_ + o + c1) | ((uint32_t)__ldg(wr_ + o + 64 * 257 + c1) << 16);
                    wf[h][8 + 2 * i + 1] = ((uint32_t)__ldg(wi_ + o + c1) | ((uint32_t)__ldg(wi_ + o + 64 * 257 + c1) << 16)) ^ 0x80008000u;
                }
            }
#pragma unroll
            for (int h = 0; h < 2; h++)
#pragma unroll
                for (int i = 0; i < 4; i++)
                    sts128(sb + SM_H + cl * 1024 + (((tid & 127) >> 4) + 8 * h) * 64 + ((i ^ ((tid >> 5) & 3)) << 4),
                           make_uint4(wf[h][4 * i], wf[h][4 * i + 1], wf[h][4 * i + 2], wf[h][4 * i + 3]));
            fence_async_smem();
            bar_arrive(0, 192);
            bar_arrive(11, 192);
        }
        bar_sync(15, 160);
        float acc[32];
        acc_def(acc);
        mbar_wait(BAR(B_FULLB), 0);
        wg_fence();
#pragma unroll 1
        for (int kb = 0; kb < 8; kb++) {
#pragma unroll
            for (int ks = 0; ks < 4; ks++)
                wgmma_n64<0>(acc, desc_a(sb + SM_A + kb * 8192 + ks * 256), desc_k(sb + SM_A + 65536 + kb * 8192 + ks * 32), 1);
            wg_commit();
        }
        wg_wait<0>();
        if (lane == 0) { mbar_arrive(BAR(B_BFREE), 1); mbar_arrive_remote(mapa(BAR(B_BFREE), par ^ 1)); }
        if (tid == 256) {
            mbar_wait_cluster(BAR(B_BFREE), 0);
            mbar_expect(BAR(B_FULLC), 65536);
#pragma unroll 1
            for (int k2 = par; k2 < 8; k2 += 2)
                tma_2d_mc(sb + SM_A + 65536 + k2 * 8192, (c & 1) ? &tm_cim : &tm_cre, 64 * (c >> 1), k2 * 64, BAR(B_FULLC));
        }
        __syncwarp();
        {
            uint8_t* dst = sm + SM_B1ST + w * 256 + q * 32 + g * 2;
            const float wj0 = (r == 0 && w == 0 && g < 2) ? (g == 0 ? 0.f : 1.f / 512.f) : 2.f / 512.f;
#pragma unroll
            for (int i = 0; i < 4; i++) {
#pragma unroll
                for (int e = 0; e < 2; e++) {
                    float2 cf = *(const float2*)(sm + SM_TAB + (8 * i + 2 * q + e) * 8);
#pragma unroll
                    for (int h = 0; h < 2; h++) {
                        float wj = h == 0 ? wj0 : 2.f / 512.f;
                        float pr = acc[4 * i + 2 * h + e] * wj, pi = acc[16 + 4 * i + 2 * h + e] * wj;
                        uint8_t* d2 = dst + i * 2048 + h * 128 + e * 16;
                        *(__nv_bfloat16*)(d2) = __float2bfloat16(cf.x * pr - cf.y * pi);
                        *(__nv_bfloat16*)(d2 + 1024) = __float2bfloat16(cf.x * pi + cf.y * pr);
                    }
                }
            }
            fence_async_smem();
            bar_arrive(12, 160);
        }
        acc_def(acc);
        mbar_wait(BAR(B_FULLC), 0);
        wg_fence();
#pragma unroll 1
        for (int kb = 0; kb < 8; kb++) {
#pragma unroll
            for (int ks = 0; ks < 4; ks++)
                wgmma_n64<1>(acc, desc_a(sb + SM_A + kb * 8192 + ks * 256), desc_mn(sb + SM_A + 65536 + kb * 8192 + ks * 2048), 1);
            wg_commit();
        }
        wg_wait<0>();
        fence_async_smem();
        if (lane == 0) mbar_arrive(BAR(B_AFREE), 1);
        uint8_t* dst = g_A2 + (uint32_t)(((c >> 1) * 8 + r) * 16384 + (c & 1) * 8192 + w * 2048 + g * 16 + 4 * q);
#pragma unroll
        for (int i = 0; i < 8; i++) {
            *(uint32_t*)(dst + i * 128) = pack_bf16(acc[4 * i], acc[4 * i + 1]);
            *(uint32_t*)(dst + 1024 + i * 128) = pack_bf16(acc[4 * i + 2], acc[4 * i + 3]);
        }
        {
            const int m = 4 * c + w, jp = 64 * r + m;
            int fp, php;
            dft_fp(jp, fp, php);
            const __nv_bfloat16* dh = (const __nv_bfloat16*)(sm + SM_RSTD);
            if (tid == 256) wait_count(&g_bar[4], s_tgt[4]);
            bar_sync(3, 128);
            float4 d4 = __ldcg((const float4*)g_Dh + (tid - 256));
            *(uint2*)(sm + SM_RSTD + (tid - 256) * 8) = make_uint2(pack_bf16(d4.x, d4.y), pack_bf16(d4.z, d4.w));
            bar_sync(3, 128);
#pragma unroll 1
            for (int it = 0; it < 2; it++) {
                const int ch = lane + 32 * it;
                float v[8];
#pragma unroll
                for (int e = 0; e < 8; e++) {
                    int j = 8 * ch + e, f, ph;
                    dft_fp(j, f, ph);
                    float wj = j == 0 ? 0.f : (j == 1 ? 1.f / 512.f : 2.f / 512.f);
                    float gsum = 0.f;
#pragma unroll
                    for (int sgn = 0; sgn < 2; sgn++) {
                        int mm = (sgn ? f - fp : f + fp) & 511, pp = (sgn ? ph - php : ph + php) & 511;
                        if (mm > 256) { mm = 512 - mm; pp = (512 - pp) & 511; }
                        int odd = (pp >> 7) & 1;
                        float t = __bfloat162float(dh[mm == 256 ? 1 : 2 * mm + odd]);
                        if (odd && (mm & 255) == 0) t = 0.f;
                        gsum += (pp & 256) ? -t : t;
                    }
                    v[e] = 0.5f * wj * gsum;
                }
                uint32_t off = (uint32_t)(r * 8 + (ch >> 3)) * 8192 + (m >> 3) * 1024 + (ch & 7) * 128 + (m & 7) * 16;
                *(uint4*)(g_E + off) = make_uint4(pack_bf16(v[0], v[1]), pack_bf16(v[2], v[3]), pack_bf16(v[4], v[5]), pack_bf16(v[6], v[7]));
            }
        }
    }

#pragma unroll 1
    for (int layer = 0; layer < 2; layer++) {
        if (wg < 2) {
            const int n1 = 32 * wg + 8 * w + g;
            const int ct = n1 >> 2;
            gen_col_consts(sb, tid);
            uint32_t tr2[4], ti2[4], tn2[4];
#pragma unroll
            for (int i = 0; i < 4; i++) {
                float cr[2], ci[2];
#pragma unroll
                for (int e = 0; e < 2; e++) {
                    int a = (n1 * (8 * i + 2 * q + e)) & 2047;
                    a = a >= 1024 ? a - 2048 : a;
                    float ang = (float)a * (-6.283185307179586f / 2048.f);
                    cr[e] = __cosf(ang); ci[e] = __sinf(ang);
                }
                tr2[i] = pack_bf16(cr[0], cr[1]); ti2[i] = pack_bf16(ci[0], ci[1]); tn2[i] = ti2[i] ^ 0x80008000u;
            }
            mbar_wait(BAR(B_WST), 0);
            mbar_wait(BAR(B_COL), layer);
            TS(4 + 12 * layer);
            if (wg == 0) TC(0 + 10 * layer);
            const uint32_t rw0 = sb + SM_RAW + ct * 1024 + q * 64 + ((q >> 1) << 4) + (g & 3) * 4, rw1 = rw0 ^ 16;
            const int pos0 = 128 * ct + 8 * q + 2 * (g & 3);
            const int sw = b == 0 ? 1 : 0;
            uint32_t xr[4][4];
            const uint32_t st0 = sb + SM_H + (n1 >> 3) * 1024 + g * 16 + 4 * q;
#pragma unroll
            for (int i = 0; i < 4; i++) {
                float2 sq = *(const float2*)(sm + SM_SSQ + (pos0 + 32 * i) * 4);
                const uint32_t rs2 = pack_bf16(rsqrtf(sq.x * (1.f / 512.f) + 1e-5f), rsqrtf(sq.y * (1.f / 512.f) + 1e-5f));
#pragma unroll
                for (int jj = 0; jj < 4; jj++) {
                    const int K = jj ^ (2 * (i & 1));
                    uint32_t a = ((K & 1) ? rw1 : rw0) + i * 256 + (K & 2) * 16;
                    if (jj < 2) a ^= sw << 4;
                    uint32_t v = lds32(a);
                    xr[jj][i] = v;
                    uint32_t o = hmul2(v, rs2);
                    if (jj == 1 && sw) o = 0u;
                    sts32(st0 + (jj & 1) * 8192 + (4 * (jj >> 1) + i) * 128, o);
                }
            }
            if (wg == 0) TC(1 + 10 * layer);
            fence_async_smem();
            bar_sync(1, 256);
            float acc[32];
            const uint32_t s1a = sb + SM_X + wg * 16384, s2b = sb + SM_X + 32768;
            wg_fence();
#pragma unroll
            for (int ks = 0; ks < 8; ks++)
                wgmma_n64<1>(acc, desc_a(s1a + (ks >> 2) * 8192 + (ks & 3) * 256), desc_b64(sb + SM_H + ks * 2048), ks != 0);
            wg_commit();
            wg_wait<0>();
            if (wg == 0) TC(2 + 10 * layer);
            uint32_t are[2][4], aim[2][4];
#pragma unroll
            for (int col = 0; col < 2; col++) {
#pragma unroll
                for (int i = 0; i < 4; i++) {
                    int o = 4 * (4 * col + i);
                    uint32_t zr = pack_bf16(acc[o], acc[o + 1]), zi = pack_bf16(acc[o + 2], acc[o + 3]);
                    are[col][i] = hfma2(zr, tr2[i], hmul2(zi, tn2[i]));
                    aim[col][i] = hfma2(zr, ti2[i], hmul2(zi, tr2[i]));
                }
            }
            wg_fence();
#pragma unroll
            for (int ks = 0; ks < 2; ks++)
                wgmma_n64_rs(acc, are[0][2 * ks], are[1][2 * ks], are[0][2 * ks + 1], are[1][2 * ks + 1], desc_b64(s2b + ks * 2048), ks != 0);
#pragma unroll
            for (int ks = 0; ks < 2; ks++)
                wgmma_n64_rs(acc, aim[0][2 * ks], aim[1][2 * ks], aim[0][2 * ks + 1], aim[1][2 * ks + 1], desc_b64(s2b + 4096 + ks * 2048), 1);
            wg_commit();
            uint32_t wf[16];
            mbar_wait(BAR(B_WRDY), layer);
#pragma unroll
            for (int i = 0; i < 4; i++) {
                const int kq = n1 * 4 + q;
                uint4 v = *(const uint4*)(sm + SM_H + 16384 + kq * 64 + ((i ^ ((kq >> 1) & 3)) << 4));
                wf[4 * i] = v.x; wf[4 * i + 1] = v.y; wf[4 * i + 2] = v.z; wf[4 * i + 3] = v.w;
            }
            wg_wait<0>();
            if (wg == 0) TC(3 + 10 * layer);
#pragma unroll
            for (int col = 0; col < 2; col++) {
#pragma unroll
                for (int i = 0; i < 4; i++) {
                    uint32_t wr = wf[col * 8 + 2 * i], wn = wf[col * 8 + 2 * i + 1];
                    uint32_t zr = pack_bf16(acc[4 * i + 2 * col], acc[4 * i + 2 * col + 1]);
                    uint32_t zi = pack_bf16(acc[16 + 4 * i + 2 * col], acc[16 + 4 * i + 2 * col + 1]);
                    are[col][i] = hfma2(zr, wr, hmul2(zi, wn));
                    aim[col][i] = hfma2(zr, wn, hmul2(zi ^ 0x80008000u, wr));
                }
            }
            wg_fence();
#pragma unroll
            for (int ks = 0; ks < 2; ks++)
                wgmma_n64_rs(acc, are[0][2 * ks], are[1][2 * ks], are[0][2 * ks + 1], are[1][2 * ks + 1], desc_b64(s2b + ks * 2048), ks != 0);
#pragma unroll
            for (int ks = 0; ks < 2; ks++)
                wgmma_n64_rs(acc, aim[0][2 * ks], aim[1][2 * ks], aim[0][2 * ks + 1], aim[1][2 * ks + 1], desc_b64(s2b + 4096 + ks * 2048), 1);
            wg_commit();
            wg_wait<0>();
            if (wg == 0) TC(4 + 10 * layer);
            bar_sync(1, 256);
#pragma unroll
            for (int col = 0; col < 2; col++) {
#pragma unroll
                for (int i = 0; i < 4; i++) {
                    uint32_t zr = pack_bf16(acc[4 * i + 2 * col], acc[4 * i + 2 * col + 1]);
                    uint32_t zi = pack_bf16(acc[16 + 4 * i + 2 * col], acc[16 + 4 * i + 2 * col + 1]);
                    sts32(st0 + 16384 + (4 * col + i) * 128, hfma2(zr, tr2[i], hmul2(zi, tn2[i])));
                    sts32(st0 + 16384 + 8192 + (4 * col + i) * 128, hfma2(zr, ti2[i], hmul2(zi, tr2[i])));
                }
            }
            if (wg == 0) TC(5 + 10 * layer);
            fence_async_smem();
            bar_sync(1, 256);
            wg_fence();
#pragma unroll
            for (int ks = 0; ks < 8; ks++)
                wgmma_n64<1>(acc, desc_a(s1a + (ks >> 2) * 8192 + (ks & 3) * 256), desc_b64(sb + SM_H + 16384 + ks * 2048), ks != 0);
            wg_commit();
            wg_wait<0>();
            if (wg == 0) TC(6 + 10 * layer);
            const float sc = 1.f / 2048.f;
            const float sci0 = sw ? 0.f : -sc;
            const float wr0 = sw ? 0.5f : 1.f, wi0 = sw ? 0.f : 1.f;
#pragma unroll
            for (int i = 0; i < 4; i++) {
                float ss0, ss1;
#pragma unroll
                for (int col = 0; col < 2; col++) {
                    int o = 4 * (4 * col + i);
                    uint32_t vr = xr[2 * col][i], vi = xr[2 * col + 1][i];
                    float si = col == 0 ? sci0 : -sc;
                    uint32_t nr = pack_bf16(fmaf(acc[o], sc, bf_lo(vr)), fmaf(acc[o + 1], sc, bf_hi(vr)));
                    uint32_t ni = pack_bf16(fmaf(acc[o + 2], si, bf_lo(vi)), fmaf(acc[o + 3], si, bf_hi(vi)));
                    float a0 = bf_lo(nr), a1 = bf_hi(nr), b0 = bf_lo(ni), b1 = bf_hi(ni);
                    if (col == 0) {
                        ss0 = wr0 * a0 * a0 + wi0 * b0 * b0;
                        ss1 = wr0 * a1 * a1 + wi0 * b1 * b1;
                    } else {
                        ss0 += a0 * a0 + b0 * b0;
                        ss1 += a1 * a1 + b1 * b1;
                    }
                    const int K = (2 * col) ^ (2 * (i & 1));
                    uint32_t a = rw0 + i * 256 + K * 16;
                    if (col == 0) a ^= sw << 4;
                    sts32(a, nr);
                    sts32(a ^ 16, ni);
                }
                *(float2*)(sm + SM_SSQ + (pos0 + 32 * i) * 4) = make_float2(ss0 * (2.f / 512.f), ss1 * (2.f / 512.f));
            }
            fence_async_smem();
        }
        TS(5 + 12 * layer);
        if (wg == 0) TC(7 + 10 * layer);
        bar_arrive(5, 416);

        float acc[64];
        float* s_rstd = (float*)(sm + SM_RSTD);
        float* s_mean = (float*)(sm + SM_MEAN);
        const unsigned epoch = s_tgt[0] >> 7;
        const uint32_t pt3 = 1u + (2u * epoch + layer) % 3u;
        const uint32_t ptag = (pt3 & 1u) | ((pt3 & 2u) << 15);
        const uint64_t dstep = layer == 0 ? 16 : 2;
        auto c_desc = [&](int s) { return layer == 0 ? desc_a(sb + SM_A + s * 16384) : desc_k(sb + SM_A + s * 16384); };
        if (wg < 2) {
            const int prow = 32 * wg + 8 * w + g;
            const float2 l1 = *(const float2*)(sm + SM_LAM + prow * 8);
            float lr32 = l1.x, li32 = l1.y;
#pragma unroll
            for (int i = 0; i < 5; i++) { float t = lr32 * lr32 - li32 * li32; li32 = 2.f * lr32 * li32; lr32 = t; }
            float lr128 = lr32, li128 = li32;
#pragma unroll
            for (int i = 0; i < 2; i++) { float t = lr128 * lr128 - li128 * li128; li128 = 2.f * lr128 * li128; lr128 = t; }
            const float lr1 = l1.x, li1 = l1.y;
            const float l2r = lr128 * lr128 - li128 * li128, l2i = 2.f * lr128 * li128;
            const float l4r = l2r * l2r - l2i * l2i, l4i = 2.f * l2r * l2i;
            float lxr = 1.f, lxi = 0.f;
            {
                const int rho = (c - 1 - q) & 3;
                if (rho & 1) { lxr = lr128; lxi = li128; }
                if (rho & 2) { float t = lxr * l2r - lxi * l2i; lxi = lxr * l2i + lxi * l2r; lxr = t; }
            }
            acc_def(acc);
#pragma unroll 1
            for (int kb = 0; kb < 8; kb++) {
                const int st = kb < 6 ? kb : kb - 6;
                mbar_wait(BAR(B_AFULL + kb), fpar(kb, 0, layer));
                mbar_wait(BAR(B_XFULL + st), st < 2 ? (uint32_t)(kb >= 6) : (uint32_t)layer);
                wg_fence();
#pragma unroll
                for (int ks = 0; ks < 4; ks++)
                    wgmma_n128<1>(acc, desc_a(sb + SM_A + kb * 16384 + wg * 8192 + ks * 256),
                                  desc_b128(sb + SM_X + st * 16384 + ks * 4096), 1);
                wg_commit();
                wg_wait<1>();
                if (kb > 0 && lane == 0) {
                    mbar_arrive(BAR(B_AEMPTY + kb - 1), 1);
                    if (kb <= 2) { mbar_arrive(BAR(B_XEMPTY + kb - 1), 1); mbar_arrive_remote(mapa(BAR(B_XEMPTY + kb - 1), par ^ 1)); }
                }
            }
            wg_wait<0>();
            if (lane == 0) {
                mbar_arrive(BAR(B_AEMPTY + 7), 1);
                mbar_arrive_remote(mapa(BAR(B_RFREE), par ^ 1));
            }
            bar_arrive(14, 384);
            TS(6 + 12 * layer);
            bar_sync(4, 384);
            TS(7 + 12 * layer);
            float er = 0.f, ei = 0.f;
#pragma unroll
            for (int i = 0; i < 16; i++) {
                float2 rs = *(const float2*)(s_rstd + 128 + 8 * i + 2 * q);
                acc[4 * i] *= rs.x; acc[4 * i + 1] *= rs.y; acc[4 * i + 2] *= rs.x; acc[4 * i + 3] *= rs.y;
                float nr = lr1 * er - li1 * ei + acc[4 * i], ni = lr1 * ei + li1 * er + acc[4 * i + 2];
                er = lr1 * nr - li1 * ni + acc[4 * i + 1];
                ei = lr1 * ni + li1 * nr + acc[4 * i + 3];
            }
            float cr = 0.f, ci = 0.f, tr = 0.f, ti = 0.f;
#pragma unroll
            for (int qq = 0; qq < 4; qq++) {
                float xr_ = __shfl_sync(~0u, er, (lane & ~3) | qq), xi_ = __shfl_sync(~0u, ei, (lane & ~3) | qq);
                if (qq == q) { cr = tr; ci = ti; }
                float nr = lr32 * tr - li32 * ti + xr_, ni = lr32 * ti + li32 * tr + xi_;
                tr = nr; ti = ni;
            }
            float4* eb = g_Ebuf + (uint32_t)(layer * 16 * 512 + 64 * r + prow);
            if (q == 0 && c < 15) st_relaxed_f4(eb + c * 512, make_float4(tr, ti, __uint_as_float(epoch), 0.f));
            TS(8 + 12 * layer);
            float acc2[32];
            acc_def(acc2);
            float pr[4], pi[4];
            {
                unsigned n = 0;
                bool ok;
#pragma unroll 1
                do {
                    ok = true;
#pragma unroll
                    for (int k = 0; k < 4; k++) {
                        float4 v = make_float4(0.f, 0.f, __uint_as_float(epoch), 0.f);
                        if (4 * k + q < c) v = ld_relaxed_f4(eb + (4 * k + q) * 512);
                        pr[k] = v.x; pi[k] = v.y;
                        ok = ok && __float_as_uint(v.z) == epoch;
                    }
                } while (!ok && ++n < SPIN_LIMIT);
            }
            __syncwarp();
            TS(9 + 12 * layer);
            float hr = 0.f, hi = 0.f;
#pragma unroll
            for (int k = 0; k < 4; k++) {
                if (4 * k + q < c) {
                    float nr = l4r * hr - l4i * hi + pr[k], ni = l4r * hi + l4i * hr + pi[k];
                    hr = nr; hi = ni;
                }
            }
            {
                float nr = lxr * hr - lxi * hi, ni = lxr * hi + lxi * hr;
                hr = nr + __shfl_xor_sync(~0u, nr, 1); hi = ni + __shfl_xor_sync(~0u, ni, 1);
                hr += __shfl_xor_sync(~0u, hr, 2); hi += __shfl_xor_sync(~0u, hi, 2);
            }
#pragma unroll
            for (int qq = 0; qq < 3; qq++) {
                if (qq < q) { float nr = lr32 * hr - li32 * hi, ni = lr32 * hi + li32 * hr; hr = nr; hi = ni; }
            }
            er = cr + hr; ei = ci + hi;
            bar_sync(7, 384);
            mbar_wait_cluster(BAR(B_RFREE), layer);
            const uint32_t ha = sb + SM_HH + par * 32768 + (prow >> 3) * 1024 + g * 16 + 4 * q;
#pragma unroll
            for (int i = 0; i < 16; i++) {
                float nr = lr1 * er - li1 * ei + acc[4 * i], ni = lr1 * ei + li1 * er + acc[4 * i + 2];
                er = lr1 * nr - li1 * ni + acc[4 * i + 1];
                ei = lr1 * ni + li1 * nr + acc[4 * i + 3];
                sts32(ha + (i >> 3) * 16384 + (i & 7) * 128, pack_bf16(nr, er));
                sts32(ha + (i >> 3) * 16384 + 8192 + (i & 7) * 128, pack_bf16(ni, ei));
                if (i == 7) { fence_async_smem(); bar_arrive(13, 288); }
            }
            fence_async_smem();
            TS(10 + 12 * layer);
            bar_arrive(10, 384);
            bar_sync(6, 288);
            TS(11 + 12 * layer);
            float (&a0)[32] = *reinterpret_cast<float (*)[32]>(&acc[0]);
            float (&a1)[32] = *reinterpret_cast<float (*)[32]>(&acc[32]);
            auto tile_mma = [&](float (&d)[32], int u) {
#pragma unroll 1
                for (int k = 0; k < 2; k++) {
                    const uint32_t hb = sb + SM_HH + (par ^ k) * 32768 + wg * 16384;
                    if (k == 1) mbar_wait(BAR(wg ? B_HPEER1 : B_HPEER), layer);
                    const int cs = cslot(2 * u + k);
                    mbar_wait(BAR(B_AFULL + cs), fpar(cs, 2, layer));
                    const uint64_t da = c_desc(cs);
                    wg_fence();
#pragma unroll
                    for (int ks = 0; ks < 4; ks++) wgmma_n64s<1>(d, da + ks * dstep, desc_b64(hb + ks * 2048), (ks | k) != 0);
#pragma unroll
                    for (int ks = 0; ks < 4; ks++) wgmma_n64s<-1>(d, da + 512 + ks * dstep, desc_b64(hb + 8192 + ks * 2048), 1);
                }
                wg_commit();
            };
            auto tile_ship = [&](float (&d)[32], int u) {
                uint4* dst = g_P + (uint32_t)(((c * 8 + 2 * ((pi_ + 1 + u) & 3) + par) * 4 + pi_) * 1024 + wg * 512 + (tid & 127));
#pragma unroll
                for (int i = 0; i < 4; i++)
                    dst[i * 128] = make_uint4((pack_bf16(d[8 * i], d[8 * i + 1]) & 0xfffefffeu) | ptag, pack_bf16(d[8 * i + 2], d[8 * i + 3]),
                                              pack_bf16(d[8 * i + 4], d[8 * i + 5]), pack_bf16(d[8 * i + 6], d[8 * i + 7]));
            };
            tile_mma(a0, 0);
            if ((tid & 127) == 0) mbar_arrive_remote(mapa(BAR(B_HDONE), par ^ 1));
            __syncwarp();
            tile_mma(a1, 1);
            wg_wait<1>();
            tile_ship(a0, 0);
            tile_mma(acc2, 2);
            bar_arrive(12, 384);
            wg_wait<1>();
            tile_ship(a1, 1);
            wg_wait<0>();
            tile_ship(acc2, 2);
            if (lane < 6) mbar_arrive(BAR(B_AEMPTY + ((lane + 6) & 7)), 1);
            TS(12 + 12 * layer);
        } else {
            const int t2 = tid - 256;
            const uint8_t* ximg = g_X + (uint32_t)layer * 16 * 8 * 16384;
            mbar_wait(BAR(B_SSQ), layer);
            TS(6 + 12 * layer);
            float sqv[16];
#pragma unroll
            for (int i = 0; i < 16; i++) sqv[i] = __ldcg(g_ssqc + (layer * 16 + i) * 2048 + 128 * c + t2);
            const unsigned short xm = __ldcg((const unsigned short*)(ximg + (uint32_t)(c * 8 * 16384 + (t2 >> 3) * 128 + (t2 & 7) * 2)));
            {
                float tot = 0.f;
#pragma unroll
                for (int i = 0; i < 16; i++) tot += sqv[i];
                float rs = rsqrtf(tot * (1.f / 512.f) + 1e-5f);
                s_rstd[t2] = rs;
                s_rstd[128 + t2] = 2.f * rs;
                s_mean[t2] = layer == 0 ? 0.f : __uint_as_float((uint32_t)xm << 16) * (1.f / 512.f);
                TS(7 + 12 * layer);
                bar_arrive(4, 384);
            }
            acc_def(acc);
            bar_sync(14, 384);
#pragma unroll 1
            for (int it = 0; it < 4; it++) {
                const int sl = (it + 1) & 3;
                mbar_wait(BAR(B_AFULL + sl), fpar(0, 1, layer));
                if (sl == 0) { mbar_wait(BAR(B_AFULL + 4), fpar(0, 1, layer)); mbar_wait(BAR(B_AFULL + 5), fpar(0, 1, layer)); }
                const uint32_t xb = sl == 0 ? sb + SM_A + 4 * 16384 : sb + SM_X + (sl < 3 ? 2 * sl : 0) * 16384;
                wg_fence();
#pragma unroll
                for (int ks = 0; ks < 8; ks++)
                    wgmma_n128<1>(acc, desc_a(sb + SM_A + sl * 16384 + (ks >> 2) * 8192 + (ks & 3) * 256), desc_b128(xb + ks * 4096), 1);
                wg_commit();
                wg_wait<1>();
                if (it >= 1 && lane == 0) mbar_arrive(BAR(B_AEMPTY + it), 2);
                if (it == 2) {
                    if (lane == 0) mbar_arrive_remote(mapa(BAR(B_RFREE), par ^ 1));
                    bar_arrive(7, 384);
                }
            }
            wg_wait<0>();
            if (lane < 3) mbar_arrive(BAR(B_AEMPTY + (lane == 0 ? 0 : lane + 3)), 2);
            bar_sync(3, 128);
            TS(9 + 12 * layer);
            const int m0 = 16 * w + g;
            const uint32_t xoff = (uint32_t)((c * 8 + own) * 16384 + w * 4096 + g * 16 + 4 * q);
            if (layer == 0) {
                const uint8_t* xs = g_X + xoff;
#pragma unroll
                for (int i = 0; i < 16; i++) {
                    float2 rs = *(const float2*)(s_rstd + 8 * i + 2 * q);
                    uint32_t x0v = __ldcg((const uint32_t*)(xs + i * 128)), x1v = __ldcg((const uint32_t*)(xs + 2048 + i * 128));
                    acc[4 * i] = acc[4 * i] * rs.x + bf_lo(x0v);
                    acc[4 * i + 1] = acc[4 * i + 1] * rs.y + bf_hi(x0v);
                    acc[4 * i + 2] = acc[4 * i + 2] * rs.x + bf_lo(x1v);
                    acc[4 * i + 3] = acc[4 * i + 3] * rs.y + bf_hi(x1v);
                }
            } else {
                float d0 = ldbf(p.dskip + 64 * own + m0), d1 = ldbf(p.dskip + 64 * own + m0 + 8);
#pragma unroll
                for (int i = 0; i < 16; i++) {
                    float2 rs = *(const float2*)(s_rstd + 8 * i + 2 * q);
                    float2 mn = *(const float2*)(s_mean + 8 * i + 2 * q);
                    acc[4 * i] = acc[4 * i] * (1.f + rs.x * d0) + mn.x;
                    acc[4 * i + 1] = acc[4 * i + 1] * (1.f + rs.y * d0) + mn.y;
                    acc[4 * i + 2] = acc[4 * i + 2] * (1.f + rs.x * d1) + mn.x;
                    acc[4 * i + 3] = acc[4 * i + 3] * (1.f + rs.y * d1) + mn.y;
                }
            }
            TS(10 + 12 * layer);
            bar_sync(10, 384);
            TS(11 + 12 * layer);
            {
                float (&a0)[32] = *reinterpret_cast<float (*)[32]>(&acc[0]);
                float (&a1)[32] = *reinterpret_cast<float (*)[32]>(&acc[32]);
#pragma unroll 1
                for (int k = 0; k < 2; k++) {
                    const uint32_t hb = sb + SM_HH + (par ^ k) * 32768;
                    if (k == 1) {
                        mbar_wait(BAR(B_HPEER), layer);
                        mbar_wait(BAR(B_HPEER1), layer);
                        bar_sync(12, 384);
                    }
                    mbar_wait(BAR(B_AFULL + 4 + k), fpar(4, 2, layer));
                    const uint64_t da = c_desc(4 + k);
                    wg_fence();
#pragma unroll
                    for (int ks = 0; ks < 4; ks++) {
                        wgmma_n64s<1>(a0, da + ks * dstep, desc_b64(hb + ks * 2048), 1);
                        wgmma_n64s<1>(a1, da + ks * dstep, desc_b64(hb + 16384 + ks * 2048), 1);
                    }
#pragma unroll
                    for (int ks = 0; ks < 4; ks++) {
                        wgmma_n64s<-1>(a0, da + 512 + ks * dstep, desc_b64(hb + 8192 + ks * 2048), 1);
                        wgmma_n64s<-1>(a1, da + 512 + ks * dstep, desc_b64(hb + 16384 + 8192 + ks * 2048), 1);
                    }
                    wg_commit();
                }
                wg_wait<0>();
            }
#pragma unroll
            for (int i = 0; i < 16; i++)
                *(float4*)(sm + SM_A + 4 * 16384 + i * 2048 + t2 * 16) = make_float4(acc[4 * i], acc[4 * i + 1], acc[4 * i + 2], acc[4 * i + 3]);
            TS(12 + 12 * layer);
        }
        {
            const int t = tid & 127;
            const int nch = wg == 2 ? 2 : 3;
            const uint4* pb = g_P + (uint32_t)((c * 8 + r) * 4 * 1024 + wg * 128 + t);
            uint4 v[3][3];
            unsigned n = 0;
#pragma unroll 1
            while (true) {
                if (lane == 31) {
#pragma unroll 1
                    while (true) {
                        uint32_t bad = 0;
#pragma unroll
                        for (int sx = 0; sx < 3; sx++) {
                            uint32_t t0;
                            asm volatile("ld.relaxed.gpu.global.u32 %0, [%1];" : "=r"(t0) : "l"(pb + ((pi_ + 1 + sx) & 3) * 1024 + (nch - 1) * 384) : "memory");
                            bad |= t0 ^ ptag;
                        }
                        if (!(bad & 0x00010001u) || ++n >= SPIN_LIMIT) break;
                    }
                }
                __syncwarp();
                uint32_t bad = 0;
#pragma unroll
                for (int k = 0; k < 3; k++)
#pragma unroll
                    for (int sx = 0; sx < 3; sx++) {
                        v[k][sx] = make_uint4(ptag, 0, 0, 0);
                        if (k < nch) v[k][sx] = ld_relaxed_u4(pb + ((pi_ + 1 + sx) & 3) * 1024 + k * 384);
                        bad |= v[k][sx].x ^ ptag;
                    }
                if (!__any_sync(~0u, bad & 0x00010001u) || ++n >= SPIN_LIMIT) break;
            }
            bar_sync(8, 384);
            TS(13 + 12 * layer);
            const int m0 = 16 * w + g;
            const float w0 = (own == 0 && m0 < 2) ? (m0 == 0 ? 0.f : 0.5f) : 1.f;
#pragma unroll
            for (int k = 0; k < 3; k++) {
                if (k < nch) {
                    const int i = wg + 3 * k;
                    float4 a = *(const float4*)(sm + SM_A + 4 * 16384 + (2 * i) * 2048 + t * 16);
                    float4 bq = *(const float4*)(sm + SM_A + 4 * 16384 + (2 * i + 1) * 2048 + t * 16);
#pragma unroll
                    for (int sx = 0; sx < 3; sx++) {
                        a.x += bf_lo(v[k][sx].x); a.y += bf_hi(v[k][sx].x); a.z += bf_lo(v[k][sx].y); a.w += bf_hi(v[k][sx].y);
                        bq.x += bf_lo(v[k][sx].z); bq.y += bf_hi(v[k][sx].z); bq.z += bf_lo(v[k][sx].w); bq.w += bf_hi(v[k][sx].w);
                    }
                    if (layer == 0) {
                        uint8_t* xd = g_X + (uint32_t)((16 * 8 + c * 8 + own) * 16384 + w * 4096 + g * 16 + 4 * q + i * 256);
                        uint32_t v0 = pack_bf16(a.x, a.y), v1 = pack_bf16(a.z, a.w), v2 = pack_bf16(bq.x, bq.y), v3 = pack_bf16(bq.z, bq.w);
                        *(uint32_t*)(xd) = v0; *(uint32_t*)(xd + 2048) = v1; *(uint32_t*)(xd + 128) = v2; *(uint32_t*)(xd + 2048 + 128) = v3;
                        float sq[4];
                        sq[0] = w0 * bf_lo(v0) * bf_lo(v0) + bf_lo(v1) * bf_lo(v1);
                        sq[1] = w0 * bf_hi(v0) * bf_hi(v0) + bf_hi(v1) * bf_hi(v1);
                        sq[2] = w0 * bf_lo(v2) * bf_lo(v2) + bf_lo(v3) * bf_lo(v3);
                        sq[3] = w0 * bf_hi(v2) * bf_hi(v2) + bf_hi(v3) * bf_hi(v3);
                        float u0 = (g & 1) ? sq[2] : sq[0], u1 = (g & 1) ? sq[3] : sq[1];
                        u0 += __shfl_xor_sync(~0u, (g & 1) ? sq[0] : sq[2], 4);
                        u1 += __shfl_xor_sync(~0u, (g & 1) ? sq[1] : sq[3], 4);
                        float z = (g & 2) ? u1 : u0;
                        z += __shfl_xor_sync(~0u, (g & 2) ? u0 : u1, 8);
                        z += __shfl_xor_sync(~0u, z, 16);
                        if (g < 4) atomicAdd(s_mean + 16 * i + 8 * (g & 1) + 2 * q + (g >> 1), z);
                    } else {
                        float* o = p.out + (uint32_t)((128 * c + 32 * q + 4 * i) * 512 + 64 * own + m0);
                        o[0] = a.x; o[512] = a.y; o[8] = a.z; o[512 + 8] = a.w;
                        o[1024] = bq.x; o[1536] = bq.y; o[1024 + 8] = bq.z; o[1536 + 8] = bq.w;
                    }
                }
            }
            if (wg < 2) mbar_wait_cluster(BAR(B_HDONE), layer);
            if (layer == 0) {
                fence_async_smem();
                bar_sync(9, 384);
                TS(14 + 12 * layer);
                if (wg == 2) {
                    atomicAdd(g_ssq + 2048 + 128 * c + t, s_mean[t] * (2.f / 512.f));
                    bar_sync(3, 128);
                    if (lane == 0) { mbar_arrive(BAR(B_AEMPTY + 4), 2); mbar_arrive(BAR(B_AEMPTY + 5), 2); }
                    if (t == 0) { fence_async(); red_release(&g_bar[2], 1); }
                }
            }
        }
        TS(15 + 12 * layer);
        if (wg == 0) TC(31);
    }
}

typedef CUresult (*EncFn)(CUtensorMap*, CUtensorMapDataType, cuuint32_t, void*, const cuuint64_t*, const cuuint64_t*,
                          const cuuint32_t*, const cuuint32_t*, CUtensorMapInterleave, CUtensorMapSwizzle,
                          CUtensorMapL2promotion, CUtensorMapFloatOOBfill);

void launch_impl(void* const* d_in, void* d_out, int stop) {
    static EncFn enc = nullptr;
    if (!enc) {
        void* fn = nullptr;
        cudaDriverEntryPointQueryResult qr;
        cudaGetDriverEntryPoint("cuTensorMapEncodeTiled", &fn, cudaEnableDefault, &qr);
        enc = (EncFn)fn;
        cudaFuncSetAttribute(fused_kernel, cudaFuncAttributeMaxDynamicSharedMemorySize, SM_TOTAL);
    }
    CUtensorMap tx, tbr, tbi, tcr, tci, tcol;
    {
        void* gx = nullptr;
        cudaGetSymbolAddress(&gx, g_X);
        cuuint64_t gd[5] = {64, 16, 64, 16, 2};
        cuuint64_t gs[4] = {128, 2048, 128 * 1024, 2048 * 1024};
        cuuint32_t bx[5] = {32, 16, 1, 16, 1};
        cuuint32_t es[5] = {1, 1, 1, 1, 1};
        enc(&tcol, CU_TENSOR_MAP_DATA_TYPE_BFLOAT16, 5, gx, gd, gs, bx, es, CU_TENSOR_MAP_INTERLEAVE_NONE,
            CU_TENSOR_MAP_SWIZZLE_64B, CU_TENSOR_MAP_L2_PROMOTION_NONE, CU_TENSOR_MAP_FLOAT_OOB_FILL_NONE);
    }
    {
        cuuint64_t gd[5] = {512, 2, 4, 16, 16};
        cuuint64_t gs[4] = {1024, 32 * 1024, 2 * 1024, 128 * 1024};
        cuuint32_t bx[5] = {64, 2, 4, 8, 1};
        cuuint32_t es[5] = {1, 1, 1, 1, 1};
        enc(&tx, CU_TENSOR_MAP_DATA_TYPE_BFLOAT16, 5, d_in[0], gd, gs, bx, es, CU_TENSOR_MAP_INTERLEAVE_NONE,
            CU_TENSOR_MAP_SWIZZLE_128B, CU_TENSOR_MAP_L2_PROMOTION_L2_128B, CU_TENSOR_MAP_FLOAT_OOB_FILL_NONE);
    }
    auto mk2 = [&](CUtensorMap* m, void* ptr, cuuint32_t rows) {
        cuuint64_t gd[2] = {512, 512};
        cuuint64_t gs[1] = {1024};
        cuuint32_t bx[2] = {64, rows};
        cuuint32_t es[2] = {1, 1};
        enc(m, CU_TENSOR_MAP_DATA_TYPE_BFLOAT16, 2, ptr, gd, gs, bx, es, CU_TENSOR_MAP_INTERLEAVE_NONE,
            CU_TENSOR_MAP_SWIZZLE_128B, CU_TENSOR_MAP_L2_PROMOTION_L2_128B, CU_TENSOR_MAP_FLOAT_OOB_FILL_NONE);
    };
    mk2(&tbr, d_in[6], 32);
    mk2(&tbi, d_in[7], 32);
    mk2(&tcr, d_in[8], 64);
    mk2(&tci, d_in[9], 64);
    Params p;
    p.x0 = (const __nv_bfloat16*)d_in[0];
    p.w_r = (const __nv_bfloat16*)d_in[1];
    p.w_i = (const __nv_bfloat16*)d_in[2];
    p.lam_re = (const __nv_bfloat16*)d_in[4];
    p.lam_im = (const __nv_bfloat16*)d_in[5];
    p.log_dt = (const __nv_bfloat16*)d_in[10];
    p.dskip = (const __nv_bfloat16*)d_in[11];
    p.out = (float*)d_out;
    p.stop = stop;
    cudaLaunchConfig_t cfg = {};
    cfg.gridDim = dim3(NCTA); cfg.blockDim = dim3(NTHREADS); cfg.dynamicSmemBytes = SM_TOTAL; cfg.stream = cudaStreamPerThread;
    cudaLaunchAttribute at[1];
    at[0].id = cudaLaunchAttributeClusterDimension;
    at[0].val.clusterDim.x = 2; at[0].val.clusterDim.y = 1; at[0].val.clusterDim.z = 1;
    cfg.attrs = at; cfg.numAttrs = 1;
    cudaLaunchKernelEx(&cfg, fused_kernel, tx, tbr, tbi, tcr, tci, tcol, p);
}

}

extern "C" void kernel_launch(void* const* d_in, const int* in_sizes, int n_in, void* d_out, int out_size) {
    (void)in_sizes; (void)n_in; (void)out_size;
    launch_impl(d_in, d_out, 100);
}
```
